```python
import torch

def _softmax(x, axis=-1):
    return torch.softmax(x, dim=axis)

def _gelu(x):
    return torch.nn.functional.gelu(x, approximate='tanh')

def _silu(x):
    return torch.nn.functional.silu(x)

def _sigmoid(x):
    return torch.sigmoid(x)

def _layernorm(x, axis=-1, eps=1e-05):
    m = x.mean(dim=axis, keepdim=True)
    v = x.var(dim=axis, keepdim=True, unbiased=False)
    return (x - m) / torch.sqrt(v + eps)

def _scatter_add(tgt, idx, src, axis=0):
    return tgt.clone().index_add_(axis, idx, src)

def _segment_sum(src, seg, n):
    out = torch.zeros((n,) + src.shape[1:], dtype=src.dtype)
    return out.index_add_(0, seg, src)

def _pad(x, pw):
    flat = tuple((v for pair in reversed(pw) for v in pair))
    return torch.nn.functional.pad(x, flat)
kernel_name = 'adaLN_cond__mha_block_cached__glu_gated_geglu__prompt'

def setup_inputs():

    _w = lambda a: (lambda t: t.to(torch.bfloat16) if t.is_floating_point() else t)(torch.as_tensor(a))

    def _A_setup():
        B, Sq, D = (1, 2048, 576)
        H, Sk, Dh = (32, 2048, 128)
        return {'x': _w((lambda *s: torch.randn(*s, dtype=torch.bfloat16) * 0.05)(B, Sq, D)), 'k_cache': _w((lambda *s: torch.randn(*s, dtype=torch.bfloat16) * 0.8)(B, H, Sk, Dh)), 'v_cache': _w((lambda *s: torch.randn(*s, dtype=torch.bfloat16) * 3.2)(B, H, Sk, Dh)), 'wq': _w((lambda *s: torch.randn(*s, dtype=torch.bfloat16) * 0.8)(D, H * Dh) * D ** (-0.5)), 'wo': _w((lambda *s: torch.randn(*s, dtype=torch.bfloat16) * 3.2)(H * Dh, D) * (H * Dh) ** (-0.5))}
    _A_in = _A_setup()

    def _B_setup():
        B, S, Dm, Df = (1, 2048, 576, 4608)
        return {'x': _w((lambda *s: torch.randn(*s, dtype=torch.bfloat16) * 0.05)(B, S, Dm)), 'w_gate': _w((lambda *s: torch.randn(*s, dtype=torch.bfloat16) * 3.2)(Dm, Df) * Dm ** (-0.5)), 'w_up': _w((lambda *s: torch.randn(*s, dtype=torch.bfloat16) * 3.2)(Dm, Df) * Dm ** (-0.5)), 'w_down': _w((lambda *s: torch.randn(*s, dtype=torch.bfloat16) * 3.2)(Df, Dm) * Df ** (-0.5))}
    _B_in = _B_setup()
    return {'A_x': _A_in['x'], 'A_k_cache': _A_in['k_cache'], 'A_v_cache': _A_in['v_cache'], 'A_wq': _A_in['wq'], 'A_wo': _A_in['wo'], 'B_x': _B_in['x'], 'B_w_gate': _B_in['w_gate'], 'B_w_up': _B_in['w_up'], 'B_w_down': _B_in['w_down'], 'c': _w((lambda *s: torch.randn(*s, dtype=torch.bfloat16) * 0.4)(1, 576) * 8.0), 'w_mod': _w((lambda *s: torch.randn(*s, dtype=torch.bfloat16) * 0.4)(576, 6 * 576) * 576 ** (-0.5) * 8.0)}

def reference(A_x, A_k_cache, A_v_cache, A_wq, A_wo, B_x, B_w_gate, B_w_up, B_w_down, c, w_mod):

    def _A_ref(x, k_cache, v_cache, wq, wo):
        B, Sq, D = x.shape
        H, Dh = (32, 128)
        q = (lambda x, *d: x.permute(*d))((x @ wq).reshape(B, Sq, H, Dh), 0, 2, 1, 3)
        scores = torch.einsum('bhqd,bhkd->bhqk', q, k_cache) * Dh ** (-0.5)
        p = _softmax(scores, axis=-1)
        o = torch.einsum('bhqk,bhkd->bhqd', p, v_cache)
        return (lambda x, *d: x.permute(*d))(o, 0, 2, 1, 3).reshape(B, Sq, H * Dh) @ wo

    def _B_ref(x, w_gate, w_up, w_down):
        g = torch.einsum('bsd,df->bsf', x, w_gate)
        u = torch.einsum('bsd,df->bsf', x, w_up)
        h = _gelu(g) * u
        return torch.einsum('bsf,fd->bsd', h, w_down)
    x = A_x
    mod = (_silu(c) @ w_mod).reshape(c.shape[0], 6, 1, -1)
    sa, ca, ga, sb, cb, gb = (mod[:, 0].clone(), mod[:, 1].clone(), mod[:, 2].clone(), mod[:, 3].clone(), mod[:, 4].clone(), mod[:, 5].clone())
    h = _layernorm(x, axis=-1) * (1 + ca) + sa
    x = x + ga * _A_ref(h, A_k_cache, A_v_cache, A_wq, A_wo)
    h = _layernorm(x, axis=-1) * (1 + cb) + sb
    x = x + gb * _B_ref(h, B_w_gate, B_w_up, B_w_down)
    return x
```

```cpp
#include <cuda_runtime.h>
#include <cuda_bf16.h>
#include <cuda.h>
#include <stdint.h>

namespace {

constexpr int DM = 576;
constexpr int SLOT_BYTES = 16384;
constexpr int BOX_BYTES = 8192;
constexpr int NUNITS = 14;
constexpr int SMEM_TAIL = NUNITS * SLOT_BYTES;
constexpr int SMEM_BYTES = SMEM_TAIL + 2048 + 1024;
constexpr int OFF_FULL = SMEM_TAIL;
constexpr int OFF_EMPTY = SMEM_TAIL + 64;
constexpr int OFF_RED = SMEM_TAIL + 128;

constexpr int CNT_MODA = 0, CNT_MODB = 1, CNT_DONE = 2, CNT_H1 = 8, CNT_P1 = 8 + 128, CNT_H2 = 8 + 256,
              CNT_P2 = 8 + 384, CNT_TOTAL = 8 + 512;

__device__ float g_mod[6 * DM];
__device__ uint4 g_h1[128 * 36 * 32];
__device__ uint4 g_h2[128 * 36 * 32];
__device__ uint2 g_part[128 * 8 * 72 * 32];
__device__ float4 g_x2[128 * 9 * 256];
__device__ unsigned g_cnt[CNT_TOTAL * 32];

struct Maps {
    CUtensorMap k, v, wq, wo, wg, wu, wd;
};

__device__ __forceinline__ uint32_t smem_u32(const void* p) { return (uint32_t)__cvta_generic_to_shared(p); }
__device__ __forceinline__ void mbar_init(uint32_t a, uint32_t c) {
    asm volatile("mbarrier.init.shared::cta.b64 [%0], %1;" ::"r"(a), "r"(c) : "memory");
}
__device__ __forceinline__ void mbar_expect_tx(uint32_t a, uint32_t bytes) {
    asm volatile("mbarrier.arrive.expect_tx.shared::cta.b64 _, [%0], %1;" ::"r"(a), "r"(bytes) : "memory");
}
__device__ __forceinline__ bool mbar_try(uint32_t a, uint32_t ph) {
    uint32_t ok;
    asm volatile(
        "{\n.reg .pred p;\nmbarrier.try_wait.parity.shared::cta.b64 p, [%1], %2;\nselp.u32 %0, 1, 0, p;\n}"
        : "=r"(ok)
        : "r"(a), "r"(ph)
        : "memory");
    return ok != 0;
}
__device__ __forceinline__ uint32_t clk32() {
    uint32_t c;
    asm volatile("mov.u32 %0, %%clock;" : "=r"(c));
    return c;
}
constexpr uint32_t WAIT_LIMIT = 1u << 30;
__device__ __forceinline__ void mbar_wait(uint32_t a, uint32_t ph) {
    if (mbar_try(a, ph)) return;
    uint32_t t0 = clk32();
    while (!mbar_try(a, ph)) {
        if (clk32() - t0 > WAIT_LIMIT) break;
    }
}
__device__ __forceinline__ void mbar_arrive_cluster(uint32_t a, uint32_t cta) {
    asm volatile(
        "{\n.reg .b32 ra;\nmapa.shared::cluster.u32 ra, %0, %1;\nmbarrier.arrive.shared::cluster.b64 _, [ra];\n}" ::"r"(a),
        "r"(cta)
        : "memory");
}
__device__ __forceinline__ void tma_mc(uint32_t dst, const CUtensorMap* m, int c0, int c1, uint32_t bar) {
    asm volatile(
        "cp.async.bulk.tensor.2d.shared::cluster.global.mbarrier::complete_tx::bytes.multicast::cluster"
        " [%0], [%1, {%3, %4}], [%2], %5;" ::"r"(dst),
        "l"(m), "r"(bar), "r"(c0), "r"(c1), "h"((uint16_t)3)
        : "memory");
}
__device__ __forceinline__ void bar_sync(int id, int n) { asm volatile("bar.sync %0, %1;" ::"r"(id), "r"(n) : "memory"); }
__device__ __forceinline__ void bar_arrive(int id, int n) {
    asm volatile("bar.arrive %0, %1;" ::"r"(id), "r"(n) : "memory");
}
__device__ __forceinline__ void wg_fence() { asm volatile("wgmma.fence.sync.aligned;" ::: "memory"); }
__device__ __forceinline__ void wg_commit() { asm volatile("wgmma.commit_group.sync.aligned;" ::: "memory"); }
template <int N>
__device__ __forceinline__ void wg_wait() {
    asm volatile("wgmma.wait_group.sync.aligned %0;" ::"n"(N) : "memory");
}
template <int N>
__device__ __forceinline__ void pin(float (&d)[N]) {
#pragma unroll
    for (int i = 0; i < N; i++) asm volatile("" : "+f"(d[i])::"memory");
}
template <int N>
__device__ __forceinline__ void pin(uint32_t (&d)[N]) {
#pragma unroll
    for (int i = 0; i < N; i++) asm volatile("" : "+r"(d[i])::"memory");
}
__device__ __forceinline__ uint32_t pack_bf16(float lo, float hi) {
    uint32_t r;
    asm("cvt.rn.bf16x2.f32 %0, %1, %2;" : "=r"(r) : "f"(hi), "f"(lo));
    return r;
}
__device__ __forceinline__ float bf_lo(uint32_t v) { return __uint_as_float(v << 16); }
__device__ __forceinline__ float bf_hi(uint32_t v) { return __uint_as_float(v & 0xffff0000u); }
__device__ __forceinline__ float round_bf16(float v) { return __bfloat162float(__float2bfloat16_rn(v)); }
__device__ __forceinline__ float ex2(float x) {
    float y;
    asm("ex2.approx.ftz.f32 %0, %1;" : "=f"(y) : "f"(x));
    return y;
}
__device__ __forceinline__ float rcp(float x) {
    float y;
    asm("rcp.approx.ftz.f32 %0, %1;" : "=f"(y) : "f"(x));
    return y;
}
__device__ __forceinline__ void sts128(uint32_t a, uint32_t x, uint32_t y, uint32_t z, uint32_t w) {
    asm volatile("st.shared.v4.b32 [%0], {%1,%2,%3,%4};" ::"r"(a), "r"(x), "r"(y), "r"(z), "r"(w) : "memory");
}
__device__ __forceinline__ void lds128(uint32_t a, uint32_t& x, uint32_t& y, uint32_t& z, uint32_t& w) {
    asm volatile("ld.shared.v4.b32 {%0,%1,%2,%3}, [%4];" : "=r"(x), "=r"(y), "=r"(z), "=r"(w) : "r"(a) : "memory");
}
__device__ __forceinline__ void sts32f(uint32_t a, float v) {
    asm volatile("st.shared.f32 [%0], %1;" ::"r"(a), "f"(v) : "memory");
}
__device__ __forceinline__ float lds32f(uint32_t a) {
    float v;
    asm volatile("ld.shared.f32 %0, [%1];" : "=f"(v) : "r"(a) : "memory");
    return v;
}
__device__ __forceinline__ void signal_cnt(int idx) {
    asm volatile("red.release.gpu.global.add.u32 [%0], 1;" ::"l"(&g_cnt[idx * 32]) : "memory");
}
__device__ __forceinline__ void wait_cnt(int idx, unsigned target) {
    if ((threadIdx.x & 31) == 0) {
        uint32_t t0 = clk32();
        while (true) {
            unsigned v;
            asm volatile("ld.acquire.gpu.global.u32 %0, [%1];" : "=r"(v) : "l"(&g_cnt[idx * 32]) : "memory");
            if (v >= target) break;
            if (clk32() - t0 > WAIT_LIMIT) break;
        }
    }
    __syncwarp();
}

#define F8(d, b) \
    "+f"(d[b]), "+f"(d[b + 1]), "+f"(d[b + 2]), "+f"(d[b + 3]), "+f"(d[b + 4]), "+f"(d[b + 5]), "+f"(d[b + 6]), "+f"(d[b + 7])

template <int TB>
__device__ __forceinline__ void wgmma_n128(float (&d)[64], uint32_t a0, uint32_t a1, uint32_t a2, uint32_t a3,
                                           uint64_t db, int sc) {
    asm volatile(
        "{\n.reg .pred p;\nsetp.ne.b32 p, %69, 0;\n"
        "wgmma.mma_async.sync.aligned.m64n128k16.f32.bf16.bf16 "
        "{%0,%1,%2,%3,%4,%5,%6,%7,%8,%9,%10,%11,%12,%13,%14,%15,%16,%17,%18,%19,%20,%21,%22,%23,%24,%25,%26,%27,%28,%29,%30,%31,"
        "%32,%33,%34,%35,%36,%37,%38,%39,%40,%41,%42,%43,%44,%45,%46,%47,%48,%49,%50,%51,%52,%53,%54,%55,%56,%57,%58,%59,%60,%61,%62,%63},"
        "{%64,%65,%66,%67}, %68, p, 1, 1, %70;\n}"
        : F8(d, 0), F8(d, 8), F8(d, 16), F8(d, 24), F8(d, 32), F8(d, 40), F8(d, 48), F8(d, 56)
        : "r"(a0), "r"(a1), "r"(a2), "r"(a3), "l"(db), "r"(sc), "n"(TB));
}
#define O8(d, b) \
    "=f"(d[b]), "=f"(d[b + 1]), "=f"(d[b + 2]), "=f"(d[b + 3]), "=f"(d[b + 4]), "=f"(d[b + 5]), "=f"(d[b + 6]), "=f"(d[b + 7])
template <int TB>
__device__ __forceinline__ void wgmma_n128_z(float (&d)[64], uint32_t a0, uint32_t a1, uint32_t a2, uint32_t a3,
                                             uint64_t db) {
    asm volatile(
        "wgmma.mma_async.sync.aligned.m64n128k16.f32.bf16.bf16 "
        "{%0,%1,%2,%3,%4,%5,%6,%7,%8,%9,%10,%11,%12,%13,%14,%15,%16,%17,%18,%19,%20,%21,%22,%23,%24,%25,%26,%27,%28,%29,%30,%31,"
        "%32,%33,%34,%35,%36,%37,%38,%39,%40,%41,%42,%43,%44,%45,%46,%47,%48,%49,%50,%51,%52,%53,%54,%55,%56,%57,%58,%59,%60,%61,%62,%63},"
        "{%64,%65,%66,%67}, %68, 0, 1, 1, %69;"
        : O8(d, 0), O8(d, 8), O8(d, 16), O8(d, 24), O8(d, 32), O8(d, 40), O8(d, 48), O8(d, 56)
        : "r"(a0), "r"(a1), "r"(a2), "r"(a3), "l"(db), "n"(TB));
}
__device__ __forceinline__ void wgmma_n64_z(float (&d)[32], uint32_t a0, uint32_t a1, uint32_t a2, uint32_t a3,
                                            uint64_t db) {
    asm volatile(
        "wgmma.mma_async.sync.aligned.m64n64k16.f32.bf16.bf16 "
        "{%0,%1,%2,%3,%4,%5,%6,%7,%8,%9,%10,%11,%12,%13,%14,%15,%16,%17,%18,%19,%20,%21,%22,%23,%24,%25,%26,%27,%28,%29,%30,%31},"
        "{%32,%33,%34,%35}, %36, 0, 1, 1, 1;"
        : O8(d, 0), O8(d, 8), O8(d, 16), O8(d, 24)
        : "r"(a0), "r"(a1), "r"(a2), "r"(a3), "l"(db));
}
__device__ __forceinline__ void wgmma_n64(float (&d)[32], uint32_t a0, uint32_t a1, uint32_t a2, uint32_t a3,
                                          uint64_t db, int sc) {
    asm volatile(
        "{\n.reg .pred p;\nsetp.ne.b32 p, %37, 0;\n"
        "wgmma.mma_async.sync.aligned.m64n64k16.f32.bf16.bf16 "
        "{%0,%1,%2,%3,%4,%5,%6,%7,%8,%9,%10,%11,%12,%13,%14,%15,%16,%17,%18,%19,%20,%21,%22,%23,%24,%25,%26,%27,%28,%29,%30,%31},"
        "{%32,%33,%34,%35}, %36, p, 1, 1, 1;\n}"
        : F8(d, 0), F8(d, 8), F8(d, 16), F8(d, 24)
        : "r"(a0), "r"(a1), "r"(a2), "r"(a3), "l"(db), "r"(sc));
}

__device__ __forceinline__ uint64_t desc_of(uint32_t saddr) {
    return (uint64_t)(((saddr >> 4) & 0x3FFFu) | (512u << 16)) | ((uint64_t)(64u | (1u << 30)) << 32);
}

struct Ring {
    uint32_t slot;
    uint32_t phase;
    template <int NS>
    __device__ __forceinline__ void next() {
        if (++slot == NS) {
            slot = 0;
            phase ^= 1;
        }
    }
};

struct Ctx {
    uint32_t sbase;
    uint32_t rel_cta;
    __device__ __forceinline__ void wait_full(uint32_t slot, uint32_t phase) const {
        mbar_wait(sbase + OFF_FULL + slot * 8, phase);
    }
    __device__ __forceinline__ void release(uint32_t slot) const {
        if (rel_cta < 2) mbar_arrive_cluster(sbase + OFF_EMPTY + slot * 8, rel_cta);
    }
};

template <int NK, int NS, int NA>
__device__ __forceinline__ void gemm_n128(float (&d)[64], const uint32_t (&a)[NA], const Ctx& c, Ring& r) {
    uint32_t prev = 0;
#pragma unroll
    for (int s = 0; s < NK; s++) {
        c.wait_full(r.slot, r.phase);
        uint64_t db = desc_of(c.sbase + r.slot * SLOT_BYTES);
        wg_fence();
#pragma unroll
        for (int k = 0; k < 4; k++) {
            if ((s | k) == 0)
                wgmma_n128_z<1>(d, a[0], a[1], a[2], a[3], db);
            else
                wgmma_n128<1>(d, a[s * 16 + k * 4], a[s * 16 + k * 4 + 1], a[s * 16 + k * 4 + 2], a[s * 16 + k * 4 + 3],
                              db + k * 128, 1);
        }
        wg_commit();
        if (s > 0) {
            wg_wait<1>();
            c.release(prev);
        }
        prev = r.slot;
        r.template next<NS>();
    }
    wg_wait<0>();
    c.release(prev);
    pin(d);
}
template <int NKS, int NS, int NA>
__device__ __forceinline__ void gemm_n64(float (&d)[32], const uint32_t (&a)[NA], const Ctx& c, Ring& r) {
    uint32_t prev = 0;
    constexpr int NSL = (NKS + 7) / 8;
#pragma unroll
    for (int s = 0; s < NSL; s++) {
        c.wait_full(r.slot, r.phase);
        uint64_t db = desc_of(c.sbase + r.slot * SLOT_BYTES);
        wg_fence();
#pragma unroll
        for (int k = 0; k < 8; k++) {
            if ((s | k) == 0)
                wgmma_n64_z(d, a[0], a[1], a[2], a[3], db);
            else if (s * 8 + k < NKS)
                wgmma_n64(d, a[s * 32 + k * 4], a[s * 32 + k * 4 + 1], a[s * 32 + k * 4 + 2], a[s * 32 + k * 4 + 3],
                          db + k * 128, 1);
        }
        wg_commit();
        if (s > 0) {
            wg_wait<1>();
            c.release(prev);
        }
        prev = r.slot;
        r.template next<NS>();
    }
    wg_wait<0>();
    c.release(prev);
    pin(d);
}

template <int NK, int NS, int NA>
__device__ __forceinline__ void proj_partials(const uint32_t (&a)[NA], const Ctx& c, Ring& r,
                                              uint2* dst  ) {
#pragma unroll 1
    for (int p = 0; p < 4; p++) {
        float d[64];
        gemm_n128<NK, NS>(d, a, c, r);
#pragma unroll
        for (int j = 0; j < 16; j++)
            __stcg(dst + (p * 16 + j) * 32, make_uint2(pack_bf16(d[4 * j], d[4 * j + 1]), pack_bf16(d[4 * j + 2], d[4 * j + 3])));
    }
    float d[32];
    gemm_n64<NK * 4, NS>(d, a, c, r);
#pragma unroll
    for (int j = 0; j < 8; j++)
        __stcg(dst + (64 + j) * 32, make_uint2(pack_bf16(d[4 * j], d[4 * j + 1]), pack_bf16(d[4 * j + 2], d[4 * j + 3])));
}

__device__ __forceinline__ void row_reduce(float& s0, float& s1, uint32_t red, int warp, int lane) {
    s0 += __shfl_xor_sync(0xffffffffu, s0, 1);
    s1 += __shfl_xor_sync(0xffffffffu, s1, 1);
    s0 += __shfl_xor_sync(0xffffffffu, s0, 2);
    s1 += __shfl_xor_sync(0xffffffffu, s1, 2);
    if ((lane & 3) == 0) {
        sts32f(red + (warp * 16 + (lane >> 2)) * 4, s0);
        sts32f(red + (warp * 16 + 8 + (lane >> 2)) * 4, s1);
    }
    bar_sync(3, 256);
    s0 = 0.f;
    s1 = 0.f;
#pragma unroll
    for (int w = 0; w < 8; w++) {
        s0 += lds32f(red + (w * 16 + (lane >> 2)) * 4);
        s1 += lds32f(red + (w * 16 + 8 + (lane >> 2)) * 4);
    }
}
__device__ __forceinline__ void layernorm_rows(float (&v)[36], uint32_t red, int warp, int lane) {
    float s0 = 0.f, s1 = 0.f;
#pragma unroll
    for (int j = 0; j < 9; j++) {
        s0 += v[4 * j] + v[4 * j + 1];
        s1 += v[4 * j + 2] + v[4 * j + 3];
    }
    row_reduce(s0, s1, red, warp, lane);
    const float m0 = s0 * (1.f / DM), m1 = s1 * (1.f / DM);
    s0 = 0.f;
    s1 = 0.f;
#pragma unroll
    for (int j = 0; j < 9; j++) {
        v[4 * j] -= m0;
        v[4 * j + 1] -= m0;
        v[4 * j + 2] -= m1;
        v[4 * j + 3] -= m1;
        s0 += v[4 * j] * v[4 * j] + v[4 * j + 1] * v[4 * j + 1];
        s1 += v[4 * j + 2] * v[4 * j + 2] + v[4 * j + 3] * v[4 * j + 3];
    }
    row_reduce(s0, s1, red + 512, warp, lane);
    const float r0 = rsqrtf(s0 * (1.f / DM) + 1e-5f), r1 = rsqrtf(s1 * (1.f / DM) + 1e-5f);
#pragma unroll
    for (int j = 0; j < 9; j++) {
        v[4 * j] *= r0;
        v[4 * j + 1] *= r0;
        v[4 * j + 2] *= r1;
        v[4 * j + 3] *= r1;
    }
}
__device__ __forceinline__ void modulate_store(const float (&v)[36], const float* shift, const float* scale,
                                               uint4* hbuf  , int warp, int lane) {
    uint2* dst = reinterpret_cast<uint2*>(hbuf);
#pragma unroll
    for (int j = 0; j < 9; j++) {
        const int grp = warp * 9 + j;
        const int col = grp * 8 + (lane & 3) * 2;
        const float2 sh = __ldcg(reinterpret_cast<const float2*>(shift + col));
        const float2 sc = __ldcg(reinterpret_cast<const float2*>(scale + col));
        const float c0 = round_bf16(1.f + sc.x), c1 = round_bf16(1.f + sc.y);
        uint2 o;
        o.x = pack_bf16(fmaf(v[4 * j], c0, sh.x), fmaf(v[4 * j + 1], c1, sh.y));
        o.y = pack_bf16(fmaf(v[4 * j + 2], c0, sh.x), fmaf(v[4 * j + 3], c1, sh.y));
        __stcg(dst + ((grp >> 1) * 32 + lane) * 2 + (grp & 1), o);
    }
}
__device__ __forceinline__ void sum_partials(float (&v)[36], const uint2* src  , int warp) {
    uint2 t[8][9];
#pragma unroll
    for (int s = 0; s < 8; s++)
#pragma unroll
        for (int j = 0; j < 9; j++) t[s][j] = __ldcg(src + (s * 72 + warp * 9 + j) * 32);
#pragma unroll
    for (int j = 0; j < 9; j++) {
        float a = 0.f, b = 0.f, c = 0.f, d = 0.f;
#pragma unroll
        for (int s = 0; s < 8; s++) {
            a += bf_lo(t[s][j].x);
            b += bf_hi(t[s][j].x);
            c += bf_lo(t[s][j].y);
            d += bf_hi(t[s][j].y);
        }
        v[4 * j] = a;
        v[4 * j + 1] = b;
        v[4 * j + 2] = c;
        v[4 * j + 3] = d;
    }
}
__device__ __forceinline__ void load_frags(uint32_t (&a)[144], const uint4* src  ) {
#pragma unroll
    for (int k = 0; k < 36; k++) {
        uint4 t = __ldcg(src + k * 32);
        a[4 * k] = t.x;
        a[4 * k + 1] = t.y;
        a[4 * k + 2] = t.z;
        a[4 * k + 3] = t.w;
    }
}

__device__ __forceinline__ void mod_block(const uint4 (&w)[5], const float (&sc)[5], int blk, uint32_t red, int warp,
                                          int lane) {
    float acc[8];
#pragma unroll
    for (int e = 0; e < 8; e++) acc[e] = 0.f;
#pragma unroll
    for (int i = 0; i < 5; i++) {
        acc[0] = fmaf(sc[i], bf_lo(w[i].x), acc[0]);
        acc[1] = fmaf(sc[i], bf_hi(w[i].x), acc[1]);
        acc[2] = fmaf(sc[i], bf_lo(w[i].y), acc[2]);
        acc[3] = fmaf(sc[i], bf_hi(w[i].y), acc[3]);
        acc[4] = fmaf(sc[i], bf_lo(w[i].z), acc[4]);
        acc[5] = fmaf(sc[i], bf_hi(w[i].z), acc[5]);
        acc[6] = fmaf(sc[i], bf_lo(w[i].w), acc[6]);
        acc[7] = fmaf(sc[i], bf_hi(w[i].w), acc[7]);
    }
#pragma unroll
    for (int o = 2; o < 32; o <<= 1)
#pragma unroll
        for (int e = 0; e < 8; e++) acc[e] += __shfl_xor_sync(0xffffffffu, acc[e], o);
    if (lane < 2) {
#pragma unroll
        for (int e = 0; e < 8; e++) sts32f(red + (warp * 16 + lane * 8 + e) * 4, acc[e]);
    }
    bar_sync(3, 256);
    if (warp == 0) {
        if (lane < 16) {
            float s = 0.f;
#pragma unroll
            for (int w8 = 0; w8 < 8; w8++) s += lds32f(red + (w8 * 16 + lane) * 4);
            __stcg(&g_mod[blk * 16 + lane], round_bf16(s));
        }
        __syncwarp();
        if (lane == 0) signal_cnt(blk < 72 ? CNT_MODA : CNT_MODB);
    }
}

__global__ void __cluster_dims__(2, 1, 1) __launch_bounds__(384, 1)
    fused_block_kernel(const __grid_constant__ Maps maps, const __nv_bfloat16* __restrict__ x,
                       const __nv_bfloat16* __restrict__ cvec, const __nv_bfloat16* __restrict__ wmod,
                       __nv_bfloat16* __restrict__ out) {
    extern __shared__ uint8_t smem_raw[];
    uint32_t sbase = (smem_u32(smem_raw) + 1023u) & ~1023u;
    asm volatile("" : "+r"(sbase));
    const int b = blockIdx.x;
    const int rank = b & 1;
    const int mt = ((b >> 1) & 7) * 2 + rank;
    const int g = b >> 4;
    const int warp = __shfl_sync(0xffffffffu, threadIdx.x >> 5, 0);
    const int lane = threadIdx.x & 31;

    if (threadIdx.x == 0) {
#pragma unroll
        for (int i = 0; i < 8; i++) {
            mbar_init(sbase + OFF_FULL + i * 8, 1);
            mbar_init(sbase + OFF_EMPTY + i * 8, 4);
        }
        asm volatile("fence.mbarrier_init.release.cluster;" ::: "memory");
    }
    __syncwarp();
    asm volatile("barrier.cluster.arrive.aligned;\nbarrier.cluster.wait.aligned;" ::: "memory");

    if (warp >= 8) {
        asm volatile("setmaxnreg.dec.sync.aligned.u32 24;");
        if (warp == 8 && lane == 0) {
            uint32_t slot = 0, phase = 1;
            const uint32_t dst0 = sbase + rank * BOX_BYTES;
            auto acquire = [&](uint32_t bytes) {
                mbar_wait(sbase + OFF_EMPTY + slot * 8, phase);
                mbar_expect_tx(sbase + OFF_FULL + slot * 8, bytes);
            };
            auto adv8 = [&]() {
                if (++slot == 8) {
                    slot = 0;
                    phase ^= 1;
                }
            };
            auto adv6 = [&]() {
                if (++slot == 6) {
                    slot = 0;
                    phase ^= 1;
                }
            };
#pragma unroll 1
            for (int hq = 0; hq < 4; hq++) {
                const int col = (g * 4 + ((hq + 1) & 3)) * 128 + rank * 64;
#pragma unroll 1
                for (int kc = 0; kc < 9; kc++) {
                    acquire(SLOT_BYTES);
                    tma_mc(dst0 + slot * SLOT_BYTES, &maps.wq, col, kc * 64, sbase + OFF_FULL + slot * 8);
                    adv8();
                }
            }
            const int row0 = g * 4 * 2048;
#pragma unroll 1
            for (int t = 0; t <= 64; t++) {
                if (t < 64) {
                    if (t < 3) mbar_wait(sbase + OFF_EMPTY + (slot + 1) * 8, phase);
                    acquire(2 * SLOT_BYTES);
                    const uint32_t bar = sbase + OFF_FULL + slot * 8;
                    tma_mc(dst0 + slot * SLOT_BYTES, &maps.k, 0, row0 + t * 128 + rank * 64, bar);
                    tma_mc(dst0 + (slot + 1) * SLOT_BYTES, &maps.k, 64, row0 + t * 128 + rank * 64, bar);
                    adv8();
                    adv8();
                }
                if (t > 0) {
                    if (t == 1) mbar_wait(sbase + OFF_EMPTY + (slot + 1) * 8, phase);
                    acquire(2 * SLOT_BYTES);
                    const uint32_t bar = sbase + OFF_FULL + slot * 8;
                    tma_mc(dst0 + slot * SLOT_BYTES, &maps.v, rank * 64, row0 + (t - 1) * 128, bar);
                    tma_mc(dst0 + (slot + 1) * SLOT_BYTES, &maps.v, rank * 64, row0 + (t - 1) * 128 + 64, bar);
                    adv8();
                    adv8();
                }
            }
#pragma unroll 1
            for (int p = 0; p < 4; p++)
#pragma unroll 1
                for (int kc = 0; kc < 8; kc++) {
                    acquire(SLOT_BYTES);
                    tma_mc(dst0 + slot * SLOT_BYTES, &maps.wo, p * 128 + rank * 64, g * 512 + kc * 64,
                           sbase + OFF_FULL + slot * 8);
                    adv8();
                }
#pragma unroll 1
            for (int kc = 0; kc < 4; kc++) {
                acquire(SLOT_BYTES);
                tma_mc(dst0 + slot * SLOT_BYTES, &maps.wo, 512, g * 512 + kc * 128 + rank * 64,
                       sbase + OFF_FULL + slot * 8);
                adv8();
            }
            const CUtensorMap* mg = rank ? &maps.wu : &maps.wg;
#pragma unroll 1
            for (int ch = 0; ch < 9; ch++)
#pragma unroll 1
                for (int kc = 0; kc < 9; kc++) {
                    acquire(SLOT_BYTES);
                    tma_mc(dst0 + slot * SLOT_BYTES, mg, g * 576 + ch * 64, kc * 64, sbase + OFF_FULL + slot * 8);
                    adv6();
                }
#pragma unroll 1
            for (int p = 0; p < 4; p++)
#pragma unroll 1
                for (int kc = 0; kc < 9; kc++) {
                    acquire(SLOT_BYTES);
                    tma_mc(dst0 + slot * SLOT_BYTES, &maps.wd, p * 128 + rank * 64, g * 576 + kc * 64,
                           sbase + OFF_FULL + slot * 8);
                    adv6();
                }
#pragma unroll 1
            for (int kc = 0; kc < 5; kc++) {
                acquire(kc < 4 ? SLOT_BYTES : BOX_BYTES);
                if (kc < 4 || rank == 0)
                    tma_mc(dst0 + slot * SLOT_BYTES, &maps.wd, 512, g * 576 + kc * 128 + rank * 64,
                           sbase + OFF_FULL + slot * 8);
                adv6();
            }
        }
    } else {
        asm volatile("setmaxnreg.inc.sync.aligned.u32 240;");
        const int wg = warp >> 2;
        const int tid = threadIdx.x;
        Ctx cx;
        cx.sbase = sbase;
        cx.rel_cta = (lane == 0 && (warp & 3) < 2) ? (warp & 3) : 2;
        const uint32_t red = sbase + OFF_RED;
        const int own = mt * 8 + g;
        const int orow = own * 16 + (lane >> 2);
        const int wown = mt * 8 + warp;
        Ring ring{0u, 0u};
        uint32_t a[144];

        {
            uint4 w1[5], w2[5];
            float sc[5];
            const int half = tid & 1, r0 = tid >> 1;
            const bool second = b < 88;
#pragma unroll
            for (int i = 0; i < 5; i++) {
                const int row = r0 + 128 * i;
                const bool ok = row < DM;
                const uint4* p = reinterpret_cast<const uint4*>(wmod + (size_t)(ok ? row : 0) * (6 * DM) + half * 8);
                w1[i] = __ldg(p + b * 2);
                w2[i] = second ? __ldg(p + (128 + b) * 2) : make_uint4(0, 0, 0, 0);
                const float cv = __bfloat162float(cvec[ok ? row : 0]);
                sc[i] = ok ? round_bf16(cv / (1.f + __expf(-cv))) : 0.f;
            }
            float v[36];
#pragma unroll
            for (int j = 0; j < 9; j++) {
                const int col = (warp * 9 + j) * 8 + (lane & 3) * 2;
                const uint32_t u0 = __ldg(reinterpret_cast<const uint32_t*>(x + (size_t)orow * DM + col));
                const uint32_t u1 = __ldg(reinterpret_cast<const uint32_t*>(x + (size_t)(orow + 8) * DM + col));
                v[4 * j] = bf_lo(u0);
                v[4 * j + 1] = bf_hi(u0);
                v[4 * j + 2] = bf_lo(u1);
                v[4 * j + 3] = bf_hi(u1);
            }
            mod_block(w1, sc, b, red + 1024, warp, lane);
            layernorm_rows(v, red, warp, lane);
            if (second) mod_block(w2, sc, 128 + b, red + 1024, warp, lane);
            wait_cnt(CNT_MODA, 72);
            modulate_store(v, g_mod, g_mod + DM, g_h1 + (size_t)own * 36 * 32, warp, lane);
            __syncwarp();
            if (lane == 0) signal_cnt(CNT_H1 + own);
        }

        const uint32_t spill = sbase + 8 * SLOT_BYTES + wg * SLOT_BYTES + (tid & 127) * 16;
        uint32_t q[32];
        wait_cnt(CNT_H1 + wown, 8);
        load_frags(a, g_h1 + (size_t)wown * 36 * 32 + lane);
        {
            float d[64];
#pragma unroll 1
            for (int hq = 0;; hq++) {
                gemm_n128<9, 8>(d, a, cx, ring);
                if (hq == 3) break;
#pragma unroll
                for (int v = 0; v < 8; v++)
                    sts128(spill + hq * 32768 + v * 2048, pack_bf16(d[8 * v], d[8 * v + 1]),
                           pack_bf16(d[8 * v + 2], d[8 * v + 3]), pack_bf16(d[8 * v + 4], d[8 * v + 5]),
                           pack_bf16(d[8 * v + 6], d[8 * v + 7]));
            }
#pragma unroll
            for (int i = 0; i < 32; i++) q[i] = pack_bf16(d[2 * i], d[2 * i + 1]);
        }

        {
            float o[64], d[64];
            uint32_t p[32];
#pragma unroll
            for (int i = 0; i < 64; i++) o[i] = 0.f;
            const float cs = 0.08838834764831845f * 1.4426950408889634f;
            float m0, m1, l0, l1;
            const uint64_t dbase = desc_of(sbase);
            const uint64_t dbk = dbase - (511u << 16);
            const int my_bar = 1 + wg, other_bar = 2 - wg;

            cx.wait_full(4, 0);
            if (wg == 1) bar_sync(my_bar, 256);
            wg_fence();
#pragma unroll
            for (int k = 0; k < 8; k++) {
                if (k == 0)
                    wgmma_n128_z<0>(d, q[0], q[1], q[2], q[3], dbk + 4 * 1024);
                else
                    wgmma_n128<0>(d, q[4 * k], q[4 * k + 1], q[4 * k + 2], q[4 * k + 3],
                                  dbk + (4 + (k >> 2)) * 1024 + (k & 3) * 2, 1);
            }
            wg_commit();
            bar_arrive(other_bar, 256);
            wg_wait<0>();
            pin(d);
            cx.release(4);
            {
                float x0 = fmaxf(d[0], d[1]), x1 = fmaxf(d[2], d[3]);
#pragma unroll
                for (int i = 1; i < 16; i++) {
                    x0 = fmaxf(x0, fmaxf(d[4 * i], d[4 * i + 1]));
                    x1 = fmaxf(x1, fmaxf(d[4 * i + 2], d[4 * i + 3]));
                }
                x0 = fmaxf(x0, __shfl_xor_sync(0xffffffffu, x0, 1));
                x1 = fmaxf(x1, __shfl_xor_sync(0xffffffffu, x1, 1));
                m0 = fmaxf(x0, __shfl_xor_sync(0xffffffffu, x0, 2));
                m1 = fmaxf(x1, __shfl_xor_sync(0xffffffffu, x1, 2));
                const float n0 = -m0 * cs, n1 = -m1 * cs;
                l0 = 0.f;
                l1 = 0.f;
#pragma unroll
                for (int i = 0; i < 16; i++) {
                    const float e0 = ex2(fmaf(d[4 * i], cs, n0)), e1 = ex2(fmaf(d[4 * i + 1], cs, n0));
                    const float e2 = ex2(fmaf(d[4 * i + 2], cs, n1)), e3 = ex2(fmaf(d[4 * i + 3], cs, n1));
                    l0 += e0 + e1;
                    l1 += e2 + e3;
                    p[2 * i] = pack_bf16(e0, e1);
                    p[2 * i + 1] = pack_bf16(e2, e3);
                }
            }
#pragma unroll 1
            for (int t = 1; t < 64; t++) {
                const int j = t & 15;
                const uint32_t ks = 2 + 4 * (t & 1), vs = 4 - 4 * (t & 1);
                const uint32_t kph = ((34 + 4 * t) >> 3) & 1, vph = ((36 + 4 * t) >> 3) & 1;
                if (j == 0) {
                    const uint32_t src = spill + ((t >> 4) - 1) * 32768;
#pragma unroll
                    for (int v = 0; v < 8; v++) lds128(src + v * 2048, q[4 * v], q[4 * v + 1], q[4 * v + 2], q[4 * v + 3]);
                }
                cx.wait_full(ks, kph);
                bar_sync(my_bar, 256);
                wg_fence();
                const uint64_t dk = dbk + ks * 1024, dv = dbase + vs * 1024;
#pragma unroll
                for (int k = 0; k < 8; k++) {
                    if (k == 0)
                        wgmma_n128_z<0>(d, q[0], q[1], q[2], q[3], dk);
                    else
                        wgmma_n128<0>(d, q[4 * k], q[4 * k + 1], q[4 * k + 2], q[4 * k + 3],
                                      dk + (k >> 2) * 1024 + (k & 3) * 2, 1);
                }
                wg_commit();
                cx.wait_full(vs, vph);
                wg_fence();
#pragma unroll
                for (int k = 0; k < 8; k++)
                    wgmma_n128<1>(o, p[4 * k], p[4 * k + 1], p[4 * k + 2], p[4 * k + 3],
                                  dv + (k >> 2) * 1024 + (k & 3) * 128, k != 0 ? 1 : (j != 1));
                wg_commit();
                bar_arrive(other_bar, 256);
                wg_wait<1>();
                pin(d);
                cx.release(ks);

                float x0 = fmaxf(d[0], d[1]), x1 = fmaxf(d[2], d[3]);
#pragma unroll
                for (int i = 1; i < 16; i++) {
                    x0 = fmaxf(x0, fmaxf(d[4 * i], d[4 * i + 1]));
                    x1 = fmaxf(x1, fmaxf(d[4 * i + 2], d[4 * i + 3]));
                }
                x0 = fmaxf(x0, __shfl_xor_sync(0xffffffffu, x0, 1));
                x1 = fmaxf(x1, __shfl_xor_sync(0xffffffffu, x1, 1));
                x0 = fmaxf(x0, __shfl_xor_sync(0xffffffffu, x0, 2));
                x1 = fmaxf(x1, __shfl_xor_sync(0xffffffffu, x1, 2));
                const float lp0 = l0, lp1 = l1;
                float al0, al1;
                if (j == 0) {
                    m0 = x0;
                    m1 = x1;
                    al0 = 0.f;
                    al1 = 0.f;
                } else {
                    x0 = fmaxf(x0, m0);
                    x1 = fmaxf(x1, m1);
                    al0 = ex2((m0 - x0) * cs);
                    al1 = ex2((m1 - x1) * cs);
                    m0 = x0;
                    m1 = x1;
                }
                const float n0 = -m0 * cs, n1 = -m1 * cs;
                float s0 = 0.f, s1 = 0.f;
#pragma unroll
                for (int i = 0; i < 16; i++) {
                    d[4 * i] = ex2(fmaf(d[4 * i], cs, n0));
                    d[4 * i + 1] = ex2(fmaf(d[4 * i + 1], cs, n0));
                    d[4 * i + 2] = ex2(fmaf(d[4 * i + 2], cs, n1));
                    d[4 * i + 3] = ex2(fmaf(d[4 * i + 3], cs, n1));
                    s0 += d[4 * i] + d[4 * i + 1];
                    s1 += d[4 * i + 2] + d[4 * i + 3];
                }
                l0 = fmaf(l0, al0, s0);
                l1 = fmaf(l1, al1, s1);
                pin(d);
                wg_wait<0>();
                pin(o);
                pin(p);
                cx.release(vs);
                if (j == 0) {
                    float t0 = lp0 + __shfl_xor_sync(0xffffffffu, lp0, 1), t1 = lp1 + __shfl_xor_sync(0xffffffffu, lp1, 1);
                    t0 += __shfl_xor_sync(0xffffffffu, t0, 2);
                    t1 += __shfl_xor_sync(0xffffffffu, t1, 2);
                    const float i0 = 1.f / t0, i1 = 1.f / t1;
                    const uint32_t dst = spill + ((t >> 4) - 1) * 32768;
#pragma unroll
                    for (int v = 0; v < 8; v++)
                        sts128(dst + v * 2048, pack_bf16(o[8 * v] * i0, o[8 * v + 1] * i0),
                               pack_bf16(o[8 * v + 2] * i1, o[8 * v + 3] * i1), pack_bf16(o[8 * v + 4] * i0, o[8 * v + 5] * i0),
                               pack_bf16(o[8 * v + 6] * i1, o[8 * v + 7] * i1));
                } else {
#pragma unroll
                    for (int i = 0; i < 16; i++) {
                        o[4 * i] *= al0;
                        o[4 * i + 1] *= al0;
                        o[4 * i + 2] *= al1;
                        o[4 * i + 3] *= al1;
                    }
                }
#pragma unroll
                for (int i = 0; i < 32; i++) p[i] = pack_bf16(d[2 * i], d[2 * i + 1]);
            }
            cx.wait_full(2, 0);
            bar_sync(my_bar, 256);
            wg_fence();
#pragma unroll
            for (int k = 0; k < 8; k++)
                wgmma_n128<1>(o, p[4 * k], p[4 * k + 1], p[4 * k + 2], p[4 * k + 3],
                              dbase + (2 + (k >> 2)) * 1024 + (k & 3) * 128, 1);
            wg_commit();
            if (wg == 0) bar_arrive(other_bar, 256);
            float t0 = l0 + __shfl_xor_sync(0xffffffffu, l0, 1), t1 = l1 + __shfl_xor_sync(0xffffffffu, l1, 1);
            t0 += __shfl_xor_sync(0xffffffffu, t0, 2);
            t1 += __shfl_xor_sync(0xffffffffu, t1, 2);
            const float i0 = 1.f / t0, i1 = 1.f / t1;
            wg_wait<0>();
            pin(o);
            cx.release(2);
#pragma unroll
            for (int i = 0; i < 16; i++) {
                a[96 + 2 * i] = pack_bf16(o[4 * i] * i0, o[4 * i + 1] * i0);
                a[96 + 2 * i + 1] = pack_bf16(o[4 * i + 2] * i1, o[4 * i + 3] * i1);
            }
#pragma unroll
            for (int v = 0; v < 24; v++)
                lds128(spill + (v >> 3) * 32768 + (v & 7) * 2048, a[4 * v], a[4 * v + 1], a[4 * v + 2], a[4 * v + 3]);
        }

        uint2* part_dst = g_part + ((size_t)wown * 8 + g) * 72 * 32 + lane;
        const uint2* part_src = g_part + (size_t)own * 8 * 72 * 32 + lane;
        float4* x2buf = g_x2 + (size_t)b * 9 * 256 + tid;
        ring.slot = 4;
        ring.phase = 0;
        proj_partials<8, 8>(a, cx, ring, part_dst);
        __syncwarp();
        if (lane == 0) signal_cnt(CNT_P1 + wown);

        {
            float v[36];
            uint32_t xs[18];
#pragma unroll
            for (int j = 0; j < 9; j++) {
                const int col = (warp * 9 + j) * 8 + (lane & 3) * 2;
                xs[2 * j] = __ldg(reinterpret_cast<const uint32_t*>(x + (size_t)orow * DM + col));
                xs[2 * j + 1] = __ldg(reinterpret_cast<const uint32_t*>(x + (size_t)(orow + 8) * DM + col));
            }
            wait_cnt(CNT_MODB, 144);
            wait_cnt(CNT_P1 + own, 8);
            sum_partials(v, part_src, warp);
#pragma unroll
            for (int j = 0; j < 9; j++) {
                const int col = (warp * 9 + j) * 8 + (lane & 3) * 2;
                const float2 ga = __ldcg(reinterpret_cast<const float2*>(g_mod + 2 * DM + col));
                v[4 * j] = fmaf(ga.x, v[4 * j], bf_lo(xs[2 * j]));
                v[4 * j + 1] = fmaf(ga.y, v[4 * j + 1], bf_hi(xs[2 * j]));
                v[4 * j + 2] = fmaf(ga.x, v[4 * j + 2], bf_lo(xs[2 * j + 1]));
                v[4 * j + 3] = fmaf(ga.y, v[4 * j + 3], bf_hi(xs[2 * j + 1]));
                __stcg(x2buf + j * 256, make_float4(v[4 * j], v[4 * j + 1], v[4 * j + 2], v[4 * j + 3]));
            }
            layernorm_rows(v, red, warp, lane);
            modulate_store(v, g_mod + 3 * DM, g_mod + 4 * DM, g_h2 + (size_t)own * 36 * 32, warp, lane);
            __syncwarp();
            if (lane == 0) signal_cnt(CNT_H2 + own);
        }

        wait_cnt(CNT_H2 + wown, 8);
        load_frags(a, g_h2 + (size_t)wown * 36 * 32 + lane);
        ring.slot = 0;
        ring.phase = 1;
        const uint32_t hsp = sbase + 6 * SLOT_BYTES + wg * BOX_BYTES + (tid & 127) * 16;
        {
            float d[64];
#pragma unroll 1
            for (int ch = 0;; ch++) {
                gemm_n128<9, 6>(d, a, cx, ring);
#pragma unroll
                for (int i = 0; i < 32; i++) {
                    const float gv = d[i];
                    const float k1 = -2.f * 0.7978845608028654f * 1.4426950408889634f;
                    const float zz = gv * fmaf(gv * gv, k1 * 0.044715f, k1);
                    d[i] = gv * rcp(1.f + ex2(zz)) * d[32 + i];
                }
                if (ch == 8) break;
                const uint32_t dst = hsp + ((ch + 2) & 7) * SLOT_BYTES;
#pragma unroll
                for (int v = 0; v < 4; v++)
                    sts128(dst + v * 2048, pack_bf16(d[8 * v], d[8 * v + 1]), pack_bf16(d[8 * v + 2], d[8 * v + 3]),
                           pack_bf16(d[8 * v + 4], d[8 * v + 5]), pack_bf16(d[8 * v + 6], d[8 * v + 7]));
            }
#pragma unroll
            for (int i = 0; i < 16; i++) a[128 + i] = pack_bf16(d[2 * i], d[2 * i + 1]);
        }
#pragma unroll
        for (int v = 0; v < 32; v++)
            lds128(hsp + (((v >> 2) + 2) & 7) * SLOT_BYTES + (v & 3) * 2048, a[4 * v], a[4 * v + 1], a[4 * v + 2],
                   a[4 * v + 3]);

        proj_partials<9, 6>(a, cx, ring, part_dst);
        asm volatile("barrier.cluster.arrive.relaxed.aligned;" ::: "memory");
        __syncwarp();
        if (lane == 0) signal_cnt(CNT_P2 + wown);

        {
            float v[36];
            float4 xr[9];
            float2 gb[9];
#pragma unroll
            for (int j = 0; j < 9; j++) {
                xr[j] = __ldcg(x2buf + j * 256);
                gb[j] = __ldcg(reinterpret_cast<const float2*>(g_mod + 5 * DM + (warp * 9 + j) * 8 + (lane & 3) * 2));
            }
            wait_cnt(CNT_P2 + own, 8);
            sum_partials(v, part_src, warp);
#pragma unroll
            for (int j = 0; j < 9; j++) {
                const int col = (warp * 9 + j) * 8 + (lane & 3) * 2;
                *reinterpret_cast<uint32_t*>(out + (size_t)orow * DM + col) =
                    pack_bf16(fmaf(gb[j].x, v[4 * j], xr[j].x), fmaf(gb[j].y, v[4 * j + 1], xr[j].y));
                *reinterpret_cast<uint32_t*>(out + (size_t)(orow + 8) * DM + col) =
                    pack_bf16(fmaf(gb[j].x, v[4 * j + 2], xr[j].z), fmaf(gb[j].y, v[4 * j + 3], xr[j].w));
            }
        }
        bar_sync(3, 256);
        if (warp == 0) {
            unsigned old = 0;
            if (lane == 0)
                asm volatile("atom.acq_rel.gpu.global.add.u32 %0, [%1], 1;" : "=r"(old) : "l"(&g_cnt[CNT_DONE * 32]) : "memory");
            old = __shfl_sync(0xffffffffu, old, 0);
            if (old == 127) {
                for (int i = lane; i < CNT_TOTAL; i += 32) g_cnt[i * 32] = 0;
            }
        }
        asm volatile("barrier.cluster.wait.aligned;" ::: "memory");
    }
}

typedef CUresult (*EncodeFn)(CUtensorMap*, CUtensorMapDataType, cuuint32_t, void*, const cuuint64_t*, const cuuint64_t*,
                             const cuuint32_t*, const cuuint32_t*, CUtensorMapInterleave, CUtensorMapSwizzle,
                             CUtensorMapL2promotion, CUtensorMapFloatOOBfill);

void make_map(EncodeFn enc, CUtensorMap* m, const void* ptr, uint64_t rows, uint64_t cols) {
    cuuint64_t gdim[2] = {cols, rows};
    cuuint64_t gstr[1] = {cols * 2};
    cuuint32_t box[2] = {64, 64};
    cuuint32_t estr[2] = {1, 1};
    enc(m, CU_TENSOR_MAP_DATA_TYPE_BFLOAT16, 2, const_cast<void*>(ptr), gdim, gstr, box, estr,
        CU_TENSOR_MAP_INTERLEAVE_NONE, CU_TENSOR_MAP_SWIZZLE_128B, CU_TENSOR_MAP_L2_PROMOTION_L2_128B,
        CU_TENSOR_MAP_FLOAT_OOB_FILL_NONE);
}

}

extern "C" void kernel_launch(void* const* d_in, const int* in_sizes, int n_in, void* d_out, int out_size) {
    (void)in_sizes;
    (void)n_in;
    (void)out_size;
    void* fn = nullptr;
    cudaDriverEntryPointQueryResult qr;
    cudaGetDriverEntryPoint("cuTensorMapEncodeTiled", &fn, cudaEnableDefault, &qr);
    EncodeFn enc = (EncodeFn)fn;
    Maps maps;
    make_map(enc, &maps.k, d_in[1], 32 * 2048, 128);
    make_map(enc, &maps.v, d_in[2], 32 * 2048, 128);
    make_map(enc, &maps.wq, d_in[3], 576, 4096);
    make_map(enc, &maps.wo, d_in[4], 4096, 576);
    make_map(enc, &maps.wg, d_in[6], 576, 4608);
    make_map(enc, &maps.wu, d_in[7], 576, 4608);
    make_map(enc, &maps.wd, d_in[8], 4608, 576);
    cudaFuncSetAttribute(fused_block_kernel, cudaFuncAttributeMaxDynamicSharedMemorySize, SMEM_BYTES);
    fused_block_kernel<<<128, 384, SMEM_BYTES>>>(maps, (const __nv_bfloat16*)d_in[0], (const __nv_bfloat16*)d_in[9],
                                                 (const __nv_bfloat16*)d_in[10], (__nv_bfloat16*)d_out);
}
```

```cpp
#include <cuda_runtime.h>
#include <cuda_bf16.h>
#include <cuda.h>
#include <stdint.h>

namespace {

constexpr int DM = 576;
constexpr int SLOT_BYTES = 16384;
constexpr int BOX_BYTES = 8192;
constexpr int NUNITS = 14;
constexpr int SMEM_TAIL = NUNITS * SLOT_BYTES;
constexpr int SMEM_BYTES = SMEM_TAIL + 2048 + 1024;
constexpr int OFF_FULL = SMEM_TAIL;
constexpr int OFF_EMPTY = SMEM_TAIL + 64;
constexpr int OFF_RED = SMEM_TAIL + 128;

constexpr int CNT_DONE = 2, CNT_H1 = 8, CNT_P1 = 8 + 128, CNT_H2 = 8 + 256,
              CNT_P2 = 8 + 384, CNT_TOTAL = 8 + 512;

__device__ __align__(16) uint32_t g_mod[6 * DM];
__device__ uint4 g_h1[128 * 36 * 32];
__device__ uint4 g_h2[128 * 36 * 32];
__device__ uint2 g_part[128 * 8 * 72 * 32];
__device__ float4 g_x2[128 * 9 * 256];
__device__ unsigned g_cnt[CNT_TOTAL * 32];

#define PROF(i)
#define PROFG(i)

struct Maps {
    CUtensorMap k, v, wq, wo, wg, wu, wd;
};

__device__ __forceinline__ uint32_t smem_u32(const void* p) { return (uint32_t)__cvta_generic_to_shared(p); }
__device__ __forceinline__ void mbar_init(uint32_t a, uint32_t c) {
    asm volatile("mbarrier.init.shared::cta.b64 [%0], %1;" ::"r"(a), "r"(c) : "memory");
}
__device__ __forceinline__ void mbar_expect_tx(uint32_t a, uint32_t bytes) {
    asm volatile("mbarrier.arrive.expect_tx.shared::cta.b64 _, [%0], %1;" ::"r"(a), "r"(bytes) : "memory");
}
__device__ __forceinline__ bool mbar_try(uint32_t a, uint32_t ph) {
    uint32_t ok;
    asm volatile(
        "{\n.reg .pred p;\nmbarrier.try_wait.parity.shared::cta.b64 p, [%1], %2;\nselp.u32 %0, 1, 0, p;\n}"
        : "=r"(ok)
        : "r"(a), "r"(ph)
        : "memory");
    return ok != 0;
}
__device__ __forceinline__ uint32_t clk32() {
    uint32_t c;
    asm volatile("mov.u32 %0, %%clock;" : "=r"(c));
    return c;
}
constexpr uint32_t WAIT_LIMIT = 1u << 30;
__device__ __forceinline__ void mbar_wait(uint32_t a, uint32_t ph) {
    if (mbar_try(a, ph)) return;
    uint32_t t0 = clk32();
    while (!mbar_try(a, ph)) {
        if (clk32() - t0 > WAIT_LIMIT) break;
    }
}
__device__ __forceinline__ void mbar_arrive_cluster(uint32_t a, uint32_t cta) {
    asm volatile(
        "{\n.reg .b32 ra;\nmapa.shared::cluster.u32 ra, %0, %1;\nmbarrier.arrive.shared::cluster.b64 _, [ra];\n}" ::"r"(a),
        "r"(cta)
        : "memory");
}
__device__ __forceinline__ void tma_mc(uint32_t dst, const CUtensorMap* m, int c0, int c1, uint32_t bar) {
    asm volatile(
        "cp.async.bulk.tensor.2d.shared::cluster.global.mbarrier::complete_tx::bytes.multicast::cluster"
        " [%0], [%1, {%3, %4}], [%2], %5;" ::"r"(dst),
        "l"(m), "r"(bar), "r"(c0), "r"(c1), "h"((uint16_t)3)
        : "memory");
}
__device__ __forceinline__ void bar_sync(int id, int n) { asm volatile("bar.sync %0, %1;" ::"r"(id), "r"(n) : "memory"); }
__device__ __forceinline__ void bar_arrive(int id, int n) {
    asm volatile("bar.arrive %0, %1;" ::"r"(id), "r"(n) : "memory");
}
__device__ __forceinline__ void wg_fence() { asm volatile("wgmma.fence.sync.aligned;" ::: "memory"); }
__device__ __forceinline__ void wg_commit() { asm volatile("wgmma.commit_group.sync.aligned;" ::: "memory"); }
template <int N>
__device__ __forceinline__ void wg_wait() {
    asm volatile("wgmma.wait_group.sync.aligned %0;" ::"n"(N) : "memory");
}
template <int N>
__device__ __forceinline__ void pin(float (&d)[N]) {
#pragma unroll
    for (int i = 0; i < N; i++) asm volatile("" : "+f"(d[i])::"memory");
}
template <int N>
__device__ __forceinline__ void pin(uint32_t (&d)[N]) {
#pragma unroll
    for (int i = 0; i < N; i++) asm volatile("" : "+r"(d[i])::"memory");
}
__device__ __forceinline__ uint32_t pack_bf16(float lo, float hi) {
    uint32_t r;
    asm("cvt.rn.bf16x2.f32 %0, %1, %2;" : "=r"(r) : "f"(hi), "f"(lo));
    return r;
}
__device__ __forceinline__ float bf_lo(uint32_t v) { return __uint_as_float(v << 16); }
__device__ __forceinline__ float bf_hi(uint32_t v) { return __uint_as_float(v & 0xffff0000u); }
__device__ __forceinline__ float round_bf16(float v) { return __bfloat162float(__float2bfloat16_rn(v)); }
__device__ __forceinline__ float ex2(float x) {
    float y;
    asm("ex2.approx.ftz.f32 %0, %1;" : "=f"(y) : "f"(x));
    return y;
}
__device__ __forceinline__ float rcp(float x) {
    float y;
    asm("rcp.approx.ftz.f32 %0, %1;" : "=f"(y) : "f"(x));
    return y;
}
__device__ __forceinline__ void sts128(uint32_t a, uint32_t x, uint32_t y, uint32_t z, uint32_t w) {
    asm volatile("st.shared.v4.b32 [%0], {%1,%2,%3,%4};" ::"r"(a), "r"(x), "r"(y), "r"(z), "r"(w) : "memory");
}
__device__ __forceinline__ void lds128(uint32_t a, uint32_t& x, uint32_t& y, uint32_t& z, uint32_t& w) {
    asm volatile("ld.shared.v4.b32 {%0,%1,%2,%3}, [%4];" : "=r"(x), "=r"(y), "=r"(z), "=r"(w) : "r"(a) : "memory");
}
__device__ __forceinline__ void sts32f(uint32_t a, float v) {
    asm volatile("st.shared.f32 [%0], %1;" ::"r"(a), "f"(v) : "memory");
}
__device__ __forceinline__ float lds32f(uint32_t a) {
    float v;
    asm volatile("ld.shared.f32 %0, [%1];" : "=f"(v) : "r"(a) : "memory");
    return v;
}
__device__ __forceinline__ void signal_cnt(int idx) {
    asm volatile("red.release.gpu.global.add.u32 [%0], 1;" ::"l"(&g_cnt[idx * 32]) : "memory");
}
__device__ __forceinline__ void wait_cnt(int idx, unsigned target) {
    if ((threadIdx.x & 31) == 0) {
        uint32_t t0 = clk32();
        while (true) {
            unsigned v;
            asm volatile("ld.acquire.gpu.global.u32 %0, [%1];" : "=r"(v) : "l"(&g_cnt[idx * 32]) : "memory");
            if (v >= target) break;
            if (clk32() - t0 > WAIT_LIMIT) break;
        }
    }
    __syncwarp();
}

#define F8(d, b) \
    "+f"(d[b]), "+f"(d[b + 1]), "+f"(d[b + 2]), "+f"(d[b + 3]), "+f"(d[b + 4]), "+f"(d[b + 5]), "+f"(d[b + 6]), "+f"(d[b + 7])

template <int TB>
__device__ __forceinline__ void wgmma_n128(float (&d)[64], uint32_t a0, uint32_t a1, uint32_t a2, uint32_t a3,
                                           uint64_t db, int sc) {
    asm volatile(
        "{\n.reg .pred p;\nsetp.ne.b32 p, %69, 0;\n"
        "wgmma.mma_async.sync.aligned.m64n128k16.f32.bf16.bf16 "
        "{%0,%1,%2,%3,%4,%5,%6,%7,%8,%9,%10,%11,%12,%13,%14,%15,%16,%17,%18,%19,%20,%21,%22,%23,%24,%25,%26,%27,%28,%29,%30,%31,"
        "%32,%33,%34,%35,%36,%37,%38,%39,%40,%41,%42,%43,%44,%45,%46,%47,%48,%49,%50,%51,%52,%53,%54,%55,%56,%57,%58,%59,%60,%61,%62,%63},"
        "{%64,%65,%66,%67}, %68, p, 1, 1, %70;\n}"
        : F8(d, 0), F8(d, 8), F8(d, 16), F8(d, 24), F8(d, 32), F8(d, 40), F8(d, 48), F8(d, 56)
        : "r"(a0), "r"(a1), "r"(a2), "r"(a3), "l"(db), "r"(sc), "n"(TB));
}
#define O8(d, b) \
    "=f"(d[b]), "=f"(d[b + 1]), "=f"(d[b + 2]), "=f"(d[b + 3]), "=f"(d[b + 4]), "=f"(d[b + 5]), "=f"(d[b + 6]), "=f"(d[b + 7])
template <int TB>
__device__ __forceinline__ void wgmma_n128_z(float (&d)[64], uint32_t a0, uint32_t a1, uint32_t a2, uint32_t a3,
                                             uint64_t db) {
    asm volatile(
        "wgmma.mma_async.sync.aligned.m64n128k16.f32.bf16.bf16 "
        "{%0,%1,%2,%3,%4,%5,%6,%7,%8,%9,%10,%11,%12,%13,%14,%15,%16,%17,%18,%19,%20,%21,%22,%23,%24,%25,%26,%27,%28,%29,%30,%31,"
        "%32,%33,%34,%35,%36,%37,%38,%39,%40,%41,%42,%43,%44,%45,%46,%47,%48,%49,%50,%51,%52,%53,%54,%55,%56,%57,%58,%59,%60,%61,%62,%63},"
        "{%64,%65,%66,%67}, %68, 0, 1, 1, %69;"
        : O8(d, 0), O8(d, 8), O8(d, 16), O8(d, 24), O8(d, 32), O8(d, 40), O8(d, 48), O8(d, 56)
        : "r"(a0), "r"(a1), "r"(a2), "r"(a3), "l"(db), "n"(TB));
}
__device__ __forceinline__ void wgmma_n64_z(float (&d)[32], uint32_t a0, uint32_t a1, uint32_t a2, uint32_t a3,
                                            uint64_t db) {
    asm volatile(
        "wgmma.mma_async.sync.aligned.m64n64k16.f32.bf16.bf16 "
        "{%0,%1,%2,%3,%4,%5,%6,%7,%8,%9,%10,%11,%12,%13,%14,%15,%16,%17,%18,%19,%20,%21,%22,%23,%24,%25,%26,%27,%28,%29,%30,%31},"
        "{%32,%33,%34,%35}, %36, 0, 1, 1, 1;"
        : O8(d, 0), O8(d, 8), O8(d, 16), O8(d, 24)
        : "r"(a0), "r"(a1), "r"(a2), "r"(a3), "l"(db));
}
__device__ __forceinline__ void wgmma_n64(float (&d)[32], uint32_t a0, uint32_t a1, uint32_t a2, uint32_t a3,
                                          uint64_t db, int sc) {
    asm volatile(
        "{\n.reg .pred p;\nsetp.ne.b32 p, %37, 0;\n"
        "wgmma.mma_async.sync.aligned.m64n64k16.f32.bf16.bf16 "
        "{%0,%1,%2,%3,%4,%5,%6,%7,%8,%9,%10,%11,%12,%13,%14,%15,%16,%17,%18,%19,%20,%21,%22,%23,%24,%25,%26,%27,%28,%29,%30,%31},"
        "{%32,%33,%34,%35}, %36, p, 1, 1, 1;\n}"
        : F8(d, 0), F8(d, 8), F8(d, 16), F8(d, 24)
        : "r"(a0), "r"(a1), "r"(a2), "r"(a3), "l"(db), "r"(sc));
}

__device__ __forceinline__ uint64_t desc_of(uint32_t saddr) {
    return (uint64_t)(((saddr >> 4) & 0x3FFFu) | (512u << 16)) | ((uint64_t)(64u | (1u << 30)) << 32);
}

struct Ring {
    uint32_t slot;
    uint32_t phase;
    template <int NS>
    __device__ __forceinline__ void next() {
        if (++slot == NS) {
            slot = 0;
            phase ^= 1;
        }
    }
};

struct Ctx {
    uint32_t sbase;
    uint32_t rel_cta;
    __device__ __forceinline__ void wait_full(uint32_t slot, uint32_t phase) const {
        mbar_wait(sbase + OFF_FULL + slot * 8, phase);
    }
    __device__ __forceinline__ void release(uint32_t slot) const {
        if (rel_cta < 2) mbar_arrive_cluster(sbase + OFF_EMPTY + slot * 8, rel_cta);
    }
};

template <int NK, int NS, int NA>
__device__ __forceinline__ void gemm_n128(float (&d)[64], const uint32_t (&a)[NA], const Ctx& c, Ring& r) {
    uint32_t prev = 0;
#pragma unroll
    for (int s = 0; s < NK; s++) {
        c.wait_full(r.slot, r.phase);
        uint64_t db = desc_of(c.sbase + r.slot * SLOT_BYTES);
        wg_fence();
#pragma unroll
        for (int k = 0; k < 4; k++) {
            if ((s | k) == 0)
                wgmma_n128_z<1>(d, a[0], a[1], a[2], a[3], db);
            else
                wgmma_n128<1>(d, a[s * 16 + k * 4], a[s * 16 + k * 4 + 1], a[s * 16 + k * 4 + 2], a[s * 16 + k * 4 + 3],
                              db + k * 128, 1);
        }
        wg_commit();
        if (s > 0) {
            wg_wait<1>();
            c.release(prev);
        }
        prev = r.slot;
        r.template next<NS>();
    }
    wg_wait<0>();
    c.release(prev);
    pin(d);
}
template <int NKS, int NS, int NA>
__device__ __forceinline__ void gemm_n64(float (&d)[32], const uint32_t (&a)[NA], const Ctx& c, Ring& r) {
    uint32_t prev = 0;
    constexpr int NSL = (NKS + 7) / 8;
#pragma unroll
    for (int s = 0; s < NSL; s++) {
        c.wait_full(r.slot, r.phase);
        uint64_t db = desc_of(c.sbase + r.slot * SLOT_BYTES);
        wg_fence();
#pragma unroll
        for (int k = 0; k < 8; k++) {
            if ((s | k) == 0)
                wgmma_n64_z(d, a[0], a[1], a[2], a[3], db);
            else if (s * 8 + k < NKS)
                wgmma_n64(d, a[s * 32 + k * 4], a[s * 32 + k * 4 + 1], a[s * 32 + k * 4 + 2], a[s * 32 + k * 4 + 3],
                          db + k * 128, 1);
        }
        wg_commit();
        if (s > 0) {
            wg_wait<1>();
            c.release(prev);
        }
        prev = r.slot;
        r.template next<NS>();
    }
    wg_wait<0>();
    c.release(prev);
    pin(d);
}

template <int NK, int NS, int NA>
__device__ __forceinline__ void proj_partials(const uint32_t (&a)[NA], const Ctx& c, Ring& r,
                                              uint2* dst  ) {
#pragma unroll 1
    for (int p = 0; p < 4; p++) {
        float d[64];
        gemm_n128<NK, NS>(d, a, c, r);
#pragma unroll
        for (int j = 0; j < 16; j++)
            __stcg(dst + (p * 16 + j) * 32, make_uint2(pack_bf16(d[4 * j], d[4 * j + 1]), pack_bf16(d[4 * j + 2], d[4 * j + 3])));
    }
    float d[32];
    gemm_n64<NK * 4, NS>(d, a, c, r);
#pragma unroll
    for (int j = 0; j < 8; j++)
        __stcg(dst + (64 + j) * 32, make_uint2(pack_bf16(d[4 * j], d[4 * j + 1]), pack_bf16(d[4 * j + 2], d[4 * j + 3])));
}

__device__ __forceinline__ void row_reduce(float& s0, float& s1, uint32_t red, int warp, int lane) {
    s0 += __shfl_xor_sync(0xffffffffu, s0, 1);
    s1 += __shfl_xor_sync(0xffffffffu, s1, 1);
    s0 += __shfl_xor_sync(0xffffffffu, s0, 2);
    s1 += __shfl_xor_sync(0xffffffffu, s1, 2);
    if ((lane & 3) == 0) {
        sts32f(red + (warp * 16 + (lane >> 2)) * 4, s0);
        sts32f(red + (warp * 16 + 8 + (lane >> 2)) * 4, s1);
    }
    bar_sync(3, 256);
    s0 = 0.f;
    s1 = 0.f;
#pragma unroll
    for (int w = 0; w < 8; w++) {
        s0 += lds32f(red + (w * 16 + (lane >> 2)) * 4);
        s1 += lds32f(red + (w * 16 + 8 + (lane >> 2)) * 4);
    }
}
__device__ __forceinline__ void layernorm_rows(float (&v)[36], uint32_t red, int warp, int lane) {
    float s0 = 0.f, s1 = 0.f;
#pragma unroll
    for (int j = 0; j < 9; j++) {
        s0 += v[4 * j] + v[4 * j + 1];
        s1 += v[4 * j + 2] + v[4 * j + 3];
    }
    row_reduce(s0, s1, red, warp, lane);
    const float m0 = s0 * (1.f / DM), m1 = s1 * (1.f / DM);
    s0 = 0.f;
    s1 = 0.f;
#pragma unroll
    for (int j = 0; j < 9; j++) {
        v[4 * j] -= m0;
        v[4 * j + 1] -= m0;
        v[4 * j + 2] -= m1;
        v[4 * j + 3] -= m1;
        s0 += v[4 * j] * v[4 * j] + v[4 * j + 1] * v[4 * j + 1];
        s1 += v[4 * j + 2] * v[4 * j + 2] + v[4 * j + 3] * v[4 * j + 3];
    }
    row_reduce(s0, s1, red + 512, warp, lane);
    const float r0 = rsqrtf(s0 * (1.f / DM) + 1e-5f), r1 = rsqrtf(s1 * (1.f / DM) + 1e-5f);
#pragma unroll
    for (int j = 0; j < 9; j++) {
        v[4 * j] *= r0;
        v[4 * j + 1] *= r0;
        v[4 * j + 2] *= r1;
        v[4 * j + 3] *= r1;
    }
}
template <int NV>
__device__ __forceinline__ void load_mod(float (&m)[NV][18], const int (&which)[NV], int warp, int lane) {
    const uint32_t t0 = clk32();
    while (true) {
        uint2 u[NV][9];
#pragma unroll
        for (int n = 0; n < NV; n++)
#pragma unroll
            for (int j = 0; j < 9; j++)
                asm volatile("ld.relaxed.gpu.global.v2.u32 {%0,%1}, [%2];"
                             : "=r"(u[n][j].x), "=r"(u[n][j].y)
                             : "l"(g_mod + which[n] * DM + (warp * 9 + j) * 8 + (lane & 3) * 2));
        uint32_t ok = 1;
#pragma unroll
        for (int n = 0; n < NV; n++)
#pragma unroll
            for (int j = 0; j < 9; j++) {
                ok &= u[n][j].x & u[n][j].y;
                m[n][2 * j] = __uint_as_float(u[n][j].x & 0xffff0000u);
                m[n][2 * j + 1] = __uint_as_float(u[n][j].y & 0xffff0000u);
            }
        if (__all_sync(0xffffffffu, ok) || clk32() - t0 > WAIT_LIMIT) break;
    }
}
__device__ __forceinline__ void modulate_store(const float (&v)[36], const float (&shift)[18], const float (&scale)[18],
                                               uint4* hbuf  , int warp, int lane) {
    uint2* dst = reinterpret_cast<uint2*>(hbuf);
#pragma unroll
    for (int j = 0; j < 9; j++) {
        const int grp = warp * 9 + j;
        const float c0 = round_bf16(1.f + scale[2 * j]), c1 = round_bf16(1.f + scale[2 * j + 1]);
        uint2 o;
        o.x = pack_bf16(fmaf(v[4 * j], c0, shift[2 * j]), fmaf(v[4 * j + 1], c1, shift[2 * j + 1]));
        o.y = pack_bf16(fmaf(v[4 * j + 2], c0, shift[2 * j]), fmaf(v[4 * j + 3], c1, shift[2 * j + 1]));
        __stcg(dst + ((grp >> 1) * 32 + lane) * 2 + (grp & 1), o);
    }
}
__device__ __forceinline__ void sum_partials(float (&v)[36], const uint2* src  , int warp) {
    uint2 t[8][9];
#pragma unroll
    for (int s = 0; s < 8; s++)
#pragma unroll
        for (int j = 0; j < 9; j++) t[s][j] = __ldcg(src + (s * 72 + warp * 9 + j) * 32);
#pragma unroll
    for (int j = 0; j < 9; j++) {
        float a = 0.f, b = 0.f, c = 0.f, d = 0.f;
#pragma unroll
        for (int s = 0; s < 8; s++) {
            a += bf_lo(t[s][j].x);
            b += bf_hi(t[s][j].x);
            c += bf_lo(t[s][j].y);
            d += bf_hi(t[s][j].y);
        }
        v[4 * j] = a;
        v[4 * j + 1] = b;
        v[4 * j + 2] = c;
        v[4 * j + 3] = d;
    }
}
__device__ __forceinline__ void load_frags(uint32_t (&a)[144], const uint4* src  ) {
#pragma unroll
    for (int k = 0; k < 36; k++) {
        uint4 t = __ldcg(src + k * 32);
        a[4 * k] = t.x;
        a[4 * k + 1] = t.y;
        a[4 * k + 2] = t.z;
        a[4 * k + 3] = t.w;
    }
}

__device__ __forceinline__ void mod_block(const uint4 (&w)[5], const float (&sc)[5], int blk, uint32_t red, int warp,
                                          int lane) {
    float acc[8];
#pragma unroll
    for (int e = 0; e < 8; e++) acc[e] = 0.f;
#pragma unroll
    for (int i = 0; i < 5; i++) {
        acc[0] = fmaf(sc[i], bf_lo(w[i].x), acc[0]);
        acc[1] = fmaf(sc[i], bf_hi(w[i].x), acc[1]);
        acc[2] = fmaf(sc[i], bf_lo(w[i].y), acc[2]);
        acc[3] = fmaf(sc[i], bf_hi(w[i].y), acc[3]);
        acc[4] = fmaf(sc[i], bf_lo(w[i].z), acc[4]);
        acc[5] = fmaf(sc[i], bf_hi(w[i].z), acc[5]);
        acc[6] = fmaf(sc[i], bf_lo(w[i].w), acc[6]);
        acc[7] = fmaf(sc[i], bf_hi(w[i].w), acc[7]);
    }
#pragma unroll
    for (int o = 2; o < 32; o <<= 1)
#pragma unroll
        for (int e = 0; e < 8; e++) acc[e] += __shfl_xor_sync(0xffffffffu, acc[e], o);
    if (lane < 2) {
#pragma unroll
        for (int e = 0; e < 8; e++) sts32f(red + (warp * 16 + lane * 8 + e) * 4, acc[e]);
    }
    bar_sync(3, 256);
    if (warp == 0 && lane < 16) {
        float s = 0.f;
#pragma unroll
        for (int w8 = 0; w8 < 8; w8++) s += lds32f(red + (w8 * 16 + lane) * 4);
        asm volatile("st.relaxed.gpu.global.u32 [%0], %1;" ::"l"(g_mod + blk * 16 + lane),
                     "r"(__float_as_uint(round_bf16(s)) | 1u)
                     : "memory");
    }
}

__global__ void __cluster_dims__(2, 1, 1) __launch_bounds__(384, 1)
    fused_block_kernel(const __grid_constant__ Maps maps, const __nv_bfloat16* __restrict__ x,
                       const __nv_bfloat16* __restrict__ cvec, const __nv_bfloat16* __restrict__ wmod,
                       __nv_bfloat16* __restrict__ out) {
    extern __shared__ uint8_t smem_raw[];
    uint32_t sbase = (smem_u32(smem_raw) + 1023u) & ~1023u;
    asm volatile("" : "+r"(sbase));
    const int b = blockIdx.x;
    const int rank = b & 1;
    const int mt = ((b >> 1) & 7) * 2 + rank;
    const int g = b >> 4;
    const int warp = __shfl_sync(0xffffffffu, threadIdx.x >> 5, 0);
    const int lane = threadIdx.x & 31;

    if (warp >= 8) {
        asm volatile("setmaxnreg.dec.sync.aligned.u32 24;");
        if (warp == 8 && lane == 0) {
#pragma unroll
            for (int i = 0; i < 8; i++) {
                mbar_init(sbase + OFF_FULL + i * 8, 1);
                mbar_init(sbase + OFF_EMPTY + i * 8, 4);
            }
            asm volatile("fence.mbarrier_init.release.cluster;" ::: "memory");
            asm volatile("barrier.cluster.arrive.relaxed;\nbarrier.cluster.wait;" ::: "memory");
            uint32_t slot = 0, phase = 1;
            const uint32_t dst0 = sbase + rank * BOX_BYTES;
            auto acquire = [&](uint32_t bytes) {
                mbar_wait(sbase + OFF_EMPTY + slot * 8, phase);
                mbar_expect_tx(sbase + OFF_FULL + slot * 8, bytes);
            };
            auto adv8 = [&]() {
                if (++slot == 8) {
                    slot = 0;
                    phase ^= 1;
                }
            };
            auto adv6 = [&]() {
                if (++slot == 6) {
                    slot = 0;
                    phase ^= 1;
                }
            };
#pragma unroll 1
            for (int hq = 0; hq < 4; hq++) {
                const int col = (g * 4 + ((hq + 1) & 3)) * 128 + rank * 64;
#pragma unroll 1
                for (int kc = 0; kc < 9; kc++) {
                    acquire(SLOT_BYTES);
                    tma_mc(dst0 + slot * SLOT_BYTES, &maps.wq, col, kc * 64, sbase + OFF_FULL + slot * 8);
                    adv8();
                }
            }
            const int row0 = g * 4 * 2048;
#pragma unroll 1
            for (int t = 0; t <= 64; t++) {
                if (t < 64) {
                    if (t < 3) mbar_wait(sbase + OFF_EMPTY + (slot + 1) * 8, phase);
                    acquire(2 * SLOT_BYTES);
                    const uint32_t bar = sbase + OFF_FULL + slot * 8;
                    tma_mc(dst0 + slot * SLOT_BYTES, &maps.k, 0, row0 + t * 128 + rank * 64, bar);
                    tma_mc(dst0 + (slot + 1) * SLOT_BYTES, &maps.k, 64, row0 + t * 128 + rank * 64, bar);
                    adv8();
                    adv8();
                }
                if (t > 0) {
                    if (t == 1) mbar_wait(sbase + OFF_EMPTY + (slot + 1) * 8, phase);
                    acquire(2 * SLOT_BYTES);
                    const uint32_t bar = sbase + OFF_FULL + slot * 8;
                    tma_mc(dst0 + slot * SLOT_BYTES, &maps.v, rank * 64, row0 + (t - 1) * 128, bar);
                    tma_mc(dst0 + (slot + 1) * SLOT_BYTES, &maps.v, rank * 64, row0 + (t - 1) * 128 + 64, bar);
                    adv8();
                    adv8();
                }
            }
#pragma unroll 1
            for (int p = 0; p < 4; p++)
#pragma unroll 1
                for (int kc = 0; kc < 8; kc++) {
                    acquire(SLOT_BYTES);
                    tma_mc(dst0 + slot * SLOT_BYTES, &maps.wo, p * 128 + rank * 64, g * 512 + kc * 64,
                           sbase + OFF_FULL + slot * 8);
                    adv8();
                }
#pragma unroll 1
            for (int kc = 0; kc < 4; kc++) {
                acquire(SLOT_BYTES);
                tma_mc(dst0 + slot * SLOT_BYTES, &maps.wo, 512, g * 512 + kc * 128 + rank * 64,
                       sbase + OFF_FULL + slot * 8);
                adv8();
            }
            const CUtensorMap* mg = rank ? &maps.wu : &maps.wg;
#pragma unroll 1
            for (int ch = 0; ch < 9; ch++)
#pragma unroll 1
                for (int kc = 0; kc < 9; kc++) {
                    acquire(SLOT_BYTES);
                    tma_mc(dst0 + slot * SLOT_BYTES, mg, g * 576 + ch * 64, kc * 64, sbase + OFF_FULL + slot * 8);
                    adv6();
                }
#pragma unroll 1
            for (int p = 0; p < 4; p++)
#pragma unroll 1
                for (int kc = 0; kc < 9; kc++) {
                    acquire(SLOT_BYTES);
                    tma_mc(dst0 + slot * SLOT_BYTES, &maps.wd, p * 128 + rank * 64, g * 576 + kc * 64,
                           sbase + OFF_FULL + slot * 8);
                    adv6();
                }
#pragma unroll 1
            for (int kc = 0; kc < 5; kc++) {
                acquire(kc < 4 ? SLOT_BYTES : BOX_BYTES);
                if (kc < 4 || rank == 0)
                    tma_mc(dst0 + slot * SLOT_BYTES, &maps.wd, 512, g * 576 + kc * 128 + rank * 64,
                           sbase + OFF_FULL + slot * 8);
                adv6();
            }
        }
    } else {
        asm volatile("setmaxnreg.inc.sync.aligned.u32 240;");
        const int wg = warp >> 2;
        const int tid = threadIdx.x;
        Ctx cx;
        cx.sbase = sbase;
        cx.rel_cta = (lane == 0 && (warp & 3) < 2) ? (warp & 3) : 2;
        const uint32_t red = sbase + OFF_RED;
        const int own = mt * 8 + g;
        const int orow = own * 16 + (lane >> 2);
        const int wown = mt * 8 + warp;
        Ring ring{0u, 0u};
        uint32_t a[144];

        PROF(0);
        PROFG(30);
        {
            uint4 w1[5], w2[5];
            float sc[5];
            uint32_t xs[18];
            unsigned short cu[5];
            const int half = tid & 1, r0 = tid >> 1;
            const bool second = b < 88;
#pragma unroll
            for (int i = 0; i < 5; i++) {
                const int row = min(r0 + 128 * i, DM - 1);
                cu[i] = __ldg(reinterpret_cast<const unsigned short*>(cvec) + row);
                w1[i] = __ldg(reinterpret_cast<const uint4*>(wmod + (size_t)row * (6 * DM) + half * 8) + b * 2);
            }
#pragma unroll
            for (int j = 0; j < 9; j++) {
                const int col = (warp * 9 + j) * 8 + (lane & 3) * 2;
                xs[2 * j] = __ldg(reinterpret_cast<const uint32_t*>(x + (size_t)orow * DM + col));
                xs[2 * j + 1] = __ldg(reinterpret_cast<const uint32_t*>(x + (size_t)(orow + 8) * DM + col));
            }
#pragma unroll
            for (int i = 0; i < 5; i++) {
                const int row = min(r0 + 128 * i, DM - 1);
                w2[i] = __ldg(reinterpret_cast<const uint4*>(wmod + (size_t)row * (6 * DM) + half * 8) +
                              (second ? 128 + b : b) * 2);
            }
            asm volatile("barrier.cluster.arrive.relaxed.aligned;" ::: "memory");
#pragma unroll
            for (int i = 0; i < 5; i++) {
                const float cv = bf_lo(cu[i]);
                const float sv = round_bf16(cv * rcp(1.f + ex2(-1.4426950408889634f * cv)));
                sc[i] = (r0 + 128 * i < DM) ? sv : 0.f;
            }
            mod_block(w1, sc, b, red + 1024, warp, lane);
            float v[36];
#pragma unroll
            for (int j = 0; j < 9; j++) {
                v[4 * j] = bf_lo(xs[2 * j]);
                v[4 * j + 1] = bf_hi(xs[2 * j]);
                v[4 * j + 2] = bf_lo(xs[2 * j + 1]);
                v[4 * j + 3] = bf_hi(xs[2 * j + 1]);
            }
            layernorm_rows(v, red, warp, lane);
            if (second) mod_block(w2, sc, 128 + b, red + 1024, warp, lane);
            PROF(1);
            float md[2][18];
            const int which[2] = {0, 1};
            load_mod<2>(md, which, warp, lane);
            PROF(2);
            modulate_store(v, md[0], md[1], g_h1 + (size_t)own * 36 * 32, warp, lane);
            __syncwarp();
            if (lane == 0) signal_cnt(CNT_H1 + own);
            asm volatile("barrier.cluster.wait.aligned;" ::: "memory");
        }

        const uint32_t spill = sbase + 8 * SLOT_BYTES + wg * SLOT_BYTES + (tid & 127) * 16;
        uint32_t q[32];
        PROF(3);
        wait_cnt(CNT_H1 + wown, 8);
        PROF(4);
        load_frags(a, g_h1 + (size_t)wown * 36 * 32 + lane);
        {
            float d[64];
#pragma unroll 1
            for (int hq = 0;; hq++) {
                gemm_n128<9, 8>(d, a, cx, ring);
                if (hq == 3) break;
#pragma unroll
                for (int v = 0; v < 8; v++)
                    sts128(spill + hq * 32768 + v * 2048, pack_bf16(d[8 * v], d[8 * v + 1]),
                           pack_bf16(d[8 * v + 2], d[8 * v + 3]), pack_bf16(d[8 * v + 4], d[8 * v + 5]),
                           pack_bf16(d[8 * v + 6], d[8 * v + 7]));
            }
#pragma unroll
            for (int i = 0; i < 32; i++) q[i] = pack_bf16(d[2 * i], d[2 * i + 1]);
        }

        PROF(5);
        {
            float o[64], d[64];
            uint32_t p[32];
#pragma unroll
            for (int i = 0; i < 64; i++) o[i] = 0.f;
            const float cs = 0.08838834764831845f * 1.4426950408889634f;
            float m0, m1, l0, l1;
            const uint64_t dbase = desc_of(sbase);
            const uint64_t dbk = dbase - (511u << 16);
            const int my_bar = 1 + wg, other_bar = 2 - wg;

            cx.wait_full(4, 0);
            if (wg == 1) bar_sync(my_bar, 256);
            wg_fence();
#pragma unroll
            for (int k = 0; k < 8; k++) {
                if (k == 0)
                    wgmma_n128_z<0>(d, q[0], q[1], q[2], q[3], dbk + 4 * 1024);
                else
                    wgmma_n128<0>(d, q[4 * k], q[4 * k + 1], q[4 * k + 2], q[4 * k + 3],
                                  dbk + (4 + (k >> 2)) * 1024 + (k & 3) * 2, 1);
            }
            wg_commit();
            bar_arrive(other_bar, 256);
            wg_wait<0>();
            pin(d);
            cx.release(4);
            {
                float x0 = fmaxf(d[0], d[1]), x1 = fmaxf(d[2], d[3]);
#pragma unroll
                for (int i = 1; i < 16; i++) {
                    x0 = fmaxf(x0, fmaxf(d[4 * i], d[4 * i + 1]));
                    x1 = fmaxf(x1, fmaxf(d[4 * i + 2], d[4 * i + 3]));
                }
                x0 = fmaxf(x0, __shfl_xor_sync(0xffffffffu, x0, 1));
                x1 = fmaxf(x1, __shfl_xor_sync(0xffffffffu, x1, 1));
                m0 = fmaxf(x0, __shfl_xor_sync(0xffffffffu, x0, 2));
                m1 = fmaxf(x1, __shfl_xor_sync(0xffffffffu, x1, 2));
                const float n0 = -m0 * cs, n1 = -m1 * cs;
                l0 = 0.f;
                l1 = 0.f;
#pragma unroll
                for (int i = 0; i < 16; i++) {
                    d[4 * i] = ex2(fmaf(d[4 * i], cs, n0));
                    d[4 * i + 1] = ex2(fmaf(d[4 * i + 1], cs, n0));
                    d[4 * i + 2] = ex2(fmaf(d[4 * i + 2], cs, n1));
                    d[4 * i + 3] = ex2(fmaf(d[4 * i + 3], cs, n1));
                    l0 += d[4 * i] + d[4 * i + 1];
                    l1 += d[4 * i + 2] + d[4 * i + 3];
                }
            }
            float al0 = 0.f, al1 = 0.f, lp0 = 1.f, lp1 = 1.f;
#pragma unroll 1
            for (int t = 1; t < 64; t++) {
                const int j = t & 15;
                const uint32_t ks = 2 + 4 * (t & 1), vs = 4 - 4 * (t & 1);
                const uint32_t kph = ((34 + 4 * t) >> 3) & 1, vph = ((36 + 4 * t) >> 3) & 1;
                wg_wait<0>();
                pin(o);
                if (t > 1) cx.release(4 - vs);
#pragma unroll
                for (int i = 0; i < 32; i++) p[i] = pack_bf16(d[2 * i], d[2 * i + 1]);
                if (j == 0) {
                    const uint32_t src = spill + ((t >> 4) - 1) * 32768;
#pragma unroll
                    for (int v = 0; v < 8; v++) lds128(src + v * 2048, q[4 * v], q[4 * v + 1], q[4 * v + 2], q[4 * v + 3]);
                }
                cx.wait_full(ks, kph);
                bar_sync(my_bar, 256);
                wg_fence();
                const uint64_t dk = dbk + ks * 1024, dv = dbase + vs * 1024;
#pragma unroll
                for (int k = 0; k < 8; k++) {
                    if (k == 0)
                        wgmma_n128_z<0>(d, q[0], q[1], q[2], q[3], dk);
                    else
                        wgmma_n128<0>(d, q[4 * k], q[4 * k + 1], q[4 * k + 2], q[4 * k + 3],
                                      dk + (k >> 2) * 1024 + (k & 3) * 2, 1);
                }
                wg_commit();
                if (j == 1) {
                    if (t > 1) {
                        float t0 = lp0 + __shfl_xor_sync(0xffffffffu, lp0, 1);
                        float t1 = lp1 + __shfl_xor_sync(0xffffffffu, lp1, 1);
                        t0 += __shfl_xor_sync(0xffffffffu, t0, 2);
                        t1 += __shfl_xor_sync(0xffffffffu, t1, 2);
                        const float i0 = rcp(t0), i1 = rcp(t1);
                        const uint32_t dst = spill + ((t >> 4) - 1) * 32768;
#pragma unroll
                        for (int v = 0; v < 8; v++)
                            sts128(dst + v * 2048, pack_bf16(o[8 * v] * i0, o[8 * v + 1] * i0),
                                   pack_bf16(o[8 * v + 2] * i1, o[8 * v + 3] * i1),
                                   pack_bf16(o[8 * v + 4] * i0, o[8 * v + 5] * i0),
                                   pack_bf16(o[8 * v + 6] * i1, o[8 * v + 7] * i1));
                    }
                } else {
#pragma unroll
                    for (int i = 0; i < 16; i++) {
                        o[4 * i] *= al0;
                        o[4 * i + 1] *= al0;
                        o[4 * i + 2] *= al1;
                        o[4 * i + 3] *= al1;
                    }
                }
                cx.wait_full(vs, vph);
                wg_fence();
#pragma unroll
                for (int k = 0; k < 8; k++)
                    wgmma_n128<1>(o, p[4 * k], p[4 * k + 1], p[4 * k + 2], p[4 * k + 3],
                                  dv + (k >> 2) * 1024 + (k & 3) * 128, k != 0 ? 1 : (j != 1));
                wg_commit();
                bar_arrive(other_bar, 256);
                wg_wait<1>();
                pin(d);
                cx.release(ks);

                float x0 = fmaxf(d[0], d[1]), x1 = fmaxf(d[2], d[3]);
#pragma unroll
                for (int i = 1; i < 16; i++) {
                    x0 = fmaxf(x0, fmaxf(d[4 * i], d[4 * i + 1]));
                    x1 = fmaxf(x1, fmaxf(d[4 * i + 2], d[4 * i + 3]));
                }
                x0 = fmaxf(x0, __shfl_xor_sync(0xffffffffu, x0, 1));
                x1 = fmaxf(x1, __shfl_xor_sync(0xffffffffu, x1, 1));
                x0 = fmaxf(x0, __shfl_xor_sync(0xffffffffu, x0, 2));
                x1 = fmaxf(x1, __shfl_xor_sync(0xffffffffu, x1, 2));
                if (j == 0) {
                    m0 = -INFINITY;
                    m1 = -INFINITY;
                }
                lp0 = l0;
                lp1 = l1;
                x0 = fmaxf(x0, m0);
                x1 = fmaxf(x1, m1);
                al0 = ex2((m0 - x0) * cs);
                al1 = ex2((m1 - x1) * cs);
                m0 = x0;
                m1 = x1;
                const float n0 = -m0 * cs, n1 = -m1 * cs;
                float s0 = 0.f, s1 = 0.f;
#pragma unroll
                for (int i = 0; i < 16; i++) {
                    d[4 * i] = ex2(fmaf(d[4 * i], cs, n0));
                    d[4 * i + 1] = ex2(fmaf(d[4 * i + 1], cs, n0));
                    d[4 * i + 2] = ex2(fmaf(d[4 * i + 2], cs, n1));
                    d[4 * i + 3] = ex2(fmaf(d[4 * i + 3], cs, n1));
                    s0 += d[4 * i] + d[4 * i + 1];
                    s1 += d[4 * i + 2] + d[4 * i + 3];
                }
                l0 = fmaf(l0, al0, s0);
                l1 = fmaf(l1, al1, s1);
            }
            wg_wait<0>();
            pin(o);
            cx.release(0);
#pragma unroll
            for (int i = 0; i < 32; i++) p[i] = pack_bf16(d[2 * i], d[2 * i + 1]);
#pragma unroll
            for (int i = 0; i < 16; i++) {
                o[4 * i] *= al0;
                o[4 * i + 1] *= al0;
                o[4 * i + 2] *= al1;
                o[4 * i + 3] *= al1;
            }
            cx.wait_full(2, 0);
            bar_sync(my_bar, 256);
            wg_fence();
#pragma unroll
            for (int k = 0; k < 8; k++)
                wgmma_n128<1>(o, p[4 * k], p[4 * k + 1], p[4 * k + 2], p[4 * k + 3],
                              dbase + (2 + (k >> 2)) * 1024 + (k & 3) * 128, 1);
            wg_commit();
            if (wg == 0) bar_arrive(other_bar, 256);
            float t0 = l0 + __shfl_xor_sync(0xffffffffu, l0, 1), t1 = l1 + __shfl_xor_sync(0xffffffffu, l1, 1);
            t0 += __shfl_xor_sync(0xffffffffu, t0, 2);
            t1 += __shfl_xor_sync(0xffffffffu, t1, 2);
            const float i0 = rcp(t0), i1 = rcp(t1);
            wg_wait<0>();
            pin(o);
            cx.release(2);
#pragma unroll
            for (int i = 0; i < 16; i++) {
                a[96 + 2 * i] = pack_bf16(o[4 * i] * i0, o[4 * i + 1] * i0);
                a[96 + 2 * i + 1] = pack_bf16(o[4 * i + 2] * i1, o[4 * i + 3] * i1);
            }
#pragma unroll
            for (int v = 0; v < 24; v++)
                lds128(spill + (v >> 3) * 32768 + (v & 7) * 2048, a[4 * v], a[4 * v + 1], a[4 * v + 2], a[4 * v + 3]);
        }

        PROF(6);
        uint2* part_dst = g_part + ((size_t)wown * 8 + g) * 72 * 32 + lane;
        const uint2* part_src = g_part + (size_t)own * 8 * 72 * 32 + lane;
        float4* x2buf = g_x2 + (size_t)b * 9 * 256 + tid;
        ring.slot = 4;
        ring.phase = 0;
        proj_partials<8, 8>(a, cx, ring, part_dst);
        __syncwarp();
        PROF(7);
        if (lane == 0) signal_cnt(CNT_P1 + wown);
        PROF(8);

        {
            float v[36];
            uint32_t xs[18];
#pragma unroll
            for (int j = 0; j < 9; j++) {
                const int col = (warp * 9 + j) * 8 + (lane & 3) * 2;
                xs[2 * j] = __ldg(reinterpret_cast<const uint32_t*>(x + (size_t)orow * DM + col));
                xs[2 * j + 1] = __ldg(reinterpret_cast<const uint32_t*>(x + (size_t)(orow + 8) * DM + col));
            }
            float md[3][18];
            const int which[3] = {2, 3, 4};
            load_mod<3>(md, which, warp, lane);
            wait_cnt(CNT_P1 + own, 8);
            PROF(9);
            sum_partials(v, part_src, warp);
#pragma unroll
            for (int j = 0; j < 9; j++) {
                v[4 * j] = fmaf(md[0][2 * j], v[4 * j], bf_lo(xs[2 * j]));
                v[4 * j + 1] = fmaf(md[0][2 * j + 1], v[4 * j + 1], bf_hi(xs[2 * j]));
                v[4 * j + 2] = fmaf(md[0][2 * j], v[4 * j + 2], bf_lo(xs[2 * j + 1]));
                v[4 * j + 3] = fmaf(md[0][2 * j + 1], v[4 * j + 3], bf_hi(xs[2 * j + 1]));
                __stcg(x2buf + j * 256, make_float4(v[4 * j], v[4 * j + 1], v[4 * j + 2], v[4 * j + 3]));
            }
            PROF(10);
            layernorm_rows(v, red, warp, lane);
            modulate_store(v, md[1], md[2], g_h2 + (size_t)own * 36 * 32, warp, lane);
            __syncwarp();
            if (lane == 0) signal_cnt(CNT_H2 + own);
        }

        PROF(11);
        wait_cnt(CNT_H2 + wown, 8);
        PROF(12);
        load_frags(a, g_h2 + (size_t)wown * 36 * 32 + lane);
        ring.slot = 0;
        ring.phase = 1;
        const uint32_t hsp = sbase + 6 * SLOT_BYTES + wg * BOX_BYTES + (tid & 127) * 16;
        {
            float d[64];
#pragma unroll 1
            for (int ch = 0;; ch++) {
                gemm_n128<9, 6>(d, a, cx, ring);
#pragma unroll
                for (int i = 0; i < 32; i++) {
                    const float gv = d[i];
                    const float k1 = -2.f * 0.7978845608028654f * 1.4426950408889634f;
                    const float zz = gv * fmaf(gv * gv, k1 * 0.044715f, k1);
                    d[i] = gv * rcp(1.f + ex2(zz)) * d[32 + i];
                }
                if (ch == 8) break;
                const uint32_t dst = hsp + ((ch + 2) & 7) * SLOT_BYTES;
#pragma unroll
                for (int v = 0; v < 4; v++)
                    sts128(dst + v * 2048, pack_bf16(d[8 * v], d[8 * v + 1]), pack_bf16(d[8 * v + 2], d[8 * v + 3]),
                           pack_bf16(d[8 * v + 4], d[8 * v + 5]), pack_bf16(d[8 * v + 6], d[8 * v + 7]));
            }
#pragma unroll
            for (int i = 0; i < 16; i++) a[128 + i] = pack_bf16(d[2 * i], d[2 * i + 1]);
        }
#pragma unroll
        for (int v = 0; v < 32; v++)
            lds128(hsp + (((v >> 2) + 2) & 7) * SLOT_BYTES + (v & 3) * 2048, a[4 * v], a[4 * v + 1], a[4 * v + 2],
                   a[4 * v + 3]);

        PROF(13);
        proj_partials<9, 6>(a, cx, ring, part_dst);
        asm volatile("barrier.cluster.arrive.relaxed.aligned;" ::: "memory");
        __syncwarp();
        PROF(14);
        if (lane == 0) signal_cnt(CNT_P2 + wown);

        {
            float v[36];
            float4 xr[9];
            float gb[1][18];
#pragma unroll
            for (int j = 0; j < 9; j++) xr[j] = __ldcg(x2buf + j * 256);
            const int which[1] = {5};
            load_mod<1>(gb, which, warp, lane);
            wait_cnt(CNT_P2 + own, 8);
            PROF(15);
            sum_partials(v, part_src, warp);
#pragma unroll
            for (int j = 0; j < 9; j++) {
                const int col = (warp * 9 + j) * 8 + (lane & 3) * 2;
                *reinterpret_cast<uint32_t*>(out + (size_t)orow * DM + col) =
                    pack_bf16(fmaf(gb[0][2 * j], v[4 * j], xr[j].x), fmaf(gb[0][2 * j + 1], v[4 * j + 1], xr[j].y));
                *reinterpret_cast<uint32_t*>(out + (size_t)(orow + 8) * DM + col) =
                    pack_bf16(fmaf(gb[0][2 * j], v[4 * j + 2], xr[j].z), fmaf(gb[0][2 * j + 1], v[4 * j + 3], xr[j].w));
            }
        }
        PROF(16);
        PROFG(31);
        bar_sync(3, 256);
        if (warp == 0) {
            unsigned old = 0;
            if (lane == 0)
                asm volatile("atom.acq_rel.gpu.global.add.u32 %0, [%1], 1;" : "=r"(old) : "l"(&g_cnt[CNT_DONE * 32]) : "memory");
            old = __shfl_sync(0xffffffffu, old, 0);
            if (old == 127) {
                for (int i = lane; i < CNT_TOTAL; i += 32) g_cnt[i * 32] = 0;
                for (int i = lane; i < 6 * DM / 4; i += 32) reinterpret_cast<uint4*>(g_mod)[i] = make_uint4(0, 0, 0, 0);
            }
        }
        asm volatile("barrier.cluster.wait.aligned;" ::: "memory");
    }
}

typedef CUresult (*EncodeFn)(CUtensorMap*, CUtensorMapDataType, cuuint32_t, void*, const cuuint64_t*, const cuuint64_t*,
                             const cuuint32_t*, const cuuint32_t*, CUtensorMapInterleave, CUtensorMapSwizzle,
                             CUtensorMapL2promotion, CUtensorMapFloatOOBfill);

void make_map(EncodeFn enc, CUtensorMap* m, const void* ptr, uint64_t rows, uint64_t cols) {
    cuuint64_t gdim[2] = {cols, rows};
    cuuint64_t gstr[1] = {cols * 2};
    cuuint32_t box[2] = {64, 64};
    cuuint32_t estr[2] = {1, 1};
    enc(m, CU_TENSOR_MAP_DATA_TYPE_BFLOAT16, 2, const_cast<void*>(ptr), gdim, gstr, box, estr,
        CU_TENSOR_MAP_INTERLEAVE_NONE, CU_TENSOR_MAP_SWIZZLE_128B, CU_TENSOR_MAP_L2_PROMOTION_L2_128B,
        CU_TENSOR_MAP_FLOAT_OOB_FILL_NONE);
}

}

extern "C" void kernel_launch(void* const* d_in, const int* in_sizes, int n_in, void* d_out, int out_size) {
    (void)in_sizes;
    (void)n_in;
    (void)out_size;
    void* fn = nullptr;
    cudaDriverEntryPointQueryResult qr;
    cudaGetDriverEntryPoint("cuTensorMapEncodeTiled", &fn, cudaEnableDefault, &qr);
    EncodeFn enc = (EncodeFn)fn;
    Maps maps;
    make_map(enc, &maps.k, d_in[1], 32 * 2048, 128);
    make_map(enc, &maps.v, d_in[2], 32 * 2048, 128);
    make_map(enc, &maps.wq, d_in[3], 576, 4096);
    make_map(enc, &maps.wo, d_in[4], 4096, 576);
    make_map(enc, &maps.wg, d_in[6], 576, 4608);
    make_map(enc, &maps.wu, d_in[7], 576, 4608);
    make_map(enc, &maps.wd, d_in[8], 4608, 576);
    cudaFuncSetAttribute(fused_block_kernel, cudaFuncAttributeMaxDynamicSharedMemorySize, SMEM_BYTES);
    fused_block_kernel<<<128, 384, SMEM_BYTES>>>(maps, (const __nv_bfloat16*)d_in[0], (const __nv_bfloat16*)d_in[9],
                                                 (const __nv_bfloat16*)d_in[10], (__nv_bfloat16*)d_out);
}
```

```cpp
#include <cuda_runtime.h>
#include <cuda_bf16.h>
#include <cuda.h>
#include <stdint.h>

namespace {

constexpr int DM = 576;
constexpr int SLOT_BYTES = 16384;
constexpr int BOX_BYTES = 8192;
constexpr int NUNITS = 14;
constexpr int SMEM_TAIL = NUNITS * SLOT_BYTES;
constexpr int SMEM_BYTES = SMEM_TAIL + 2048 + 1024;
constexpr int OFF_FULL = SMEM_TAIL;
constexpr int OFF_EMPTY = SMEM_TAIL + 64;
constexpr int OFF_RED = SMEM_TAIL + 128;

constexpr int CNT_DONE = 2, CNT_H1 = 8, CNT_P1 = 8 + 128, CNT_H2 = 8 + 256,
              CNT_P2 = 8 + 384, CNT_TOTAL = 8 + 512;

__device__ __align__(16) uint32_t g_mod[6 * DM];
__device__ uint4 g_h1[128 * 36 * 32];
__device__ uint4 g_h2[128 * 36 * 32];
__device__ uint2 g_part[128 * 8 * 72 * 32];
__device__ float4 g_x2[128 * 9 * 256];
__device__ unsigned g_cnt[CNT_TOTAL * 32];

#define TL(i)
#define PROFR(i)
#define PROF(i)
#define PROFG(i)

struct Maps {
    CUtensorMap k, v, wq, wo, wg, wu, wd;
};

__device__ __forceinline__ uint32_t smem_u32(const void* p) { return (uint32_t)__cvta_generic_to_shared(p); }
__device__ __forceinline__ void mbar_init(uint32_t a, uint32_t c) {
    asm volatile("mbarrier.init.shared::cta.b64 [%0], %1;" ::"r"(a), "r"(c) : "memory");
}
__device__ __forceinline__ void mbar_expect_tx(uint32_t a, uint32_t bytes) {
    asm volatile("mbarrier.arrive.expect_tx.shared::cta.b64 _, [%0], %1;" ::"r"(a), "r"(bytes) : "memory");
}
__device__ __forceinline__ bool mbar_try(uint32_t a, uint32_t ph) {
    uint32_t ok;
    asm volatile(
        "{\n.reg .pred p;\nmbarrier.try_wait.parity.shared::cta.b64 p, [%1], %2;\nselp.u32 %0, 1, 0, p;\n}"
        : "=r"(ok)
        : "r"(a), "r"(ph)
        : "memory");
    return ok != 0;
}
__device__ __forceinline__ uint32_t clk32() {
    uint32_t c;
    asm volatile("mov.u32 %0, %%clock;" : "=r"(c));
    return c;
}
constexpr uint32_t WAIT_LIMIT = 1u << 30;
__device__ __forceinline__ void mbar_wait(uint32_t a, uint32_t ph) {
    if (mbar_try(a, ph)) return;
    uint32_t t0 = clk32();
    while (!mbar_try(a, ph)) {
        if (clk32() - t0 > WAIT_LIMIT) break;
    }
}
__device__ __forceinline__ void mbar_arrive_cluster(uint32_t a, uint32_t cta) {
    asm volatile(
        "{\n.reg .b32 ra;\nmapa.shared::cluster.u32 ra, %0, %1;\nmbarrier.arrive.shared::cluster.b64 _, [ra];\n}" ::"r"(a),
        "r"(cta)
        : "memory");
}
__device__ __forceinline__ void tma_mc(uint32_t dst, const CUtensorMap* m, int c0, int c1, uint32_t bar) {
    asm volatile(
        "cp.async.bulk.tensor.2d.shared::cluster.global.mbarrier::complete_tx::bytes.multicast::cluster"
        " [%0], [%1, {%3, %4}], [%2], %5;" ::"r"(dst),
        "l"(m), "r"(bar), "r"(c0), "r"(c1), "h"((uint16_t)3)
        : "memory");
}
__device__ __forceinline__ void bar_sync(int id, int n) { asm volatile("bar.sync %0, %1;" ::"r"(id), "r"(n) : "memory"); }
__device__ __forceinline__ void bar_arrive(int id, int n) {
    asm volatile("bar.arrive %0, %1;" ::"r"(id), "r"(n) : "memory");
}
__device__ __forceinline__ void wg_fence() { asm volatile("wgmma.fence.sync.aligned;" ::: "memory"); }
__device__ __forceinline__ void wg_commit() { asm volatile("wgmma.commit_group.sync.aligned;" ::: "memory"); }
template <int N>
__device__ __forceinline__ void wg_wait() {
    asm volatile("wgmma.wait_group.sync.aligned %0;" ::"n"(N) : "memory");
}
template <int N>
__device__ __forceinline__ void pin(float (&d)[N]) {
#pragma unroll
    for (int i = 0; i < N; i++) asm volatile("" : "+f"(d[i])::"memory");
}
template <int N>
__device__ __forceinline__ void pin(uint32_t (&d)[N]) {
#pragma unroll
    for (int i = 0; i < N; i++) asm volatile("" : "+r"(d[i])::"memory");
}
__device__ __forceinline__ uint32_t pack_bf16(float lo, float hi) {
    uint32_t r;
    asm("cvt.rn.bf16x2.f32 %0, %1, %2;" : "=r"(r) : "f"(hi), "f"(lo));
    return r;
}
__device__ __forceinline__ float bf_lo(uint32_t v) { return __uint_as_float(v << 16); }
__device__ __forceinline__ float bf_hi(uint32_t v) { return __uint_as_float(v & 0xffff0000u); }
__device__ __forceinline__ float round_bf16(float v) { return __bfloat162float(__float2bfloat16_rn(v)); }
__device__ __forceinline__ float ex2(float x) {
    float y;
    asm("ex2.approx.ftz.f32 %0, %1;" : "=f"(y) : "f"(x));
    return y;
}
__device__ __forceinline__ float rcp(float x) {
    float y;
    asm("rcp.approx.ftz.f32 %0, %1;" : "=f"(y) : "f"(x));
    return y;
}
__device__ __forceinline__ void sts128(uint32_t a, uint32_t x, uint32_t y, uint32_t z, uint32_t w) {
    asm volatile("st.shared.v4.b32 [%0], {%1,%2,%3,%4};" ::"r"(a), "r"(x), "r"(y), "r"(z), "r"(w) : "memory");
}
__device__ __forceinline__ void lds128(uint32_t a, uint32_t& x, uint32_t& y, uint32_t& z, uint32_t& w) {
    asm volatile("ld.shared.v4.b32 {%0,%1,%2,%3}, [%4];" : "=r"(x), "=r"(y), "=r"(z), "=r"(w) : "r"(a) : "memory");
}
__device__ __forceinline__ void sts32f(uint32_t a, float v) {
    asm volatile("st.shared.f32 [%0], %1;" ::"r"(a), "f"(v) : "memory");
}
__device__ __forceinline__ float lds32f(uint32_t a) {
    float v;
    asm volatile("ld.shared.f32 %0, [%1];" : "=f"(v) : "r"(a) : "memory");
    return v;
}
__device__ __forceinline__ void signal_cnt(int idx) {
    asm volatile("red.release.gpu.global.add.u32 [%0], 1;" ::"l"(&g_cnt[idx * 32]) : "memory");
}
__device__ __forceinline__ void wait_cnt(int idx, unsigned target) {
    if ((threadIdx.x & 31) == 0) {
        uint32_t t0 = clk32();
        while (true) {
            unsigned v;
            asm volatile("ld.acquire.gpu.global.u32 %0, [%1];" : "=r"(v) : "l"(&g_cnt[idx * 32]) : "memory");
            if (v >= target) break;
            if (clk32() - t0 > WAIT_LIMIT) break;
        }
    }
    __syncwarp();
}

#define F8(d, b) \
    "+f"(d[b]), "+f"(d[b + 1]), "+f"(d[b + 2]), "+f"(d[b + 3]), "+f"(d[b + 4]), "+f"(d[b + 5]), "+f"(d[b + 6]), "+f"(d[b + 7])

template <int TB>
__device__ __forceinline__ void wgmma_n128(float (&d)[64], uint32_t a0, uint32_t a1, uint32_t a2, uint32_t a3,
                                           uint64_t db, int sc) {
    asm volatile(
        "{\n.reg .pred p;\nsetp.ne.b32 p, %69, 0;\n"
        "wgmma.mma_async.sync.aligned.m64n128k16.f32.bf16.bf16 "
        "{%0,%1,%2,%3,%4,%5,%6,%7,%8,%9,%10,%11,%12,%13,%14,%15,%16,%17,%18,%19,%20,%21,%22,%23,%24,%25,%26,%27,%28,%29,%30,%31,"
        "%32,%33,%34,%35,%36,%37,%38,%39,%40,%41,%42,%43,%44,%45,%46,%47,%48,%49,%50,%51,%52,%53,%54,%55,%56,%57,%58,%59,%60,%61,%62,%63},"
        "{%64,%65,%66,%67}, %68, p, 1, 1, %70;\n}"
        : F8(d, 0), F8(d, 8), F8(d, 16), F8(d, 24), F8(d, 32), F8(d, 40), F8(d, 48), F8(d, 56)
        : "r"(a0), "r"(a1), "r"(a2), "r"(a3), "l"(db), "r"(sc), "n"(TB));
}
#define O8(d, b) \
    "=f"(d[b]), "=f"(d[b + 1]), "=f"(d[b + 2]), "=f"(d[b + 3]), "=f"(d[b + 4]), "=f"(d[b + 5]), "=f"(d[b + 6]), "=f"(d[b + 7])
template <int TB>
__device__ __forceinline__ void wgmma_n128_z(float (&d)[64], uint32_t a0, uint32_t a1, uint32_t a2, uint32_t a3,
                                             uint64_t db) {
    asm volatile(
        "wgmma.mma_async.sync.aligned.m64n128k16.f32.bf16.bf16 "
        "{%0,%1,%2,%3,%4,%5,%6,%7,%8,%9,%10,%11,%12,%13,%14,%15,%16,%17,%18,%19,%20,%21,%22,%23,%24,%25,%26,%27,%28,%29,%30,%31,"
        "%32,%33,%34,%35,%36,%37,%38,%39,%40,%41,%42,%43,%44,%45,%46,%47,%48,%49,%50,%51,%52,%53,%54,%55,%56,%57,%58,%59,%60,%61,%62,%63},"
        "{%64,%65,%66,%67}, %68, 0, 1, 1, %69;"
        : O8(d, 0), O8(d, 8), O8(d, 16), O8(d, 24), O8(d, 32), O8(d, 40), O8(d, 48), O8(d, 56)
        : "r"(a0), "r"(a1), "r"(a2), "r"(a3), "l"(db), "n"(TB));
}
template <int TB>
__device__ __forceinline__ void wgmma_n64_z(float (&d)[32], uint32_t a0, uint32_t a1, uint32_t a2, uint32_t a3,
                                            uint64_t db) {
    asm volatile(
        "wgmma.mma_async.sync.aligned.m64n64k16.f32.bf16.bf16 "
        "{%0,%1,%2,%3,%4,%5,%6,%7,%8,%9,%10,%11,%12,%13,%14,%15,%16,%17,%18,%19,%20,%21,%22,%23,%24,%25,%26,%27,%28,%29,%30,%31},"
        "{%32,%33,%34,%35}, %36, 0, 1, 1, %37;"
        : O8(d, 0), O8(d, 8), O8(d, 16), O8(d, 24)
        : "r"(a0), "r"(a1), "r"(a2), "r"(a3), "l"(db), "n"(TB));
}
template <int TB>
__device__ __forceinline__ void wgmma_n64(float (&d)[32], uint32_t a0, uint32_t a1, uint32_t a2, uint32_t a3,
                                          uint64_t db) {
    asm volatile(
        "wgmma.mma_async.sync.aligned.m64n64k16.f32.bf16.bf16 "
        "{%0,%1,%2,%3,%4,%5,%6,%7,%8,%9,%10,%11,%12,%13,%14,%15,%16,%17,%18,%19,%20,%21,%22,%23,%24,%25,%26,%27,%28,%29,%30,%31},"
        "{%32,%33,%34,%35}, %36, 1, 1, 1, %37;"
        : F8(d, 0), F8(d, 8), F8(d, 16), F8(d, 24)
        : "r"(a0), "r"(a1), "r"(a2), "r"(a3), "l"(db), "n"(TB));
}

__device__ __forceinline__ uint64_t desc_of(uint32_t saddr) {
    return (uint64_t)(((saddr >> 4) & 0x3FFFu) | (512u << 16)) | ((uint64_t)(64u | (1u << 30)) << 32);
}

struct Ring {
    uint32_t slot;
    uint32_t phase;
    template <int NS>
    __device__ __forceinline__ void next() {
        if (++slot == NS) {
            slot = 0;
            phase ^= 1;
        }
    }
};

struct Ctx {
    uint32_t sbase;
    uint32_t rel_cta;
    __device__ __forceinline__ void wait_full(uint32_t slot, uint32_t phase) const {
        mbar_wait(sbase + OFF_FULL + slot * 8, phase);
    }
    __device__ __forceinline__ void release(uint32_t slot) const {
        if (rel_cta < 2) mbar_arrive_cluster(sbase + OFF_EMPTY + slot * 8, rel_cta);
    }
};

template <int NK, int NS, int NA>
__device__ __forceinline__ void gemm_n128(float (&d)[64], const uint32_t (&a)[NA], const Ctx& c, Ring& r) {
    uint32_t prev = 0;
#pragma unroll
    for (int s = 0; s < NK; s++) {
        c.wait_full(r.slot, r.phase);
        uint64_t db = desc_of(c.sbase + r.slot * SLOT_BYTES);
        wg_fence();
#pragma unroll
        for (int k = 0; k < 4; k++) {
            if ((s | k) == 0)
                wgmma_n128_z<1>(d, a[0], a[1], a[2], a[3], db);
            else
                wgmma_n128<1>(d, a[s * 16 + k * 4], a[s * 16 + k * 4 + 1], a[s * 16 + k * 4 + 2], a[s * 16 + k * 4 + 3],
                              db + k * 128, 1);
        }
        wg_commit();
        if (s > 0) {
            wg_wait<1>();
            c.release(prev);
        }
        prev = r.slot;
        r.template next<NS>();
    }
    wg_wait<0>();
    c.release(prev);
    pin(d);
}
template <int NKS, int NS, int NA>
__device__ __forceinline__ void gemm_n64(float (&d)[32], const uint32_t (&a)[NA], const Ctx& c, Ring& r) {
    uint32_t prev = 0;
    constexpr int NSL = (NKS + 7) / 8;
#pragma unroll
    for (int s = 0; s < NSL; s++) {
        c.wait_full(r.slot, r.phase);
        uint64_t db = desc_of(c.sbase + r.slot * SLOT_BYTES);
        wg_fence();
#pragma unroll
        for (int k = 0; k < 8; k++) {
            if ((s | k) == 0)
                wgmma_n64_z<1>(d, a[0], a[1], a[2], a[3], db);
            else if (s * 8 + k < NKS)
                wgmma_n64<1>(d, a[s * 32 + k * 4], a[s * 32 + k * 4 + 1], a[s * 32 + k * 4 + 2], a[s * 32 + k * 4 + 3],
                             db + k * 128);
        }
        wg_commit();
        if (s > 0) {
            wg_wait<1>();
            c.release(prev);
        }
        prev = r.slot;
        r.template next<NS>();
    }
    wg_wait<0>();
    c.release(prev);
    pin(d);
}

template <int NK, int NS, int NA>
__device__ __forceinline__ void proj_partials(const uint32_t (&a)[NA], const Ctx& c, Ring& r,
                                              uint2* dst  ) {
#pragma unroll 1
    for (int p = 0; p < 4; p++) {
        float d[64];
        gemm_n128<NK, NS>(d, a, c, r);
#pragma unroll
        for (int j = 0; j < 16; j++)
            __stcg(dst + (p * 16 + j) * 32, make_uint2(pack_bf16(d[4 * j], d[4 * j + 1]), pack_bf16(d[4 * j + 2], d[4 * j + 3])));
    }
    float d[32];
    gemm_n64<NK * 4, NS>(d, a, c, r);
#pragma unroll
    for (int j = 0; j < 8; j++)
        __stcg(dst + (64 + j) * 32, make_uint2(pack_bf16(d[4 * j], d[4 * j + 1]), pack_bf16(d[4 * j + 2], d[4 * j + 3])));
}

__device__ __forceinline__ void row_reduce(float& s0, float& s1, uint32_t red, int warp, int lane) {
    s0 += __shfl_xor_sync(0xffffffffu, s0, 1);
    s1 += __shfl_xor_sync(0xffffffffu, s1, 1);
    s0 += __shfl_xor_sync(0xffffffffu, s0, 2);
    s1 += __shfl_xor_sync(0xffffffffu, s1, 2);
    if ((lane & 3) == 0) {
        sts32f(red + (warp * 16 + (lane >> 2)) * 4, s0);
        sts32f(red + (warp * 16 + 8 + (lane >> 2)) * 4, s1);
    }
    bar_sync(3, 256);
    s0 = 0.f;
    s1 = 0.f;
#pragma unroll
    for (int w = 0; w < 8; w++) {
        s0 += lds32f(red + (w * 16 + (lane >> 2)) * 4);
        s1 += lds32f(red + (w * 16 + 8 + (lane >> 2)) * 4);
    }
}
__device__ __forceinline__ void layernorm_rows(float (&v)[36], uint32_t red, int warp, int lane) {
    float s0 = 0.f, s1 = 0.f;
#pragma unroll
    for (int j = 0; j < 9; j++) {
        s0 += v[4 * j] + v[4 * j + 1];
        s1 += v[4 * j + 2] + v[4 * j + 3];
    }
    row_reduce(s0, s1, red, warp, lane);
    const float m0 = s0 * (1.f / DM), m1 = s1 * (1.f / DM);
    s0 = 0.f;
    s1 = 0.f;
#pragma unroll
    for (int j = 0; j < 9; j++) {
        v[4 * j] -= m0;
        v[4 * j + 1] -= m0;
        v[4 * j + 2] -= m1;
        v[4 * j + 3] -= m1;
        s0 += v[4 * j] * v[4 * j] + v[4 * j + 1] * v[4 * j + 1];
        s1 += v[4 * j + 2] * v[4 * j + 2] + v[4 * j + 3] * v[4 * j + 3];
    }
    row_reduce(s0, s1, red + 512, warp, lane);
    const float r0 = rsqrtf(s0 * (1.f / DM) + 1e-5f), r1 = rsqrtf(s1 * (1.f / DM) + 1e-5f);
#pragma unroll
    for (int j = 0; j < 9; j++) {
        v[4 * j] *= r0;
        v[4 * j + 1] *= r0;
        v[4 * j + 2] *= r1;
        v[4 * j + 3] *= r1;
    }
}
template <int NV>
__device__ __forceinline__ void load_mod(float (&m)[NV][18], const int (&which)[NV], int warp, int lane) {
    const uint32_t t0 = clk32();
    while (true) {
        uint2 u[NV][9];
#pragma unroll
        for (int n = 0; n < NV; n++)
#pragma unroll
            for (int j = 0; j < 9; j++)
                asm volatile("ld.relaxed.gpu.global.v2.u32 {%0,%1}, [%2];"
                             : "=r"(u[n][j].x), "=r"(u[n][j].y)
                             : "l"(g_mod + which[n] * DM + (warp * 9 + j) * 8 + (lane & 3) * 2));
        uint32_t ok = 1;
#pragma unroll
        for (int n = 0; n < NV; n++)
#pragma unroll
            for (int j = 0; j < 9; j++) {
                ok &= u[n][j].x & u[n][j].y;
                m[n][2 * j] = __uint_as_float(u[n][j].x & 0xffff0000u);
                m[n][2 * j + 1] = __uint_as_float(u[n][j].y & 0xffff0000u);
            }
        if (__all_sync(0xffffffffu, ok) || clk32() - t0 > WAIT_LIMIT) break;
    }
}
__device__ __forceinline__ void modulate_store(const float (&v)[36], const float (&shift)[18], const float (&scale)[18],
                                               uint4* hbuf  , int warp, int lane) {
    uint2* dst = reinterpret_cast<uint2*>(hbuf);
#pragma unroll
    for (int j = 0; j < 9; j++) {
        const int grp = warp * 9 + j;
        const float c0 = round_bf16(1.f + scale[2 * j]), c1 = round_bf16(1.f + scale[2 * j + 1]);
        uint2 o;
        o.x = pack_bf16(fmaf(v[4 * j], c0, shift[2 * j]), fmaf(v[4 * j + 1], c1, shift[2 * j + 1]));
        o.y = pack_bf16(fmaf(v[4 * j + 2], c0, shift[2 * j]), fmaf(v[4 * j + 3], c1, shift[2 * j + 1]));
        __stcg(dst + ((grp >> 1) * 32 + lane) * 2 + (grp & 1), o);
    }
}
__device__ __forceinline__ void sum_partials(float (&v)[36], const uint2* src  , int warp) {
    uint2 t[8][9];
#pragma unroll
    for (int s = 0; s < 8; s++)
#pragma unroll
        for (int j = 0; j < 9; j++) t[s][j] = __ldcg(src + (s * 72 + warp * 9 + j) * 32);
#pragma unroll
    for (int j = 0; j < 9; j++) {
        float a = 0.f, b = 0.f, c = 0.f, d = 0.f;
#pragma unroll
        for (int s = 0; s < 8; s++) {
            a += bf_lo(t[s][j].x);
            b += bf_hi(t[s][j].x);
            c += bf_lo(t[s][j].y);
            d += bf_hi(t[s][j].y);
        }
        v[4 * j] = a;
        v[4 * j + 1] = b;
        v[4 * j + 2] = c;
        v[4 * j + 3] = d;
    }
}
__device__ __forceinline__ void load_frags(uint32_t (&a)[144], const uint4* src  ) {
#pragma unroll
    for (int k = 0; k < 36; k++) {
        uint4 t = __ldcg(src + k * 32);
        a[4 * k] = t.x;
        a[4 * k + 1] = t.y;
        a[4 * k + 2] = t.z;
        a[4 * k + 3] = t.w;
    }
}

constexpr float SM_SCALE = 0.08838834764831845f * 1.4426950408889634f;
constexpr float SM_LIMIT = 4294967296.f;
__device__ __forceinline__ void qk_half(float (&s)[32], const uint32_t (&q)[32], uint64_t dk) {
#pragma unroll
    for (int k = 0; k < 8; k++) {
        if (k == 0)
            wgmma_n64_z<0>(s, q[0], q[1], q[2], q[3], dk);
        else
            wgmma_n64<0>(s, q[4 * k], q[4 * k + 1], q[4 * k + 2], q[4 * k + 3], dk + (k >> 2) * 1024 + (k & 3) * 2);
    }
}
template <int OFF>
__device__ __forceinline__ void exp_half(const float (&s)[32], uint32_t (&p)[32], float n0, float n1, float& s0,
                                         float& s1) {
#pragma unroll
    for (int i = 0; i < 8; i++) {
        const float e0 = ex2(fmaf(s[4 * i], SM_SCALE, n0)), e1 = ex2(fmaf(s[4 * i + 1], SM_SCALE, n0));
        const float e2 = ex2(fmaf(s[4 * i + 2], SM_SCALE, n1)), e3 = ex2(fmaf(s[4 * i + 3], SM_SCALE, n1));
        s0 += e0 + e1;
        s1 += e2 + e3;
        p[OFF + 2 * i] = pack_bf16(e0, e1);
        p[OFF + 2 * i + 1] = pack_bf16(e2, e3);
    }
}
__device__ __forceinline__ void row_max(const float (&sa)[32], const float (&sb)[32], float& x0, float& x1) {
    float xa[8];
#pragma unroll
    for (int i = 0; i < 8; i++) xa[i] = fmaxf(sa[i], sb[i]);
#pragma unroll
    for (int k = 1; k < 4; k++)
#pragma unroll
        for (int i = 0; i < 8; i++) xa[i] = fmaxf(xa[i], fmaxf(sa[8 * k + i], sb[8 * k + i]));
    x0 = fmaxf(fmaxf(xa[0], xa[1]), fmaxf(xa[4], xa[5]));
    x1 = fmaxf(fmaxf(xa[2], xa[3]), fmaxf(xa[6], xa[7]));
    x0 = fmaxf(x0, __shfl_xor_sync(0xffffffffu, x0, 1));
    x1 = fmaxf(x1, __shfl_xor_sync(0xffffffffu, x1, 1));
    x0 = fmaxf(x0, __shfl_xor_sync(0xffffffffu, x0, 2));
    x1 = fmaxf(x1, __shfl_xor_sync(0xffffffffu, x1, 2));
}

__device__ __forceinline__ void mod_block(const uint4 (&w)[5], const float (&sc)[5], int blk, uint32_t red, int warp,
                                          int lane) {
    float acc[8];
#pragma unroll
    for (int e = 0; e < 8; e++) acc[e] = 0.f;
#pragma unroll
    for (int i = 0; i < 5; i++) {
        acc[0] = fmaf(sc[i], bf_lo(w[i].x), acc[0]);
        acc[1] = fmaf(sc[i], bf_hi(w[i].x), acc[1]);
        acc[2] = fmaf(sc[i], bf_lo(w[i].y), acc[2]);
        acc[3] = fmaf(sc[i], bf_hi(w[i].y), acc[3]);
        acc[4] = fmaf(sc[i], bf_lo(w[i].z), acc[4]);
        acc[5] = fmaf(sc[i], bf_hi(w[i].z), acc[5]);
        acc[6] = fmaf(sc[i], bf_lo(w[i].w), acc[6]);
        acc[7] = fmaf(sc[i], bf_hi(w[i].w), acc[7]);
    }
#pragma unroll
    for (int o = 2; o < 32; o <<= 1)
#pragma unroll
        for (int e = 0; e < 8; e++) acc[e] += __shfl_xor_sync(0xffffffffu, acc[e], o);
    if (lane < 2) {
#pragma unroll
        for (int e = 0; e < 8; e++) sts32f(red + (warp * 16 + lane * 8 + e) * 4, acc[e]);
    }
    bar_sync(3, 256);
    if (warp == 0 && lane < 16) {
        float s = 0.f;
#pragma unroll
        for (int w8 = 0; w8 < 8; w8++) s += lds32f(red + (w8 * 16 + lane) * 4);
        asm volatile("st.relaxed.gpu.global.u32 [%0], %1;" ::"l"(g_mod + blk * 16 + lane),
                     "r"(__float_as_uint(round_bf16(s)) | 1u)
                     : "memory");
    }
}

__global__ void __cluster_dims__(2, 1, 1) __launch_bounds__(384, 1)
    fused_block_kernel(const __grid_constant__ Maps maps, const __nv_bfloat16* __restrict__ x,
                       const __nv_bfloat16* __restrict__ cvec, const __nv_bfloat16* __restrict__ wmod,
                       __nv_bfloat16* __restrict__ out) {
    extern __shared__ uint8_t smem_raw[];
    uint32_t sbase = (smem_u32(smem_raw) + 1023u) & ~1023u;
    asm volatile("" : "+r"(sbase));
    const int b = blockIdx.x;
    const int rank = b & 1;
    const int mt = ((b >> 1) & 7) * 2 + rank;
    const int g = b >> 4;
    const int warp = __shfl_sync(0xffffffffu, threadIdx.x >> 5, 0);
    const int lane = threadIdx.x & 31;

    if (warp >= 8) {
        asm volatile("setmaxnreg.dec.sync.aligned.u32 24;");
        if (warp == 8 && lane == 0) {
#pragma unroll
            for (int i = 0; i < 8; i++) {
                mbar_init(sbase + OFF_FULL + i * 8, 1);
                mbar_init(sbase + OFF_EMPTY + i * 8, 4);
            }
            asm volatile("fence.mbarrier_init.release.cluster;" ::: "memory");
            asm volatile("barrier.cluster.arrive.relaxed;\nbarrier.cluster.wait;" ::: "memory");
            uint32_t slot = 0, phase = 1;
            const uint32_t dst0 = sbase + rank * BOX_BYTES;
            auto acquire = [&](uint32_t bytes) {
                mbar_wait(sbase + OFF_EMPTY + slot * 8, phase);
                mbar_expect_tx(sbase + OFF_FULL + slot * 8, bytes);
            };
            auto adv8 = [&]() {
                if (++slot == 8) {
                    slot = 0;
                    phase ^= 1;
                }
            };
            auto adv6 = [&]() {
                if (++slot == 6) {
                    slot = 0;
                    phase ^= 1;
                }
            };
#pragma unroll 1
            for (int hq = 0; hq < 4; hq++) {
                const int col = (g * 4 + ((hq + 1) & 3)) * 128 + rank * 64;
#pragma unroll 1
                for (int kc = 0; kc < 9; kc++) {
                    acquire(SLOT_BYTES);
                    tma_mc(dst0 + slot * SLOT_BYTES, &maps.wq, col, kc * 64, sbase + OFF_FULL + slot * 8);
                    adv8();
                }
            }
            const int row0 = g * 4 * 2048;
#pragma unroll 1
            for (int t = 0; t < 64; t++) {
                {
                    if (t < 2) mbar_wait(sbase + OFF_EMPTY + (slot + 1) * 8, phase);
                    acquire(2 * SLOT_BYTES);
                    const uint32_t bar = sbase + OFF_FULL + slot * 8;
                    tma_mc(dst0 + slot * SLOT_BYTES, &maps.k, 0, row0 + t * 128 + rank * 64, bar);
                    tma_mc(dst0 + (slot + 1) * SLOT_BYTES, &maps.k, 64, row0 + t * 128 + rank * 64, bar);
                    adv8();
                    adv8();
                }
                {
                    if (t < 2) mbar_wait(sbase + OFF_EMPTY + (slot + 1) * 8, phase);
                    acquire(2 * SLOT_BYTES);
                    const uint32_t bar = sbase + OFF_FULL + slot * 8;
                    tma_mc(dst0 + slot * SLOT_BYTES, &maps.v, rank * 64, row0 + t * 128, bar);
                    tma_mc(dst0 + (slot + 1) * SLOT_BYTES, &maps.v, rank * 64, row0 + t * 128 + 64, bar);
                    adv8();
                    adv8();
                }
            }
#pragma unroll 1
            for (int p = 0; p < 4; p++)
#pragma unroll 1
                for (int kc = 0; kc < 8; kc++) {
                    acquire(SLOT_BYTES);
                    tma_mc(dst0 + slot * SLOT_BYTES, &maps.wo, p * 128 + rank * 64, g * 512 + kc * 64,
                           sbase + OFF_FULL + slot * 8);
                    adv8();
                }
#pragma unroll 1
            for (int kc = 0; kc < 4; kc++) {
                acquire(SLOT_BYTES);
                tma_mc(dst0 + slot * SLOT_BYTES, &maps.wo, 512, g * 512 + kc * 128 + rank * 64,
                       sbase + OFF_FULL + slot * 8);
                adv8();
            }
            const CUtensorMap* mg = rank ? &maps.wu : &maps.wg;
#pragma unroll 1
            for (int ch = 0; ch < 9; ch++)
#pragma unroll 1
                for (int kc = 0; kc < 9; kc++) {
                    acquire(SLOT_BYTES);
                    tma_mc(dst0 + slot * SLOT_BYTES, mg, g * 576 + ch * 64, kc * 64, sbase + OFF_FULL + slot * 8);
                    adv6();
                }
#pragma unroll 1
            for (int p = 0; p < 4; p++)
#pragma unroll 1
                for (int kc = 0; kc < 9; kc++) {
                    acquire(SLOT_BYTES);
                    tma_mc(dst0 + slot * SLOT_BYTES, &maps.wd, p * 128 + rank * 64, g * 576 + kc * 64,
                           sbase + OFF_FULL + slot * 8);
                    adv6();
                }
#pragma unroll 1
            for (int kc = 0; kc < 5; kc++) {
                acquire(kc < 4 ? SLOT_BYTES : BOX_BYTES);
                if (kc < 4 || rank == 0)
                    tma_mc(dst0 + slot * SLOT_BYTES, &maps.wd, 512, g * 576 + kc * 128 + rank * 64,
                           sbase + OFF_FULL + slot * 8);
                adv6();
            }
        }
    } else {
        asm volatile("setmaxnreg.inc.sync.aligned.u32 240;");
        const int wg = warp >> 2;
        const int tid = threadIdx.x;
        Ctx cx;
        cx.sbase = sbase;
        cx.rel_cta = (lane == 0 && (warp & 3) < 2) ? (warp & 3) : 2;
        const uint32_t red = sbase + OFF_RED;
        const int own = mt * 8 + g;
        const int orow = own * 16 + (lane >> 2);
        const int wown = mt * 8 + warp;
        Ring ring{0u, 0u};
        uint32_t a[144];

        PROF(0);
        PROFG(30);
        {
            uint4 w1[5], w2[5];
            float sc[5];
            uint32_t xs[18];
            unsigned short cu[5];
            const int half = tid & 1, r0 = tid >> 1;
            const bool second = b < 88;
#pragma unroll
            for (int i = 0; i < 5; i++) {
                const int row = min(r0 + 128 * i, DM - 1);
                cu[i] = __ldg(reinterpret_cast<const unsigned short*>(cvec) + row);
                w1[i] = __ldg(reinterpret_cast<const uint4*>(wmod + (size_t)row * (6 * DM) + half * 8) + b * 2);
            }
#pragma unroll
            for (int j = 0; j < 9; j++) {
                const int col = (warp * 9 + j) * 8 + (lane & 3) * 2;
                xs[2 * j] = __ldg(reinterpret_cast<const uint32_t*>(x + (size_t)orow * DM + col));
                xs[2 * j + 1] = __ldg(reinterpret_cast<const uint32_t*>(x + (size_t)(orow + 8) * DM + col));
            }
#pragma unroll
            for (int i = 0; i < 5; i++) {
                const int row = min(r0 + 128 * i, DM - 1);
                w2[i] = __ldg(reinterpret_cast<const uint4*>(wmod + (size_t)row * (6 * DM) + half * 8) +
                              (second ? 128 + b : b) * 2);
            }
            PROFR(17);
            asm volatile("barrier.cluster.arrive.relaxed.aligned;" ::: "memory");
#pragma unroll
            for (int i = 0; i < 5; i++) {
                const float cv = bf_lo(cu[i]);
                const float sv = round_bf16(cv * rcp(1.f + ex2(-1.4426950408889634f * cv)));
                sc[i] = (r0 + 128 * i < DM) ? sv : 0.f;
            }
            pin(sc);
            PROFR(18);
            mod_block(w1, sc, b, red + 1024, warp, lane);
            PROFR(19);
            float v[36];
#pragma unroll
            for (int j = 0; j < 9; j++) {
                v[4 * j] = bf_lo(xs[2 * j]);
                v[4 * j + 1] = bf_hi(xs[2 * j]);
                v[4 * j + 2] = bf_lo(xs[2 * j + 1]);
                v[4 * j + 3] = bf_hi(xs[2 * j + 1]);
            }
            pin(v);
            PROFR(20);
            layernorm_rows(v, red, warp, lane);
            PROFR(21);
            if (second) mod_block(w2, sc, 128 + b, red + 1024, warp, lane);
            PROF(1);
            PROFR(22);
            float md[2][18];
            const int which[2] = {0, 1};
            load_mod<2>(md, which, warp, lane);
            PROF(2);
            modulate_store(v, md[0], md[1], g_h1 + (size_t)own * 36 * 32, warp, lane);
            __syncwarp();
            if (lane == 0) signal_cnt(CNT_H1 + own);
            asm volatile("barrier.cluster.wait.aligned;" ::: "memory");
        }

        const uint32_t spill = sbase + 8 * SLOT_BYTES + wg * SLOT_BYTES + (tid & 127) * 16;
        uint32_t q[32];
        PROF(3);
        wait_cnt(CNT_H1 + wown, 8);
        PROF(4);
        load_frags(a, g_h1 + (size_t)wown * 36 * 32 + lane);
        {
            float d[64];
#pragma unroll 1
            for (int hq = 0;; hq++) {
                gemm_n128<9, 8>(d, a, cx, ring);
                if (hq == 3) break;
#pragma unroll
                for (int v = 0; v < 8; v++)
                    sts128(spill + hq * 32768 + v * 2048, pack_bf16(d[8 * v], d[8 * v + 1]),
                           pack_bf16(d[8 * v + 2], d[8 * v + 3]), pack_bf16(d[8 * v + 4], d[8 * v + 5]),
                           pack_bf16(d[8 * v + 6], d[8 * v + 7]));
            }
#pragma unroll
            for (int i = 0; i < 32; i++) q[i] = pack_bf16(d[2 * i], d[2 * i + 1]);
        }

        PROF(5);
        {
            float o[64], sa[32], sb[32];
            uint32_t p[32];
#pragma unroll
            for (int i = 0; i < 64; i++) o[i] = 0.f;
            float n0, n1, l0 = 0.f, l1 = 0.f;
            const uint64_t dbase = desc_of(sbase);
            const uint64_t dbk = dbase - (511u << 16);
            const int my_bar = 1 + wg, other_bar = 2 - wg;

            cx.wait_full(4, 0);
            if (wg == 1) bar_sync(my_bar, 256);
            wg_fence();
            qk_half(sa, q, dbk + 4 * 1024);
            qk_half(sb, q, dbk + 4 * 1024 + 512);
            wg_commit();
            bar_arrive(other_bar, 256);
            wg_wait<0>();
            pin(sa);
            pin(sb);
            cx.release(4);
            row_max(sa, sb, n0, n1);
            n0 *= -SM_SCALE;
            n1 *= -SM_SCALE;
            exp_half<0>(sa, p, n0, n1, l0, l1);
            exp_half<16>(sb, p, n0, n1, l0, l1);
#pragma unroll 1
            for (int t = 1; t < 64; t++) {
                const int j = t & 15;
                const uint32_t ks = 4 - 4 * (t & 1), vs = 2 + 4 * (t & 1);
                const uint32_t kph = ((36 + 4 * t) >> 3) & 1, vph = ((34 + 4 * t) >> 3) & 1;
                if (j == 0) {
                    const uint32_t src = spill + ((t >> 4) - 1) * 32768;
#pragma unroll
                    for (int v = 0; v < 8; v++) lds128(src + v * 2048, q[4 * v], q[4 * v + 1], q[4 * v + 2], q[4 * v + 3]);
                }
                TL(0);
                cx.wait_full(vs, vph);
                cx.wait_full(ks, kph);
                TL(1);
                bar_sync(my_bar, 256);
                TL(2);
                wg_fence();
                const uint64_t dk = dbk + ks * 1024, dv = dbase + vs * 1024;
#pragma unroll
                for (int k = 0; k < 8; k++)
                    wgmma_n128<1>(o, p[4 * k], p[4 * k + 1], p[4 * k + 2], p[4 * k + 3],
                                  dv + (k >> 2) * 1024 + (k & 3) * 128, k != 0 ? 1 : (j != 1));
                qk_half(sa, q, dk);
                wg_commit();
                qk_half(sb, q, dk + 512);
                wg_commit();
                bar_arrive(other_bar, 256);
                TL(3);
                wg_wait<1>();
                pin(o);
                pin(sa);
                pin(p);
                TL(4);
                cx.release(vs);
                float s0 = 0.f, s1 = 0.f;
                bool slow = (j == 0);
                if (slow) {
                    float t0 = l0 + __shfl_xor_sync(0xffffffffu, l0, 1);
                    float t1 = l1 + __shfl_xor_sync(0xffffffffu, l1, 1);
                    t0 += __shfl_xor_sync(0xffffffffu, t0, 2);
                    t1 += __shfl_xor_sync(0xffffffffu, t1, 2);
                    const float i0 = rcp(t0), i1 = rcp(t1);
                    const uint32_t dst = spill + ((t >> 4) - 1) * 32768;
#pragma unroll
                    for (int v = 0; v < 8; v++)
                        sts128(dst + v * 2048, pack_bf16(o[8 * v] * i0, o[8 * v + 1] * i0),
                               pack_bf16(o[8 * v + 2] * i1, o[8 * v + 3] * i1),
                               pack_bf16(o[8 * v + 4] * i0, o[8 * v + 5] * i0),
                               pack_bf16(o[8 * v + 6] * i1, o[8 * v + 7] * i1));
                    n0 = INFINITY;
                    n1 = INFINITY;
                } else {
                    exp_half<0>(sa, p, n0, n1, s0, s1);
                }
                TL(5);
                wg_wait<0>();
                pin(sb);
                TL(6);
                cx.release(ks);
                if (!slow) {
                    exp_half<16>(sb, p, n0, n1, s0, s1);
                    slow = __any_sync(0xffffffffu, !(fmaxf(s0, s1) <= SM_LIMIT));
                }
                if (slow) {
                    float x0, x1;
                    row_max(sa, sb, x0, x1);
                    x0 = fminf(-x0 * SM_SCALE, n0);
                    x1 = fminf(-x1 * SM_SCALE, n1);
                    const float al0 = ex2(x0 - n0), al1 = ex2(x1 - n1);
                    n0 = x0;
                    n1 = x1;
                    l0 *= al0;
                    l1 *= al1;
                    if (j != 0) {
#pragma unroll
                        for (int i = 0; i < 16; i++) {
                            o[4 * i] *= al0;
                            o[4 * i + 1] *= al0;
                            o[4 * i + 2] *= al1;
                            o[4 * i + 3] *= al1;
                        }
                    }
                    s0 = 0.f;
                    s1 = 0.f;
                    exp_half<0>(sa, p, n0, n1, s0, s1);
                    exp_half<16>(sb, p, n0, n1, s0, s1);
                }
                l0 += s0;
                l1 += s1;
                TL(7);
            }
            cx.wait_full(2, 0);
            bar_sync(my_bar, 256);
            wg_fence();
#pragma unroll
            for (int k = 0; k < 8; k++)
                wgmma_n128<1>(o, p[4 * k], p[4 * k + 1], p[4 * k + 2], p[4 * k + 3],
                              dbase + (2 + (k >> 2)) * 1024 + (k & 3) * 128, 1);
            wg_commit();
            if (wg == 0) bar_arrive(other_bar, 256);
            float t0 = l0 + __shfl_xor_sync(0xffffffffu, l0, 1), t1 = l1 + __shfl_xor_sync(0xffffffffu, l1, 1);
            t0 += __shfl_xor_sync(0xffffffffu, t0, 2);
            t1 += __shfl_xor_sync(0xffffffffu, t1, 2);
            const float i0 = rcp(t0), i1 = rcp(t1);
            wg_wait<0>();
            pin(o);
            cx.release(2);
#pragma unroll
            for (int i = 0; i < 16; i++) {
                a[96 + 2 * i] = pack_bf16(o[4 * i] * i0, o[4 * i + 1] * i0);
                a[96 + 2 * i + 1] = pack_bf16(o[4 * i + 2] * i1, o[4 * i + 3] * i1);
            }
#pragma unroll
            for (int v = 0; v < 24; v++)
                lds128(spill + (v >> 3) * 32768 + (v & 7) * 2048, a[4 * v], a[4 * v + 1], a[4 * v + 2], a[4 * v + 3]);
        }

        PROF(6);
        uint2* part_dst = g_part + ((size_t)wown * 8 + g) * 72 * 32 + lane;
        const uint2* part_src = g_part + (size_t)own * 8 * 72 * 32 + lane;
        float4* x2buf = g_x2 + (size_t)b * 9 * 256 + tid;
        ring.slot = 4;
        ring.phase = 0;
        proj_partials<8, 8>(a, cx, ring, part_dst);
        __syncwarp();
        PROF(7);
        if (lane == 0) signal_cnt(CNT_P1 + wown);
        PROF(8);

        {
            float v[36];
            uint32_t xs[18];
#pragma unroll
            for (int j = 0; j < 9; j++) {
                const int col = (warp * 9 + j) * 8 + (lane & 3) * 2;
                xs[2 * j] = __ldg(reinterpret_cast<const uint32_t*>(x + (size_t)orow * DM + col));
                xs[2 * j + 1] = __ldg(reinterpret_cast<const uint32_t*>(x + (size_t)(orow + 8) * DM + col));
            }
            float md[3][18];
            const int which[3] = {2, 3, 4};
            load_mod<3>(md, which, warp, lane);
            wait_cnt(CNT_P1 + own, 8);
            PROF(9);
            sum_partials(v, part_src, warp);
#pragma unroll
            for (int j = 0; j < 9; j++) {
                v[4 * j] = fmaf(md[0][2 * j], v[4 * j], bf_lo(xs[2 * j]));
                v[4 * j + 1] = fmaf(md[0][2 * j + 1], v[4 * j + 1], bf_hi(xs[2 * j]));
                v[4 * j + 2] = fmaf(md[0][2 * j], v[4 * j + 2], bf_lo(xs[2 * j + 1]));
                v[4 * j + 3] = fmaf(md[0][2 * j + 1], v[4 * j + 3], bf_hi(xs[2 * j + 1]));
                __stcg(x2buf + j * 256, make_float4(v[4 * j], v[4 * j + 1], v[4 * j + 2], v[4 * j + 3]));
            }
            PROF(10);
            layernorm_rows(v, red, warp, lane);
            modulate_store(v, md[1], md[2], g_h2 + (size_t)own * 36 * 32, warp, lane);
            __syncwarp();
            if (lane == 0) signal_cnt(CNT_H2 + own);
        }

        PROF(11);
        wait_cnt(CNT_H2 + wown, 8);
        PROF(12);
        load_frags(a, g_h2 + (size_t)wown * 36 * 32 + lane);
        ring.slot = 0;
        ring.phase = 1;
        const uint32_t hsp = sbase + 6 * SLOT_BYTES + wg * BOX_BYTES + (tid & 127) * 16;
        {
            float d[64];
#pragma unroll 1
            for (int ch = 0;; ch++) {
                gemm_n128<9, 6>(d, a, cx, ring);
#pragma unroll
                for (int i = 0; i < 32; i++) {
                    const float gv = d[i];
                    const float k1 = -2.f * 0.7978845608028654f * 1.4426950408889634f;
                    const float zz = gv * fmaf(gv * gv, k1 * 0.044715f, k1);
                    d[i] = gv * rcp(1.f + ex2(zz)) * d[32 + i];
                }
                if (ch == 8) break;
                const uint32_t dst = hsp + ((ch + 2) & 7) * SLOT_BYTES;
#pragma unroll
                for (int v = 0; v < 4; v++)
                    sts128(dst + v * 2048, pack_bf16(d[8 * v], d[8 * v + 1]), pack_bf16(d[8 * v + 2], d[8 * v + 3]),
                           pack_bf16(d[8 * v + 4], d[8 * v + 5]), pack_bf16(d[8 * v + 6], d[8 * v + 7]));
            }
#pragma unroll
            for (int i = 0; i < 16; i++) a[128 + i] = pack_bf16(d[2 * i], d[2 * i + 1]);
        }
#pragma unroll
        for (int v = 0; v < 32; v++)
            lds128(hsp + (((v >> 2) + 2) & 7) * SLOT_BYTES + (v & 3) * 2048, a[4 * v], a[4 * v + 1], a[4 * v + 2],
                   a[4 * v + 3]);

        PROF(13);
        proj_partials<9, 6>(a, cx, ring, part_dst);
        asm volatile("barrier.cluster.arrive.relaxed.aligned;" ::: "memory");
        __syncwarp();
        PROF(14);
        if (lane == 0) signal_cnt(CNT_P2 + wown);

        {
            float v[36];
            float4 xr[9];
            float gb[1][18];
#pragma unroll
            for (int j = 0; j < 9; j++) xr[j] = __ldcg(x2buf + j * 256);
            const int which[1] = {5};
            load_mod<1>(gb, which, warp, lane);
            wait_cnt(CNT_P2 + own, 8);
            PROF(15);
            sum_partials(v, part_src, warp);
#pragma unroll
            for (int j = 0; j < 9; j++) {
                const int col = (warp * 9 + j) * 8 + (lane & 3) * 2;
                *reinterpret_cast<uint32_t*>(out + (size_t)orow * DM + col) =
                    pack_bf16(fmaf(gb[0][2 * j], v[4 * j], xr[j].x), fmaf(gb[0][2 * j + 1], v[4 * j + 1], xr[j].y));
                *reinterpret_cast<uint32_t*>(out + (size_t)(orow + 8) * DM + col) =
                    pack_bf16(fmaf(gb[0][2 * j], v[4 * j + 2], xr[j].z), fmaf(gb[0][2 * j + 1], v[4 * j + 3], xr[j].w));
            }
        }
        PROF(16);
        PROFG(31);
        bar_sync(3, 256);
        if (warp == 0) {
            unsigned old = 0;
            if (lane == 0)
                asm volatile("atom.acq_rel.gpu.global.add.u32 %0, [%1], 1;" : "=r"(old) : "l"(&g_cnt[CNT_DONE * 32]) : "memory");
            old = __shfl_sync(0xffffffffu, old, 0);
            if (old == 127) {
                for (int i = lane; i < CNT_TOTAL; i += 32) g_cnt[i * 32] = 0;
                for (int i = lane; i < 6 * DM / 4; i += 32) reinterpret_cast<uint4*>(g_mod)[i] = make_uint4(0, 0, 0, 0);
            }
        }
        asm volatile("barrier.cluster.wait.aligned;" ::: "memory");
    }
}

typedef CUresult (*EncodeFn)(CUtensorMap*, CUtensorMapDataType, cuuint32_t, void*, const cuuint64_t*, const cuuint64_t*,
                             const cuuint32_t*, const cuuint32_t*, CUtensorMapInterleave, CUtensorMapSwizzle,
                             CUtensorMapL2promotion, CUtensorMapFloatOOBfill);

void make_map(EncodeFn enc, CUtensorMap* m, const void* ptr, uint64_t rows, uint64_t cols) {
    cuuint64_t gdim[2] = {cols, rows};
    cuuint64_t gstr[1] = {cols * 2};
    cuuint32_t box[2] = {64, 64};
    cuuint32_t estr[2] = {1, 1};
    enc(m, CU_TENSOR_MAP_DATA_TYPE_BFLOAT16, 2, const_cast<void*>(ptr), gdim, gstr, box, estr,
        CU_TENSOR_MAP_INTERLEAVE_NONE, CU_TENSOR_MAP_SWIZZLE_128B, CU_TENSOR_MAP_L2_PROMOTION_L2_128B,
        CU_TENSOR_MAP_FLOAT_OOB_FILL_NONE);
}

}

extern "C" void kernel_launch(void* const* d_in, const int* in_sizes, int n_in, void* d_out, int out_size) {
    (void)in_sizes;
    (void)n_in;
    (void)out_size;
    void* fn = nullptr;
    cudaDriverEntryPointQueryResult qr;
    cudaGetDriverEntryPoint("cuTensorMapEncodeTiled", &fn, cudaEnableDefault, &qr);
    EncodeFn enc = (EncodeFn)fn;
    Maps maps;
    make_map(enc, &maps.k, d_in[1], 32 * 2048, 128);
    make_map(enc, &maps.v, d_in[2], 32 * 2048, 128);
    make_map(enc, &maps.wq, d_in[3], 576, 4096);
    make_map(enc, &maps.wo, d_in[4], 4096, 576);
    make_map(enc, &maps.wg, d_in[6], 576, 4608);
    make_map(enc, &maps.wu, d_in[7], 576, 4608);
    make_map(enc, &maps.wd, d_in[8], 4608, 576);
    cudaFuncSetAttribute(fused_block_kernel, cudaFuncAttributeMaxDynamicSharedMemorySize, SMEM_BYTES);
    fused_block_kernel<<<128, 384, SMEM_BYTES>>>(maps, (const __nv_bfloat16*)d_in[0], (const __nv_bfloat16*)d_in[9],
                                                 (const __nv_bfloat16*)d_in[10], (__nv_bfloat16*)d_out);
}
```

```cpp
#include <cuda_runtime.h>
#include <cuda_bf16.h>
#include <cuda.h>
#include <stdint.h>

namespace {

constexpr int DM = 576;
constexpr int SLOT_BYTES = 16384;
constexpr int BOX_BYTES = 8192;
constexpr int NUNITS = 14;
constexpr int SMEM_TAIL = NUNITS * SLOT_BYTES;
constexpr int SMEM_BYTES = SMEM_TAIL + 2048 + 1024;
constexpr int OFF_FULL = SMEM_TAIL;
constexpr int OFF_EMPTY = SMEM_TAIL + 64;
constexpr int OFF_RED = SMEM_TAIL + 128;

constexpr int CNT_DONE = 2, CNT_H1 = 8, CNT_P1 = 8 + 128, CNT_H2 = 8 + 256,
              CNT_P2 = 8 + 384, CNT_TOTAL = 8 + 512;

__device__ __align__(16) uint32_t g_mod[6 * DM];
__device__ uint4 g_h1[128 * 36 * 32];
__device__ uint4 g_h2[128 * 36 * 32];
__device__ uint2 g_part[128 * 8 * 72 * 32];
__device__ float4 g_x2[128 * 9 * 256];
__device__ unsigned g_cnt[CNT_TOTAL * 32];

#define TL(i)
#define PROFR(i)
#define PROF(i)
#define PROFG(i)

struct Maps {
    CUtensorMap k, v, wq, wo, wg, wu, wd;
};

__device__ __forceinline__ uint32_t smem_u32(const void* p) { return (uint32_t)__cvta_generic_to_shared(p); }
__device__ __forceinline__ void mbar_init(uint32_t a, uint32_t c) {
    asm volatile("mbarrier.init.shared::cta.b64 [%0], %1;" ::"r"(a), "r"(c) : "memory");
}
__device__ __forceinline__ void mbar_expect_tx(uint32_t a, uint32_t bytes) {
    asm volatile("mbarrier.arrive.expect_tx.shared::cta.b64 _, [%0], %1;" ::"r"(a), "r"(bytes) : "memory");
}
__device__ __forceinline__ bool mbar_try(uint32_t a, uint32_t ph) {
    uint32_t ok;
    asm volatile(
        "{\n.reg .pred p;\nmbarrier.try_wait.parity.shared::cta.b64 p, [%1], %2;\nselp.u32 %0, 1, 0, p;\n}"
        : "=r"(ok)
        : "r"(a), "r"(ph)
        : "memory");
    return ok != 0;
}
__device__ __forceinline__ uint32_t clk32() {
    uint32_t c;
    asm volatile("mov.u32 %0, %%clock;" : "=r"(c));
    return c;
}
constexpr uint32_t WAIT_LIMIT = 1u << 30;
__device__ __forceinline__ void mbar_wait(uint32_t a, uint32_t ph) {
    if (mbar_try(a, ph)) return;
    uint32_t t0 = clk32();
    while (!mbar_try(a, ph)) {
        if (clk32() - t0 > WAIT_LIMIT) break;
    }
}
__device__ __forceinline__ void mbar_arrive_cluster(uint32_t a, uint32_t cta) {
    asm volatile(
        "{\n.reg .b32 ra;\nmapa.shared::cluster.u32 ra, %0, %1;\nmbarrier.arrive.shared::cluster.b64 _, [ra];\n}" ::"r"(a),
        "r"(cta)
        : "memory");
}
__device__ __forceinline__ void tma_mc(uint32_t dst, const CUtensorMap* m, int c0, int c1, uint32_t bar) {
    asm volatile(
        "cp.async.bulk.tensor.2d.shared::cluster.global.mbarrier::complete_tx::bytes.multicast::cluster"
        " [%0], [%1, {%3, %4}], [%2], %5;" ::"r"(dst),
        "l"(m), "r"(bar), "r"(c0), "r"(c1), "h"((uint16_t)3)
        : "memory");
}
__device__ __forceinline__ void bar_sync(int id, int n) { asm volatile("bar.sync %0, %1;" ::"r"(id), "r"(n) : "memory"); }
__device__ __forceinline__ void bar_arrive(int id, int n) {
    asm volatile("bar.arrive %0, %1;" ::"r"(id), "r"(n) : "memory");
}
__device__ __forceinline__ void wg_fence() { asm volatile("wgmma.fence.sync.aligned;" ::: "memory"); }
__device__ __forceinline__ void wg_commit() { asm volatile("wgmma.commit_group.sync.aligned;" ::: "memory"); }
template <int N>
__device__ __forceinline__ void wg_wait() {
    asm volatile("wgmma.wait_group.sync.aligned %0;" ::"n"(N) : "memory");
}
template <int N>
__device__ __forceinline__ void pin(float (&d)[N]) {
#pragma unroll
    for (int i = 0; i < N; i++) asm volatile("" : "+f"(d[i])::"memory");
}
template <int N>
__device__ __forceinline__ void pin(uint32_t (&d)[N]) {
#pragma unroll
    for (int i = 0; i < N; i++) asm volatile("" : "+r"(d[i])::"memory");
}
__device__ __forceinline__ uint32_t pack_bf16(float lo, float hi) {
    uint32_t r;
    asm("cvt.rn.bf16x2.f32 %0, %1, %2;" : "=r"(r) : "f"(hi), "f"(lo));
    return r;
}
__device__ __forceinline__ float bf_lo(uint32_t v) { return __uint_as_float(v << 16); }
__device__ __forceinline__ float bf_hi(uint32_t v) { return __uint_as_float(v & 0xffff0000u); }
__device__ __forceinline__ float round_bf16(float v) { return __bfloat162float(__float2bfloat16_rn(v)); }
__device__ __forceinline__ float ex2(float x) {
    float y;
    asm("ex2.approx.ftz.f32 %0, %1;" : "=f"(y) : "f"(x));
    return y;
}
__device__ __forceinline__ float rcp(float x) {
    float y;
    asm("rcp.approx.ftz.f32 %0, %1;" : "=f"(y) : "f"(x));
    return y;
}
__device__ __forceinline__ void sts128(uint32_t a, uint32_t x, uint32_t y, uint32_t z, uint32_t w) {
    asm volatile("st.shared.v4.b32 [%0], {%1,%2,%3,%4};" ::"r"(a), "r"(x), "r"(y), "r"(z), "r"(w) : "memory");
}
__device__ __forceinline__ void lds128(uint32_t a, uint32_t& x, uint32_t& y, uint32_t& z, uint32_t& w) {
    asm volatile("ld.shared.v4.b32 {%0,%1,%2,%3}, [%4];" : "=r"(x), "=r"(y), "=r"(z), "=r"(w) : "r"(a) : "memory");
}
__device__ __forceinline__ void sts32f(uint32_t a, float v) {
    asm volatile("st.shared.f32 [%0], %1;" ::"r"(a), "f"(v) : "memory");
}
__device__ __forceinline__ float lds32f(uint32_t a) {
    float v;
    asm volatile("ld.shared.f32 %0, [%1];" : "=f"(v) : "r"(a) : "memory");
    return v;
}
__device__ __forceinline__ void signal_cnt(int idx) {
    asm volatile("red.release.gpu.global.add.u32 [%0], 1;" ::"l"(&g_cnt[idx * 32]) : "memory");
}
__device__ __forceinline__ void wait_cnt(int idx, unsigned target) {
    if ((threadIdx.x & 31) == 0) {
        uint32_t t0 = clk32();
        while (true) {
            unsigned v;
            asm volatile("ld.acquire.gpu.global.u32 %0, [%1];" : "=r"(v) : "l"(&g_cnt[idx * 32]) : "memory");
            if (v >= target) break;
            if (clk32() - t0 > WAIT_LIMIT) break;
        }
    }
    __syncwarp();
}

#define F8(d, b) \
    "+f"(d[b]), "+f"(d[b + 1]), "+f"(d[b + 2]), "+f"(d[b + 3]), "+f"(d[b + 4]), "+f"(d[b + 5]), "+f"(d[b + 6]), "+f"(d[b + 7])

template <int TB>
__device__ __forceinline__ void wgmma_n128(float (&d)[64], uint32_t a0, uint32_t a1, uint32_t a2, uint32_t a3,
                                           uint64_t db, int sc) {
    asm volatile(
        "{\n.reg .pred p;\nsetp.ne.b32 p, %69, 0;\n"
        "wgmma.mma_async.sync.aligned.m64n128k16.f32.bf16.bf16 "
        "{%0,%1,%2,%3,%4,%5,%6,%7,%8,%9,%10,%11,%12,%13,%14,%15,%16,%17,%18,%19,%20,%21,%22,%23,%24,%25,%26,%27,%28,%29,%30,%31,"
        "%32,%33,%34,%35,%36,%37,%38,%39,%40,%41,%42,%43,%44,%45,%46,%47,%48,%49,%50,%51,%52,%53,%54,%55,%56,%57,%58,%59,%60,%61,%62,%63},"
        "{%64,%65,%66,%67}, %68, p, 1, 1, %70;\n}"
        : F8(d, 0), F8(d, 8), F8(d, 16), F8(d, 24), F8(d, 32), F8(d, 40), F8(d, 48), F8(d, 56)
        : "r"(a0), "r"(a1), "r"(a2), "r"(a3), "l"(db), "r"(sc), "n"(TB));
}
#define O8(d, b) \
    "=f"(d[b]), "=f"(d[b + 1]), "=f"(d[b + 2]), "=f"(d[b + 3]), "=f"(d[b + 4]), "=f"(d[b + 5]), "=f"(d[b + 6]), "=f"(d[b + 7])
template <int TB>
__device__ __forceinline__ void wgmma_n128_z(float (&d)[64], uint32_t a0, uint32_t a1, uint32_t a2, uint32_t a3,
                                             uint64_t db) {
    asm volatile(
        "wgmma.mma_async.sync.aligned.m64n128k16.f32.bf16.bf16 "
        "{%0,%1,%2,%3,%4,%5,%6,%7,%8,%9,%10,%11,%12,%13,%14,%15,%16,%17,%18,%19,%20,%21,%22,%23,%24,%25,%26,%27,%28,%29,%30,%31,"
        "%32,%33,%34,%35,%36,%37,%38,%39,%40,%41,%42,%43,%44,%45,%46,%47,%48,%49,%50,%51,%52,%53,%54,%55,%56,%57,%58,%59,%60,%61,%62,%63},"
        "{%64,%65,%66,%67}, %68, 0, 1, 1, %69;"
        : O8(d, 0), O8(d, 8), O8(d, 16), O8(d, 24), O8(d, 32), O8(d, 40), O8(d, 48), O8(d, 56)
        : "r"(a0), "r"(a1), "r"(a2), "r"(a3), "l"(db), "n"(TB));
}
template <int TB>
__device__ __forceinline__ void wgmma_n64_z(float (&d)[32], uint32_t a0, uint32_t a1, uint32_t a2, uint32_t a3,
                                            uint64_t db) {
    asm volatile(
        "wgmma.mma_async.sync.aligned.m64n64k16.f32.bf16.bf16 "
        "{%0,%1,%2,%3,%4,%5,%6,%7,%8,%9,%10,%11,%12,%13,%14,%15,%16,%17,%18,%19,%20,%21,%22,%23,%24,%25,%26,%27,%28,%29,%30,%31},"
        "{%32,%33,%34,%35}, %36, 0, 1, 1, %37;"
        : O8(d, 0), O8(d, 8), O8(d, 16), O8(d, 24)
        : "r"(a0), "r"(a1), "r"(a2), "r"(a3), "l"(db), "n"(TB));
}
template <int TB>
__device__ __forceinline__ void wgmma_n64(float (&d)[32], uint32_t a0, uint32_t a1, uint32_t a2, uint32_t a3,
                                          uint64_t db) {
    asm volatile(
        "wgmma.mma_async.sync.aligned.m64n64k16.f32.bf16.bf16 "
        "{%0,%1,%2,%3,%4,%5,%6,%7,%8,%9,%10,%11,%12,%13,%14,%15,%16,%17,%18,%19,%20,%21,%22,%23,%24,%25,%26,%27,%28,%29,%30,%31},"
        "{%32,%33,%34,%35}, %36, 1, 1, 1, %37;"
        : F8(d, 0), F8(d, 8), F8(d, 16), F8(d, 24)
        : "r"(a0), "r"(a1), "r"(a2), "r"(a3), "l"(db), "n"(TB));
}

__device__ __forceinline__ uint64_t desc_of(uint32_t saddr) {
    return (uint64_t)(((saddr >> 4) & 0x3FFFu) | (512u << 16)) | ((uint64_t)(64u | (1u << 30)) << 32);
}

struct Ring {
    uint32_t slot;
    uint32_t phase;
    template <int NS>
    __device__ __forceinline__ void next() {
        if (++slot == NS) {
            slot = 0;
            phase ^= 1;
        }
    }
};

struct Ctx {
    uint32_t sbase;
    uint32_t rel_cta;
    __device__ __forceinline__ void wait_full(uint32_t slot, uint32_t phase) const {
        mbar_wait(sbase + OFF_FULL + slot * 8, phase);
    }
    __device__ __forceinline__ void release(uint32_t slot) const {
        if (rel_cta < 2) mbar_arrive_cluster(sbase + OFF_EMPTY + slot * 8, rel_cta);
    }
};

template <int NK, int NS, int NA>
__device__ __forceinline__ void gemm_n128(float (&d)[64], const uint32_t (&a)[NA], const Ctx& c, Ring& r) {
    uint32_t prev = 0;
#pragma unroll
    for (int s = 0; s < NK; s++) {
        c.wait_full(r.slot, r.phase);
        uint64_t db = desc_of(c.sbase + r.slot * SLOT_BYTES);
        wg_fence();
#pragma unroll
        for (int k = 0; k < 4; k++) {
            if ((s | k) == 0)
                wgmma_n128_z<1>(d, a[0], a[1], a[2], a[3], db);
            else
                wgmma_n128<1>(d, a[s * 16 + k * 4], a[s * 16 + k * 4 + 1], a[s * 16 + k * 4 + 2], a[s * 16 + k * 4 + 3],
                              db + k * 128, 1);
        }
        wg_commit();
        if (s > 0) {
            wg_wait<1>();
            c.release(prev);
        }
        prev = r.slot;
        r.template next<NS>();
    }
    wg_wait<0>();
    c.release(prev);
    pin(d);
}
template <int NKS, int NS, int NA>
__device__ __forceinline__ void gemm_n64(float (&d)[32], const uint32_t (&a)[NA], const Ctx& c, Ring& r) {
    uint32_t prev = 0;
    constexpr int NSL = (NKS + 7) / 8;
#pragma unroll
    for (int s = 0; s < NSL; s++) {
        c.wait_full(r.slot, r.phase);
        uint64_t db = desc_of(c.sbase + r.slot * SLOT_BYTES);
        wg_fence();
#pragma unroll
        for (int k = 0; k < 8; k++) {
            if ((s | k) == 0)
                wgmma_n64_z<1>(d, a[0], a[1], a[2], a[3], db);
            else if (s * 8 + k < NKS)
                wgmma_n64<1>(d, a[s * 32 + k * 4], a[s * 32 + k * 4 + 1], a[s * 32 + k * 4 + 2], a[s * 32 + k * 4 + 3],
                             db + k * 128);
        }
        wg_commit();
        if (s > 0) {
            wg_wait<1>();
            c.release(prev);
        }
        prev = r.slot;
        r.template next<NS>();
    }
    wg_wait<0>();
    c.release(prev);
    pin(d);
}

template <int NK, int NS, int NA>
__device__ __forceinline__ void proj_partials(const uint32_t (&a)[NA], const Ctx& c, Ring& r,
                                              uint2* dst  ) {
#pragma unroll 1
    for (int p = 0; p < 4; p++) {
        float d[64];
        gemm_n128<NK, NS>(d, a, c, r);
#pragma unroll
        for (int j = 0; j < 16; j++)
            __stcg(dst + (p * 16 + j) * 32, make_uint2(pack_bf16(d[4 * j], d[4 * j + 1]), pack_bf16(d[4 * j + 2], d[4 * j + 3])));
    }
    float d[32];
    gemm_n64<NK * 4, NS>(d, a, c, r);
#pragma unroll
    for (int j = 0; j < 8; j++)
        __stcg(dst + (64 + j) * 32, make_uint2(pack_bf16(d[4 * j], d[4 * j + 1]), pack_bf16(d[4 * j + 2], d[4 * j + 3])));
}

__device__ __forceinline__ void row_reduce(float& s0, float& s1, uint32_t red, int warp, int lane) {
    s0 += __shfl_xor_sync(0xffffffffu, s0, 1);
    s1 += __shfl_xor_sync(0xffffffffu, s1, 1);
    s0 += __shfl_xor_sync(0xffffffffu, s0, 2);
    s1 += __shfl_xor_sync(0xffffffffu, s1, 2);
    if ((lane & 3) == 0) {
        sts32f(red + (warp * 16 + (lane >> 2)) * 4, s0);
        sts32f(red + (warp * 16 + 8 + (lane >> 2)) * 4, s1);
    }
    bar_sync(3, 256);
    s0 = 0.f;
    s1 = 0.f;
#pragma unroll
    for (int w = 0; w < 8; w++) {
        s0 += lds32f(red + (w * 16 + (lane >> 2)) * 4);
        s1 += lds32f(red + (w * 16 + 8 + (lane >> 2)) * 4);
    }
}
__device__ __forceinline__ void layernorm_rows(float (&v)[36], uint32_t red, int warp, int lane) {
    float s0 = 0.f, s1 = 0.f;
#pragma unroll
    for (int j = 0; j < 9; j++) {
        s0 += v[4 * j] + v[4 * j + 1];
        s1 += v[4 * j + 2] + v[4 * j + 3];
    }
    row_reduce(s0, s1, red, warp, lane);
    const float m0 = s0 * (1.f / DM), m1 = s1 * (1.f / DM);
    s0 = 0.f;
    s1 = 0.f;
#pragma unroll
    for (int j = 0; j < 9; j++) {
        v[4 * j] -= m0;
        v[4 * j + 1] -= m0;
        v[4 * j + 2] -= m1;
        v[4 * j + 3] -= m1;
        s0 += v[4 * j] * v[4 * j] + v[4 * j + 1] * v[4 * j + 1];
        s1 += v[4 * j + 2] * v[4 * j + 2] + v[4 * j + 3] * v[4 * j + 3];
    }
    row_reduce(s0, s1, red + 512, warp, lane);
    const float r0 = rsqrtf(s0 * (1.f / DM) + 1e-5f), r1 = rsqrtf(s1 * (1.f / DM) + 1e-5f);
#pragma unroll
    for (int j = 0; j < 9; j++) {
        v[4 * j] *= r0;
        v[4 * j + 1] *= r0;
        v[4 * j + 2] *= r1;
        v[4 * j + 3] *= r1;
    }
}
template <int NV>
__device__ __forceinline__ void load_mod(float (&m)[NV][18], const int (&which)[NV], int warp, int lane) {
    const uint32_t t0 = clk32();
    while (true) {
        uint2 u[NV][9];
#pragma unroll
        for (int n = 0; n < NV; n++)
#pragma unroll
            for (int j = 0; j < 9; j++)
                asm volatile("ld.relaxed.gpu.global.v2.u32 {%0,%1}, [%2];"
                             : "=r"(u[n][j].x), "=r"(u[n][j].y)
                             : "l"(g_mod + which[n] * DM + (warp * 9 + j) * 8 + (lane & 3) * 2));
        uint32_t ok = 1;
#pragma unroll
        for (int n = 0; n < NV; n++)
#pragma unroll
            for (int j = 0; j < 9; j++) {
                ok &= u[n][j].x & u[n][j].y;
                m[n][2 * j] = __uint_as_float(u[n][j].x & 0xffff0000u);
                m[n][2 * j + 1] = __uint_as_float(u[n][j].y & 0xffff0000u);
            }
        if (__all_sync(0xffffffffu, ok) || clk32() - t0 > WAIT_LIMIT) break;
    }
}
__device__ __forceinline__ void modulate_store(const float (&v)[36], const float (&shift)[18], const float (&scale)[18],
                                               uint4* hbuf  , int warp, int lane) {
    uint2* dst = reinterpret_cast<uint2*>(hbuf);
#pragma unroll
    for (int j = 0; j < 9; j++) {
        const int grp = warp * 9 + j;
        const float c0 = round_bf16(1.f + scale[2 * j]), c1 = round_bf16(1.f + scale[2 * j + 1]);
        uint2 o;
        o.x = pack_bf16(fmaf(v[4 * j], c0, shift[2 * j]), fmaf(v[4 * j + 1], c1, shift[2 * j + 1]));
        o.y = pack_bf16(fmaf(v[4 * j + 2], c0, shift[2 * j]), fmaf(v[4 * j + 3], c1, shift[2 * j + 1]));
        __stcg(dst + ((grp >> 1) * 32 + lane) * 2 + (grp & 1), o);
    }
}
__device__ __forceinline__ void sum_partials(float (&v)[36], const uint2* src  , int warp) {
    uint2 t[8][9];
#pragma unroll
    for (int s = 0; s < 8; s++)
#pragma unroll
        for (int j = 0; j < 9; j++) t[s][j] = __ldcg(src + (s * 72 + warp * 9 + j) * 32);
#pragma unroll
    for (int j = 0; j < 9; j++) {
        float a = 0.f, b = 0.f, c = 0.f, d = 0.f;
#pragma unroll
        for (int s = 0; s < 8; s++) {
            a += bf_lo(t[s][j].x);
            b += bf_hi(t[s][j].x);
            c += bf_lo(t[s][j].y);
            d += bf_hi(t[s][j].y);
        }
        v[4 * j] = a;
        v[4 * j + 1] = b;
        v[4 * j + 2] = c;
        v[4 * j + 3] = d;
    }
}
__device__ __forceinline__ void load_frags(uint32_t (&a)[144], const uint4* src  ) {
#pragma unroll
    for (int k = 0; k < 36; k++) {
        uint4 t = __ldcg(src + k * 32);
        a[4 * k] = t.x;
        a[4 * k + 1] = t.y;
        a[4 * k + 2] = t.z;
        a[4 * k + 3] = t.w;
    }
}

constexpr float SM_SCALE = 0.08838834764831845f * 1.4426950408889634f;
constexpr float SM_LIMIT = 4294967296.f;
__device__ __forceinline__ void qk_step(float (&s)[32], const uint32_t (&q)[32], uint64_t dk) {
#pragma unroll
    for (int k = 0; k < 8; k++) {
        if (k == 0)
            wgmma_n64_z<0>(s, q[0], q[1], q[2], q[3], dk);
        else
            wgmma_n64<0>(s, q[4 * k], q[4 * k + 1], q[4 * k + 2], q[4 * k + 3], dk + (k >> 2) * 512 + (k & 3) * 2);
    }
}
__device__ __forceinline__ void pv_step(float (&o)[64], const uint32_t (&p)[16], uint64_t dv, int acc) {
#pragma unroll
    for (int k = 0; k < 4; k++)
        wgmma_n128<1>(o, p[4 * k], p[4 * k + 1], p[4 * k + 2], p[4 * k + 3], dv + k * 128, k != 0 ? 1 : acc);
}
__device__ __forceinline__ void exp_step(const float (&s)[32], uint32_t (&p)[16], float n0, float n1, float& s0,
                                         float& s1) {
#pragma unroll
    for (int i = 0; i < 8; i++) {
        const float e0 = ex2(fmaf(s[4 * i], SM_SCALE, n0)), e1 = ex2(fmaf(s[4 * i + 1], SM_SCALE, n0));
        const float e2 = ex2(fmaf(s[4 * i + 2], SM_SCALE, n1)), e3 = ex2(fmaf(s[4 * i + 3], SM_SCALE, n1));
        if (i == 0) {
            s0 = e0 + e1;
            s1 = e2 + e3;
        } else {
            s0 += e0 + e1;
            s1 += e2 + e3;
        }
        p[2 * i] = pack_bf16(e0, e1);
        p[2 * i + 1] = pack_bf16(e2, e3);
    }
}
struct SmState {
    float n0, n1;
    float l0, l1;
    float al0, al1;
    bool resc;
};
__device__ __forceinline__ void softmax_step(const float (&s)[32], uint32_t (&p)[16], SmState& st, bool fresh) {
    float s0, s1;
    bool slow = fresh;
    if (!slow) {
        exp_step(s, p, st.n0, st.n1, s0, s1);
        slow = __any_sync(0xffffffffu, !(fmaxf(s0, s1) <= SM_LIMIT));
    }
    if (slow) {
        float xa[8];
#pragma unroll
        for (int i = 0; i < 8; i++) xa[i] = fmaxf(fmaxf(s[i], s[8 + i]), fmaxf(s[16 + i], s[24 + i]));
        float x0 = fmaxf(fmaxf(xa[0], xa[1]), fmaxf(xa[4], xa[5]));
        float x1 = fmaxf(fmaxf(xa[2], xa[3]), fmaxf(xa[6], xa[7]));
        x0 = fmaxf(x0, __shfl_xor_sync(0xffffffffu, x0, 1));
        x1 = fmaxf(x1, __shfl_xor_sync(0xffffffffu, x1, 1));
        x0 = fmaxf(x0, __shfl_xor_sync(0xffffffffu, x0, 2));
        x1 = fmaxf(x1, __shfl_xor_sync(0xffffffffu, x1, 2));
        x0 *= -SM_SCALE;
        x1 *= -SM_SCALE;
        if (fresh) {
            st.l0 = 0.f;
            st.l1 = 0.f;
        } else {
            x0 = fminf(x0, st.n0);
            x1 = fminf(x1, st.n1);
            st.al0 = ex2(x0 - st.n0);
            st.al1 = ex2(x1 - st.n1);
            st.l0 *= st.al0;
            st.l1 *= st.al1;
            st.resc = true;
        }
        st.n0 = x0;
        st.n1 = x1;
        exp_step(s, p, x0, x1, s0, s1);
    }
    st.l0 += s0;
    st.l1 += s1;
}
__device__ __forceinline__ void apply_rescale(float (&o)[64], SmState& st) {
    if (st.resc) {
#pragma unroll
        for (int i = 0; i < 16; i++) {
            o[4 * i] *= st.al0;
            o[4 * i + 1] *= st.al0;
            o[4 * i + 2] *= st.al1;
            o[4 * i + 3] *= st.al1;
        }
        st.resc = false;
    }
}
__device__ __forceinline__ void inv_row_sums(float l0, float l1, float& i0, float& i1) {
    l0 += __shfl_xor_sync(0xffffffffu, l0, 1);
    l1 += __shfl_xor_sync(0xffffffffu, l1, 1);
    l0 += __shfl_xor_sync(0xffffffffu, l0, 2);
    l1 += __shfl_xor_sync(0xffffffffu, l1, 2);
    i0 = rcp(l0);
    i1 = rcp(l1);
}

__device__ __forceinline__ void mod_block(const uint4 (&w)[5], const float (&sc)[5], int blk, uint32_t red, int warp,
                                          int lane) {
    float acc[8];
#pragma unroll
    for (int e = 0; e < 8; e++) acc[e] = 0.f;
#pragma unroll
    for (int i = 0; i < 5; i++) {
        acc[0] = fmaf(sc[i], bf_lo(w[i].x), acc[0]);
        acc[1] = fmaf(sc[i], bf_hi(w[i].x), acc[1]);
        acc[2] = fmaf(sc[i], bf_lo(w[i].y), acc[2]);
        acc[3] = fmaf(sc[i], bf_hi(w[i].y), acc[3]);
        acc[4] = fmaf(sc[i], bf_lo(w[i].z), acc[4]);
        acc[5] = fmaf(sc[i], bf_hi(w[i].z), acc[5]);
        acc[6] = fmaf(sc[i], bf_lo(w[i].w), acc[6]);
        acc[7] = fmaf(sc[i], bf_hi(w[i].w), acc[7]);
    }
#pragma unroll
    for (int o = 2; o < 32; o <<= 1)
#pragma unroll
        for (int e = 0; e < 8; e++) acc[e] += __shfl_xor_sync(0xffffffffu, acc[e], o);
    if (lane < 2) {
#pragma unroll
        for (int e = 0; e < 8; e++) sts32f(red + (warp * 16 + lane * 8 + e) * 4, acc[e]);
    }
    bar_sync(3, 256);
    if (warp == 0 && lane < 16) {
        float s = 0.f;
#pragma unroll
        for (int w8 = 0; w8 < 8; w8++) s += lds32f(red + (w8 * 16 + lane) * 4);
        asm volatile("st.relaxed.gpu.global.u32 [%0], %1;" ::"l"(g_mod + blk * 16 + lane),
                     "r"(__float_as_uint(round_bf16(s)) | 1u)
                     : "memory");
    }
}

__global__ void __cluster_dims__(2, 1, 1) __launch_bounds__(384, 1)
    fused_block_kernel(const __grid_constant__ Maps maps, const __nv_bfloat16* __restrict__ x,
                       const __nv_bfloat16* __restrict__ cvec, const __nv_bfloat16* __restrict__ wmod,
                       __nv_bfloat16* __restrict__ out) {
    extern __shared__ uint8_t smem_raw[];
    uint32_t sbase = (smem_u32(smem_raw) + 1023u) & ~1023u;
    asm volatile("" : "+r"(sbase));
    const int b = blockIdx.x;
    const int rank = b & 1;
    const int mt = ((b >> 1) & 7) * 2 + rank;
    const int g = b >> 4;
    const int warp = __shfl_sync(0xffffffffu, threadIdx.x >> 5, 0);
    const int lane = threadIdx.x & 31;

    if (warp >= 8) {
        asm volatile("setmaxnreg.dec.sync.aligned.u32 24;");
        if (warp == 8 && lane == 0) {
#pragma unroll
            for (int i = 0; i < 8; i++) {
                mbar_init(sbase + OFF_FULL + i * 8, 1);
                mbar_init(sbase + OFF_EMPTY + i * 8, 4);
            }
            asm volatile("fence.mbarrier_init.release.cluster;" ::: "memory");
            asm volatile("barrier.cluster.arrive.relaxed;\nbarrier.cluster.wait;" ::: "memory");
            uint32_t slot = 0, phase = 1;
            const uint32_t dst0 = sbase + rank * BOX_BYTES;
            auto acquire = [&](uint32_t bytes) {
                mbar_wait(sbase + OFF_EMPTY + slot * 8, phase);
                mbar_expect_tx(sbase + OFF_FULL + slot * 8, bytes);
            };
            auto adv8 = [&]() {
                if (++slot == 8) {
                    slot = 0;
                    phase ^= 1;
                }
            };
            auto adv6 = [&]() {
                if (++slot == 6) {
                    slot = 0;
                    phase ^= 1;
                }
            };
#pragma unroll 1
            for (int hq = 0; hq < 4; hq++) {
                const int col = (g * 4 + ((hq + 1) & 3)) * 128 + rank * 64;
#pragma unroll 1
                for (int kc = 0; kc < 9; kc++) {
                    acquire(SLOT_BYTES);
                    tma_mc(dst0 + slot * SLOT_BYTES, &maps.wq, col, kc * 64, sbase + OFF_FULL + slot * 8);
                    adv8();
                }
            }
            const int row0 = g * 4 * 2048;
#pragma unroll 1
            for (int n = 0; n < 128; n++) {
                if (n < 4) mbar_wait(sbase + OFF_EMPTY + (slot + 1) * 8, phase);
                acquire(2 * SLOT_BYTES);
                const uint32_t bar = sbase + OFF_FULL + slot * 8;
                const int r0 = n == 0 ? 0 : (n == 127 ? 126 : n + 1);
                const int r1 = n == 0 ? 1 : (n == 127 ? 127 : n - 1);
                tma_mc(dst0 + slot * SLOT_BYTES, n == 127 ? &maps.v : &maps.k, rank * 64, row0 + r0 * 64, bar);
                tma_mc(dst0 + (slot + 1) * SLOT_BYTES, n == 0 ? &maps.k : &maps.v, rank * 64, row0 + r1 * 64, bar);
                adv8();
                adv8();
            }
#pragma unroll 1
            for (int p = 0; p < 4; p++)
#pragma unroll 1
                for (int kc = 0; kc < 8; kc++) {
                    acquire(SLOT_BYTES);
                    tma_mc(dst0 + slot * SLOT_BYTES, &maps.wo, p * 128 + rank * 64, g * 512 + kc * 64,
                           sbase + OFF_FULL + slot * 8);
                    adv8();
                }
#pragma unroll 1
            for (int kc = 0; kc < 4; kc++) {
                acquire(SLOT_BYTES);
                tma_mc(dst0 + slot * SLOT_BYTES, &maps.wo, 512, g * 512 + kc * 128 + rank * 64,
                       sbase + OFF_FULL + slot * 8);
                adv8();
            }
            const CUtensorMap* mg = rank ? &maps.wu : &maps.wg;
#pragma unroll 1
            for (int ch = 0; ch < 9; ch++)
#pragma unroll 1
                for (int kc = 0; kc < 9; kc++) {
                    acquire(SLOT_BYTES);
                    tma_mc(dst0 + slot * SLOT_BYTES, mg, g * 576 + ch * 64, kc * 64, sbase + OFF_FULL + slot * 8);
                    adv6();
                }
#pragma unroll 1
            for (int p = 0; p < 4; p++)
#pragma unroll 1
                for (int kc = 0; kc < 9; kc++) {
                    acquire(SLOT_BYTES);
                    tma_mc(dst0 + slot * SLOT_BYTES, &maps.wd, p * 128 + rank * 64, g * 576 + kc * 64,
                           sbase + OFF_FULL + slot * 8);
                    adv6();
                }
#pragma unroll 1
            for (int kc = 0; kc < 5; kc++) {
                acquire(kc < 4 ? SLOT_BYTES : BOX_BYTES);
                if (kc < 4 || rank == 0)
                    tma_mc(dst0 + slot * SLOT_BYTES, &maps.wd, 512, g * 576 + kc * 128 + rank * 64,
                           sbase + OFF_FULL + slot * 8);
                adv6();
            }
        }
    } else {
        asm volatile("setmaxnreg.inc.sync.aligned.u32 240;");
        const int wg = warp >> 2;
        const int tid = threadIdx.x;
        Ctx cx;
        cx.sbase = sbase;
        cx.rel_cta = (lane == 0 && (warp & 3) < 2) ? (warp & 3) : 2;
        const uint32_t red = sbase + OFF_RED;
        const int own = mt * 8 + g;
        const int orow = own * 16 + (lane >> 2);
        const int wown = mt * 8 + warp;
        Ring ring{0u, 0u};
        uint32_t a[144];

        PROF(0);
        PROFG(30);
        {
            uint4 w1[5], w2[5];
            float sc[5];
            uint32_t xs[18];
            unsigned short cu[5];
            const int half = tid & 1, r0 = tid >> 1;
            const bool second = b < 88;
#pragma unroll
            for (int i = 0; i < 5; i++) {
                const int row = min(r0 + 128 * i, DM - 1);
                cu[i] = __ldg(reinterpret_cast<const unsigned short*>(cvec) + row);
                w1[i] = __ldg(reinterpret_cast<const uint4*>(wmod + (size_t)row * (6 * DM) + half * 8) + b * 2);
            }
#pragma unroll
            for (int j = 0; j < 9; j++) {
                const int col = (warp * 9 + j) * 8 + (lane & 3) * 2;
                xs[2 * j] = __ldg(reinterpret_cast<const uint32_t*>(x + (size_t)orow * DM + col));
                xs[2 * j + 1] = __ldg(reinterpret_cast<const uint32_t*>(x + (size_t)(orow + 8) * DM + col));
            }
#pragma unroll
            for (int i = 0; i < 5; i++) {
                const int row = min(r0 + 128 * i, DM - 1);
                w2[i] = __ldg(reinterpret_cast<const uint4*>(wmod + (size_t)row * (6 * DM) + half * 8) +
                              (second ? 128 + b : b) * 2);
            }
            PROFR(17);
            asm volatile("barrier.cluster.arrive.relaxed.aligned;" ::: "memory");
#pragma unroll
            for (int i = 0; i < 5; i++) {
                const float cv = bf_lo(cu[i]);
                const float sv = round_bf16(cv * rcp(1.f + ex2(-1.4426950408889634f * cv)));
                sc[i] = (r0 + 128 * i < DM) ? sv : 0.f;
            }
            pin(sc);
            PROFR(18);
            mod_block(w1, sc, b, red + 1024, warp, lane);
            PROFR(19);
            float v[36];
#pragma unroll
            for (int j = 0; j < 9; j++) {
                v[4 * j] = bf_lo(xs[2 * j]);
                v[4 * j + 1] = bf_hi(xs[2 * j]);
                v[4 * j + 2] = bf_lo(xs[2 * j + 1]);
                v[4 * j + 3] = bf_hi(xs[2 * j + 1]);
            }
            pin(v);
            PROFR(20);
            layernorm_rows(v, red, warp, lane);
            PROFR(21);
            if (second) mod_block(w2, sc, 128 + b, red + 1024, warp, lane);
            PROF(1);
            PROFR(22);
            float md[2][18];
            const int which[2] = {0, 1};
            load_mod<2>(md, which, warp, lane);
            PROF(2);
            modulate_store(v, md[0], md[1], g_h1 + (size_t)own * 36 * 32, warp, lane);
            __syncwarp();
            if (lane == 0) signal_cnt(CNT_H1 + own);
            asm volatile("barrier.cluster.wait.aligned;" ::: "memory");
        }

        const uint32_t spill = sbase + 8 * SLOT_BYTES + wg * SLOT_BYTES + (tid & 127) * 16;
        uint32_t q[32];
        PROF(3);
        wait_cnt(CNT_H1 + wown, 8);
        PROF(4);
        load_frags(a, g_h1 + (size_t)wown * 36 * 32 + lane);
        {
            float d[64];
#pragma unroll 1
            for (int hq = 0;; hq++) {
                gemm_n128<9, 8>(d, a, cx, ring);
                if (hq == 3) break;
#pragma unroll
                for (int v = 0; v < 8; v++)
                    sts128(spill + hq * 32768 + v * 2048, pack_bf16(d[8 * v], d[8 * v + 1]),
                           pack_bf16(d[8 * v + 2], d[8 * v + 3]), pack_bf16(d[8 * v + 4], d[8 * v + 5]),
                           pack_bf16(d[8 * v + 6], d[8 * v + 7]));
            }
#pragma unroll
            for (int i = 0; i < 32; i++) q[i] = pack_bf16(d[2 * i], d[2 * i + 1]);
        }

        PROF(5);
        {
            float o[64], sa[32], sb[32];
            uint32_t pa[16], pb[16];
#pragma unroll
            for (int i = 0; i < 64; i++) o[i] = 0.f;
            SmState st;
            st.resc = false;
            st.al0 = st.al1 = 1.f;
            float lp0 = 1.f, lp1 = 1.f;
            const uint64_t dbase = desc_of(sbase);
            const uint64_t dbk = dbase - (511u << 16);
            const int my_bar = 1 + wg, other_bar = 2 - wg;

            cx.wait_full(4, 0);
            if (wg == 1) bar_sync(my_bar, 256);
            wg_fence();
            qk_step(sa, q, dbk + 4 * 1024);
            wg_commit();
            qk_step(sb, q, dbk + 5 * 1024);
            wg_commit();
            bar_arrive(other_bar, 256);
            wg_wait<1>();
            pin(sa);
            softmax_step(sa, pa, st, true);
#pragma unroll 1
            for (int t = 1; t < 64; t++) {
                const int j = t & 15;
                const uint32_t s0 = 2 + 4 * (t & 1), s1 = 4 - 4 * (t & 1);
                const uint32_t ph0 = ((34 + 4 * t) >> 3) & 1, ph1 = ((36 + 4 * t) >> 3) & 1;
                TL(0);
                cx.wait_full(s0, ph0);
                wg_wait<0>();
                pin(o);
                pin(sb);
                pin(pb);
                TL(1);
                cx.release(4 - s1);
                apply_rescale(o, st);
                if (j == 0) {
                    const uint32_t src = spill + ((t >> 4) - 1) * 32768;
#pragma unroll
                    for (int v = 0; v < 8; v++) lds128(src + v * 2048, q[4 * v], q[4 * v + 1], q[4 * v + 2], q[4 * v + 3]);
                }
                if (j == 1 && t > 1) {
                    float i0, i1;
                    inv_row_sums(lp0, lp1, i0, i1);
                    const uint32_t dst = spill + ((t >> 4) - 1) * 32768;
#pragma unroll
                    for (int v = 0; v < 8; v++)
                        sts128(dst + v * 2048, pack_bf16(o[8 * v] * i0, o[8 * v + 1] * i0),
                               pack_bf16(o[8 * v + 2] * i1, o[8 * v + 3] * i1),
                               pack_bf16(o[8 * v + 4] * i0, o[8 * v + 5] * i0),
                               pack_bf16(o[8 * v + 6] * i1, o[8 * v + 7] * i1));
                }
                bar_sync(my_bar, 256);
                TL(2);
                wg_fence();
                pv_step(o, pa, dbase + (s0 + 1) * 1024, j != 1);
                qk_step(sa, q, dbk + s0 * 1024);
                wg_commit();
                bar_arrive(other_bar, 256);
                TL(3);
                softmax_step(sb, pb, st, false);
                TL(4);
                cx.wait_full(s1, ph1);
                wg_wait<0>();
                pin(o);
                pin(sa);
                pin(pa);
                TL(5);
                cx.release(s0);
                apply_rescale(o, st);
                bar_sync(my_bar, 256);
                TL(6);
                wg_fence();
                pv_step(o, pb, dbase + (s1 + 1) * 1024, 1);
                qk_step(sb, q, dbk + s1 * 1024);
                wg_commit();
                bar_arrive(other_bar, 256);
                TL(7);
                if (j == 0) {
                    lp0 = st.l0;
                    lp1 = st.l1;
                }
                softmax_step(sa, pa, st, j == 0);
            }
            cx.wait_full(2, 0);
            wg_wait<0>();
            pin(o);
            pin(sb);
            pin(pb);
            cx.release(0);
            apply_rescale(o, st);
            bar_sync(my_bar, 256);
            wg_fence();
            pv_step(o, pa, dbase + 2 * 1024, 1);
            wg_commit();
            if (wg == 0) bar_arrive(other_bar, 256);
            softmax_step(sb, pb, st, false);
            wg_wait<0>();
            pin(o);
            apply_rescale(o, st);
            wg_fence();
            pv_step(o, pb, dbase + 3 * 1024, 1);
            wg_commit();
            float i0, i1;
            inv_row_sums(st.l0, st.l1, i0, i1);
            wg_wait<0>();
            pin(o);
            cx.release(2);
#pragma unroll
            for (int i = 0; i < 16; i++) {
                a[96 + 2 * i] = pack_bf16(o[4 * i] * i0, o[4 * i + 1] * i0);
                a[96 + 2 * i + 1] = pack_bf16(o[4 * i + 2] * i1, o[4 * i + 3] * i1);
            }
#pragma unroll
            for (int v = 0; v < 24; v++)
                lds128(spill + (v >> 3) * 32768 + (v & 7) * 2048, a[4 * v], a[4 * v + 1], a[4 * v + 2], a[4 * v + 3]);
        }

        PROF(6);
        uint2* part_dst = g_part + ((size_t)wown * 8 + g) * 72 * 32 + lane;
        const uint2* part_src = g_part + (size_t)own * 8 * 72 * 32 + lane;
        float4* x2buf = g_x2 + (size_t)b * 9 * 256 + tid;
        ring.slot = 4;
        ring.phase = 0;
        proj_partials<8, 8>(a, cx, ring, part_dst);
        __syncwarp();
        PROF(7);
        if (lane == 0) signal_cnt(CNT_P1 + wown);
        PROF(8);

        {
            float v[36];
            uint32_t xs[18];
#pragma unroll
            for (int j = 0; j < 9; j++) {
                const int col = (warp * 9 + j) * 8 + (lane & 3) * 2;
                xs[2 * j] = __ldg(reinterpret_cast<const uint32_t*>(x + (size_t)orow * DM + col));
                xs[2 * j + 1] = __ldg(reinterpret_cast<const uint32_t*>(x + (size_t)(orow + 8) * DM + col));
            }
            float md[3][18];
            const int which[3] = {2, 3, 4};
            load_mod<3>(md, which, warp, lane);
            wait_cnt(CNT_P1 + own, 8);
            PROF(9);
            sum_partials(v, part_src, warp);
#pragma unroll
            for (int j = 0; j < 9; j++) {
                v[4 * j] = fmaf(md[0][2 * j], v[4 * j], bf_lo(xs[2 * j]));
                v[4 * j + 1] = fmaf(md[0][2 * j + 1], v[4 * j + 1], bf_hi(xs[2 * j]));
                v[4 * j + 2] = fmaf(md[0][2 * j], v[4 * j + 2], bf_lo(xs[2 * j + 1]));
                v[4 * j + 3] = fmaf(md[0][2 * j + 1], v[4 * j + 3], bf_hi(xs[2 * j + 1]));
                __stcg(x2buf + j * 256, make_float4(v[4 * j], v[4 * j + 1], v[4 * j + 2], v[4 * j + 3]));
            }
            PROF(10);
            layernorm_rows(v, red, warp, lane);
            modulate_store(v, md[1], md[2], g_h2 + (size_t)own * 36 * 32, warp, lane);
            __syncwarp();
            if (lane == 0) signal_cnt(CNT_H2 + own);
        }

        PROF(11);
        wait_cnt(CNT_H2 + wown, 8);
        PROF(12);
        load_frags(a, g_h2 + (size_t)wown * 36 * 32 + lane);
        ring.slot = 0;
        ring.phase = 1;
        const uint32_t hsp = sbase + 6 * SLOT_BYTES + wg * BOX_BYTES + (tid & 127) * 16;
        {
            float d[64];
#pragma unroll 1
            for (int ch = 0;; ch++) {
                gemm_n128<9, 6>(d, a, cx, ring);
#pragma unroll
                for (int i = 0; i < 32; i++) {
                    const float gv = d[i];
                    const float k1 = -2.f * 0.7978845608028654f * 1.4426950408889634f;
                    const float zz = gv * fmaf(gv * gv, k1 * 0.044715f, k1);
                    d[i] = gv * rcp(1.f + ex2(zz)) * d[32 + i];
                }
                if (ch == 8) break;
                const uint32_t dst = hsp + ((ch + 2) & 7) * SLOT_BYTES;
#pragma unroll
                for (int v = 0; v < 4; v++)
                    sts128(dst + v * 2048, pack_bf16(d[8 * v], d[8 * v + 1]), pack_bf16(d[8 * v + 2], d[8 * v + 3]),
                           pack_bf16(d[8 * v + 4], d[8 * v + 5]), pack_bf16(d[8 * v + 6], d[8 * v + 7]));
            }
#pragma unroll
            for (int i = 0; i < 16; i++) a[128 + i] = pack_bf16(d[2 * i], d[2 * i + 1]);
        }
#pragma unroll
        for (int v = 0; v < 32; v++)
            lds128(hsp + (((v >> 2) + 2) & 7) * SLOT_BYTES + (v & 3) * 2048, a[4 * v], a[4 * v + 1], a[4 * v + 2],
                   a[4 * v + 3]);

        PROF(13);
        proj_partials<9, 6>(a, cx, ring, part_dst);
        asm volatile("barrier.cluster.arrive.relaxed.aligned;" ::: "memory");
        __syncwarp();
        PROF(14);
        if (lane == 0) signal_cnt(CNT_P2 + wown);

        {
            float v[36];
            float4 xr[9];
            float gb[1][18];
#pragma unroll
            for (int j = 0; j < 9; j++) xr[j] = __ldcg(x2buf + j * 256);
            const int which[1] = {5};
            load_mod<1>(gb, which, warp, lane);
            wait_cnt(CNT_P2 + own, 8);
            PROF(15);
            sum_partials(v, part_src, warp);
#pragma unroll
            for (int j = 0; j < 9; j++) {
                const int col = (warp * 9 + j) * 8 + (lane & 3) * 2;
                *reinterpret_cast<uint32_t*>(out + (size_t)orow * DM + col) =
                    pack_bf16(fmaf(gb[0][2 * j], v[4 * j], xr[j].x), fmaf(gb[0][2 * j + 1], v[4 * j + 1], xr[j].y));
                *reinterpret_cast<uint32_t*>(out + (size_t)(orow + 8) * DM + col) =
                    pack_bf16(fmaf(gb[0][2 * j], v[4 * j + 2], xr[j].z), fmaf(gb[0][2 * j + 1], v[4 * j + 3], xr[j].w));
            }
        }
        PROF(16);
        PROFG(31);
        bar_sync(3, 256);
        if (warp == 0) {
            unsigned old = 0;
            if (lane == 0)
                asm volatile("atom.acq_rel.gpu.global.add.u32 %0, [%1], 1;" : "=r"(old) : "l"(&g_cnt[CNT_DONE * 32]) : "memory");
            old = __shfl_sync(0xffffffffu, old, 0);
            if (old == 127) {
                for (int i = lane; i < CNT_TOTAL; i += 32) g_cnt[i * 32] = 0;
                for (int i = lane; i < 6 * DM / 4; i += 32) reinterpret_cast<uint4*>(g_mod)[i] = make_uint4(0, 0, 0, 0);
            }
        }
        asm volatile("barrier.cluster.wait.aligned;" ::: "memory");
    }
}

typedef CUresult (*EncodeFn)(CUtensorMap*, CUtensorMapDataType, cuuint32_t, void*, const cuuint64_t*, const cuuint64_t*,
                             const cuuint32_t*, const cuuint32_t*, CUtensorMapInterleave, CUtensorMapSwizzle,
                             CUtensorMapL2promotion, CUtensorMapFloatOOBfill);

void make_map(EncodeFn enc, CUtensorMap* m, const void* ptr, uint64_t rows, uint64_t cols) {
    cuuint64_t gdim[2] = {cols, rows};
    cuuint64_t gstr[1] = {cols * 2};
    cuuint32_t box[2] = {64, 64};
    cuuint32_t estr[2] = {1, 1};
    enc(m, CU_TENSOR_MAP_DATA_TYPE_BFLOAT16, 2, const_cast<void*>(ptr), gdim, gstr, box, estr,
        CU_TENSOR_MAP_INTERLEAVE_NONE, CU_TENSOR_MAP_SWIZZLE_128B, CU_TENSOR_MAP_L2_PROMOTION_L2_128B,
        CU_TENSOR_MAP_FLOAT_OOB_FILL_NONE);
}

}

extern "C" void kernel_launch(void* const* d_in, const int* in_sizes, int n_in, void* d_out, int out_size) {
    (void)in_sizes;
    (void)n_in;
    (void)out_size;
    void* fn = nullptr;
    cudaDriverEntryPointQueryResult qr;
    cudaGetDriverEntryPoint("cuTensorMapEncodeTiled", &fn, cudaEnableDefault, &qr);
    EncodeFn enc = (EncodeFn)fn;
    Maps maps;
    make_map(enc, &maps.k, d_in[1], 32 * 2048, 128);
    make_map(enc, &maps.v, d_in[2], 32 * 2048, 128);
    make_map(enc, &maps.wq, d_in[3], 576, 4096);
    make_map(enc, &maps.wo, d_in[4], 4096, 576);
    make_map(enc, &maps.wg, d_in[6], 576, 4608);
    make_map(enc, &maps.wu, d_in[7], 576, 4608);
    make_map(enc, &maps.wd, d_in[8], 4608, 576);
    cudaFuncSetAttribute(fused_block_kernel, cudaFuncAttributeMaxDynamicSharedMemorySize, SMEM_BYTES);
    fused_block_kernel<<<128, 384, SMEM_BYTES>>>(maps, (const __nv_bfloat16*)d_in[0], (const __nv_bfloat16*)d_in[9],
                                                 (const __nv_bfloat16*)d_in[10], (__nv_bfloat16*)d_out);
}
```

```cpp
#include <cuda_runtime.h>
#include <cuda_bf16.h>
#include <cuda.h>
#include <stdint.h>

namespace {

constexpr int DM = 576;
constexpr int SLOT_BYTES = 16384;
constexpr int BOX_BYTES = 8192;
constexpr int NUNITS = 14;
constexpr int SMEM_TAIL = NUNITS * SLOT_BYTES;
constexpr int SMEM_BYTES = SMEM_TAIL + 2048 + 1024;
constexpr int OFF_FULL = SMEM_TAIL;
constexpr int OFF_EMPTY = SMEM_TAIL + 64;
constexpr int OFF_RED = SMEM_TAIL + 128;

constexpr int CNT_DONE = 2, CNT_H1 = 8, CNT_P1 = 8 + 128, CNT_H2 = 8 + 256,
              CNT_P2 = 8 + 384, CNT_TOTAL = 8 + 512;

__device__ __align__(16) uint32_t g_mod[6 * DM];
__device__ uint4 g_h1[128 * 36 * 32];
__device__ uint4 g_h2[128 * 36 * 32];
__device__ uint2 g_part[128 * 8 * 72 * 32];
__device__ float4 g_x2[128 * 9 * 256];
__device__ unsigned g_cnt[CNT_TOTAL * 32];

#define TL(i)
#define PROFR(i)
#define PROF(i)
#define PROFG(i)

struct Maps {
    CUtensorMap k, v, wq, wo, wg, wu, wd;
};

__device__ __forceinline__ uint32_t smem_u32(const void* p) { return (uint32_t)__cvta_generic_to_shared(p); }
__device__ __forceinline__ void mbar_init(uint32_t a, uint32_t c) {
    asm volatile("mbarrier.init.shared::cta.b64 [%0], %1;" ::"r"(a), "r"(c) : "memory");
}
__device__ __forceinline__ void mbar_expect_tx(uint32_t a, uint32_t bytes) {
    asm volatile("mbarrier.arrive.expect_tx.shared::cta.b64 _, [%0], %1;" ::"r"(a), "r"(bytes) : "memory");
}
__device__ __forceinline__ bool mbar_try(uint32_t a, uint32_t ph) {
    uint32_t ok;
    asm volatile(
        "{\n.reg .pred p;\nmbarrier.try_wait.parity.shared::cta.b64 p, [%1], %2;\nselp.u32 %0, 1, 0, p;\n}"
        : "=r"(ok)
        : "r"(a), "r"(ph)
        : "memory");
    return ok != 0;
}
__device__ __forceinline__ uint32_t clk32() {
    uint32_t c;
    asm volatile("mov.u32 %0, %%clock;" : "=r"(c));
    return c;
}
constexpr uint32_t WAIT_LIMIT = 1u << 30;
__device__ __forceinline__ void mbar_wait(uint32_t a, uint32_t ph) {
    if (mbar_try(a, ph)) return;
    uint32_t t0 = clk32();
    while (!mbar_try(a, ph)) {
        if (clk32() - t0 > WAIT_LIMIT) break;
    }
}
__device__ __forceinline__ void mbar_arrive_cluster(uint32_t a, uint32_t cta) {
    asm volatile(
        "{\n.reg .b32 ra;\nmapa.shared::cluster.u32 ra, %0, %1;\nmbarrier.arrive.shared::cluster.b64 _, [ra];\n}" ::"r"(a),
        "r"(cta)
        : "memory");
}
__device__ __forceinline__ void tma_mc(uint32_t dst, const CUtensorMap* m, int c0, int c1, uint32_t bar) {
    asm volatile(
        "cp.async.bulk.tensor.2d.shared::cluster.global.mbarrier::complete_tx::bytes.multicast::cluster"
        " [%0], [%1, {%3, %4}], [%2], %5;" ::"r"(dst),
        "l"(m), "r"(bar), "r"(c0), "r"(c1), "h"((uint16_t)3)
        : "memory");
}
__device__ __forceinline__ void bar_sync(int id, int n) { asm volatile("bar.sync %0, %1;" ::"r"(id), "r"(n) : "memory"); }
__device__ __forceinline__ void bar_arrive(int id, int n) {
    asm volatile("bar.arrive %0, %1;" ::"r"(id), "r"(n) : "memory");
}
__device__ __forceinline__ void wg_fence() { asm volatile("wgmma.fence.sync.aligned;" ::: "memory"); }
__device__ __forceinline__ void wg_commit() { asm volatile("wgmma.commit_group.sync.aligned;" ::: "memory"); }
template <int N>
__device__ __forceinline__ void wg_wait() {
    asm volatile("wgmma.wait_group.sync.aligned %0;" ::"n"(N) : "memory");
}
template <int N>
__device__ __forceinline__ void pin(float (&d)[N]) {
#pragma unroll
    for (int i = 0; i < N; i++) asm volatile("" : "+f"(d[i])::"memory");
}
template <int N>
__device__ __forceinline__ void pin(uint32_t (&d)[N]) {
#pragma unroll
    for (int i = 0; i < N; i++) asm volatile("" : "+r"(d[i])::"memory");
}
__device__ __forceinline__ uint32_t pack_bf16(float lo, float hi) {
    uint32_t r;
    asm("cvt.rn.bf16x2.f32 %0, %1, %2;" : "=r"(r) : "f"(hi), "f"(lo));
    return r;
}
__device__ __forceinline__ float bf_lo(uint32_t v) { return __uint_as_float(v << 16); }
__device__ __forceinline__ float bf_hi(uint32_t v) { return __uint_as_float(v & 0xffff0000u); }
__device__ __forceinline__ float round_bf16(float v) { return __bfloat162float(__float2bfloat16_rn(v)); }
__device__ __forceinline__ float ex2(float x) {
    float y;
    asm("ex2.approx.ftz.f32 %0, %1;" : "=f"(y) : "f"(x));
    return y;
}
__device__ __forceinline__ float rcp(float x) {
    float y;
    asm("rcp.approx.ftz.f32 %0, %1;" : "=f"(y) : "f"(x));
    return y;
}
__device__ __forceinline__ void sts128(uint32_t a, uint32_t x, uint32_t y, uint32_t z, uint32_t w) {
    asm volatile("st.shared.v4.b32 [%0], {%1,%2,%3,%4};" ::"r"(a), "r"(x), "r"(y), "r"(z), "r"(w) : "memory");
}
__device__ __forceinline__ void lds128(uint32_t a, uint32_t& x, uint32_t& y, uint32_t& z, uint32_t& w) {
    asm volatile("ld.shared.v4.b32 {%0,%1,%2,%3}, [%4];" : "=r"(x), "=r"(y), "=r"(z), "=r"(w) : "r"(a) : "memory");
}
__device__ __forceinline__ void sts32f(uint32_t a, float v) {
    asm volatile("st.shared.f32 [%0], %1;" ::"r"(a), "f"(v) : "memory");
}
__device__ __forceinline__ float lds32f(uint32_t a) {
    float v;
    asm volatile("ld.shared.f32 %0, [%1];" : "=f"(v) : "r"(a) : "memory");
    return v;
}
__device__ __forceinline__ void signal_cnt(int idx) {
    asm volatile("red.release.gpu.global.add.u32 [%0], 1;" ::"l"(&g_cnt[idx * 32]) : "memory");
}
__device__ __forceinline__ void wait_cnt(int idx, unsigned target) {
    if ((threadIdx.x & 31) == 0) {
        uint32_t t0 = clk32();
        while (true) {
            unsigned v;
            asm volatile("ld.acquire.gpu.global.u32 %0, [%1];" : "=r"(v) : "l"(&g_cnt[idx * 32]) : "memory");
            if (v >= target) break;
            if (clk32() - t0 > WAIT_LIMIT) break;
        }
    }
    __syncwarp();
}

#define F8(d, b) \
    "+f"(d[b]), "+f"(d[b + 1]), "+f"(d[b + 2]), "+f"(d[b + 3]), "+f"(d[b + 4]), "+f"(d[b + 5]), "+f"(d[b + 6]), "+f"(d[b + 7])

template <int TB>
__device__ __forceinline__ void wgmma_n128(float (&d)[64], uint32_t a0, uint32_t a1, uint32_t a2, uint32_t a3,
                                           uint64_t db, int sc) {
    asm volatile(
        "{\n.reg .pred p;\nsetp.ne.b32 p, %69, 0;\n"
        "wgmma.mma_async.sync.aligned.m64n128k16.f32.bf16.bf16 "
        "{%0,%1,%2,%3,%4,%5,%6,%7,%8,%9,%10,%11,%12,%13,%14,%15,%16,%17,%18,%19,%20,%21,%22,%23,%24,%25,%26,%27,%28,%29,%30,%31,"
        "%32,%33,%34,%35,%36,%37,%38,%39,%40,%41,%42,%43,%44,%45,%46,%47,%48,%49,%50,%51,%52,%53,%54,%55,%56,%57,%58,%59,%60,%61,%62,%63},"
        "{%64,%65,%66,%67}, %68, p, 1, 1, %70;\n}"
        : F8(d, 0), F8(d, 8), F8(d, 16), F8(d, 24), F8(d, 32), F8(d, 40), F8(d, 48), F8(d, 56)
        : "r"(a0), "r"(a1), "r"(a2), "r"(a3), "l"(db), "r"(sc), "n"(TB));
}
#define O8(d, b) \
    "=f"(d[b]), "=f"(d[b + 1]), "=f"(d[b + 2]), "=f"(d[b + 3]), "=f"(d[b + 4]), "=f"(d[b + 5]), "=f"(d[b + 6]), "=f"(d[b + 7])
template <int TB>
__device__ __forceinline__ void wgmma_n128_z(float (&d)[64], uint32_t a0, uint32_t a1, uint32_t a2, uint32_t a3,
                                             uint64_t db) {
    asm volatile(
        "wgmma.mma_async.sync.aligned.m64n128k16.f32.bf16.bf16 "
        "{%0,%1,%2,%3,%4,%5,%6,%7,%8,%9,%10,%11,%12,%13,%14,%15,%16,%17,%18,%19,%20,%21,%22,%23,%24,%25,%26,%27,%28,%29,%30,%31,"
        "%32,%33,%34,%35,%36,%37,%38,%39,%40,%41,%42,%43,%44,%45,%46,%47,%48,%49,%50,%51,%52,%53,%54,%55,%56,%57,%58,%59,%60,%61,%62,%63},"
        "{%64,%65,%66,%67}, %68, 0, 1, 1, %69;"
        : O8(d, 0), O8(d, 8), O8(d, 16), O8(d, 24), O8(d, 32), O8(d, 40), O8(d, 48), O8(d, 56)
        : "r"(a0), "r"(a1), "r"(a2), "r"(a3), "l"(db), "n"(TB));
}
template <int TB>
__device__ __forceinline__ void wgmma_n64_z(float (&d)[32], uint32_t a0, uint32_t a1, uint32_t a2, uint32_t a3,
                                            uint64_t db) {
    asm volatile(
        "wgmma.mma_async.sync.aligned.m64n64k16.f32.bf16.bf16 "
        "{%0,%1,%2,%3,%4,%5,%6,%7,%8,%9,%10,%11,%12,%13,%14,%15,%16,%17,%18,%19,%20,%21,%22,%23,%24,%25,%26,%27,%28,%29,%30,%31},"
        "{%32,%33,%34,%35}, %36, 0, 1, 1, %37;"
        : O8(d, 0), O8(d, 8), O8(d, 16), O8(d, 24)
        : "r"(a0), "r"(a1), "r"(a2), "r"(a3), "l"(db), "n"(TB));
}
template <int TB>
__device__ __forceinline__ void wgmma_n64(float (&d)[32], uint32_t a0, uint32_t a1, uint32_t a2, uint32_t a3,
                                          uint64_t db) {
    asm volatile(
        "wgmma.mma_async.sync.aligned.m64n64k16.f32.bf16.bf16 "
        "{%0,%1,%2,%3,%4,%5,%6,%7,%8,%9,%10,%11,%12,%13,%14,%15,%16,%17,%18,%19,%20,%21,%22,%23,%24,%25,%26,%27,%28,%29,%30,%31},"
        "{%32,%33,%34,%35}, %36, 1, 1, 1, %37;"
        : F8(d, 0), F8(d, 8), F8(d, 16), F8(d, 24)
        : "r"(a0), "r"(a1), "r"(a2), "r"(a3), "l"(db), "n"(TB));
}

__device__ __forceinline__ uint64_t desc_of(uint32_t saddr) {
    return (uint64_t)(((saddr >> 4) & 0x3FFFu) | (512u << 16)) | ((uint64_t)(64u | (1u << 30)) << 32);
}

struct Ring {
    uint32_t slot;
    uint32_t phase;
    template <int NS>
    __device__ __forceinline__ void next() {
        if (++slot == NS) {
            slot = 0;
            phase ^= 1;
        }
    }
};

struct Ctx {
    uint32_t sbase;
    uint32_t rel_cta;
    __device__ __forceinline__ void wait_full(uint32_t slot, uint32_t phase) const {
        mbar_wait(sbase + OFF_FULL + slot * 8, phase);
    }
    __device__ __forceinline__ void release(uint32_t slot) const {
        if (rel_cta < 2) mbar_arrive_cluster(sbase + OFF_EMPTY + slot * 8, rel_cta);
    }
};

template <int NK, int NS, int NA>
__device__ __forceinline__ void gemm_n128(float (&d)[64], const uint32_t (&a)[NA], const Ctx& c, Ring& r) {
    uint32_t prev = 0;
#pragma unroll
    for (int s = 0; s < NK; s++) {
        c.wait_full(r.slot, r.phase);
        uint64_t db = desc_of(c.sbase + r.slot * SLOT_BYTES);
        wg_fence();
#pragma unroll
        for (int k = 0; k < 4; k++) {
            if ((s | k) == 0)
                wgmma_n128_z<1>(d, a[0], a[1], a[2], a[3], db);
            else
                wgmma_n128<1>(d, a[s * 16 + k * 4], a[s * 16 + k * 4 + 1], a[s * 16 + k * 4 + 2], a[s * 16 + k * 4 + 3],
                              db + k * 128, 1);
        }
        wg_commit();
        if (s > 0) {
            wg_wait<1>();
            c.release(prev);
        }
        prev = r.slot;
        r.template next<NS>();
    }
    wg_wait<0>();
    c.release(prev);
    pin(d);
}
template <int NKS, int NS, int NA>
__device__ __forceinline__ void gemm_n64(float (&d)[32], const uint32_t (&a)[NA], const Ctx& c, Ring& r) {
    uint32_t prev = 0;
    constexpr int NSL = (NKS + 7) / 8;
#pragma unroll
    for (int s = 0; s < NSL; s++) {
        c.wait_full(r.slot, r.phase);
        uint64_t db = desc_of(c.sbase + r.slot * SLOT_BYTES);
        wg_fence();
#pragma unroll
        for (int k = 0; k < 8; k++) {
            if ((s | k) == 0)
                wgmma_n64_z<1>(d, a[0], a[1], a[2], a[3], db);
            else if (s * 8 + k < NKS)
                wgmma_n64<1>(d, a[s * 32 + k * 4], a[s * 32 + k * 4 + 1], a[s * 32 + k * 4 + 2], a[s * 32 + k * 4 + 3],
                             db + k * 128);
        }
        wg_commit();
        if (s > 0) {
            wg_wait<1>();
            c.release(prev);
        }
        prev = r.slot;
        r.template next<NS>();
    }
    wg_wait<0>();
    c.release(prev);
    pin(d);
}

template <int NK, int NS, int NA>
__device__ __forceinline__ void proj_partials(const uint32_t (&a)[NA], const Ctx& c, Ring& r,
                                              uint2* dst  ) {
#pragma unroll 1
    for (int p = 0; p < 4; p++) {
        float d[64];
        gemm_n128<NK, NS>(d, a, c, r);
#pragma unroll
        for (int j = 0; j < 16; j++)
            __stcg(dst + (p * 16 + j) * 32, make_uint2(pack_bf16(d[4 * j], d[4 * j + 1]), pack_bf16(d[4 * j + 2], d[4 * j + 3])));
    }
    float d[32];
    gemm_n64<NK * 4, NS>(d, a, c, r);
#pragma unroll
    for (int j = 0; j < 8; j++)
        __stcg(dst + (64 + j) * 32, make_uint2(pack_bf16(d[4 * j], d[4 * j + 1]), pack_bf16(d[4 * j + 2], d[4 * j + 3])));
}

__device__ __forceinline__ void row_reduce(float& s0, float& s1, uint32_t red, int warp, int lane) {
    s0 += __shfl_xor_sync(0xffffffffu, s0, 1);
    s1 += __shfl_xor_sync(0xffffffffu, s1, 1);
    s0 += __shfl_xor_sync(0xffffffffu, s0, 2);
    s1 += __shfl_xor_sync(0xffffffffu, s1, 2);
    if ((lane & 3) == 0) {
        sts32f(red + (warp * 16 + (lane >> 2)) * 4, s0);
        sts32f(red + (warp * 16 + 8 + (lane >> 2)) * 4, s1);
    }
    bar_sync(3, 256);
    s0 = 0.f;
    s1 = 0.f;
#pragma unroll
    for (int w = 0; w < 8; w++) {
        s0 += lds32f(red + (w * 16 + (lane >> 2)) * 4);
        s1 += lds32f(red + (w * 16 + 8 + (lane >> 2)) * 4);
    }
}
__device__ __forceinline__ void layernorm_rows(float (&v)[36], uint32_t red, int warp, int lane) {
    float s0 = 0.f, s1 = 0.f;
#pragma unroll
    for (int j = 0; j < 9; j++) {
        s0 += v[4 * j] + v[4 * j + 1];
        s1 += v[4 * j + 2] + v[4 * j + 3];
    }
    row_reduce(s0, s1, red, warp, lane);
    const float m0 = s0 * (1.f / DM), m1 = s1 * (1.f / DM);
    s0 = 0.f;
    s1 = 0.f;
#pragma unroll
    for (int j = 0; j < 9; j++) {
        v[4 * j] -= m0;
        v[4 * j + 1] -= m0;
        v[4 * j + 2] -= m1;
        v[4 * j + 3] -= m1;
        s0 += v[4 * j] * v[4 * j] + v[4 * j + 1] * v[4 * j + 1];
        s1 += v[4 * j + 2] * v[4 * j + 2] + v[4 * j + 3] * v[4 * j + 3];
    }
    row_reduce(s0, s1, red + 512, warp, lane);
    const float r0 = rsqrtf(s0 * (1.f / DM) + 1e-5f), r1 = rsqrtf(s1 * (1.f / DM) + 1e-5f);
#pragma unroll
    for (int j = 0; j < 9; j++) {
        v[4 * j] *= r0;
        v[4 * j + 1] *= r0;
        v[4 * j + 2] *= r1;
        v[4 * j + 3] *= r1;
    }
}
template <int NV>
__device__ __forceinline__ void load_mod(float (&m)[NV][18], const int (&which)[NV], int warp, int lane) {
    const uint32_t t0 = clk32();
    while (true) {
        uint2 u[NV][9];
#pragma unroll
        for (int n = 0; n < NV; n++)
#pragma unroll
            for (int j = 0; j < 9; j++)
                asm volatile("ld.relaxed.gpu.global.v2.u32 {%0,%1}, [%2];"
                             : "=r"(u[n][j].x), "=r"(u[n][j].y)
                             : "l"(g_mod + which[n] * DM + (warp * 9 + j) * 8 + (lane & 3) * 2));
        uint32_t ok = 1;
#pragma unroll
        for (int n = 0; n < NV; n++)
#pragma unroll
            for (int j = 0; j < 9; j++) {
                ok &= u[n][j].x & u[n][j].y;
                m[n][2 * j] = __uint_as_float(u[n][j].x & 0xffff0000u);
                m[n][2 * j + 1] = __uint_as_float(u[n][j].y & 0xffff0000u);
            }
        if (__all_sync(0xffffffffu, ok) || clk32() - t0 > WAIT_LIMIT) break;
    }
}
__device__ __forceinline__ void modulate_store(const float (&v)[36], const float (&shift)[18], const float (&scale)[18],
                                               uint4* hbuf  , int warp, int lane) {
    uint2* dst = reinterpret_cast<uint2*>(hbuf);
#pragma unroll
    for (int j = 0; j < 9; j++) {
        const int grp = warp * 9 + j;
        const float c0 = round_bf16(1.f + scale[2 * j]), c1 = round_bf16(1.f + scale[2 * j + 1]);
        uint2 o;
        o.x = pack_bf16(fmaf(v[4 * j], c0, shift[2 * j]), fmaf(v[4 * j + 1], c1, shift[2 * j + 1]));
        o.y = pack_bf16(fmaf(v[4 * j + 2], c0, shift[2 * j]), fmaf(v[4 * j + 3], c1, shift[2 * j + 1]));
        __stcg(dst + ((grp >> 1) * 32 + lane) * 2 + (grp & 1), o);
    }
}
__device__ __forceinline__ void sum_partials(float (&v)[36], const uint2* src  , int warp) {
    uint2 t[8][9];
#pragma unroll
    for (int s = 0; s < 8; s++)
#pragma unroll
        for (int j = 0; j < 9; j++) t[s][j] = __ldcg(src + (s * 72 + warp * 9 + j) * 32);
#pragma unroll
    for (int j = 0; j < 9; j++) {
        float a = 0.f, b = 0.f, c = 0.f, d = 0.f;
#pragma unroll
        for (int s = 0; s < 8; s++) {
            a += bf_lo(t[s][j].x);
            b += bf_hi(t[s][j].x);
            c += bf_lo(t[s][j].y);
            d += bf_hi(t[s][j].y);
        }
        v[4 * j] = a;
        v[4 * j + 1] = b;
        v[4 * j + 2] = c;
        v[4 * j + 3] = d;
    }
}
__device__ __forceinline__ void load_frags(uint32_t (&a)[144], const uint4* src  ) {
#pragma unroll
    for (int k = 0; k < 36; k++) {
        uint4 t = __ldcg(src + k * 32);
        a[4 * k] = t.x;
        a[4 * k + 1] = t.y;
        a[4 * k + 2] = t.z;
        a[4 * k + 3] = t.w;
    }
}

constexpr float SM_SCALE = 0.08838834764831845f * 1.4426950408889634f;
constexpr float SM_LIMIT = 4294967296.f;
__device__ __forceinline__ void qk_step(float (&s)[32], const uint32_t (&q)[32], uint64_t dk) {
#pragma unroll
    for (int k = 0; k < 8; k++) {
        if (k == 0)
            wgmma_n64_z<0>(s, q[0], q[1], q[2], q[3], dk);
        else
            wgmma_n64<0>(s, q[4 * k], q[4 * k + 1], q[4 * k + 2], q[4 * k + 3], dk + (k >> 2) * 512 + (k & 3) * 2);
    }
}
__device__ __forceinline__ void pv_step(float (&o)[64], const uint32_t (&p)[16], uint64_t dv, int acc) {
#pragma unroll
    for (int k = 0; k < 4; k++)
        wgmma_n128<1>(o, p[4 * k], p[4 * k + 1], p[4 * k + 2], p[4 * k + 3], dv + k * 128, k != 0 ? 1 : acc);
}
__device__ __forceinline__ void exp_step(const float (&s)[32], uint32_t (&p)[16], float n0, float n1, float& s0,
                                         float& s1) {
#pragma unroll
    for (int i = 0; i < 8; i++) {
        const float e0 = ex2(fmaf(s[4 * i], SM_SCALE, n0)), e1 = ex2(fmaf(s[4 * i + 1], SM_SCALE, n0));
        const float e2 = ex2(fmaf(s[4 * i + 2], SM_SCALE, n1)), e3 = ex2(fmaf(s[4 * i + 3], SM_SCALE, n1));
        if (i == 0) {
            s0 = e0 + e1;
            s1 = e2 + e3;
        } else {
            s0 += e0 + e1;
            s1 += e2 + e3;
        }
        p[2 * i] = pack_bf16(e0, e1);
        p[2 * i + 1] = pack_bf16(e2, e3);
    }
}
__device__ __forceinline__ void row_max(const float (&sa)[32], const float (&sb)[32], float& x0, float& x1) {
    float xa[8];
#pragma unroll
    for (int i = 0; i < 8; i++) xa[i] = fmaxf(sa[i], sb[i]);
#pragma unroll
    for (int k = 1; k < 4; k++)
#pragma unroll
        for (int i = 0; i < 8; i++) xa[i] = fmaxf(xa[i], fmaxf(sa[8 * k + i], sb[8 * k + i]));
    x0 = fmaxf(fmaxf(xa[0], xa[1]), fmaxf(xa[4], xa[5]));
    x1 = fmaxf(fmaxf(xa[2], xa[3]), fmaxf(xa[6], xa[7]));
    x0 = fmaxf(x0, __shfl_xor_sync(0xffffffffu, x0, 1));
    x1 = fmaxf(x1, __shfl_xor_sync(0xffffffffu, x1, 1));
    x0 = fmaxf(x0, __shfl_xor_sync(0xffffffffu, x0, 2));
    x1 = fmaxf(x1, __shfl_xor_sync(0xffffffffu, x1, 2));
}
__device__ __forceinline__ void inv_row_sums(float l0, float l1, float& i0, float& i1) {
    l0 += __shfl_xor_sync(0xffffffffu, l0, 1);
    l1 += __shfl_xor_sync(0xffffffffu, l1, 1);
    l0 += __shfl_xor_sync(0xffffffffu, l0, 2);
    l1 += __shfl_xor_sync(0xffffffffu, l1, 2);
    i0 = rcp(l0);
    i1 = rcp(l1);
}

__device__ __forceinline__ void mod_block(const uint4 (&w)[5], const float (&sc)[5], int blk, uint32_t red, int warp,
                                          int lane) {
    float acc[8];
#pragma unroll
    for (int e = 0; e < 8; e++) acc[e] = 0.f;
#pragma unroll
    for (int i = 0; i < 5; i++) {
        acc[0] = fmaf(sc[i], bf_lo(w[i].x), acc[0]);
        acc[1] = fmaf(sc[i], bf_hi(w[i].x), acc[1]);
        acc[2] = fmaf(sc[i], bf_lo(w[i].y), acc[2]);
        acc[3] = fmaf(sc[i], bf_hi(w[i].y), acc[3]);
        acc[4] = fmaf(sc[i], bf_lo(w[i].z), acc[4]);
        acc[5] = fmaf(sc[i], bf_hi(w[i].z), acc[5]);
        acc[6] = fmaf(sc[i], bf_lo(w[i].w), acc[6]);
        acc[7] = fmaf(sc[i], bf_hi(w[i].w), acc[7]);
    }
#pragma unroll
    for (int o = 2; o < 32; o <<= 1)
#pragma unroll
        for (int e = 0; e < 8; e++) acc[e] += __shfl_xor_sync(0xffffffffu, acc[e], o);
    if (lane < 2) {
#pragma unroll
        for (int e = 0; e < 8; e++) sts32f(red + (warp * 16 + lane * 8 + e) * 4, acc[e]);
    }
    bar_sync(3, 256);
    if (warp == 0 && lane < 16) {
        float s = 0.f;
#pragma unroll
        for (int w8 = 0; w8 < 8; w8++) s += lds32f(red + (w8 * 16 + lane) * 4);
        asm volatile("st.relaxed.gpu.global.u32 [%0], %1;" ::"l"(g_mod + blk * 16 + lane),
                     "r"(__float_as_uint(round_bf16(s)) | 1u)
                     : "memory");
    }
}

__global__ void __cluster_dims__(2, 1, 1) __launch_bounds__(384, 1)
    fused_block_kernel(const __grid_constant__ Maps maps, const __nv_bfloat16* __restrict__ x,
                       const __nv_bfloat16* __restrict__ cvec, const __nv_bfloat16* __restrict__ wmod,
                       __nv_bfloat16* __restrict__ out) {
    extern __shared__ uint8_t smem_raw[];
    uint32_t sbase = (smem_u32(smem_raw) + 1023u) & ~1023u;
    asm volatile("" : "+r"(sbase));
    const int b = blockIdx.x;
    const int rank = b & 1;
    const int mt = ((b >> 1) & 7) * 2 + rank;
    const int g = b >> 4;
    const int warp = __shfl_sync(0xffffffffu, threadIdx.x >> 5, 0);
    const int lane = threadIdx.x & 31;

    if (warp >= 8) {
        asm volatile("setmaxnreg.dec.sync.aligned.u32 24;");
        if (warp == 8 && lane == 0) {
#pragma unroll
            for (int i = 0; i < 8; i++) {
                mbar_init(sbase + OFF_FULL + i * 8, 1);
                mbar_init(sbase + OFF_EMPTY + i * 8, 4);
            }
            asm volatile("fence.mbarrier_init.release.cluster;" ::: "memory");
            asm volatile("barrier.cluster.arrive.relaxed;\nbarrier.cluster.wait;" ::: "memory");
            uint32_t slot = 0, phase = 1;
            const uint32_t dst0 = sbase + rank * BOX_BYTES;
            auto acquire = [&](uint32_t bytes) {
                mbar_wait(sbase + OFF_EMPTY + slot * 8, phase);
                mbar_expect_tx(sbase + OFF_FULL + slot * 8, bytes);
            };
            auto adv8 = [&]() {
                if (++slot == 8) {
                    slot = 0;
                    phase ^= 1;
                }
            };
            auto adv6 = [&]() {
                if (++slot == 6) {
                    slot = 0;
                    phase ^= 1;
                }
            };
#pragma unroll 1
            for (int hq = 0; hq < 4; hq++) {
                const int col = (g * 4 + ((hq + 1) & 3)) * 128 + rank * 64;
#pragma unroll 1
                for (int kc = 0; kc < 9; kc++) {
                    acquire(SLOT_BYTES);
                    tma_mc(dst0 + slot * SLOT_BYTES, &maps.wq, col, kc * 64, sbase + OFF_FULL + slot * 8);
                    adv8();
                }
            }
            const int row0 = g * 4 * 2048;
#pragma unroll 1
            for (int n = 0; n < 128; n++) {
                if (n < 4) mbar_wait(sbase + OFF_EMPTY + (slot + 1) * 8, phase);
                acquire(2 * SLOT_BYTES);
                const uint32_t bar = sbase + OFF_FULL + slot * 8;
                const CUtensorMap* m = (n & 1) ? &maps.v : &maps.k;
                tma_mc(dst0 + slot * SLOT_BYTES, m, rank * 64, row0 + (n >> 1) * 128, bar);
                tma_mc(dst0 + (slot + 1) * SLOT_BYTES, m, rank * 64, row0 + (n >> 1) * 128 + 64, bar);
                adv8();
                adv8();
            }
#pragma unroll 1
            for (int p = 0; p < 4; p++)
#pragma unroll 1
                for (int kc = 0; kc < 8; kc++) {
                    acquire(SLOT_BYTES);
                    tma_mc(dst0 + slot * SLOT_BYTES, &maps.wo, p * 128 + rank * 64, g * 512 + kc * 64,
                           sbase + OFF_FULL + slot * 8);
                    adv8();
                }
#pragma unroll 1
            for (int kc = 0; kc < 4; kc++) {
                acquire(SLOT_BYTES);
                tma_mc(dst0 + slot * SLOT_BYTES, &maps.wo, 512, g * 512 + kc * 128 + rank * 64,
                       sbase + OFF_FULL + slot * 8);
                adv8();
            }
            const CUtensorMap* mg = rank ? &maps.wu : &maps.wg;
#pragma unroll 1
            for (int ch = 0; ch < 9; ch++)
#pragma unroll 1
                for (int kc = 0; kc < 9; kc++) {
                    acquire(SLOT_BYTES);
                    tma_mc(dst0 + slot * SLOT_BYTES, mg, g * 576 + ch * 64, kc * 64, sbase + OFF_FULL + slot * 8);
                    adv6();
                }
#pragma unroll 1
            for (int p = 0; p < 4; p++)
#pragma unroll 1
                for (int kc = 0; kc < 9; kc++) {
                    acquire(SLOT_BYTES);
                    tma_mc(dst0 + slot * SLOT_BYTES, &maps.wd, p * 128 + rank * 64, g * 576 + kc * 64,
                           sbase + OFF_FULL + slot * 8);
                    adv6();
                }
#pragma unroll 1
            for (int kc = 0; kc < 5; kc++) {
                acquire(kc < 4 ? SLOT_BYTES : BOX_BYTES);
                if (kc < 4 || rank == 0)
                    tma_mc(dst0 + slot * SLOT_BYTES, &maps.wd, 512, g * 576 + kc * 128 + rank * 64,
                           sbase + OFF_FULL + slot * 8);
                adv6();
            }
        }
    } else {
        asm volatile("setmaxnreg.inc.sync.aligned.u32 240;");
        const int wg = warp >> 2;
        const int tid = threadIdx.x;
        Ctx cx;
        cx.sbase = sbase;
        cx.rel_cta = (lane == 0 && (warp & 3) < 2) ? (warp & 3) : 2;
        const uint32_t red = sbase + OFF_RED;
        const int own = mt * 8 + g;
        const int orow = own * 16 + (lane >> 2);
        const int wown = mt * 8 + warp;
        Ring ring{0u, 0u};
        uint32_t a[144];

        PROF(0);
        PROFG(30);
        {
            uint4 w1[5], w2[5];
            float sc[5];
            uint32_t xs[18];
            unsigned short cu[5];
            const int half = tid & 1, r0 = tid >> 1;
            const bool second = b < 88;
#pragma unroll
            for (int i = 0; i < 5; i++) {
                const int row = min(r0 + 128 * i, DM - 1);
                cu[i] = __ldg(reinterpret_cast<const unsigned short*>(cvec) + row);
                w1[i] = __ldg(reinterpret_cast<const uint4*>(wmod + (size_t)row * (6 * DM) + half * 8) + b * 2);
            }
#pragma unroll
            for (int j = 0; j < 9; j++) {
                const int col = (warp * 9 + j) * 8 + (lane & 3) * 2;
                xs[2 * j] = __ldg(reinterpret_cast<const uint32_t*>(x + (size_t)orow * DM + col));
                xs[2 * j + 1] = __ldg(reinterpret_cast<const uint32_t*>(x + (size_t)(orow + 8) * DM + col));
            }
#pragma unroll
            for (int i = 0; i < 5; i++) {
                const int row = min(r0 + 128 * i, DM - 1);
                w2[i] = __ldg(reinterpret_cast<const uint4*>(wmod + (size_t)row * (6 * DM) + half * 8) +
                              (second ? 128 + b : b) * 2);
            }
            PROFR(17);
            asm volatile("barrier.cluster.arrive.relaxed.aligned;" ::: "memory");
#pragma unroll
            for (int i = 0; i < 5; i++) {
                const float cv = bf_lo(cu[i]);
                const float sv = round_bf16(cv * rcp(1.f + ex2(-1.4426950408889634f * cv)));
                sc[i] = (r0 + 128 * i < DM) ? sv : 0.f;
            }
            pin(sc);
            PROFR(18);
            mod_block(w1, sc, b, red + 1024, warp, lane);
            PROFR(19);
            float v[36];
#pragma unroll
            for (int j = 0; j < 9; j++) {
                v[4 * j] = bf_lo(xs[2 * j]);
                v[4 * j + 1] = bf_hi(xs[2 * j]);
                v[4 * j + 2] = bf_lo(xs[2 * j + 1]);
                v[4 * j + 3] = bf_hi(xs[2 * j + 1]);
            }
            pin(v);
            PROFR(20);
            layernorm_rows(v, red, warp, lane);
            PROFR(21);
            if (second) mod_block(w2, sc, 128 + b, red + 1024, warp, lane);
            PROF(1);
            PROFR(22);
            float md[2][18];
            const int which[2] = {0, 1};
            load_mod<2>(md, which, warp, lane);
            PROF(2);
            modulate_store(v, md[0], md[1], g_h1 + (size_t)own * 36 * 32, warp, lane);
            __syncwarp();
            if (lane == 0) signal_cnt(CNT_H1 + own);
            asm volatile("barrier.cluster.wait.aligned;" ::: "memory");
        }

        const uint32_t spill = sbase + 8 * SLOT_BYTES + wg * SLOT_BYTES + (tid & 127) * 16;
        uint32_t q[32];
        PROF(3);
        wait_cnt(CNT_H1 + wown, 8);
        PROF(4);
        load_frags(a, g_h1 + (size_t)wown * 36 * 32 + lane);
        {
            float d[64];
#pragma unroll 1
            for (int hq = 0;; hq++) {
                gemm_n128<9, 8>(d, a, cx, ring);
                if (hq == 3) break;
#pragma unroll
                for (int v = 0; v < 8; v++)
                    sts128(spill + hq * 32768 + v * 2048, pack_bf16(d[8 * v], d[8 * v + 1]),
                           pack_bf16(d[8 * v + 2], d[8 * v + 3]), pack_bf16(d[8 * v + 4], d[8 * v + 5]),
                           pack_bf16(d[8 * v + 6], d[8 * v + 7]));
            }
#pragma unroll
            for (int i = 0; i < 32; i++) q[i] = pack_bf16(d[2 * i], d[2 * i + 1]);
        }

        PROF(5);
        {
            float o[64], sa[32], sb[32];
            uint32_t pa[16], pb[16];
#pragma unroll
            for (int i = 0; i < 64; i++) o[i] = 0.f;
            float n0, n1, l0, l1;
            const uint64_t dbase = desc_of(sbase);
            const uint64_t dbk = dbase - (511u << 16);
            const int my_bar = 1 + wg, other_bar = 2 - wg;

            cx.wait_full(4, 0);
            if (wg == 1) bar_sync(my_bar, 256);
            wg_fence();
            qk_step(sa, q, dbk + 4 * 1024);
            qk_step(sb, q, dbk + 5 * 1024);
            wg_commit();
            bar_arrive(other_bar, 256);
            wg_wait<0>();
            pin(sa);
            pin(sb);
            cx.release(4);
            cx.wait_full(6, 0);
            cx.wait_full(0, 1);
            row_max(sa, sb, n0, n1);
            n0 *= -SM_SCALE;
            n1 *= -SM_SCALE;
            {
                float u0, u1;
                exp_step(sa, pa, n0, n1, l0, l1);
                exp_step(sb, pb, n0, n1, u0, u1);
                l0 += u0;
                l1 += u1;
            }
#pragma unroll 1
            for (int t = 1; t < 64; t++) {
                const int j = t & 15;
                const uint32_t ks = 4 - 4 * (t & 1), vs = 2 + 4 * (t & 1);
                TL(0);
                bar_sync(my_bar, 256);
                TL(2);
                wg_fence();
                const uint64_t dk = dbk + ks * 1024, dv = dbase + vs * 1024;
                pv_step(o, pa, dv, j != 1);
                pv_step(o, pb, dv + 1024, 1);
                qk_step(sa, q, dk);
                wg_commit();
                qk_step(sb, q, dk + 1024);
                wg_commit();
                bar_arrive(other_bar, 256);
                TL(3);
                wg_wait<1>();
                pin(o);
                pin(sa);
                pin(pa);
                pin(pb);
                TL(4);
                cx.release(vs);
                float s0, s1, u0, u1;
                bool slow = (j == 0);
                if (slow) {
                    float i0, i1;
                    inv_row_sums(l0, l1, i0, i1);
                    const uint32_t dst = spill + ((t >> 4) - 1) * 32768;
#pragma unroll
                    for (int v = 0; v < 8; v++)
                        sts128(dst + v * 2048, pack_bf16(o[8 * v] * i0, o[8 * v + 1] * i0),
                               pack_bf16(o[8 * v + 2] * i1, o[8 * v + 3] * i1),
                               pack_bf16(o[8 * v + 4] * i0, o[8 * v + 5] * i0),
                               pack_bf16(o[8 * v + 6] * i1, o[8 * v + 7] * i1));
                    n0 = INFINITY;
                    n1 = INFINITY;
                    s0 = s1 = 0.f;
                } else {
                    exp_step(sa, pa, n0, n1, s0, s1);
                }
                TL(5);
                wg_wait<0>();
                pin(sb);
                TL(6);
                cx.release(ks);
                cx.wait_full(8 - vs, ((38 + 4 * t) >> 3) & 1);
                if (t < 63) cx.wait_full(4 - ks, ((40 + 4 * t) >> 3) & 1);
                if (j == 15 && t < 63) {
                    const uint32_t src = spill + (t >> 4) * 32768;
#pragma unroll
                    for (int v = 0; v < 8; v++) lds128(src + v * 2048, q[4 * v], q[4 * v + 1], q[4 * v + 2], q[4 * v + 3]);
                }
                TL(1);
                if (!slow) {
                    exp_step(sb, pb, n0, n1, u0, u1);
                    s0 += u0;
                    s1 += u1;
                    slow = __any_sync(0xffffffffu, !(fmaxf(s0, s1) <= SM_LIMIT));
                }
                if (slow) {
                    float x0, x1;
                    row_max(sa, sb, x0, x1);
                    x0 = fminf(-x0 * SM_SCALE, n0);
                    x1 = fminf(-x1 * SM_SCALE, n1);
                    const float al0 = ex2(x0 - n0), al1 = ex2(x1 - n1);
                    n0 = x0;
                    n1 = x1;
                    l0 *= al0;
                    l1 *= al1;
                    if (j != 0) {
#pragma unroll
                        for (int i = 0; i < 16; i++) {
                            o[4 * i] *= al0;
                            o[4 * i + 1] *= al0;
                            o[4 * i + 2] *= al1;
                            o[4 * i + 3] *= al1;
                        }
                    }
                    exp_step(sa, pa, n0, n1, s0, s1);
                    exp_step(sb, pb, n0, n1, u0, u1);
                    s0 += u0;
                    s1 += u1;
                }
                l0 += s0;
                l1 += s1;
                TL(7);
            }
            bar_sync(my_bar, 256);
            wg_fence();
            pv_step(o, pa, dbase + 2 * 1024, 1);
            pv_step(o, pb, dbase + 3 * 1024, 1);
            wg_commit();
            if (wg == 0) bar_arrive(other_bar, 256);
            float i0, i1;
            inv_row_sums(l0, l1, i0, i1);
            wg_wait<0>();
            pin(o);
            cx.release(2);
#pragma unroll
            for (int i = 0; i < 16; i++) {
                a[96 + 2 * i] = pack_bf16(o[4 * i] * i0, o[4 * i + 1] * i0);
                a[96 + 2 * i + 1] = pack_bf16(o[4 * i + 2] * i1, o[4 * i + 3] * i1);
            }
#pragma unroll
            for (int v = 0; v < 24; v++)
                lds128(spill + (v >> 3) * 32768 + (v & 7) * 2048, a[4 * v], a[4 * v + 1], a[4 * v + 2], a[4 * v + 3]);
        }

        PROF(6);
        uint2* part_dst = g_part + ((size_t)wown * 8 + g) * 72 * 32 + lane;
        const uint2* part_src = g_part + (size_t)own * 8 * 72 * 32 + lane;
        float4* x2buf = g_x2 + (size_t)b * 9 * 256 + tid;
        ring.slot = 4;
        ring.phase = 0;
        proj_partials<8, 8>(a, cx, ring, part_dst);
        __syncwarp();
        PROF(7);
        if (lane == 0) signal_cnt(CNT_P1 + wown);
        PROF(8);

        {
            float v[36];
            uint32_t xs[18];
#pragma unroll
            for (int j = 0; j < 9; j++) {
                const int col = (warp * 9 + j) * 8 + (lane & 3) * 2;
                xs[2 * j] = __ldg(reinterpret_cast<const uint32_t*>(x + (size_t)orow * DM + col));
                xs[2 * j + 1] = __ldg(reinterpret_cast<const uint32_t*>(x + (size_t)(orow + 8) * DM + col));
            }
            float md[3][18];
            const int which[3] = {2, 3, 4};
            load_mod<3>(md, which, warp, lane);
            wait_cnt(CNT_P1 + own, 8);
            PROF(9);
            sum_partials(v, part_src, warp);
#pragma unroll
            for (int j = 0; j < 9; j++) {
                v[4 * j] = fmaf(md[0][2 * j], v[4 * j], bf_lo(xs[2 * j]));
                v[4 * j + 1] = fmaf(md[0][2 * j + 1], v[4 * j + 1], bf_hi(xs[2 * j]));
                v[4 * j + 2] = fmaf(md[0][2 * j], v[4 * j + 2], bf_lo(xs[2 * j + 1]));
                v[4 * j + 3] = fmaf(md[0][2 * j + 1], v[4 * j + 3], bf_hi(xs[2 * j + 1]));
                __stcg(x2buf + j * 256, make_float4(v[4 * j], v[4 * j + 1], v[4 * j + 2], v[4 * j + 3]));
            }
            PROF(10);
            layernorm_rows(v, red, warp, lane);
            modulate_store(v, md[1], md[2], g_h2 + (size_t)own * 36 * 32, warp, lane);
            __syncwarp();
            if (lane == 0) signal_cnt(CNT_H2 + own);
        }

        PROF(11);
        wait_cnt(CNT_H2 + wown, 8);
        PROF(12);
        load_frags(a, g_h2 + (size_t)wown * 36 * 32 + lane);
        ring.slot = 0;
        ring.phase = 1;
        const uint32_t hsp = sbase + 6 * SLOT_BYTES + wg * BOX_BYTES + (tid & 127) * 16;
        {
            float d[64];
#pragma unroll 1
            for (int ch = 0;; ch++) {
                gemm_n128<9, 6>(d, a, cx, ring);
#pragma unroll
                for (int i = 0; i < 32; i++) {
                    const float gv = d[i];
                    const float k1 = -2.f * 0.7978845608028654f * 1.4426950408889634f;
                    const float zz = gv * fmaf(gv * gv, k1 * 0.044715f, k1);
                    d[i] = gv * rcp(1.f + ex2(zz)) * d[32 + i];
                }
                if (ch == 8) break;
                const uint32_t dst = hsp + ((ch + 2) & 7) * SLOT_BYTES;
#pragma unroll
                for (int v = 0; v < 4; v++)
                    sts128(dst + v * 2048, pack_bf16(d[8 * v], d[8 * v + 1]), pack_bf16(d[8 * v + 2], d[8 * v + 3]),
                           pack_bf16(d[8 * v + 4], d[8 * v + 5]), pack_bf16(d[8 * v + 6], d[8 * v + 7]));
            }
#pragma unroll
            for (int i = 0; i < 16; i++) a[128 + i] = pack_bf16(d[2 * i], d[2 * i + 1]);
        }
#pragma unroll
        for (int v = 0; v < 32; v++)
            lds128(hsp + (((v >> 2) + 2) & 7) * SLOT_BYTES + (v & 3) * 2048, a[4 * v], a[4 * v + 1], a[4 * v + 2],
                   a[4 * v + 3]);

        PROF(13);
        proj_partials<9, 6>(a, cx, ring, part_dst);
        asm volatile("barrier.cluster.arrive.relaxed.aligned;" ::: "memory");
        __syncwarp();
        PROF(14);
        if (lane == 0) signal_cnt(CNT_P2 + wown);

        {
            float v[36];
            float4 xr[9];
            float gb[1][18];
#pragma unroll
            for (int j = 0; j < 9; j++) xr[j] = __ldcg(x2buf + j * 256);
            const int which[1] = {5};
            load_mod<1>(gb, which, warp, lane);
            wait_cnt(CNT_P2 + own, 8);
            PROF(15);
            sum_partials(v, part_src, warp);
#pragma unroll
            for (int j = 0; j < 9; j++) {
                const int col = (warp * 9 + j) * 8 + (lane & 3) * 2;
                *reinterpret_cast<uint32_t*>(out + (size_t)orow * DM + col) =
                    pack_bf16(fmaf(gb[0][2 * j], v[4 * j], xr[j].x), fmaf(gb[0][2 * j + 1], v[4 * j + 1], xr[j].y));
                *reinterpret_cast<uint32_t*>(out + (size_t)(orow + 8) * DM + col) =
                    pack_bf16(fmaf(gb[0][2 * j], v[4 * j + 2], xr[j].z), fmaf(gb[0][2 * j + 1], v[4 * j + 3], xr[j].w));
            }
        }
        PROF(16);
        PROFG(31);
        bar_sync(3, 256);
        if (warp == 0) {
            unsigned old = 0;
            if (lane == 0)
                asm volatile("atom.acq_rel.gpu.global.add.u32 %0, [%1], 1;" : "=r"(old) : "l"(&g_cnt[CNT_DONE * 32]) : "memory");
            old = __shfl_sync(0xffffffffu, old, 0);
            if (old == 127) {
                for (int i = lane; i < CNT_TOTAL; i += 32) g_cnt[i * 32] = 0;
                for (int i = lane; i < 6 * DM / 4; i += 32) reinterpret_cast<uint4*>(g_mod)[i] = make_uint4(0, 0, 0, 0);
            }
        }
        asm volatile("barrier.cluster.wait.aligned;" ::: "memory");
    }
}

typedef CUresult (*EncodeFn)(CUtensorMap*, CUtensorMapDataType, cuuint32_t, void*, const cuuint64_t*, const cuuint64_t*,
                             const cuuint32_t*, const cuuint32_t*, CUtensorMapInterleave, CUtensorMapSwizzle,
                             CUtensorMapL2promotion, CUtensorMapFloatOOBfill);

void make_map(EncodeFn enc, CUtensorMap* m, const void* ptr, uint64_t rows, uint64_t cols) {
    cuuint64_t gdim[2] = {cols, rows};
    cuuint64_t gstr[1] = {cols * 2};
    cuuint32_t box[2] = {64, 64};
    cuuint32_t estr[2] = {1, 1};
    enc(m, CU_TENSOR_MAP_DATA_TYPE_BFLOAT16, 2, const_cast<void*>(ptr), gdim, gstr, box, estr,
        CU_TENSOR_MAP_INTERLEAVE_NONE, CU_TENSOR_MAP_SWIZZLE_128B, CU_TENSOR_MAP_L2_PROMOTION_L2_128B,
        CU_TENSOR_MAP_FLOAT_OOB_FILL_NONE);
}

}

extern "C" void kernel_launch(void* const* d_in, const int* in_sizes, int n_in, void* d_out, int out_size) {
    (void)in_sizes;
    (void)n_in;
    (void)out_size;
    void* fn = nullptr;
    cudaDriverEntryPointQueryResult qr;
    cudaGetDriverEntryPoint("cuTensorMapEncodeTiled", &fn, cudaEnableDefault, &qr);
    EncodeFn enc = (EncodeFn)fn;
    Maps maps;
    make_map(enc, &maps.k, d_in[1], 32 * 2048, 128);
    make_map(enc, &maps.v, d_in[2], 32 * 2048, 128);
    make_map(enc, &maps.wq, d_in[3], 576, 4096);
    make_map(enc, &maps.wo, d_in[4], 4096, 576);
    make_map(enc, &maps.wg, d_in[6], 576, 4608);
    make_map(enc, &maps.wu, d_in[7], 576, 4608);
    make_map(enc, &maps.wd, d_in[8], 4608, 576);
    cudaFuncSetAttribute(fused_block_kernel, cudaFuncAttributeMaxDynamicSharedMemorySize, SMEM_BYTES);
    fused_block_kernel<<<128, 384, SMEM_BYTES>>>(maps, (const __nv_bfloat16*)d_in[0], (const __nv_bfloat16*)d_in[9],
                                                 (const __nv_bfloat16*)d_in[10], (__nv_bfloat16*)d_out);
}
```

```cpp
#include <cuda_runtime.h>
#include <cuda_bf16.h>
#include <cuda.h>
#include <stdint.h>

namespace {

constexpr int DM = 576;
constexpr int SLOT_BYTES = 16384;
constexpr int BOX_BYTES = 8192;
constexpr int NUNITS = 14;
constexpr int SMEM_TAIL = NUNITS * SLOT_BYTES;
constexpr int SMEM_BYTES = SMEM_TAIL + 2048 + 1024;
constexpr int OFF_FULL = SMEM_TAIL;
constexpr int OFF_EMPTY = SMEM_TAIL + 64;
constexpr int OFF_RED = SMEM_TAIL + 128;

constexpr int CNT_DONE = 2, CNT_H1 = 8, CNT_P1 = 8 + 128, CNT_H2 = 8 + 256,
              CNT_P2 = 8 + 384, CNT_TOTAL = 8 + 512;

__device__ __align__(16) uint32_t g_mod[6 * DM];
__device__ uint4 g_h1[128 * 36 * 32];
__device__ uint4 g_h2[128 * 36 * 32];
__device__ uint2 g_part[128 * 8 * 72 * 32];
__device__ float4 g_x2[128 * 9 * 256];
__device__ unsigned g_cnt[CNT_TOTAL * 32];

#define TL(i)
#define PROFR(i)
#define PROF(i)
#define PROFG(i)

struct Maps {
    CUtensorMap k, v, wq, wo, wg, wu, wd;
};

__device__ __forceinline__ uint32_t smem_u32(const void* p) { return (uint32_t)__cvta_generic_to_shared(p); }
__device__ __forceinline__ void mbar_init(uint32_t a, uint32_t c) {
    asm volatile("mbarrier.init.shared::cta.b64 [%0], %1;" ::"r"(a), "r"(c) : "memory");
}
__device__ __forceinline__ void mbar_expect_tx(uint32_t a, uint32_t bytes) {
    asm volatile("mbarrier.arrive.expect_tx.shared::cta.b64 _, [%0], %1;" ::"r"(a), "r"(bytes) : "memory");
}
__device__ __forceinline__ bool mbar_try(uint32_t a, uint32_t ph) {
    uint32_t ok;
    asm volatile(
        "{\n.reg .pred p;\nmbarrier.try_wait.parity.shared::cta.b64 p, [%1], %2;\nselp.u32 %0, 1, 0, p;\n}"
        : "=r"(ok)
        : "r"(a), "r"(ph)
        : "memory");
    return ok != 0;
}
__device__ __forceinline__ uint32_t clk32() {
    uint32_t c;
    asm volatile("mov.u32 %0, %%clock;" : "=r"(c));
    return c;
}
constexpr uint32_t WAIT_LIMIT = 1u << 30;
__device__ __forceinline__ void mbar_wait(uint32_t a, uint32_t ph) {
    if (mbar_try(a, ph)) return;
    uint32_t t0 = clk32();
    while (!mbar_try(a, ph)) {
        if (clk32() - t0 > WAIT_LIMIT) break;
    }
}
__device__ __forceinline__ void mbar_arrive_cluster(uint32_t a, uint32_t cta) {
    asm volatile(
        "{\n.reg .b32 ra;\nmapa.shared::cluster.u32 ra, %0, %1;\nmbarrier.arrive.shared::cluster.b64 _, [ra];\n}" ::"r"(a),
        "r"(cta)
        : "memory");
}
__device__ __forceinline__ void tma_mc(uint32_t dst, const CUtensorMap* m, int c0, int c1, uint32_t bar) {
    asm volatile(
        "cp.async.bulk.tensor.2d.shared::cluster.global.mbarrier::complete_tx::bytes.multicast::cluster"
        " [%0], [%1, {%3, %4}], [%2], %5;" ::"r"(dst),
        "l"(m), "r"(bar), "r"(c0), "r"(c1), "h"((uint16_t)3)
        : "memory");
}
__device__ __forceinline__ void bar_sync(int id, int n) { asm volatile("bar.sync %0, %1;" ::"r"(id), "r"(n) : "memory"); }
__device__ __forceinline__ void bar_arrive(int id, int n) {
    asm volatile("bar.arrive %0, %1;" ::"r"(id), "r"(n) : "memory");
}
__device__ __forceinline__ void wg_fence() { asm volatile("wgmma.fence.sync.aligned;" ::: "memory"); }
__device__ __forceinline__ void wg_commit() { asm volatile("wgmma.commit_group.sync.aligned;" ::: "memory"); }
template <int N>
__device__ __forceinline__ void wg_wait() {
    asm volatile("wgmma.wait_group.sync.aligned %0;" ::"n"(N) : "memory");
}
template <int N>
__device__ __forceinline__ void pin(float (&d)[N]) {
#pragma unroll
    for (int i = 0; i < N; i++) asm volatile("" : "+f"(d[i])::"memory");
}
template <int N>
__device__ __forceinline__ void pin(uint32_t (&d)[N]) {
#pragma unroll
    for (int i = 0; i < N; i++) asm volatile("" : "+r"(d[i])::"memory");
}
__device__ __forceinline__ uint32_t pack_bf16(float lo, float hi) {
    uint32_t r;
    asm("cvt.rn.bf16x2.f32 %0, %1, %2;" : "=r"(r) : "f"(hi), "f"(lo));
    return r;
}
__device__ __forceinline__ float bf_lo(uint32_t v) { return __uint_as_float(v << 16); }
__device__ __forceinline__ float bf_hi(uint32_t v) { return __uint_as_float(v & 0xffff0000u); }
__device__ __forceinline__ float round_bf16(float v) { return __bfloat162float(__float2bfloat16_rn(v)); }
__device__ __forceinline__ float ex2(float x) {
    float y;
    asm("ex2.approx.ftz.f32 %0, %1;" : "=f"(y) : "f"(x));
    return y;
}
__device__ __forceinline__ float rcp(float x) {
    float y;
    asm("rcp.approx.ftz.f32 %0, %1;" : "=f"(y) : "f"(x));
    return y;
}
__device__ __forceinline__ void sts128(uint32_t a, uint32_t x, uint32_t y, uint32_t z, uint32_t w) {
    asm volatile("st.shared.v4.b32 [%0], {%1,%2,%3,%4};" ::"r"(a), "r"(x), "r"(y), "r"(z), "r"(w) : "memory");
}
__device__ __forceinline__ void lds128(uint32_t a, uint32_t& x, uint32_t& y, uint32_t& z, uint32_t& w) {
    asm volatile("ld.shared.v4.b32 {%0,%1,%2,%3}, [%4];" : "=r"(x), "=r"(y), "=r"(z), "=r"(w) : "r"(a) : "memory");
}
__device__ __forceinline__ void sts32f(uint32_t a, float v) {
    asm volatile("st.shared.f32 [%0], %1;" ::"r"(a), "f"(v) : "memory");
}
__device__ __forceinline__ float lds32f(uint32_t a) {
    float v;
    asm volatile("ld.shared.f32 %0, [%1];" : "=f"(v) : "r"(a) : "memory");
    return v;
}
__device__ __forceinline__ void signal_cnt(int idx) {
    asm volatile("red.release.gpu.global.add.u32 [%0], 1;" ::"l"(&g_cnt[idx * 32]) : "memory");
}
__device__ __forceinline__ void wait_cnt(int idx, unsigned target) {
    if ((threadIdx.x & 31) == 0) {
        uint32_t t0 = clk32();
        while (true) {
            unsigned v;
            asm volatile("ld.acquire.gpu.global.u32 %0, [%1];" : "=r"(v) : "l"(&g_cnt[idx * 32]) : "memory");
            if (v >= target) break;
            if (clk32() - t0 > WAIT_LIMIT) break;
        }
    }
    __syncwarp();
}

#define F8(d, b) \
    "+f"(d[b]), "+f"(d[b + 1]), "+f"(d[b + 2]), "+f"(d[b + 3]), "+f"(d[b + 4]), "+f"(d[b + 5]), "+f"(d[b + 6]), "+f"(d[b + 7])

template <int TB>
__device__ __forceinline__ void wgmma_n128(float (&d)[64], uint32_t a0, uint32_t a1, uint32_t a2, uint32_t a3,
                                           uint64_t db, int sc) {
    asm volatile(
        "{\n.reg .pred p;\nsetp.ne.b32 p, %69, 0;\n"
        "wgmma.mma_async.sync.aligned.m64n128k16.f32.bf16.bf16 "
        "{%0,%1,%2,%3,%4,%5,%6,%7,%8,%9,%10,%11,%12,%13,%14,%15,%16,%17,%18,%19,%20,%21,%22,%23,%24,%25,%26,%27,%28,%29,%30,%31,"
        "%32,%33,%34,%35,%36,%37,%38,%39,%40,%41,%42,%43,%44,%45,%46,%47,%48,%49,%50,%51,%52,%53,%54,%55,%56,%57,%58,%59,%60,%61,%62,%63},"
        "{%64,%65,%66,%67}, %68, p, 1, 1, %70;\n}"
        : F8(d, 0), F8(d, 8), F8(d, 16), F8(d, 24), F8(d, 32), F8(d, 40), F8(d, 48), F8(d, 56)
        : "r"(a0), "r"(a1), "r"(a2), "r"(a3), "l"(db), "r"(sc), "n"(TB));
}
#define O8(d, b) \
    "=f"(d[b]), "=f"(d[b + 1]), "=f"(d[b + 2]), "=f"(d[b + 3]), "=f"(d[b + 4]), "=f"(d[b + 5]), "=f"(d[b + 6]), "=f"(d[b + 7])
template <int TB>
__device__ __forceinline__ void wgmma_n128_z(float (&d)[64], uint32_t a0, uint32_t a1, uint32_t a2, uint32_t a3,
                                             uint64_t db) {
    asm volatile(
        "wgmma.mma_async.sync.aligned.m64n128k16.f32.bf16.bf16 "
        "{%0,%1,%2,%3,%4,%5,%6,%7,%8,%9,%10,%11,%12,%13,%14,%15,%16,%17,%18,%19,%20,%21,%22,%23,%24,%25,%26,%27,%28,%29,%30,%31,"
        "%32,%33,%34,%35,%36,%37,%38,%39,%40,%41,%42,%43,%44,%45,%46,%47,%48,%49,%50,%51,%52,%53,%54,%55,%56,%57,%58,%59,%60,%61,%62,%63},"
        "{%64,%65,%66,%67}, %68, 0, 1, 1, %69;"
        : O8(d, 0), O8(d, 8), O8(d, 16), O8(d, 24), O8(d, 32), O8(d, 40), O8(d, 48), O8(d, 56)
        : "r"(a0), "r"(a1), "r"(a2), "r"(a3), "l"(db), "n"(TB));
}
template <int TB>
__device__ __forceinline__ void wgmma_n64_z(float (&d)[32], uint32_t a0, uint32_t a1, uint32_t a2, uint32_t a3,
                                            uint64_t db) {
    asm volatile(
        "wgmma.mma_async.sync.aligned.m64n64k16.f32.bf16.bf16 "
        "{%0,%1,%2,%3,%4,%5,%6,%7,%8,%9,%10,%11,%12,%13,%14,%15,%16,%17,%18,%19,%20,%21,%22,%23,%24,%25,%26,%27,%28,%29,%30,%31},"
        "{%32,%33,%34,%35}, %36, 0, 1, 1, %37;"
        : O8(d, 0), O8(d, 8), O8(d, 16), O8(d, 24)
        : "r"(a0), "r"(a1), "r"(a2), "r"(a3), "l"(db), "n"(TB));
}
template <int TB>
__device__ __forceinline__ void wgmma_n64(float (&d)[32], uint32_t a0, uint32_t a1, uint32_t a2, uint32_t a3,
                                          uint64_t db) {
    asm volatile(
        "wgmma.mma_async.sync.aligned.m64n64k16.f32.bf16.bf16 "
        "{%0,%1,%2,%3,%4,%5,%6,%7,%8,%9,%10,%11,%12,%13,%14,%15,%16,%17,%18,%19,%20,%21,%22,%23,%24,%25,%26,%27,%28,%29,%30,%31},"
        "{%32,%33,%34,%35}, %36, 1, 1, 1, %37;"
        : F8(d, 0), F8(d, 8), F8(d, 16), F8(d, 24)
        : "r"(a0), "r"(a1), "r"(a2), "r"(a3), "l"(db), "n"(TB));
}

__device__ __forceinline__ uint64_t desc_of(uint32_t saddr) {
    return (uint64_t)(((saddr >> 4) & 0x3FFFu) | (512u << 16)) | ((uint64_t)(64u | (1u << 30)) << 32);
}

struct Ring {
    uint32_t slot;
    uint32_t phase;
    template <int NS>
    __device__ __forceinline__ void next() {
        if (++slot == NS) {
            slot = 0;
            phase ^= 1;
        }
    }
};

struct Ctx {
    uint32_t sbase;
    uint32_t rel_cta;
    __device__ __forceinline__ void wait_full(uint32_t slot, uint32_t phase) const {
        mbar_wait(sbase + OFF_FULL + slot * 8, phase);
    }
    __device__ __forceinline__ void release(uint32_t slot) const {
        if (rel_cta < 2) mbar_arrive_cluster(sbase + OFF_EMPTY + slot * 8, rel_cta);
    }
};

template <int NK, int NS, int NA>
__device__ __forceinline__ void gemm_n128(float (&d)[64], const uint32_t (&a)[NA], const Ctx& c, Ring& r) {
    uint32_t prev = 0;
#pragma unroll
    for (int s = 0; s < NK; s++) {
        c.wait_full(r.slot, r.phase);
        uint64_t db = desc_of(c.sbase + r.slot * SLOT_BYTES);
        wg_fence();
#pragma unroll
        for (int k = 0; k < 4; k++) {
            if ((s | k) == 0)
                wgmma_n128_z<1>(d, a[0], a[1], a[2], a[3], db);
            else
                wgmma_n128<1>(d, a[s * 16 + k * 4], a[s * 16 + k * 4 + 1], a[s * 16 + k * 4 + 2], a[s * 16 + k * 4 + 3],
                              db + k * 128, 1);
        }
        wg_commit();
        if (s > 0) {
            wg_wait<1>();
            c.release(prev);
        }
        prev = r.slot;
        r.template next<NS>();
    }
    wg_wait<0>();
    c.release(prev);
    pin(d);
}
template <int NKS, int NS, int NA>
__device__ __forceinline__ void gemm_n64(float (&d)[32], const uint32_t (&a)[NA], const Ctx& c, Ring& r) {
    uint32_t prev = 0;
    constexpr int NSL = (NKS + 7) / 8;
#pragma unroll
    for (int s = 0; s < NSL; s++) {
        c.wait_full(r.slot, r.phase);
        uint64_t db = desc_of(c.sbase + r.slot * SLOT_BYTES);
        wg_fence();
#pragma unroll
        for (int k = 0; k < 8; k++) {
            if ((s | k) == 0)
                wgmma_n64_z<1>(d, a[0], a[1], a[2], a[3], db);
            else if (s * 8 + k < NKS)
                wgmma_n64<1>(d, a[s * 32 + k * 4], a[s * 32 + k * 4 + 1], a[s * 32 + k * 4 + 2], a[s * 32 + k * 4 + 3],
                             db + k * 128);
        }
        wg_commit();
        if (s > 0) {
            wg_wait<1>();
            c.release(prev);
        }
        prev = r.slot;
        r.template next<NS>();
    }
    wg_wait<0>();
    c.release(prev);
    pin(d);
}

template <int NK, int NS, int NA>
__device__ __forceinline__ void proj_partials(const uint32_t (&a)[NA], const Ctx& c, Ring& r,
                                              uint2* dst  ) {
#pragma unroll 1
    for (int p = 0; p < 4; p++) {
        float d[64];
        gemm_n128<NK, NS>(d, a, c, r);
#pragma unroll
        for (int j = 0; j < 16; j++)
            __stcg(dst + (p * 16 + j) * 32, make_uint2(pack_bf16(d[4 * j], d[4 * j + 1]), pack_bf16(d[4 * j + 2], d[4 * j + 3])));
    }
    float d[32];
    gemm_n64<NK * 4, NS>(d, a, c, r);
#pragma unroll
    for (int j = 0; j < 8; j++)
        __stcg(dst + (64 + j) * 32, make_uint2(pack_bf16(d[4 * j], d[4 * j + 1]), pack_bf16(d[4 * j + 2], d[4 * j + 3])));
}

__device__ __forceinline__ void row_reduce(float& s0, float& s1, uint32_t red, int warp, int lane) {
    s0 += __shfl_xor_sync(0xffffffffu, s0, 1);
    s1 += __shfl_xor_sync(0xffffffffu, s1, 1);
    s0 += __shfl_xor_sync(0xffffffffu, s0, 2);
    s1 += __shfl_xor_sync(0xffffffffu, s1, 2);
    if ((lane & 3) == 0) {
        sts32f(red + (warp * 16 + (lane >> 2)) * 4, s0);
        sts32f(red + (warp * 16 + 8 + (lane >> 2)) * 4, s1);
    }
    bar_sync(3, 256);
    s0 = 0.f;
    s1 = 0.f;
#pragma unroll
    for (int w = 0; w < 8; w++) {
        s0 += lds32f(red + (w * 16 + (lane >> 2)) * 4);
        s1 += lds32f(red + (w * 16 + 8 + (lane >> 2)) * 4);
    }
}
__device__ __forceinline__ void layernorm_rows(float (&v)[36], uint32_t red, int warp, int lane) {
    float s0 = 0.f, s1 = 0.f;
#pragma unroll
    for (int j = 0; j < 9; j++) {
        s0 += v[4 * j] + v[4 * j + 1];
        s1 += v[4 * j + 2] + v[4 * j + 3];
    }
    row_reduce(s0, s1, red, warp, lane);
    const float m0 = s0 * (1.f / DM), m1 = s1 * (1.f / DM);
    s0 = 0.f;
    s1 = 0.f;
#pragma unroll
    for (int j = 0; j < 9; j++) {
        v[4 * j] -= m0;
        v[4 * j + 1] -= m0;
        v[4 * j + 2] -= m1;
        v[4 * j + 3] -= m1;
        s0 += v[4 * j] * v[4 * j] + v[4 * j + 1] * v[4 * j + 1];
        s1 += v[4 * j + 2] * v[4 * j + 2] + v[4 * j + 3] * v[4 * j + 3];
    }
    row_reduce(s0, s1, red + 512, warp, lane);
    const float r0 = rsqrtf(s0 * (1.f / DM) + 1e-5f), r1 = rsqrtf(s1 * (1.f / DM) + 1e-5f);
#pragma unroll
    for (int j = 0; j < 9; j++) {
        v[4 * j] *= r0;
        v[4 * j + 1] *= r0;
        v[4 * j + 2] *= r1;
        v[4 * j + 3] *= r1;
    }
}
template <int NV>
__device__ __forceinline__ void load_mod(float (&m)[NV][18], const int (&which)[NV], int warp, int lane) {
    const uint32_t t0 = clk32();
    while (true) {
        uint2 u[NV][9];
#pragma unroll
        for (int n = 0; n < NV; n++)
#pragma unroll
            for (int j = 0; j < 9; j++)
                asm volatile("ld.relaxed.gpu.global.v2.u32 {%0,%1}, [%2];"
                             : "=r"(u[n][j].x), "=r"(u[n][j].y)
                             : "l"(g_mod + which[n] * DM + (warp * 9 + j) * 8 + (lane & 3) * 2));
        uint32_t ok = 1;
#pragma unroll
        for (int n = 0; n < NV; n++)
#pragma unroll
            for (int j = 0; j < 9; j++) {
                ok &= u[n][j].x & u[n][j].y;
                m[n][2 * j] = __uint_as_float(u[n][j].x & 0xffff0000u);
                m[n][2 * j + 1] = __uint_as_float(u[n][j].y & 0xffff0000u);
            }
        if (__all_sync(0xffffffffu, ok) || clk32() - t0 > WAIT_LIMIT) break;
    }
}
__device__ __forceinline__ void modulate_store(const float (&v)[36], const float (&shift)[18], const float (&scale)[18],
                                               uint4* hbuf  , int warp, int lane) {
    uint2* dst = reinterpret_cast<uint2*>(hbuf);
#pragma unroll
    for (int j = 0; j < 9; j++) {
        const int grp = warp * 9 + j;
        const float c0 = round_bf16(1.f + scale[2 * j]), c1 = round_bf16(1.f + scale[2 * j + 1]);
        uint2 o;
        o.x = pack_bf16(fmaf(v[4 * j], c0, shift[2 * j]), fmaf(v[4 * j + 1], c1, shift[2 * j + 1]));
        o.y = pack_bf16(fmaf(v[4 * j + 2], c0, shift[2 * j]), fmaf(v[4 * j + 3], c1, shift[2 * j + 1]));
        __stcg(dst + ((grp >> 1) * 32 + lane) * 2 + (grp & 1), o);
    }
}
__device__ __forceinline__ void sum_partials(float (&v)[36], const uint2* src  , int warp) {
    uint2 t[8][9];
#pragma unroll
    for (int s = 0; s < 8; s++)
#pragma unroll
        for (int j = 0; j < 9; j++) t[s][j] = __ldcg(src + (s * 72 + warp * 9 + j) * 32);
#pragma unroll
    for (int j = 0; j < 9; j++) {
        float a = 0.f, b = 0.f, c = 0.f, d = 0.f;
#pragma unroll
        for (int s = 0; s < 8; s++) {
            a += bf_lo(t[s][j].x);
            b += bf_hi(t[s][j].x);
            c += bf_lo(t[s][j].y);
            d += bf_hi(t[s][j].y);
        }
        v[4 * j] = a;
        v[4 * j + 1] = b;
        v[4 * j + 2] = c;
        v[4 * j + 3] = d;
    }
}
__device__ __forceinline__ void load_frags(uint32_t (&a)[144], const uint4* src  ) {
#pragma unroll
    for (int k = 0; k < 36; k++) {
        uint4 t = __ldcg(src + k * 32);
        a[4 * k] = t.x;
        a[4 * k + 1] = t.y;
        a[4 * k + 2] = t.z;
        a[4 * k + 3] = t.w;
    }
}

constexpr float SM_SCALE = 0.08838834764831845f * 1.4426950408889634f;
constexpr float SM_HI = 1.2089258e24f;
constexpr float SM_LO = 9.0949470e-13f;
__device__ __forceinline__ void qk_step(float (&s)[32], const uint32_t (&q)[32], uint64_t dk) {
#pragma unroll
    for (int k = 0; k < 8; k++) {
        if (k == 0)
            wgmma_n64_z<0>(s, q[0], q[1], q[2], q[3], dk);
        else
            wgmma_n64<0>(s, q[4 * k], q[4 * k + 1], q[4 * k + 2], q[4 * k + 3], dk + (k >> 2) * 512 + (k & 3) * 2);
    }
}
__device__ __forceinline__ void pv_step(float (&o)[64], const uint32_t (&p)[16], uint64_t dv, int acc) {
#pragma unroll
    for (int k = 0; k < 4; k++)
        wgmma_n128<1>(o, p[4 * k], p[4 * k + 1], p[4 * k + 2], p[4 * k + 3], dv + k * 128, k != 0 ? 1 : acc);
}
template <bool SHIFT>
__device__ __forceinline__ void exp_step(const float (&s)[32], uint32_t (&p)[16], float n0, float n1, float& s0,
                                         float& s1) {
#pragma unroll
    for (int i = 0; i < 8; i++) {
        const float e0 = ex2(SHIFT ? s[4 * i] + n0 : s[4 * i]), e1 = ex2(SHIFT ? s[4 * i + 1] + n0 : s[4 * i + 1]);
        const float e2 = ex2(SHIFT ? s[4 * i + 2] + n1 : s[4 * i + 2]), e3 = ex2(SHIFT ? s[4 * i + 3] + n1 : s[4 * i + 3]);
        if (i == 0) {
            s0 = e0 + e1;
            s1 = e2 + e3;
        } else {
            s0 += e0 + e1;
            s1 += e2 + e3;
        }
        p[2 * i] = pack_bf16(e0, e1);
        p[2 * i + 1] = pack_bf16(e2, e3);
    }
}
__device__ __forceinline__ void row_max(const float (&sa)[32], const float (&sb)[32], float& x0, float& x1) {
    float xa[8];
#pragma unroll
    for (int i = 0; i < 8; i++) xa[i] = fmaxf(sa[i], sb[i]);
#pragma unroll
    for (int k = 1; k < 4; k++)
#pragma unroll
        for (int i = 0; i < 8; i++) xa[i] = fmaxf(xa[i], fmaxf(sa[8 * k + i], sb[8 * k + i]));
    x0 = fmaxf(fmaxf(xa[0], xa[1]), fmaxf(xa[4], xa[5]));
    x1 = fmaxf(fmaxf(xa[2], xa[3]), fmaxf(xa[6], xa[7]));
    x0 = fmaxf(x0, __shfl_xor_sync(0xffffffffu, x0, 1));
    x1 = fmaxf(x1, __shfl_xor_sync(0xffffffffu, x1, 1));
    x0 = fmaxf(x0, __shfl_xor_sync(0xffffffffu, x0, 2));
    x1 = fmaxf(x1, __shfl_xor_sync(0xffffffffu, x1, 2));
}
__device__ __forceinline__ void inv_row_sums(float l0, float l1, float& i0, float& i1) {
    l0 += __shfl_xor_sync(0xffffffffu, l0, 1);
    l1 += __shfl_xor_sync(0xffffffffu, l1, 1);
    l0 += __shfl_xor_sync(0xffffffffu, l0, 2);
    l1 += __shfl_xor_sync(0xffffffffu, l1, 2);
    i0 = rcp(l0);
    i1 = rcp(l1);
}

__device__ __forceinline__ void mod_block(const uint4 (&w)[5], const float (&sc)[5], int blk, uint32_t red, int warp,
                                          int lane) {
    float acc[8];
#pragma unroll
    for (int e = 0; e < 8; e++) acc[e] = 0.f;
#pragma unroll
    for (int i = 0; i < 5; i++) {
        acc[0] = fmaf(sc[i], bf_lo(w[i].x), acc[0]);
        acc[1] = fmaf(sc[i], bf_hi(w[i].x), acc[1]);
        acc[2] = fmaf(sc[i], bf_lo(w[i].y), acc[2]);
        acc[3] = fmaf(sc[i], bf_hi(w[i].y), acc[3]);
        acc[4] = fmaf(sc[i], bf_lo(w[i].z), acc[4]);
        acc[5] = fmaf(sc[i], bf_hi(w[i].z), acc[5]);
        acc[6] = fmaf(sc[i], bf_lo(w[i].w), acc[6]);
        acc[7] = fmaf(sc[i], bf_hi(w[i].w), acc[7]);
    }
#pragma unroll
    for (int o = 2; o < 32; o <<= 1)
#pragma unroll
        for (int e = 0; e < 8; e++) acc[e] += __shfl_xor_sync(0xffffffffu, acc[e], o);
    if (lane < 2) {
#pragma unroll
        for (int e = 0; e < 8; e++) sts32f(red + (warp * 16 + lane * 8 + e) * 4, acc[e]);
    }
    bar_sync(3, 256);
    if (warp == 0 && lane < 16) {
        float s = 0.f;
#pragma unroll
        for (int w8 = 0; w8 < 8; w8++) s += lds32f(red + (w8 * 16 + lane) * 4);
        asm volatile("st.relaxed.gpu.global.u32 [%0], %1;" ::"l"(g_mod + blk * 16 + lane),
                     "r"(__float_as_uint(round_bf16(s)) | 1u)
                     : "memory");
    }
}

__global__ void __cluster_dims__(2, 1, 1) __launch_bounds__(384, 1)
    fused_block_kernel(const __grid_constant__ Maps maps, const __nv_bfloat16* __restrict__ x,
                       const __nv_bfloat16* __restrict__ cvec, const __nv_bfloat16* __restrict__ wmod,
                       __nv_bfloat16* __restrict__ out) {
    extern __shared__ uint8_t smem_raw[];
    uint32_t sbase = (smem_u32(smem_raw) + 1023u) & ~1023u;
    asm volatile("" : "+r"(sbase));
    const int b = blockIdx.x;
    const int rank = b & 1;
    const int mt = ((b >> 1) & 7) * 2 + rank;
    const int g = b >> 4;
    const int warp = __shfl_sync(0xffffffffu, threadIdx.x >> 5, 0);
    const int lane = threadIdx.x & 31;

    if (warp >= 8) {
        asm volatile("setmaxnreg.dec.sync.aligned.u32 24;");
        if (warp == 8 && lane == 0) {
#pragma unroll
            for (int i = 0; i < 8; i++) {
                mbar_init(sbase + OFF_FULL + i * 8, 1);
                mbar_init(sbase + OFF_EMPTY + i * 8, 4);
            }
            asm volatile("fence.mbarrier_init.release.cluster;" ::: "memory");
            asm volatile("barrier.cluster.arrive.relaxed;\nbarrier.cluster.wait;" ::: "memory");
            uint32_t slot = 0, phase = 1;
            const uint32_t dst0 = sbase + rank * BOX_BYTES;
            auto acquire = [&](uint32_t bytes) {
                mbar_wait(sbase + OFF_EMPTY + slot * 8, phase);
                mbar_expect_tx(sbase + OFF_FULL + slot * 8, bytes);
            };
            auto adv8 = [&]() {
                if (++slot == 8) {
                    slot = 0;
                    phase ^= 1;
                }
            };
            auto adv6 = [&]() {
                if (++slot == 6) {
                    slot = 0;
                    phase ^= 1;
                }
            };
#pragma unroll 1
            for (int hq = 0; hq < 4; hq++) {
                const int col = (g * 4 + ((hq + 1) & 3)) * 128 + rank * 64;
#pragma unroll 1
                for (int kc = 0; kc < 9; kc++) {
                    acquire(SLOT_BYTES);
                    tma_mc(dst0 + slot * SLOT_BYTES, &maps.wq, col, kc * 64, sbase + OFF_FULL + slot * 8);
                    adv8();
                }
            }
            const int row0 = g * 4 * 2048;
#pragma unroll 1
            for (int n = 0; n < 128; n++) {
                if (n < 4) mbar_wait(sbase + OFF_EMPTY + (slot + 1) * 8, phase);
                acquire(2 * SLOT_BYTES);
                const uint32_t bar = sbase + OFF_FULL + slot * 8;
                const CUtensorMap* m = (n & 1) ? &maps.v : &maps.k;
                tma_mc(dst0 + slot * SLOT_BYTES, m, rank * 64, row0 + (n >> 1) * 128, bar);
                tma_mc(dst0 + (slot + 1) * SLOT_BYTES, m, rank * 64, row0 + (n >> 1) * 128 + 64, bar);
                adv8();
                adv8();
            }
#pragma unroll 1
            for (int p = 0; p < 4; p++)
#pragma unroll 1
                for (int kc = 0; kc < 8; kc++) {
                    acquire(SLOT_BYTES);
                    tma_mc(dst0 + slot * SLOT_BYTES, &maps.wo, p * 128 + rank * 64, g * 512 + kc * 64,
                           sbase + OFF_FULL + slot * 8);
                    adv8();
                }
#pragma unroll 1
            for (int kc = 0; kc < 4; kc++) {
                acquire(SLOT_BYTES);
                tma_mc(dst0 + slot * SLOT_BYTES, &maps.wo, 512, g * 512 + kc * 128 + rank * 64,
                       sbase + OFF_FULL + slot * 8);
                adv8();
            }
            const CUtensorMap* mg = rank ? &maps.wu : &maps.wg;
#pragma unroll 1
            for (int ch = 0; ch < 9; ch++)
#pragma unroll 1
                for (int kc = 0; kc < 9; kc++) {
                    acquire(SLOT_BYTES);
                    tma_mc(dst0 + slot * SLOT_BYTES, mg, g * 576 + ch * 64, kc * 64, sbase + OFF_FULL + slot * 8);
                    adv6();
                }
#pragma unroll 1
            for (int p = 0; p < 4; p++)
#pragma unroll 1
                for (int kc = 0; kc < 9; kc++) {
                    acquire(SLOT_BYTES);
                    tma_mc(dst0 + slot * SLOT_BYTES, &maps.wd, p * 128 + rank * 64, g * 576 + kc * 64,
                           sbase + OFF_FULL + slot * 8);
                    adv6();
                }
#pragma unroll 1
            for (int kc = 0; kc < 5; kc++) {
                acquire(kc < 4 ? SLOT_BYTES : BOX_BYTES);
                if (kc < 4 || rank == 0)
                    tma_mc(dst0 + slot * SLOT_BYTES, &maps.wd, 512, g * 576 + kc * 128 + rank * 64,
                           sbase + OFF_FULL + slot * 8);
                adv6();
            }
        }
    } else {
        asm volatile("setmaxnreg.inc.sync.aligned.u32 240;");
        const int wg = warp >> 2;
        const int tid = threadIdx.x;
        Ctx cx;
        cx.sbase = sbase;
        cx.rel_cta = (lane == 0 && (warp & 3) < 2) ? (warp & 3) : 2;
        const uint32_t red = sbase + OFF_RED;
        const int own = mt * 8 + g;
        const int orow = own * 16 + (lane >> 2);
        const int wown = mt * 8 + warp;
        Ring ring{0u, 0u};
        uint32_t a[144];

        PROF(0);
        PROFG(30);
        {
            uint4 w1[5], w2[5];
            float sc[5];
            uint32_t xs[18];
            unsigned short cu[5];
            const int half = tid & 1, r0 = tid >> 1;
            const bool second = b < 88;
#pragma unroll
            for (int i = 0; i < 5; i++) {
                const int row = min(r0 + 128 * i, DM - 1);
                cu[i] = __ldg(reinterpret_cast<const unsigned short*>(cvec) + row);
                w1[i] = __ldg(reinterpret_cast<const uint4*>(wmod + (size_t)row * (6 * DM) + half * 8) + b * 2);
            }
#pragma unroll
            for (int j = 0; j < 9; j++) {
                const int col = (warp * 9 + j) * 8 + (lane & 3) * 2;
                xs[2 * j] = __ldg(reinterpret_cast<const uint32_t*>(x + (size_t)orow * DM + col));
                xs[2 * j + 1] = __ldg(reinterpret_cast<const uint32_t*>(x + (size_t)(orow + 8) * DM + col));
            }
#pragma unroll
            for (int i = 0; i < 5; i++) {
                const int row = min(r0 + 128 * i, DM - 1);
                w2[i] = __ldg(reinterpret_cast<const uint4*>(wmod + (size_t)row * (6 * DM) + half * 8) +
                              (second ? 128 + b : b) * 2);
            }
            PROFR(17);
            asm volatile("barrier.cluster.arrive.relaxed.aligned;" ::: "memory");
#pragma unroll
            for (int i = 0; i < 5; i++) {
                const float cv = bf_lo(cu[i]);
                const float sv = round_bf16(cv * rcp(1.f + ex2(-1.4426950408889634f * cv)));
                sc[i] = (r0 + 128 * i < DM) ? sv : 0.f;
            }
            pin(sc);
            PROFR(18);
            mod_block(w1, sc, b, red + 1024, warp, lane);
            PROFR(19);
            float v[36];
#pragma unroll
            for (int j = 0; j < 9; j++) {
                v[4 * j] = bf_lo(xs[2 * j]);
                v[4 * j + 1] = bf_hi(xs[2 * j]);
                v[4 * j + 2] = bf_lo(xs[2 * j + 1]);
                v[4 * j + 3] = bf_hi(xs[2 * j + 1]);
            }
            pin(v);
            PROFR(20);
            layernorm_rows(v, red, warp, lane);
            PROFR(21);
            if (second) mod_block(w2, sc, 128 + b, red + 1024, warp, lane);
            PROF(1);
            PROFR(22);
            float md[2][18];
            const int which[2] = {0, 1};
            load_mod<2>(md, which, warp, lane);
            PROF(2);
            modulate_store(v, md[0], md[1], g_h1 + (size_t)own * 36 * 32, warp, lane);
            __syncwarp();
            if (lane == 0) signal_cnt(CNT_H1 + own);
            asm volatile("barrier.cluster.wait.aligned;" ::: "memory");
        }

        const uint32_t spill = sbase + 8 * SLOT_BYTES + wg * SLOT_BYTES + (tid & 127) * 16;
        uint32_t q[32];
        PROF(3);
        wait_cnt(CNT_H1 + wown, 8);
        PROF(4);
        load_frags(a, g_h1 + (size_t)wown * 36 * 32 + lane);
        {
            float d[64];
#pragma unroll 1
            for (int hq = 0;; hq++) {
                gemm_n128<9, 8>(d, a, cx, ring);
#pragma unroll
                for (int i = 0; i < 64; i++) d[i] *= SM_SCALE;
                if (hq == 3) break;
#pragma unroll
                for (int v = 0; v < 8; v++)
                    sts128(spill + hq * 32768 + v * 2048, pack_bf16(d[8 * v], d[8 * v + 1]),
                           pack_bf16(d[8 * v + 2], d[8 * v + 3]), pack_bf16(d[8 * v + 4], d[8 * v + 5]),
                           pack_bf16(d[8 * v + 6], d[8 * v + 7]));
            }
#pragma unroll
            for (int i = 0; i < 32; i++) q[i] = pack_bf16(d[2 * i], d[2 * i + 1]);
        }

        PROF(5);
        {
            float o[64], sa[32], sb[32];
            uint32_t pa[16], pb[16];
#pragma unroll
            for (int i = 0; i < 64; i++) o[i] = 0.f;
            float n0 = 0.f, n1 = 0.f, l0 = 1.f, l1 = 1.f;
            bool shifted = false;
            const uint64_t dbase = desc_of(sbase);
            const uint64_t dbk = dbase - (511u << 16);
            const int my_bar = 1 + wg, other_bar = 2 - wg;

            auto softmax_a = [&](bool first, float& s0, float& s1) {
                if (first) {
                    shifted = false;
                    n0 = n1 = 0.f;
                    l0 = l1 = 0.f;
                }
                if (shifted)
                    exp_step<true>(sa, pa, n0, n1, s0, s1);
                else
                    exp_step<false>(sa, pa, n0, n1, s0, s1);
            };
            auto softmax_b = [&](bool first, float s0, float s1) {
                float u0, u1;
                if (shifted)
                    exp_step<true>(sb, pb, n0, n1, u0, u1);
                else
                    exp_step<false>(sb, pb, n0, n1, u0, u1);
                s0 += u0;
                s1 += u1;
                bool bad = !(fmaxf(s0, s1) <= SM_HI);
                if (first) {
                    float r0 = s0 + __shfl_xor_sync(0xffffffffu, s0, 1), r1 = s1 + __shfl_xor_sync(0xffffffffu, s1, 1);
                    r0 += __shfl_xor_sync(0xffffffffu, r0, 2);
                    r1 += __shfl_xor_sync(0xffffffffu, r1, 2);
                    bad = bad || !(fminf(r0, r1) >= SM_LO);
                }
                if (__any_sync(0xffffffffu, bad)) {
                    float x0, x1;
                    row_max(sa, sb, x0, x1);
                    x0 = -x0;
                    x1 = -x1;
                    if (!first) {
                        x0 = fminf(x0, n0);
                        x1 = fminf(x1, n1);
                        const float al0 = ex2(x0 - n0), al1 = ex2(x1 - n1);
                        l0 *= al0;
                        l1 *= al1;
#pragma unroll
                        for (int i = 0; i < 16; i++) {
                            o[4 * i] *= al0;
                            o[4 * i + 1] *= al0;
                            o[4 * i + 2] *= al1;
                            o[4 * i + 3] *= al1;
                        }
                    }
                    n0 = x0;
                    n1 = x1;
                    shifted = true;
                    exp_step<true>(sa, pa, n0, n1, s0, s1);
                    exp_step<true>(sb, pb, n0, n1, u0, u1);
                    s0 += u0;
                    s1 += u1;
                }
                l0 += s0;
                l1 += s1;
            };

            cx.wait_full(4, 0);
            if (wg == 1) bar_sync(my_bar, 256);
            wg_fence();
            qk_step(sa, q, dbk + 4 * 1024);
            qk_step(sb, q, dbk + 5 * 1024);
            wg_commit();
            bar_arrive(other_bar, 256);
            wg_wait<0>();
            pin(sa);
            pin(sb);
            cx.release(4);
            cx.wait_full(6, 0);
            cx.wait_full(0, 1);
            {
                float s0, s1;
                softmax_a(true, s0, s1);
                softmax_b(true, s0, s1);
            }
#pragma unroll 1
            for (int t = 1; t < 64; t++) {
                const int j = t & 15;
                const uint32_t ks = 4 - 4 * (t & 1), vs = 2 + 4 * (t & 1);
                TL(0);
                bar_sync(my_bar, 256);
                TL(2);
                wg_fence();
                const uint64_t dk = dbk + ks * 1024, dv = dbase + vs * 1024;
                pv_step(o, pa, dv, j != 1);
                pv_step(o, pb, dv + 1024, 1);
                qk_step(sa, q, dk);
                wg_commit();
                qk_step(sb, q, dk + 1024);
                wg_commit();
                bar_arrive(other_bar, 256);
                TL(3);
                wg_wait<1>();
                pin(o);
                pin(sa);
                pin(pa);
                pin(pb);
                TL(4);
                cx.release(vs);
                if (j == 0) {
                    float i0, i1;
                    inv_row_sums(l0, l1, i0, i1);
                    const uint32_t dst = spill + ((t >> 4) - 1) * 32768;
#pragma unroll
                    for (int v = 0; v < 8; v++)
                        sts128(dst + v * 2048, pack_bf16(o[8 * v] * i0, o[8 * v + 1] * i0),
                               pack_bf16(o[8 * v + 2] * i1, o[8 * v + 3] * i1),
                               pack_bf16(o[8 * v + 4] * i0, o[8 * v + 5] * i0),
                               pack_bf16(o[8 * v + 6] * i1, o[8 * v + 7] * i1));
                }
                float s0, s1;
                softmax_a(j == 0, s0, s1);
                TL(5);
                wg_wait<0>();
                pin(sb);
                TL(6);
                cx.release(ks);
                const uint32_t bv = sbase + OFF_FULL + (8 - vs) * 8, pv = ((38 + 4 * t) >> 3) & 1;
                const uint32_t bk = t < 63 ? sbase + OFF_FULL + (4 - ks) * 8 : bv, pk = t < 63 ? ((40 + 4 * t) >> 3) & 1 : pv;
                const bool okv = mbar_try(bv, pv), okk = mbar_try(bk, pk);
                TL(1);
                softmax_b(j == 0, s0, s1);
                if (!(okv && okk) || j == 15) {
                    mbar_wait(bv, pv);
                    mbar_wait(bk, pk);
                    if (j == 15 && t < 63) {
                        const uint32_t src = spill + (t >> 4) * 32768;
#pragma unroll
                        for (int v = 0; v < 8; v++)
                            lds128(src + v * 2048, q[4 * v], q[4 * v + 1], q[4 * v + 2], q[4 * v + 3]);
                    }
                }
                TL(7);
            }
            bar_sync(my_bar, 256);
            wg_fence();
            pv_step(o, pa, dbase + 2 * 1024, 1);
            pv_step(o, pb, dbase + 3 * 1024, 1);
            wg_commit();
            if (wg == 0) bar_arrive(other_bar, 256);
            float i0, i1;
            inv_row_sums(l0, l1, i0, i1);
            wg_wait<0>();
            pin(o);
            cx.release(2);
#pragma unroll
            for (int i = 0; i < 16; i++) {
                a[96 + 2 * i] = pack_bf16(o[4 * i] * i0, o[4 * i + 1] * i0);
                a[96 + 2 * i + 1] = pack_bf16(o[4 * i + 2] * i1, o[4 * i + 3] * i1);
            }
#pragma unroll
            for (int v = 0; v < 24; v++)
                lds128(spill + (v >> 3) * 32768 + (v & 7) * 2048, a[4 * v], a[4 * v + 1], a[4 * v + 2], a[4 * v + 3]);
        }

        PROF(6);
        uint2* part_dst = g_part + ((size_t)wown * 8 + g) * 72 * 32 + lane;
        const uint2* part_src = g_part + (size_t)own * 8 * 72 * 32 + lane;
        float4* x2buf = g_x2 + (size_t)b * 9 * 256 + tid;
        ring.slot = 4;
        ring.phase = 0;
        proj_partials<8, 8>(a, cx, ring, part_dst);
        __syncwarp();
        PROF(7);
        if (lane == 0) signal_cnt(CNT_P1 + wown);
        PROF(8);

        {
            float v[36];
            uint32_t xs[18];
#pragma unroll
            for (int j = 0; j < 9; j++) {
                const int col = (warp * 9 + j) * 8 + (lane & 3) * 2;
                xs[2 * j] = __ldg(reinterpret_cast<const uint32_t*>(x + (size_t)orow * DM + col));
                xs[2 * j + 1] = __ldg(reinterpret_cast<const uint32_t*>(x + (size_t)(orow + 8) * DM + col));
            }
            float md[3][18];
            const int which[3] = {2, 3, 4};
            load_mod<3>(md, which, warp, lane);
            wait_cnt(CNT_P1 + own, 8);
            PROF(9);
            sum_partials(v, part_src, warp);
#pragma unroll
            for (int j = 0; j < 9; j++) {
                v[4 * j] = fmaf(md[0][2 * j], v[4 * j], bf_lo(xs[2 * j]));
                v[4 * j + 1] = fmaf(md[0][2 * j + 1], v[4 * j + 1], bf_hi(xs[2 * j]));
                v[4 * j + 2] = fmaf(md[0][2 * j], v[4 * j + 2], bf_lo(xs[2 * j + 1]));
                v[4 * j + 3] = fmaf(md[0][2 * j + 1], v[4 * j + 3], bf_hi(xs[2 * j + 1]));
                __stcg(x2buf + j * 256, make_float4(v[4 * j], v[4 * j + 1], v[4 * j + 2], v[4 * j + 3]));
            }
            PROF(10);
            layernorm_rows(v, red, warp, lane);
            modulate_store(v, md[1], md[2], g_h2 + (size_t)own * 36 * 32, warp, lane);
            __syncwarp();
            if (lane == 0) signal_cnt(CNT_H2 + own);
        }

        PROF(11);
        wait_cnt(CNT_H2 + wown, 8);
        PROF(12);
        load_frags(a, g_h2 + (size_t)wown * 36 * 32 + lane);
        ring.slot = 0;
        ring.phase = 1;
        const uint32_t hsp = sbase + 6 * SLOT_BYTES + wg * BOX_BYTES + (tid & 127) * 16;
        {
            float d[64];
#pragma unroll 1
            for (int ch = 0;; ch++) {
                gemm_n128<9, 6>(d, a, cx, ring);
#pragma unroll
                for (int i = 0; i < 32; i++) {
                    const float gv = d[i];
                    const float k1 = -2.f * 0.7978845608028654f * 1.4426950408889634f;
                    const float zz = gv * fmaf(gv * gv, k1 * 0.044715f, k1);
                    d[i] = gv * rcp(1.f + ex2(zz)) * d[32 + i];
                }
                if (ch == 8) break;
                const uint32_t dst = hsp + ((ch + 2) & 7) * SLOT_BYTES;
#pragma unroll
                for (int v = 0; v < 4; v++)
                    sts128(dst + v * 2048, pack_bf16(d[8 * v], d[8 * v + 1]), pack_bf16(d[8 * v + 2], d[8 * v + 3]),
                           pack_bf16(d[8 * v + 4], d[8 * v + 5]), pack_bf16(d[8 * v + 6], d[8 * v + 7]));
            }
#pragma unroll
            for (int i = 0; i < 16; i++) a[128 + i] = pack_bf16(d[2 * i], d[2 * i + 1]);
        }
#pragma unroll
        for (int v = 0; v < 32; v++)
            lds128(hsp + (((v >> 2) + 2) & 7) * SLOT_BYTES + (v & 3) * 2048, a[4 * v], a[4 * v + 1], a[4 * v + 2],
                   a[4 * v + 3]);

        PROF(13);
        proj_partials<9, 6>(a, cx, ring, part_dst);
        asm volatile("barrier.cluster.arrive.relaxed.aligned;" ::: "memory");
        __syncwarp();
        PROF(14);
        if (lane == 0) signal_cnt(CNT_P2 + wown);

        {
            float v[36];
            float4 xr[9];
            float gb[1][18];
#pragma unroll
            for (int j = 0; j < 9; j++) xr[j] = __ldcg(x2buf + j * 256);
            const int which[1] = {5};
            load_mod<1>(gb, which, warp, lane);
            wait_cnt(CNT_P2 + own, 8);
            PROF(15);
            sum_partials(v, part_src, warp);
#pragma unroll
            for (int j = 0; j < 9; j++) {
                const int col = (warp * 9 + j) * 8 + (lane & 3) * 2;
                *reinterpret_cast<uint32_t*>(out + (size_t)orow * DM + col) =
                    pack_bf16(fmaf(gb[0][2 * j], v[4 * j], xr[j].x), fmaf(gb[0][2 * j + 1], v[4 * j + 1], xr[j].y));
                *reinterpret_cast<uint32_t*>(out + (size_t)(orow + 8) * DM + col) =
                    pack_bf16(fmaf(gb[0][2 * j], v[4 * j + 2], xr[j].z), fmaf(gb[0][2 * j + 1], v[4 * j + 3], xr[j].w));
            }
        }
        PROF(16);
        PROFG(31);
        bar_sync(3, 256);
        if (warp == 0) {
            unsigned old = 0;
            if (lane == 0)
                asm volatile("atom.acq_rel.gpu.global.add.u32 %0, [%1], 1;" : "=r"(old) : "l"(&g_cnt[CNT_DONE * 32]) : "memory");
            old = __shfl_sync(0xffffffffu, old, 0);
            if (old == 127) {
                for (int i = lane; i < CNT_TOTAL; i += 32) g_cnt[i * 32] = 0;
                for (int i = lane; i < 6 * DM / 4; i += 32) reinterpret_cast<uint4*>(g_mod)[i] = make_uint4(0, 0, 0, 0);
            }
        }
        asm volatile("barrier.cluster.wait.aligned;" ::: "memory");
    }
}

typedef CUresult (*EncodeFn)(CUtensorMap*, CUtensorMapDataType, cuuint32_t, void*, const cuuint64_t*, const cuuint64_t*,
                             const cuuint32_t*, const cuuint32_t*, CUtensorMapInterleave, CUtensorMapSwizzle,
                             CUtensorMapL2promotion, CUtensorMapFloatOOBfill);

void make_map(EncodeFn enc, CUtensorMap* m, const void* ptr, uint64_t rows, uint64_t cols) {
    cuuint64_t gdim[2] = {cols, rows};
    cuuint64_t gstr[1] = {cols * 2};
    cuuint32_t box[2] = {64, 64};
    cuuint32_t estr[2] = {1, 1};
    enc(m, CU_TENSOR_MAP_DATA_TYPE_BFLOAT16, 2, const_cast<void*>(ptr), gdim, gstr, box, estr,
        CU_TENSOR_MAP_INTERLEAVE_NONE, CU_TENSOR_MAP_SWIZZLE_128B, CU_TENSOR_MAP_L2_PROMOTION_L2_128B,
        CU_TENSOR_MAP_FLOAT_OOB_FILL_NONE);
}

}

extern "C" void kernel_launch(void* const* d_in, const int* in_sizes, int n_in, void* d_out, int out_size) {
    (void)in_sizes;
    (void)n_in;
    (void)out_size;
    void* fn = nullptr;
    cudaDriverEntryPointQueryResult qr;
    cudaGetDriverEntryPoint("cuTensorMapEncodeTiled", &fn, cudaEnableDefault, &qr);
    EncodeFn enc = (EncodeFn)fn;
    Maps maps;
    make_map(enc, &maps.k, d_in[1], 32 * 2048, 128);
    make_map(enc, &maps.v, d_in[2], 32 * 2048, 128);
    make_map(enc, &maps.wq, d_in[3], 576, 4096);
    make_map(enc, &maps.wo, d_in[4], 4096, 576);
    make_map(enc, &maps.wg, d_in[6], 576, 4608);
    make_map(enc, &maps.wu, d_in[7], 576, 4608);
    make_map(enc, &maps.wd, d_in[8], 4608, 576);
    cudaFuncSetAttribute(fused_block_kernel, cudaFuncAttributeMaxDynamicSharedMemorySize, SMEM_BYTES);
    fused_block_kernel<<<128, 384, SMEM_BYTES>>>(maps, (const __nv_bfloat16*)d_in[0], (const __nv_bfloat16*)d_in[9],
                                                 (const __nv_bfloat16*)d_in[10], (__nv_bfloat16*)d_out);
}
```

```cpp
#include <cuda_runtime.h>
#include <cuda_bf16.h>
#include <cuda.h>
#include <stdint.h>

namespace {

constexpr int DM = 576;
constexpr int SLOT_BYTES = 16384;
constexpr int BOX_BYTES = 8192;
constexpr int NUNITS = 14;
constexpr int SMEM_TAIL = NUNITS * SLOT_BYTES;
constexpr int SMEM_BYTES = SMEM_TAIL + 2048 + 1024;
constexpr int OFF_FULL = SMEM_TAIL;
constexpr int OFF_EMPTY = SMEM_TAIL + 64;
constexpr int OFF_RED = SMEM_TAIL + 128;

constexpr int OFF_XBAR = SMEM_TAIL + 1792;
constexpr int XROW_STRIDE = DM * 2 + 16;

__device__ unsigned g_epoch;
__device__ __align__(16) uint32_t g_mod[6 * DM];
__device__ uint4 g_h[2][128 * 36 * 32];
__device__ unsigned long long g_part[128 * 8 * 72 * 32];
__device__ float4 g_x2[128 * 9 * 256];
__device__ uint4 g_hh[128 * 8 * 256];
__device__ unsigned g_cnt[256 * 32];

#define TL(i)
#define PROFR(i)
#define PROF(i)
#define PROFG(i)

struct Maps {
    CUtensorMap k, v, wq, wo, wg, wu, wd;
};

__device__ __forceinline__ uint32_t smem_u32(const void* p) { return (uint32_t)__cvta_generic_to_shared(p); }
__device__ __forceinline__ void mbar_init(uint32_t a, uint32_t c) {
    asm volatile("mbarrier.init.shared::cta.b64 [%0], %1;" ::"r"(a), "r"(c) : "memory");
}
__device__ __forceinline__ void mbar_expect_tx(uint32_t a, uint32_t bytes) {
    asm volatile("mbarrier.arrive.expect_tx.shared::cta.b64 _, [%0], %1;" ::"r"(a), "r"(bytes) : "memory");
}
__device__ __forceinline__ bool mbar_try(uint32_t a, uint32_t ph) {
    uint32_t ok;
    asm volatile(
        "{\n.reg .pred p;\nmbarrier.try_wait.parity.shared::cta.b64 p, [%1], %2;\nselp.u32 %0, 1, 0, p;\n}"
        : "=r"(ok)
        : "r"(a), "r"(ph)
        : "memory");
    return ok != 0;
}
__device__ __forceinline__ uint32_t clk32() {
    uint32_t c;
    asm volatile("mov.u32 %0, %%clock;" : "=r"(c));
    return c;
}
constexpr uint32_t WAIT_LIMIT = 1u << 30;
__device__ __forceinline__ void mbar_wait(uint32_t a, uint32_t ph) {
    if (mbar_try(a, ph)) return;
    uint32_t t0 = clk32();
    while (!mbar_try(a, ph)) {
        if (clk32() - t0 > WAIT_LIMIT) break;
    }
}
__device__ __forceinline__ void mbar_arrive_cluster(uint32_t a, uint32_t cta) {
    asm volatile(
        "{\n.reg .b32 ra;\nmapa.shared::cluster.u32 ra, %0, %1;\nmbarrier.arrive.shared::cluster.b64 _, [ra];\n}" ::"r"(a),
        "r"(cta)
        : "memory");
}
__device__ __forceinline__ void tma_mc(uint32_t dst, const CUtensorMap* m, int c0, int c1, uint32_t bar) {
    asm volatile(
        "cp.async.bulk.tensor.2d.shared::cluster.global.mbarrier::complete_tx::bytes.multicast::cluster"
        " [%0], [%1, {%3, %4}], [%2], %5;" ::"r"(dst),
        "l"(m), "r"(bar), "r"(c0), "r"(c1), "h"((uint16_t)3)
        : "memory");
}
__device__ __forceinline__ void bar_sync(int id, int n) { asm volatile("bar.sync %0, %1;" ::"r"(id), "r"(n) : "memory"); }
__device__ __forceinline__ void bar_arrive(int id, int n) {
    asm volatile("bar.arrive %0, %1;" ::"r"(id), "r"(n) : "memory");
}
__device__ __forceinline__ void wg_fence() { asm volatile("wgmma.fence.sync.aligned;" ::: "memory"); }
__device__ __forceinline__ void wg_commit() { asm volatile("wgmma.commit_group.sync.aligned;" ::: "memory"); }
template <int N>
__device__ __forceinline__ void wg_wait() {
    asm volatile("wgmma.wait_group.sync.aligned %0;" ::"n"(N) : "memory");
}
template <int N>
__device__ __forceinline__ void pin(float (&d)[N]) {
#pragma unroll
    for (int i = 0; i < N; i++) asm volatile("" : "+f"(d[i])::"memory");
}
template <int N>
__device__ __forceinline__ void pin(uint32_t (&d)[N]) {
#pragma unroll
    for (int i = 0; i < N; i++) asm volatile("" : "+r"(d[i])::"memory");
}
__device__ __forceinline__ uint32_t pack_bf16(float lo, float hi) {
    uint32_t r;
    asm("cvt.rn.bf16x2.f32 %0, %1, %2;" : "=r"(r) : "f"(hi), "f"(lo));
    return r;
}
__device__ __forceinline__ float bf_lo(uint32_t v) { return __uint_as_float(v << 16); }
__device__ __forceinline__ float bf_hi(uint32_t v) { return __uint_as_float(v & 0xffff0000u); }
__device__ __forceinline__ float round_bf16(float v) { return __bfloat162float(__float2bfloat16_rn(v)); }
__device__ __forceinline__ float ex2(float x) {
    float y;
    asm("ex2.approx.ftz.f32 %0, %1;" : "=f"(y) : "f"(x));
    return y;
}
__device__ __forceinline__ float rcp(float x) {
    float y;
    asm("rcp.approx.ftz.f32 %0, %1;" : "=f"(y) : "f"(x));
    return y;
}
__device__ __forceinline__ float tanh_fast(float x) {
    float y;
    asm("tanh.approx.f32 %0, %1;" : "=f"(y) : "f"(x));
    return y;
}
__device__ __forceinline__ void sts128(uint32_t a, uint32_t x, uint32_t y, uint32_t z, uint32_t w) {
    asm volatile("st.shared.v4.b32 [%0], {%1,%2,%3,%4};" ::"r"(a), "r"(x), "r"(y), "r"(z), "r"(w) : "memory");
}
__device__ __forceinline__ void lds128(uint32_t a, uint32_t& x, uint32_t& y, uint32_t& z, uint32_t& w) {
    asm volatile("ld.shared.v4.b32 {%0,%1,%2,%3}, [%4];" : "=r"(x), "=r"(y), "=r"(z), "=r"(w) : "r"(a) : "memory");
}
__device__ __forceinline__ void sts32f(uint32_t a, float v) {
    asm volatile("st.shared.f32 [%0], %1;" ::"r"(a), "f"(v) : "memory");
}
__device__ __forceinline__ float lds32f(uint32_t a) {
    float v;
    asm volatile("ld.shared.f32 %0, [%1];" : "=f"(v) : "r"(a) : "memory");
    return v;
}
__device__ __forceinline__ void signal_cnt(int idx) {
    asm volatile("red.release.gpu.global.add.u32 [%0], 1;" ::"l"(&g_cnt[idx * 32]) : "memory");
}
__device__ __forceinline__ void wait_cnt(int idx, unsigned target) {
    if ((threadIdx.x & 31) == 0) {
        uint32_t t0 = clk32();
        while (true) {
            unsigned v;
            asm volatile("ld.acquire.gpu.global.u32 %0, [%1];" : "=r"(v) : "l"(&g_cnt[idx * 32]) : "memory");
            if ((int)(v - target) >= 0) break;
            if (clk32() - t0 > WAIT_LIMIT) break;
        }
    }
    __syncwarp();
}

#define F8(d, b) \
    "+f"(d[b]), "+f"(d[b + 1]), "+f"(d[b + 2]), "+f"(d[b + 3]), "+f"(d[b + 4]), "+f"(d[b + 5]), "+f"(d[b + 6]), "+f"(d[b + 7])

template <int TB>
__device__ __forceinline__ void wgmma_n128(float (&d)[64], uint32_t a0, uint32_t a1, uint32_t a2, uint32_t a3,
                                           uint64_t db, int sc) {
    asm volatile(
        "{\n.reg .pred p;\nsetp.ne.b32 p, %69, 0;\n"
        "wgmma.mma_async.sync.aligned.m64n128k16.f32.bf16.bf16 "
        "{%0,%1,%2,%3,%4,%5,%6,%7,%8,%9,%10,%11,%12,%13,%14,%15,%16,%17,%18,%19,%20,%21,%22,%23,%24,%25,%26,%27,%28,%29,%30,%31,"
        "%32,%33,%34,%35,%36,%37,%38,%39,%40,%41,%42,%43,%44,%45,%46,%47,%48,%49,%50,%51,%52,%53,%54,%55,%56,%57,%58,%59,%60,%61,%62,%63},"
        "{%64,%65,%66,%67}, %68, p, 1, 1, %70;\n}"
        : F8(d, 0), F8(d, 8), F8(d, 16), F8(d, 24), F8(d, 32), F8(d, 40), F8(d, 48), F8(d, 56)
        : "r"(a0), "r"(a1), "r"(a2), "r"(a3), "l"(db), "r"(sc), "n"(TB));
}
#define O8(d, b) \
    "=f"(d[b]), "=f"(d[b + 1]), "=f"(d[b + 2]), "=f"(d[b + 3]), "=f"(d[b + 4]), "=f"(d[b + 5]), "=f"(d[b + 6]), "=f"(d[b + 7])
template <int TB>
__device__ __forceinline__ void wgmma_n128_z(float (&d)[64], uint32_t a0, uint32_t a1, uint32_t a2, uint32_t a3,
                                             uint64_t db) {
    asm volatile(
        "wgmma.mma_async.sync.aligned.m64n128k16.f32.bf16.bf16 "
        "{%0,%1,%2,%3,%4,%5,%6,%7,%8,%9,%10,%11,%12,%13,%14,%15,%16,%17,%18,%19,%20,%21,%22,%23,%24,%25,%26,%27,%28,%29,%30,%31,"
        "%32,%33,%34,%35,%36,%37,%38,%39,%40,%41,%42,%43,%44,%45,%46,%47,%48,%49,%50,%51,%52,%53,%54,%55,%56,%57,%58,%59,%60,%61,%62,%63},"
        "{%64,%65,%66,%67}, %68, 0, 1, 1, %69;"
        : O8(d, 0), O8(d, 8), O8(d, 16), O8(d, 24), O8(d, 32), O8(d, 40), O8(d, 48), O8(d, 56)
        : "r"(a0), "r"(a1), "r"(a2), "r"(a3), "l"(db), "n"(TB));
}
template <int TB>
__device__ __forceinline__ void wgmma_n64_z(float (&d)[32], uint32_t a0, uint32_t a1, uint32_t a2, uint32_t a3,
                                            uint64_t db) {
    asm volatile(
        "wgmma.mma_async.sync.aligned.m64n64k16.f32.bf16.bf16 "
        "{%0,%1,%2,%3,%4,%5,%6,%7,%8,%9,%10,%11,%12,%13,%14,%15,%16,%17,%18,%19,%20,%21,%22,%23,%24,%25,%26,%27,%28,%29,%30,%31},"
        "{%32,%33,%34,%35}, %36, 0, 1, 1, %37;"
        : O8(d, 0), O8(d, 8), O8(d, 16), O8(d, 24)
        : "r"(a0), "r"(a1), "r"(a2), "r"(a3), "l"(db), "n"(TB));
}
template <int TB>
__device__ __forceinline__ void wgmma_n64(float (&d)[32], uint32_t a0, uint32_t a1, uint32_t a2, uint32_t a3,
                                          uint64_t db) {
    asm volatile(
        "wgmma.mma_async.sync.aligned.m64n64k16.f32.bf16.bf16 "
        "{%0,%1,%2,%3,%4,%5,%6,%7,%8,%9,%10,%11,%12,%13,%14,%15,%16,%17,%18,%19,%20,%21,%22,%23,%24,%25,%26,%27,%28,%29,%30,%31},"
        "{%32,%33,%34,%35}, %36, 1, 1, 1, %37;"
        : F8(d, 0), F8(d, 8), F8(d, 16), F8(d, 24)
        : "r"(a0), "r"(a1), "r"(a2), "r"(a3), "l"(db), "n"(TB));
}

__device__ __forceinline__ uint64_t desc_of(uint32_t saddr) {
    return (uint64_t)(((saddr >> 4) & 0x3FFFu) | (512u << 16)) | ((uint64_t)(64u | (1u << 30)) << 32);
}

struct Ring {
    uint32_t slot;
    uint32_t phase;
    __device__ __forceinline__ void next() {
        if (++slot == 8) {
            slot = 0;
            phase ^= 1;
        }
    }
};

struct Ctx {
    uint32_t sbase;
    uint32_t rel_cta;
    __device__ __forceinline__ void wait_full(uint32_t slot, uint32_t phase) const {
        mbar_wait(sbase + OFF_FULL + slot * 8, phase);
    }
    __device__ __forceinline__ void release(uint32_t slot) const {
        if (rel_cta < 2) mbar_arrive_cluster(sbase + OFF_EMPTY + slot * 8, rel_cta);
    }
};

__device__ __forceinline__ void gemm_n128(float (&d)[64], const uint32_t (&a)[144], const Ctx& c, Ring& r, bool nine,
                                          int kick) {
    uint32_t prev = 0;
#pragma unroll
    for (int s = 0; s < 9; s++) {
        if (s < 8 || nine) {
            c.wait_full(r.slot, r.phase);
            uint64_t db = desc_of(c.sbase + r.slot * SLOT_BYTES);
            wg_fence();
#pragma unroll
            for (int k = 0; k < 4; k++) {
                if ((s | k) == 0)
                    wgmma_n128_z<1>(d, a[0], a[1], a[2], a[3], db);
                else
                    wgmma_n128<1>(d, a[s * 16 + k * 4], a[s * 16 + k * 4 + 1], a[s * 16 + k * 4 + 2],
                                  a[s * 16 + k * 4 + 3], db + k * 128, 1);
            }
            wg_commit();
            if (s == 3 && kick) bar_arrive(kick, 256);
            if (s > 0) {
                wg_wait<1>();
                c.release(prev);
            }
            prev = r.slot;
            r.next();
        }
    }
    wg_wait<0>();
    c.release(prev);
    pin(d);
}
__device__ __forceinline__ void gemm_n64(float (&d)[32], const uint32_t (&a)[144], const Ctx& c, Ring& r, bool nine) {
    uint32_t prev = 0;
#pragma unroll
    for (int s = 0; s < 5; s++) {
        if (s < 4 || nine) {
            c.wait_full(r.slot, r.phase);
            uint64_t db = desc_of(c.sbase + r.slot * SLOT_BYTES);
            wg_fence();
#pragma unroll
            for (int k = 0; k < 8; k++) {
                if ((s | k) == 0)
                    wgmma_n64_z<1>(d, a[0], a[1], a[2], a[3], db);
                else if (s * 8 + k < 36)
                    wgmma_n64<1>(d, a[s * 32 + k * 4], a[s * 32 + k * 4 + 1], a[s * 32 + k * 4 + 2],
                                 a[s * 32 + k * 4 + 3], db + k * 128);
            }
            wg_commit();
            if (s > 0) {
                wg_wait<1>();
                c.release(prev);
            }
            prev = r.slot;
            r.next();
        }
    }
    wg_wait<0>();
    c.release(prev);
    pin(d);
}
__device__ __forceinline__ void st_part(unsigned long long* p, float a, float b, float c, float d, uint32_t tag) {
    const uint32_t lo = (pack_bf16(a, b) & ~1u) | tag, hi = pack_bf16(c, d);
    asm volatile("{\n.reg .b64 t;\nmov.b64 t, {%1, %2};\nst.relaxed.gpu.global.b64 [%0], t;\n}" ::"l"(p), "r"(lo), "r"(hi)
                 : "memory");
}
__device__ __forceinline__ uint2 ld_part(const unsigned long long* p) {
    uint2 r;
    asm volatile("{\n.reg .b64 t;\nld.relaxed.gpu.global.b64 t, [%2];\nmov.b64 {%0, %1}, t;\n}"
                 : "=r"(r.x), "=r"(r.y)
                 : "l"(p));
    return r;
}
__device__ __forceinline__ void proj_partials(const uint32_t (&a)[144], const Ctx& c, Ring& r, bool nine,
                                              unsigned long long* dst  , uint32_t tag) {
#pragma unroll 1
    for (int p = 0; p < 4; p++) {
        float d[64];
        gemm_n128(d, a, c, r, nine, 0);
#pragma unroll
        for (int j = 0; j < 16; j++) st_part(dst + (p * 16 + j) * 32, d[4 * j], d[4 * j + 1], d[4 * j + 2], d[4 * j + 3], tag);
    }
    float d[32];
    gemm_n64(d, a, c, r, nine);
#pragma unroll
    for (int j = 0; j < 8; j++) st_part(dst + (64 + j) * 32, d[4 * j], d[4 * j + 1], d[4 * j + 2], d[4 * j + 3], tag);
}

__device__ __forceinline__ void row_reduce(float& s0, float& s1, uint32_t red, int warp, int lane) {
    s0 += __shfl_xor_sync(0xffffffffu, s0, 1);
    s1 += __shfl_xor_sync(0xffffffffu, s1, 1);
    s0 += __shfl_xor_sync(0xffffffffu, s0, 2);
    s1 += __shfl_xor_sync(0xffffffffu, s1, 2);
    if ((lane & 3) == 0) {
        sts32f(red + (warp * 16 + (lane >> 2)) * 4, s0);
        sts32f(red + (warp * 16 + 8 + (lane >> 2)) * 4, s1);
    }
    bar_sync(3, 256);
    s0 = 0.f;
    s1 = 0.f;
#pragma unroll
    for (int w = 0; w < 8; w++) {
        s0 += lds32f(red + (w * 16 + (lane >> 2)) * 4);
        s1 += lds32f(red + (w * 16 + 8 + (lane >> 2)) * 4);
    }
}
__device__ __forceinline__ void layernorm_rows(float (&v)[36], uint32_t red, int warp, int lane) {
    float s0 = 0.f, s1 = 0.f;
#pragma unroll
    for (int j = 0; j < 9; j++) {
        s0 += v[4 * j] + v[4 * j + 1];
        s1 += v[4 * j + 2] + v[4 * j + 3];
    }
    row_reduce(s0, s1, red, warp, lane);
    const float m0 = s0 * (1.f / DM), m1 = s1 * (1.f / DM);
    s0 = 0.f;
    s1 = 0.f;
#pragma unroll
    for (int j = 0; j < 9; j++) {
        v[4 * j] -= m0;
        v[4 * j + 1] -= m0;
        v[4 * j + 2] -= m1;
        v[4 * j + 3] -= m1;
        s0 += v[4 * j] * v[4 * j] + v[4 * j + 1] * v[4 * j + 1];
        s1 += v[4 * j + 2] * v[4 * j + 2] + v[4 * j + 3] * v[4 * j + 3];
    }
    row_reduce(s0, s1, red + 512, warp, lane);
    const float r0 = rsqrtf(s0 * (1.f / DM) + 1e-5f), r1 = rsqrtf(s1 * (1.f / DM) + 1e-5f);
#pragma unroll
    for (int j = 0; j < 9; j++) {
        v[4 * j] *= r0;
        v[4 * j + 1] *= r0;
        v[4 * j + 2] *= r1;
        v[4 * j + 3] *= r1;
    }
}
template <int NV>
__device__ __forceinline__ void load_mod(float (&m)[NV][18], int first, uint32_t tag, int warp, int lane) {
    const uint32_t t0 = clk32();
    const uint32_t* src = g_mod + first * DM + warp * 8 + (lane & 3) * 2;
    while (true) {
        uint2 u[NV][9];
#pragma unroll
        for (int n = 0; n < NV; n++)
#pragma unroll
            for (int j = 0; j < 9; j++)
                asm volatile("ld.relaxed.gpu.global.v2.u32 {%0,%1}, [%2];"
                             : "=r"(u[n][j].x), "=r"(u[n][j].y)
                             : "l"(src + n * DM + j * 64));
        uint32_t bad = 0;
#pragma unroll
        for (int n = 0; n < NV; n++)
#pragma unroll
            for (int j = 0; j < 9; j++) {
                bad |= (u[n][j].x ^ tag) | (u[n][j].y ^ tag);
                m[n][2 * j] = __uint_as_float(u[n][j].x & 0xffff0000u);
                m[n][2 * j + 1] = __uint_as_float(u[n][j].y & 0xffff0000u);
            }
        if (__all_sync(0xffffffffu, (bad & 0xffffu) == 0) || clk32() - t0 > WAIT_LIMIT) break;
    }
}
__device__ __forceinline__ void modulate_store(const float (&v)[36], const float (&shift)[18], const float (&scale)[18],
                                               uint4* hbuf  , int warp, int lane) {
    uint2* dst = reinterpret_cast<uint2*>(hbuf) + ((warp >> 1) * 32 + lane) * 2 + (warp & 1);
#pragma unroll
    for (int j = 0; j < 9; j++) {
        const float c0 = round_bf16(1.f + scale[2 * j]), c1 = round_bf16(1.f + scale[2 * j + 1]);
        uint2 o;
        o.x = pack_bf16(fmaf(v[4 * j], c0, shift[2 * j]), fmaf(v[4 * j + 1], c1, shift[2 * j + 1]));
        o.y = pack_bf16(fmaf(v[4 * j + 2], c0, shift[2 * j]), fmaf(v[4 * j + 3], c1, shift[2 * j + 1]));
        __stcg(dst + j * 256, o);
    }
}
__device__ __forceinline__ void sum_partials(float (&v)[36], const unsigned long long* src  ,
                                             uint32_t tag) {
    const uint32_t t0 = clk32();
    while (true) {
        uint2 t[8][8];
#pragma unroll
        for (int s = 0; s < 8; s++)
#pragma unroll
            for (int j = 0; j < 8; j++) t[s][j] = ld_part(src + (s * 72 + j * 8) * 32);
        uint32_t bad = 0;
#pragma unroll
        for (int s = 0; s < 8; s++)
#pragma unroll
            for (int j = 0; j < 8; j++) {
                bad |= t[s][j].x ^ tag;
                if (s == 0) {
                    v[4 * j] = bf_lo(t[s][j].x);
                    v[4 * j + 1] = bf_hi(t[s][j].x);
                    v[4 * j + 2] = bf_lo(t[s][j].y);
                    v[4 * j + 3] = bf_hi(t[s][j].y);
                } else {
                    v[4 * j] += bf_lo(t[s][j].x);
                    v[4 * j + 1] += bf_hi(t[s][j].x);
                    v[4 * j + 2] += bf_lo(t[s][j].y);
                    v[4 * j + 3] += bf_hi(t[s][j].y);
                }
            }
        if (__all_sync(0xffffffffu, (bad & 1u) == 0) || clk32() - t0 > WAIT_LIMIT) break;
    }
    while (true) {
        uint2 t[8];
#pragma unroll
        for (int s = 0; s < 8; s++) t[s] = ld_part(src + (s * 72 + 64) * 32);
        uint32_t bad = 0;
        v[32] = v[33] = v[34] = v[35] = 0.f;
#pragma unroll
        for (int s = 0; s < 8; s++) {
            bad |= t[s].x ^ tag;
            v[32] += bf_lo(t[s].x);
            v[33] += bf_hi(t[s].x);
            v[34] += bf_lo(t[s].y);
            v[35] += bf_hi(t[s].y);
        }
        if (__all_sync(0xffffffffu, (bad & 1u) == 0) || clk32() - t0 > WAIT_LIMIT) break;
    }
}
__device__ __forceinline__ void load_frags(uint32_t (&a)[144], const uint4* src  ) {
#pragma unroll
    for (int k = 0; k < 36; k++) {
        uint4 t = __ldcg(src + k * 32);
        a[4 * k] = t.x;
        a[4 * k + 1] = t.y;
        a[4 * k + 2] = t.z;
        a[4 * k + 3] = t.w;
    }
}

constexpr float SM_SCALE = 0.08838834764831845f * 1.4426950408889634f;
constexpr float SM_HI = 1.2089258e24f;
constexpr float SM_LO = 9.0949470e-13f;
__device__ __forceinline__ void qk_step(float (&s)[32], const uint32_t (&q)[32], uint64_t dk) {
#pragma unroll
    for (int k = 0; k < 8; k++) {
        if (k == 0)
            wgmma_n64_z<0>(s, q[0], q[1], q[2], q[3], dk);
        else
            wgmma_n64<0>(s, q[4 * k], q[4 * k + 1], q[4 * k + 2], q[4 * k + 3], dk + (k >> 2) * 512 + (k & 3) * 2);
    }
}
__device__ __forceinline__ void pv_step(float (&o)[64], const uint32_t (&p)[16], uint64_t dv, int acc) {
#pragma unroll
    for (int k = 0; k < 4; k++)
        wgmma_n128<1>(o, p[4 * k], p[4 * k + 1], p[4 * k + 2], p[4 * k + 3], dv + k * 128, k != 0 ? 1 : acc);
}
template <bool SHIFT>
__device__ __forceinline__ void exp_step(const float (&s)[32], uint32_t (&p)[16], float n0, float n1, float& s0,
                                         float& s1) {
#pragma unroll
    for (int i = 0; i < 8; i++) {
        const float e0 = ex2(SHIFT ? s[4 * i] + n0 : s[4 * i]), e1 = ex2(SHIFT ? s[4 * i + 1] + n0 : s[4 * i + 1]);
        const float e2 = ex2(SHIFT ? s[4 * i + 2] + n1 : s[4 * i + 2]), e3 = ex2(SHIFT ? s[4 * i + 3] + n1 : s[4 * i + 3]);
        if (i == 0) {
            s0 = e0 + e1;
            s1 = e2 + e3;
        } else {
            s0 += e0 + e1;
            s1 += e2 + e3;
        }
        p[2 * i] = pack_bf16(e0, e1);
        p[2 * i + 1] = pack_bf16(e2, e3);
    }
}
__device__ __forceinline__ void row_max(const float (&sa)[32], const float (&sb)[32], float& x0, float& x1) {
    float xa[8];
#pragma unroll
    for (int i = 0; i < 8; i++) xa[i] = fmaxf(sa[i], sb[i]);
#pragma unroll
    for (int k = 1; k < 4; k++)
#pragma unroll
        for (int i = 0; i < 8; i++) xa[i] = fmaxf(xa[i], fmaxf(sa[8 * k + i], sb[8 * k + i]));
    x0 = fmaxf(fmaxf(xa[0], xa[1]), fmaxf(xa[4], xa[5]));
    x1 = fmaxf(fmaxf(xa[2], xa[3]), fmaxf(xa[6], xa[7]));
    x0 = fmaxf(x0, __shfl_xor_sync(0xffffffffu, x0, 1));
    x1 = fmaxf(x1, __shfl_xor_sync(0xffffffffu, x1, 1));
    x0 = fmaxf(x0, __shfl_xor_sync(0xffffffffu, x0, 2));
    x1 = fmaxf(x1, __shfl_xor_sync(0xffffffffu, x1, 2));
}
__device__ __forceinline__ void inv_row_sums(float l0, float l1, float& i0, float& i1) {
    l0 += __shfl_xor_sync(0xffffffffu, l0, 1);
    l1 += __shfl_xor_sync(0xffffffffu, l1, 1);
    l0 += __shfl_xor_sync(0xffffffffu, l0, 2);
    l1 += __shfl_xor_sync(0xffffffffu, l1, 2);
    i0 = rcp(l0);
    i1 = rcp(l1);
}

__device__ __forceinline__ uint32_t ld_epoch() {
    uint32_t e;
    asm volatile("ld.relaxed.gpu.global.u32 %0, [%1];" : "=r"(e) : "l"(&g_epoch) : "memory");
    return e;
}
__device__ __forceinline__ float silu_bf16(unsigned short c) {
    const float cv = bf_lo(c);
    return round_bf16(cv * rcp(1.f + ex2(-1.4426950408889634f * cv)));
}
__device__ __forceinline__ void st_mod(int idx, float v, uint32_t tag) {
    asm volatile("st.relaxed.gpu.global.u32 [%0], %1;" ::"l"(g_mod + idx), "r"(__float_as_uint(round_bf16(v)) | tag)
                 : "memory");
}
__device__ __forceinline__ void mod_block(const uint4 (&w)[5], const float (&sc)[5], int blk, uint32_t red, int warp,
                                          int lane, uint32_t tag) {
    float acc[8];
#pragma unroll
    for (int e = 0; e < 8; e++) acc[e] = 0.f;
#pragma unroll
    for (int i = 0; i < 5; i++) {
        acc[0] = fmaf(sc[i], bf_lo(w[i].x), acc[0]);
        acc[1] = fmaf(sc[i], bf_hi(w[i].x), acc[1]);
        acc[2] = fmaf(sc[i], bf_lo(w[i].y), acc[2]);
        acc[3] = fmaf(sc[i], bf_hi(w[i].y), acc[3]);
        acc[4] = fmaf(sc[i], bf_lo(w[i].z), acc[4]);
        acc[5] = fmaf(sc[i], bf_hi(w[i].z), acc[5]);
        acc[6] = fmaf(sc[i], bf_lo(w[i].w), acc[6]);
        acc[7] = fmaf(sc[i], bf_hi(w[i].w), acc[7]);
    }
#pragma unroll
    for (int o = 2; o < 32; o <<= 1)
#pragma unroll
        for (int e = 0; e < 8; e++) acc[e] += __shfl_xor_sync(0xffffffffu, acc[e], o);
    if (lane < 2) {
#pragma unroll
        for (int e = 0; e < 8; e++) sts32f(red + (warp * 16 + lane * 8 + e) * 4, acc[e]);
    }
    bar_sync(3, 256);
    if (warp == 0 && lane < 16) {
        float s = 0.f;
#pragma unroll
        for (int w8 = 0; w8 < 8; w8++) s += lds32f(red + (w8 * 16 + lane) * 4);
        if (blk < 72) st_mod(blk * 16 + lane, s, tag);
    }
}

__global__ void __cluster_dims__(2, 1, 1) __launch_bounds__(384, 1)
    fused_block_kernel(const __grid_constant__ Maps maps, const __nv_bfloat16* __restrict__ x,
                       const __nv_bfloat16* __restrict__ cvec, const __nv_bfloat16* __restrict__ wmod,
                       __nv_bfloat16* __restrict__ out) {
    extern __shared__ uint8_t smem_raw[];
    uint32_t sbase = (smem_u32(smem_raw) + 1023u) & ~1023u;
    asm volatile("" : "+r"(sbase));
    const int b = blockIdx.x;
    const int rank = b & 1;
    const int mt = ((b >> 1) & 7) * 2 + rank;
    const int g = b >> 4;
    const int warp = __shfl_sync(0xffffffffu, threadIdx.x >> 5, 0);
    const int lane = threadIdx.x & 31;

    if (warp >= 8) {
        asm volatile("setmaxnreg.dec.sync.aligned.u32 24;");
        if (warp == 8 && lane == 0) {
#pragma unroll
            for (int i = 0; i < 8; i++) {
                mbar_init(sbase + OFF_FULL + i * 8, 1);
                mbar_init(sbase + OFF_EMPTY + i * 8, 4);
            }
            asm volatile("fence.mbarrier_init.release.cluster;" ::: "memory");
            asm volatile("barrier.cluster.arrive.relaxed;\nbarrier.cluster.wait;" ::: "memory");
            uint32_t slot = 0, phase = 1;
            const uint32_t dst0 = sbase + rank * BOX_BYTES;
            auto acquire = [&](uint32_t bytes) {
                mbar_wait(sbase + OFF_EMPTY + slot * 8, phase);
                mbar_expect_tx(sbase + OFF_FULL + slot * 8, bytes);
            };
            auto adv8 = [&]() {
                if (++slot == 8) {
                    slot = 0;
                    phase ^= 1;
                }
            };
#pragma unroll 1
            for (int hq = 0; hq < 4; hq++) {
                const int col = (g * 4 + ((hq + 1) & 3)) * 128 + rank * 64;
#pragma unroll 1
                for (int kc = 0; kc < 9; kc++) {
                    acquire(SLOT_BYTES);
                    tma_mc(dst0 + slot * SLOT_BYTES, &maps.wq, col, kc * 64, sbase + OFF_FULL + slot * 8);
                    adv8();
                }
            }
            const int row0 = g * 4 * 2048;
#pragma unroll 1
            for (int n = 0; n < 128; n++) {
                if (n < 4) mbar_wait(sbase + OFF_EMPTY + (slot + 1) * 8, phase);
                acquire(2 * SLOT_BYTES);
                const uint32_t bar = sbase + OFF_FULL + slot * 8;
                const CUtensorMap* m = (n & 1) ? &maps.v : &maps.k;
                tma_mc(dst0 + slot * SLOT_BYTES, m, rank * 64, row0 + (n >> 1) * 128, bar);
                tma_mc(dst0 + (slot + 1) * SLOT_BYTES, m, rank * 64, row0 + (n >> 1) * 128 + 64, bar);
                adv8();
                adv8();
            }
#pragma unroll 1
            for (int p = 0; p < 4; p++)
#pragma unroll 1
                for (int kc = 0; kc < 8; kc++) {
                    acquire(SLOT_BYTES);
                    tma_mc(dst0 + slot * SLOT_BYTES, &maps.wo, p * 128 + rank * 64, g * 512 + kc * 64,
                           sbase + OFF_FULL + slot * 8);
                    adv8();
                }
#pragma unroll 1
            for (int kc = 0; kc < 4; kc++) {
                acquire(SLOT_BYTES);
                tma_mc(dst0 + slot * SLOT_BYTES, &maps.wo, 512, g * 512 + kc * 128 + rank * 64,
                       sbase + OFF_FULL + slot * 8);
                adv8();
            }
            const CUtensorMap* mg = rank ? &maps.wu : &maps.wg;
#pragma unroll 1
            for (int ch = 0; ch < 9; ch++)
#pragma unroll 1
                for (int kc = 0; kc < 9; kc++) {
                    acquire(SLOT_BYTES);
                    tma_mc(dst0 + slot * SLOT_BYTES, mg, g * 576 + ch * 64, kc * 64, sbase + OFF_FULL + slot * 8);
                    adv8();
                }
#pragma unroll 1
            for (int p = 0; p < 4; p++)
#pragma unroll 1
                for (int kc = 2; kc < 11; kc++) {
                    acquire(SLOT_BYTES);
                    tma_mc(dst0 + slot * SLOT_BYTES, &maps.wd, p * 128 + rank * 64, g * 576 + (kc < 9 ? kc : kc - 9) * 64,
                           sbase + OFF_FULL + slot * 8);
                    adv8();
                }
#pragma unroll 1
            for (int i = 0; i < 5; i++) {
                acquire(i < 4 ? SLOT_BYTES : BOX_BYTES);
                const int kc = 2 * i + rank + 2;
                if (i < 4 || rank == 0)
                    tma_mc(dst0 + slot * SLOT_BYTES, &maps.wd, 512, g * 576 + (kc < 9 ? kc : kc - 9) * 64,
                           sbase + OFF_FULL + slot * 8);
                adv8();
            }
        } else if (warp == 9 || warp == 10) {
            asm volatile("barrier.cluster.arrive.relaxed.aligned;" ::: "memory");
            const uint32_t tag = (ld_epoch() + 1) & 0xffffu;
            bar_sync(4, 320);
            const int blk = warp == 9 ? 72 + b : 200 + b;
            if (blk < 216) {
                float acc[8];
#pragma unroll
                for (int e = 0; e < 8; e++) acc[e] = 0.f;
                const uint4* wp = reinterpret_cast<const uint4*>(wmod + (size_t)(lane >> 1) * (6 * DM) + blk * 16) + (lane & 1);
                const unsigned short* cp = reinterpret_cast<const unsigned short*>(cvec) + (lane >> 1);
#pragma unroll 1
                for (int i = 0; i < 36; i++) {
                    const uint4 w = __ldg(wp + (size_t)i * (16 * 6 * DM / 8));
                    const float sc = silu_bf16(__ldg(cp + i * 16));
                    acc[0] = fmaf(sc, bf_lo(w.x), acc[0]);
                    acc[1] = fmaf(sc, bf_hi(w.x), acc[1]);
                    acc[2] = fmaf(sc, bf_lo(w.y), acc[2]);
                    acc[3] = fmaf(sc, bf_hi(w.y), acc[3]);
                    acc[4] = fmaf(sc, bf_lo(w.z), acc[4]);
                    acc[5] = fmaf(sc, bf_hi(w.z), acc[5]);
                    acc[6] = fmaf(sc, bf_lo(w.w), acc[6]);
                    acc[7] = fmaf(sc, bf_hi(w.w), acc[7]);
                }
#pragma unroll
                for (int o = 2; o < 32; o <<= 1)
#pragma unroll
                    for (int e = 0; e < 8; e++) acc[e] += __shfl_xor_sync(0xffffffffu, acc[e], o);
                if (lane < 2) {
#pragma unroll
                    for (int e = 0; e < 8; e++) st_mod(blk * 16 + lane * 8 + e, acc[e], tag);
                }
            }
        }
    } else {
        asm volatile("setmaxnreg.inc.sync.aligned.u32 240;");
        const int wg = warp >> 2;
        const int tid = threadIdx.x;
        Ctx cx;
        cx.sbase = sbase;
        cx.rel_cta = (lane == 0 && (warp & 3) < 2) ? (warp & 3) : 2;
        const uint32_t red = sbase + OFF_RED;
        const int own = mt * 8 + g;
        const int wown = mt * 8 + warp;
        const uint32_t spill = sbase + 8 * SLOT_BYTES + wg * 3 * SLOT_BYTES + (tid & 127) * 16;
        PROF(0);
        PROFG(30);
        const uint32_t epoch = ld_epoch();
        {
            uint4 w1[5];
            unsigned short cu[5];
            const int half = tid & 1, r0 = tid >> 1;
            if (b < 72) {
#pragma unroll
                for (int i = 0; i < 5; i++) {
                    const int row = min(r0 + 128 * i, DM - 1);
                    cu[i] = __ldg(reinterpret_cast<const unsigned short*>(cvec) + row);
                    w1[i] = __ldg(reinterpret_cast<const uint4*>(wmod + (size_t)row * (6 * DM) + half * 8) + b * 2);
                }
            }
            if (warp == 0) {
                if (lane == 0) {
                    mbar_init(sbase + OFF_XBAR, 1);
                    asm volatile("fence.mbarrier_init.release.cluster;\nfence.proxy.async.shared::cta;" ::: "memory");
                    mbar_expect_tx(sbase + OFF_XBAR, 16 * DM * 2);
                }
                __syncwarp();
                if (lane < 16)
                    asm volatile(
                        "cp.async.bulk.shared::cluster.global.mbarrier::complete_tx::bytes [%0], [%1], %2, [%3];" ::"r"(
                            sbase + 8 * SLOT_BYTES + lane * XROW_STRIDE),
                        "l"(x + (size_t)(own * 16 + lane) * DM), "r"(DM * 2), "r"(sbase + OFF_XBAR)
                        : "memory");
                __syncwarp();
            }
            asm volatile("barrier.cluster.arrive.relaxed.aligned;" ::: "memory");
            if (b < 72) {
                float sc[5];
#pragma unroll
                for (int i = 0; i < 5; i++) sc[i] = (r0 + 128 * i < DM) ? silu_bf16(cu[i]) : 0.f;
                mod_block(w1, sc, b, red + 1024, warp, lane, (epoch + 1) & 0xffffu);
            } else {
                bar_sync(3, 256);
            }
            asm volatile("" ::"r"(epoch) : "memory");
            bar_arrive(4, 320);
        }

        Ring ring{0u, 0u};
        int stage = 0;
        asm volatile("" : "+r"(stage));
#pragma unroll 1
        for (;; stage++) {
            {
                float v[36];
                float4* x2buf = g_x2 + (size_t)b * 9 * 256 + tid;
                const uint32_t tag = (epoch + 1) & 0xffffu;
                if (stage == 0) {
                    mbar_wait(sbase + OFF_XBAR, 0);
                    const uint32_t src = sbase + 8 * SLOT_BYTES + (lane >> 2) * XROW_STRIDE + warp * 16 + (lane & 3) * 4;
#pragma unroll
                    for (int j = 0; j < 9; j++) {
                        const uint32_t u0 = __float_as_uint(lds32f(src + j * 128));
                        const uint32_t u1 = __float_as_uint(lds32f(src + j * 128 + 8 * XROW_STRIDE));
                        v[4 * j] = bf_lo(u0);
                        v[4 * j + 1] = bf_hi(u0);
                        v[4 * j + 2] = bf_lo(u1);
                        v[4 * j + 3] = bf_hi(u1);
                    }
                } else {
                    sum_partials(v, g_part + (size_t)own * 8 * 72 * 32 + tid, stage & 1);
                    PROF(stage == 1 ? 8 : 15);
                    float4 xr[9];
#pragma unroll
                    for (int j = 0; j < 9; j++) xr[j] = __ldcg(x2buf + j * 256);
                    float gate[1][18];
                    load_mod<1>(gate, stage * 3 - 1, tag, warp, lane);
                    const float gs = stage == 1 ? 1.f : 0.5f;
#pragma unroll
                    for (int j = 0; j < 9; j++) {
                        const float g0 = gate[0][2 * j] * gs, g1 = gate[0][2 * j + 1] * gs;
                        v[4 * j] = fmaf(g0, v[4 * j], xr[j].x);
                        v[4 * j + 1] = fmaf(g1, v[4 * j + 1], xr[j].y);
                        v[4 * j + 2] = fmaf(g0, v[4 * j + 2], xr[j].z);
                        v[4 * j + 3] = fmaf(g1, v[4 * j + 3], xr[j].w);
                    }
                    if (stage == 2) {
                        __nv_bfloat16* dst = out + (size_t)(own * 16 + (lane >> 2)) * DM + warp * 8 + (lane & 3) * 2;
#pragma unroll
                        for (int j = 0; j < 9; j++) {
                            *reinterpret_cast<uint32_t*>(dst + j * 64) = pack_bf16(v[4 * j], v[4 * j + 1]);
                            *reinterpret_cast<uint32_t*>(dst + j * 64 + 8 * DM) = pack_bf16(v[4 * j + 2], v[4 * j + 3]);
                        }
                        break;
                    }
                }
                PROF(stage == 0 ? 1 : 9);
                float keep[36];
#pragma unroll
                for (int i = 0; i < 36; i++) keep[i] = v[i];
                layernorm_rows(v, red, warp, lane);
                float md[2][18];
                load_mod<2>(md, stage * 3, tag, warp, lane);
                PROF(stage == 0 ? 2 : 10);
                modulate_store(v, md[0], md[1], g_h[stage] + (size_t)own * 36 * 32, warp, lane);
                __syncwarp();
                if (lane == 0) signal_cnt(stage * 128 + own);
#pragma unroll
                for (int j = 0; j < 9; j++)
                    __stcg(x2buf + j * 256, make_float4(keep[4 * j], keep[4 * j + 1], keep[4 * j + 2], keep[4 * j + 3]));
                if (stage == 0) asm volatile("barrier.cluster.wait.aligned;" ::: "memory");
            }

            uint32_t a[144];
            PROF(stage == 0 ? 3 : 11);
            wait_cnt(stage * 128 + wown, (epoch + 1) * 8);
            PROF(stage == 0 ? 4 : 12);
            if (stage == 1) PROFG(25);
            load_frags(a, g_h[stage] + (size_t)wown * 36 * 32 + lane);
            uint4* hhbuf = g_hh + (size_t)b * 8 * 256 + tid;
            float d[64];
            if (wg == 1) bar_sync(5, 256);
#pragma unroll 1
            for (int ch = 0;; ch++) {
                gemm_n128(d, a, cx, ring, true, (ch == 0 && wg == 0) ? 5 : 0);
                if (stage == 0) {
#pragma unroll
                    for (int i = 0; i < 64; i++) d[i] *= SM_SCALE;
                    if (ch == 3) break;
#pragma unroll
                    for (int v = 0; v < 8; v++)
                        sts128(spill + (ch * 8 + v) * 2048, pack_bf16(d[8 * v], d[8 * v + 1]),
                               pack_bf16(d[8 * v + 2], d[8 * v + 3]), pack_bf16(d[8 * v + 4], d[8 * v + 5]),
                               pack_bf16(d[8 * v + 6], d[8 * v + 7]));
                } else {
#pragma unroll
                    for (int i = 0; i < 32; i++) {
                        const float gv = d[i], gu = gv * d[32 + i];
                        const float z = gv * fmaf(gv * gv, 0.7978845608028654f * 0.044715f, 0.7978845608028654f);
                        d[i] = fmaf(gu, tanh_fast(z), gu);
                    }
                    if (ch == 8) break;
#pragma unroll
                    for (int v = 0; v < 4; v++) {
                        const uint4 h4 = make_uint4(pack_bf16(d[8 * v], d[8 * v + 1]), pack_bf16(d[8 * v + 2], d[8 * v + 3]),
                                                    pack_bf16(d[8 * v + 4], d[8 * v + 5]), pack_bf16(d[8 * v + 6], d[8 * v + 7]));
                        if (ch < 2)
                            __stcg(hhbuf + (ch * 4 + v) * 256, h4);
                        else
                            sts128(spill + ((ch - 2) * 4 + v) * 2048, h4.x, h4.y, h4.z, h4.w);
                    }
                }
            }
            if (stage == 0) {
                uint32_t q[32];
#pragma unroll
                for (int i = 0; i < 32; i++) q[i] = pack_bf16(d[2 * i], d[2 * i + 1]);
                PROF(5);
                PROFG(23);
                {
                    float o[64], sa[32], sb[32];
                    uint32_t pa[16], pb[16];
#pragma unroll
                    for (int i = 0; i < 64; i++) o[i] = 0.f;
                    float n0 = 0.f, n1 = 0.f, l0 = 1.f, l1 = 1.f;
                    bool shifted = false;
                    const uint64_t dbase = desc_of(sbase);
                    const uint64_t dbk = dbase - (511u << 16);
                    const int my_bar = 1 + wg, other_bar = 2 - wg;

                    auto softmax_a = [&](bool first, float& s0, float& s1) {
                        if (first) {
                            shifted = false;
                            n0 = n1 = 0.f;
                            l0 = l1 = 0.f;
                        }
                        if (shifted)
                            exp_step<true>(sa, pa, n0, n1, s0, s1);
                        else
                            exp_step<false>(sa, pa, n0, n1, s0, s1);
                    };
                    auto softmax_b = [&](bool first, float s0, float s1) {
                        float u0, u1;
                        if (shifted)
                            exp_step<true>(sb, pb, n0, n1, u0, u1);
                        else
                            exp_step<false>(sb, pb, n0, n1, u0, u1);
                        s0 += u0;
                        s1 += u1;
                        bool bad = !(fmaxf(s0, s1) <= SM_HI);
                        if (first) {
                            float r0 = s0 + __shfl_xor_sync(0xffffffffu, s0, 1), r1 = s1 + __shfl_xor_sync(0xffffffffu, s1, 1);
                            r0 += __shfl_xor_sync(0xffffffffu, r0, 2);
                            r1 += __shfl_xor_sync(0xffffffffu, r1, 2);
                            bad = bad || !(fminf(r0, r1) >= SM_LO);
                        }
                        if (__any_sync(0xffffffffu, bad)) {
                            float x0, x1;
                            row_max(sa, sb, x0, x1);
                            x0 = -x0;
                            x1 = -x1;
                            if (!first) {
                                x0 = fminf(x0, n0);
                                x1 = fminf(x1, n1);
                                const float al0 = ex2(x0 - n0), al1 = ex2(x1 - n1);
                                l0 *= al0;
                                l1 *= al1;
#pragma unroll
                                for (int i = 0; i < 16; i++) {
                                    o[4 * i] *= al0;
                                    o[4 * i + 1] *= al0;
                                    o[4 * i + 2] *= al1;
                                    o[4 * i + 3] *= al1;
                                }
                            }
                            n0 = x0;
                            n1 = x1;
                            shifted = true;
                            exp_step<true>(sa, pa, n0, n1, s0, s1);
                            exp_step<true>(sb, pb, n0, n1, u0, u1);
                            s0 += u0;
                            s1 += u1;
                        }
                        l0 += s0;
                        l1 += s1;
                    };

                    cx.wait_full(4, 0);
                    if (wg == 1) bar_sync(my_bar, 256);
                    wg_fence();
                    qk_step(sa, q, dbk + 4 * 1024);
                    qk_step(sb, q, dbk + 5 * 1024);
                    wg_commit();
                    bar_arrive(other_bar, 256);
                    wg_wait<0>();
                    pin(sa);
                    pin(sb);
                    cx.release(4);
                    cx.wait_full(6, 0);
                    cx.wait_full(0, 1);
                    {
                        float s0, s1;
                        softmax_a(true, s0, s1);
                        softmax_b(true, s0, s1);
                    }
#pragma unroll 1
                    for (int t = 1; t < 64; t++) {
                        const int j = t & 15;
                        const uint32_t ks = 4 - 4 * (t & 1), vs = 2 + 4 * (t & 1);
                        TL(0);
                        bar_sync(my_bar, 256);
                        TL(2);
                        wg_fence();
                        const uint64_t dk = dbk + ks * 1024, dv = dbase + vs * 1024;
                        pv_step(o, pa, dv, j != 1);
                        pv_step(o, pb, dv + 1024, 1);
                        qk_step(sa, q, dk);
                        wg_commit();
                        qk_step(sb, q, dk + 1024);
                        wg_commit();
                        bar_arrive(other_bar, 256);
                        TL(3);
                        wg_wait<1>();
                        pin(o);
                        pin(sa);
                        pin(pa);
                        pin(pb);
                        TL(4);
                        cx.release(vs);
                        if (j == 0) {
                            float i0, i1;
                            inv_row_sums(l0, l1, i0, i1);
                            const uint32_t dst = spill + ((t >> 4) - 1) * 16384;
#pragma unroll
                            for (int v = 0; v < 8; v++)
                                sts128(dst + v * 2048, pack_bf16(o[8 * v] * i0, o[8 * v + 1] * i0),
                                       pack_bf16(o[8 * v + 2] * i1, o[8 * v + 3] * i1),
                                       pack_bf16(o[8 * v + 4] * i0, o[8 * v + 5] * i0),
                                       pack_bf16(o[8 * v + 6] * i1, o[8 * v + 7] * i1));
                        }
                        float s0, s1;
                        softmax_a(j == 0, s0, s1);
                        TL(5);
                        wg_wait<0>();
                        pin(sb);
                        TL(6);
                        cx.release(ks);
                        const uint32_t bv = sbase + OFF_FULL + (8 - vs) * 8, pv = ((38 + 4 * t) >> 3) & 1;
                        const uint32_t bk = t < 63 ? sbase + OFF_FULL + (4 - ks) * 8 : bv, pk = t < 63 ? ((40 + 4 * t) >> 3) & 1 : pv;
                        const bool okv = mbar_try(bv, pv), okk = mbar_try(bk, pk);
                        TL(1);
                        softmax_b(j == 0, s0, s1);
                        if (!(okv && okk) || j == 15) {
                            mbar_wait(bv, pv);
                            mbar_wait(bk, pk);
                            if (j == 15 && t < 63) {
                                const uint32_t src = spill + (t >> 4) * 16384;
#pragma unroll
                                for (int v = 0; v < 8; v++)
                                    lds128(src + v * 2048, q[4 * v], q[4 * v + 1], q[4 * v + 2], q[4 * v + 3]);
                            }
                        }
                        TL(7);
                    }
                    bar_sync(my_bar, 256);
                    wg_fence();
                    pv_step(o, pa, dbase + 2 * 1024, 1);
                    pv_step(o, pb, dbase + 3 * 1024, 1);
                    wg_commit();
                    if (wg == 0) bar_arrive(other_bar, 256);
                    float i0, i1;
                    inv_row_sums(l0, l1, i0, i1);
                    wg_wait<0>();
                    pin(o);
                    cx.release(2);
#pragma unroll
                    for (int i = 0; i < 16; i++) {
                        a[96 + 2 * i] = pack_bf16(o[4 * i] * i0, o[4 * i + 1] * i0);
                        a[96 + 2 * i + 1] = pack_bf16(o[4 * i + 2] * i1, o[4 * i + 3] * i1);
                    }
#pragma unroll
                    for (int i = 128; i < 144; i++) a[i] = 0;
                }
                ring.slot = 4;
                ring.phase = 0;
                PROF(6);
                PROFG(24);
            } else {
#pragma unroll
                for (int v = 0; v < 8; v++) {
                    const uint4 t = __ldcg(hhbuf + v * 256);
                    a[112 + 4 * v] = t.x;
                    a[113 + 4 * v] = t.y;
                    a[114 + 4 * v] = t.z;
                    a[115 + 4 * v] = t.w;
                }
#pragma unroll
                for (int i = 0; i < 16; i++) a[96 + i] = pack_bf16(d[2 * i], d[2 * i + 1]);
                PROF(13);
            }
#pragma unroll
            for (int v = 0; v < 24; v++) lds128(spill + v * 2048, a[4 * v], a[4 * v + 1], a[4 * v + 2], a[4 * v + 3]);

            proj_partials(a, cx, ring, stage != 0, g_part + ((size_t)wown * 8 + g) * 72 * 32 + lane, (stage + 1) & 1);
            PROF(stage == 0 ? 7 : 14);
            if (stage == 1) {
                PROFG(26);
                asm volatile("barrier.cluster.arrive.relaxed.aligned;" ::: "memory");
            }
        }
        PROF(16);
        PROFG(31);
        if (b == 0) {
            bar_sync(3, 256);
            if (tid == 0) g_epoch = epoch + 1;
        }
        asm volatile("barrier.cluster.wait.aligned;" ::: "memory");
    }
}

typedef CUresult (*EncodeFn)(CUtensorMap*, CUtensorMapDataType, cuuint32_t, void*, const cuuint64_t*, const cuuint64_t*,
                             const cuuint32_t*, const cuuint32_t*, CUtensorMapInterleave, CUtensorMapSwizzle,
                             CUtensorMapL2promotion, CUtensorMapFloatOOBfill);

void make_map(EncodeFn enc, CUtensorMap* m, const void* ptr, uint64_t rows, uint64_t cols) {
    cuuint64_t gdim[2] = {cols, rows};
    cuuint64_t gstr[1] = {cols * 2};
    cuuint32_t box[2] = {64, 64};
    cuuint32_t estr[2] = {1, 1};
    enc(m, CU_TENSOR_MAP_DATA_TYPE_BFLOAT16, 2, const_cast<void*>(ptr), gdim, gstr, box, estr,
        CU_TENSOR_MAP_INTERLEAVE_NONE, CU_TENSOR_MAP_SWIZZLE_128B, CU_TENSOR_MAP_L2_PROMOTION_L2_128B,
        CU_TENSOR_MAP_FLOAT_OOB_FILL_NONE);
}

}

extern "C" void kernel_launch(void* const* d_in, const int* in_sizes, int n_in, void* d_out, int out_size) {
    (void)in_sizes;
    (void)n_in;
    (void)out_size;
    void* fn = nullptr;
    cudaDriverEntryPointQueryResult qr;
    cudaGetDriverEntryPoint("cuTensorMapEncodeTiled", &fn, cudaEnableDefault, &qr);
    EncodeFn enc = (EncodeFn)fn;
    Maps maps;
    make_map(enc, &maps.k, d_in[1], 32 * 2048, 128);
    make_map(enc, &maps.v, d_in[2], 32 * 2048, 128);
    make_map(enc, &maps.wq, d_in[3], 576, 4096);
    make_map(enc, &maps.wo, d_in[4], 4096, 576);
    make_map(enc, &maps.wg, d_in[6], 576, 4608);
    make_map(enc, &maps.wu, d_in[7], 576, 4608);
    make_map(enc, &maps.wd, d_in[8], 4608, 576);
    cudaFuncSetAttribute(fused_block_kernel, cudaFuncAttributeMaxDynamicSharedMemorySize, SMEM_BYTES);
    fused_block_kernel<<<128, 384, SMEM_BYTES>>>(maps, (const __nv_bfloat16*)d_in[0], (const __nv_bfloat16*)d_in[9],
                                                 (const __nv_bfloat16*)d_in[10], (__nv_bfloat16*)d_out);
}
```

```cpp
#include <cuda_runtime.h>
#include <cuda_bf16.h>
#include <cuda.h>
#include <stdint.h>

namespace {

constexpr int DM = 576;
constexpr int SLOT_BYTES = 16384;
constexpr int BOX_BYTES = 8192;
constexpr int NUNITS = 14;
constexpr int SMEM_TAIL = NUNITS * SLOT_BYTES;
constexpr int SMEM_BYTES = SMEM_TAIL + 2048 + 1024;
constexpr int OFF_FULL = SMEM_TAIL;
constexpr int OFF_EMPTY = SMEM_TAIL + 64;
constexpr int OFF_RED = SMEM_TAIL + 128;

constexpr int OFF_XBAR = SMEM_TAIL + 1792;
constexpr int XROW_STRIDE = DM * 2 + 16;

__device__ unsigned g_epoch;
__device__ __align__(16) uint32_t g_mod[6 * DM];
__device__ uint4 g_h[2][128 * 36 * 32];
__device__ unsigned long long g_part[128 * 8 * 72 * 32];
__device__ float4 g_x2[128 * 9 * 256];
__device__ uint4 g_hh[128 * 8 * 256];
__device__ unsigned g_cnt[256 * 32];

#define TL(i)
#define PROFR(i)
#define PROF(i)
#define PROFG(i)

struct Maps {
    CUtensorMap k, v, wq, wo, wg, wu, wd;
};

__device__ __forceinline__ uint32_t smem_u32(const void* p) { return (uint32_t)__cvta_generic_to_shared(p); }
__device__ __forceinline__ void mbar_init(uint32_t a, uint32_t c) {
    asm volatile("mbarrier.init.shared::cta.b64 [%0], %1;" ::"r"(a), "r"(c) : "memory");
}
__device__ __forceinline__ void mbar_expect_tx(uint32_t a, uint32_t bytes) {
    asm volatile("mbarrier.arrive.expect_tx.shared::cta.b64 _, [%0], %1;" ::"r"(a), "r"(bytes) : "memory");
}
__device__ __forceinline__ bool mbar_try(uint32_t a, uint32_t ph) {
    uint32_t ok;
    asm volatile(
        "{\n.reg .pred p;\nmbarrier.try_wait.parity.shared::cta.b64 p, [%1], %2;\nselp.u32 %0, 1, 0, p;\n}"
        : "=r"(ok)
        : "r"(a), "r"(ph)
        : "memory");
    return ok != 0;
}
__device__ __forceinline__ uint32_t clk32() {
    uint32_t c;
    asm volatile("mov.u32 %0, %%clock;" : "=r"(c));
    return c;
}
constexpr uint32_t WAIT_LIMIT = 1u << 30;
__device__ __forceinline__ void mbar_wait(uint32_t a, uint32_t ph) {
    if (mbar_try(a, ph)) return;
    uint32_t t0 = clk32();
    while (!mbar_try(a, ph)) {
        if (clk32() - t0 > WAIT_LIMIT) break;
    }
}
__device__ __forceinline__ void mbar_arrive_cluster(uint32_t a, uint32_t cta) {
    asm volatile(
        "{\n.reg .b32 ra;\nmapa.shared::cluster.u32 ra, %0, %1;\nmbarrier.arrive.shared::cluster.b64 _, [ra];\n}" ::"r"(a),
        "r"(cta)
        : "memory");
}
__device__ __forceinline__ void tma_mc(uint32_t dst, const CUtensorMap* m, int c0, int c1, uint32_t bar) {
    asm volatile(
        "cp.async.bulk.tensor.2d.shared::cluster.global.mbarrier::complete_tx::bytes.multicast::cluster"
        " [%0], [%1, {%3, %4}], [%2], %5;" ::"r"(dst),
        "l"(m), "r"(bar), "r"(c0), "r"(c1), "h"((uint16_t)3)
        : "memory");
}
__device__ __forceinline__ void bar_sync(int id, int n) { asm volatile("bar.sync %0, %1;" ::"r"(id), "r"(n) : "memory"); }
__device__ __forceinline__ void bar_arrive(int id, int n) {
    asm volatile("bar.arrive %0, %1;" ::"r"(id), "r"(n) : "memory");
}
__device__ __forceinline__ void wg_fence() { asm volatile("wgmma.fence.sync.aligned;" ::: "memory"); }
__device__ __forceinline__ void wg_commit() { asm volatile("wgmma.commit_group.sync.aligned;" ::: "memory"); }
template <int N>
__device__ __forceinline__ void wg_wait() {
    asm volatile("wgmma.wait_group.sync.aligned %0;" ::"n"(N) : "memory");
}
template <int N>
__device__ __forceinline__ void pin(float (&d)[N]) {
#pragma unroll
    for (int i = 0; i < N; i++) asm volatile("" : "+f"(d[i])::"memory");
}
template <int N>
__device__ __forceinline__ void pin(uint32_t (&d)[N]) {
#pragma unroll
    for (int i = 0; i < N; i++) asm volatile("" : "+r"(d[i])::"memory");
}
__device__ __forceinline__ uint32_t pack_bf16(float lo, float hi) {
    uint32_t r;
    asm("cvt.rn.bf16x2.f32 %0, %1, %2;" : "=r"(r) : "f"(hi), "f"(lo));
    return r;
}
__device__ __forceinline__ float bf_lo(uint32_t v) { return __uint_as_float(v << 16); }
__device__ __forceinline__ float bf_hi(uint32_t v) { return __uint_as_float(v & 0xffff0000u); }
__device__ __forceinline__ float round_bf16(float v) { return __bfloat162float(__float2bfloat16_rn(v)); }
__device__ __forceinline__ float ex2(float x) {
    float y;
    asm("ex2.approx.ftz.f32 %0, %1;" : "=f"(y) : "f"(x));
    return y;
}
__device__ __forceinline__ float rcp(float x) {
    float y;
    asm("rcp.approx.ftz.f32 %0, %1;" : "=f"(y) : "f"(x));
    return y;
}
__device__ __forceinline__ float tanh_fast(float x) {
    float y;
    asm("tanh.approx.f32 %0, %1;" : "=f"(y) : "f"(x));
    return y;
}
__device__ __forceinline__ void sts128(uint32_t a, uint32_t x, uint32_t y, uint32_t z, uint32_t w) {
    asm volatile("st.shared.v4.b32 [%0], {%1,%2,%3,%4};" ::"r"(a), "r"(x), "r"(y), "r"(z), "r"(w) : "memory");
}
__device__ __forceinline__ void lds128(uint32_t a, uint32_t& x, uint32_t& y, uint32_t& z, uint32_t& w) {
    asm volatile("ld.shared.v4.b32 {%0,%1,%2,%3}, [%4];" : "=r"(x), "=r"(y), "=r"(z), "=r"(w) : "r"(a) : "memory");
}
__device__ __forceinline__ void sts32f(uint32_t a, float v) {
    asm volatile("st.shared.f32 [%0], %1;" ::"r"(a), "f"(v) : "memory");
}
__device__ __forceinline__ float lds32f(uint32_t a) {
    float v;
    asm volatile("ld.shared.f32 %0, [%1];" : "=f"(v) : "r"(a) : "memory");
    return v;
}
__device__ __forceinline__ void signal_cnt(int idx) {
    asm volatile("red.release.gpu.global.add.u32 [%0], 1;" ::"l"(&g_cnt[idx * 32]) : "memory");
}
__device__ __forceinline__ void wait_cnt(int idx, unsigned target) {
    if ((threadIdx.x & 31) == 0) {
        uint32_t t0 = clk32();
        while (true) {
            unsigned v;
            asm volatile("ld.acquire.gpu.global.u32 %0, [%1];" : "=r"(v) : "l"(&g_cnt[idx * 32]) : "memory");
            if ((int)(v - target) >= 0) break;
            if (clk32() - t0 > WAIT_LIMIT) break;
        }
    }
    __syncwarp();
}

#define F8(d, b) \
    "+f"(d[b]), "+f"(d[b + 1]), "+f"(d[b + 2]), "+f"(d[b + 3]), "+f"(d[b + 4]), "+f"(d[b + 5]), "+f"(d[b + 6]), "+f"(d[b + 7])

template <int TB>
__device__ __forceinline__ void wgmma_n128(float (&d)[64], uint32_t a0, uint32_t a1, uint32_t a2, uint32_t a3,
                                           uint64_t db, int sc) {
    asm volatile(
        "{\n.reg .pred p;\nsetp.ne.b32 p, %69, 0;\n"
        "wgmma.mma_async.sync.aligned.m64n128k16.f32.bf16.bf16 "
        "{%0,%1,%2,%3,%4,%5,%6,%7,%8,%9,%10,%11,%12,%13,%14,%15,%16,%17,%18,%19,%20,%21,%22,%23,%24,%25,%26,%27,%28,%29,%30,%31,"
        "%32,%33,%34,%35,%36,%37,%38,%39,%40,%41,%42,%43,%44,%45,%46,%47,%48,%49,%50,%51,%52,%53,%54,%55,%56,%57,%58,%59,%60,%61,%62,%63},"
        "{%64,%65,%66,%67}, %68, p, 1, 1, %70;\n}"
        : F8(d, 0), F8(d, 8), F8(d, 16), F8(d, 24), F8(d, 32), F8(d, 40), F8(d, 48), F8(d, 56)
        : "r"(a0), "r"(a1), "r"(a2), "r"(a3), "l"(db), "r"(sc), "n"(TB));
}
#define O8(d, b) \
    "=f"(d[b]), "=f"(d[b + 1]), "=f"(d[b + 2]), "=f"(d[b + 3]), "=f"(d[b + 4]), "=f"(d[b + 5]), "=f"(d[b + 6]), "=f"(d[b + 7])
template <int TB>
__device__ __forceinline__ void wgmma_n128_z(float (&d)[64], uint32_t a0, uint32_t a1, uint32_t a2, uint32_t a3,
                                             uint64_t db) {
    asm volatile(
        "wgmma.mma_async.sync.aligned.m64n128k16.f32.bf16.bf16 "
        "{%0,%1,%2,%3,%4,%5,%6,%7,%8,%9,%10,%11,%12,%13,%14,%15,%16,%17,%18,%19,%20,%21,%22,%23,%24,%25,%26,%27,%28,%29,%30,%31,"
        "%32,%33,%34,%35,%36,%37,%38,%39,%40,%41,%42,%43,%44,%45,%46,%47,%48,%49,%50,%51,%52,%53,%54,%55,%56,%57,%58,%59,%60,%61,%62,%63},"
        "{%64,%65,%66,%67}, %68, 0, 1, 1, %69;"
        : O8(d, 0), O8(d, 8), O8(d, 16), O8(d, 24), O8(d, 32), O8(d, 40), O8(d, 48), O8(d, 56)
        : "r"(a0), "r"(a1), "r"(a2), "r"(a3), "l"(db), "n"(TB));
}
template <int TB>
__device__ __forceinline__ void wgmma_n64_z(float (&d)[32], uint32_t a0, uint32_t a1, uint32_t a2, uint32_t a3,
                                            uint64_t db) {
    asm volatile(
        "wgmma.mma_async.sync.aligned.m64n64k16.f32.bf16.bf16 "
        "{%0,%1,%2,%3,%4,%5,%6,%7,%8,%9,%10,%11,%12,%13,%14,%15,%16,%17,%18,%19,%20,%21,%22,%23,%24,%25,%26,%27,%28,%29,%30,%31},"
        "{%32,%33,%34,%35}, %36, 0, 1, 1, %37;"
        : O8(d, 0), O8(d, 8), O8(d, 16), O8(d, 24)
        : "r"(a0), "r"(a1), "r"(a2), "r"(a3), "l"(db), "n"(TB));
}
template <int TB>
__device__ __forceinline__ void wgmma_n64(float (&d)[32], uint32_t a0, uint32_t a1, uint32_t a2, uint32_t a3,
                                          uint64_t db) {
    asm volatile(
        "wgmma.mma_async.sync.aligned.m64n64k16.f32.bf16.bf16 "
        "{%0,%1,%2,%3,%4,%5,%6,%7,%8,%9,%10,%11,%12,%13,%14,%15,%16,%17,%18,%19,%20,%21,%22,%23,%24,%25,%26,%27,%28,%29,%30,%31},"
        "{%32,%33,%34,%35}, %36, 1, 1, 1, %37;"
        : F8(d, 0), F8(d, 8), F8(d, 16), F8(d, 24)
        : "r"(a0), "r"(a1), "r"(a2), "r"(a3), "l"(db), "n"(TB));
}

__device__ __forceinline__ uint64_t desc_of(uint32_t saddr) {
    return (uint64_t)(((saddr >> 4) & 0x3FFFu) | (512u << 16)) | ((uint64_t)(64u | (1u << 30)) << 32);
}

struct Ring {
    uint32_t slot;
    uint32_t phase;
    __device__ __forceinline__ void next() {
        if (++slot == 8) {
            slot = 0;
            phase ^= 1;
        }
    }
};

struct Ctx {
    uint32_t sbase;
    uint32_t rel_cta;
    __device__ __forceinline__ void wait_full(uint32_t slot, uint32_t phase) const {
        mbar_wait(sbase + OFF_FULL + slot * 8, phase);
    }
    __device__ __forceinline__ void release(uint32_t slot) const {
        if (rel_cta < 2) mbar_arrive_cluster(sbase + OFF_EMPTY + slot * 8, rel_cta);
    }
};

__device__ __forceinline__ void gemm_n128(float (&d)[64], const uint32_t (&a)[144], const Ctx& c, Ring& r, bool nine,
                                          int kick) {
    uint32_t prev = 0;
#pragma unroll
    for (int s = 0; s < 9; s++) {
        if (s < 8 || nine) {
            c.wait_full(r.slot, r.phase);
            uint64_t db = desc_of(c.sbase + r.slot * SLOT_BYTES);
            wg_fence();
#pragma unroll
            for (int k = 0; k < 4; k++) {
                if ((s | k) == 0)
                    wgmma_n128_z<1>(d, a[0], a[1], a[2], a[3], db);
                else
                    wgmma_n128<1>(d, a[s * 16 + k * 4], a[s * 16 + k * 4 + 1], a[s * 16 + k * 4 + 2],
                                  a[s * 16 + k * 4 + 3], db + k * 128, 1);
            }
            wg_commit();
            if (s == 3 && kick) bar_arrive(kick, 256);
            if (s > 0) {
                wg_wait<1>();
                c.release(prev);
            }
            prev = r.slot;
            r.next();
        }
    }
    wg_wait<0>();
    c.release(prev);
    pin(d);
}
__device__ __forceinline__ void gemm_n64(float (&d)[32], const uint32_t (&a)[144], const Ctx& c, Ring& r, bool nine) {
    uint32_t prev = 0;
#pragma unroll
    for (int s = 0; s < 5; s++) {
        if (s < 4 || nine) {
            c.wait_full(r.slot, r.phase);
            uint64_t db = desc_of(c.sbase + r.slot * SLOT_BYTES);
            wg_fence();
#pragma unroll
            for (int k = 0; k < 8; k++) {
                if ((s | k) == 0)
                    wgmma_n64_z<1>(d, a[0], a[1], a[2], a[3], db);
                else if (s * 8 + k < 36)
                    wgmma_n64<1>(d, a[s * 32 + k * 4], a[s * 32 + k * 4 + 1], a[s * 32 + k * 4 + 2],
                                 a[s * 32 + k * 4 + 3], db + k * 128);
            }
            wg_commit();
            if (s > 0) {
                wg_wait<1>();
                c.release(prev);
            }
            prev = r.slot;
            r.next();
        }
    }
    wg_wait<0>();
    c.release(prev);
    pin(d);
}
__device__ __forceinline__ void st_part(unsigned long long* p, float a, float b, float c, float d, uint32_t tag) {
    const uint32_t lo = (pack_bf16(a, b) & ~1u) | tag, hi = pack_bf16(c, d);
    asm volatile("{\n.reg .b64 t;\nmov.b64 t, {%1, %2};\nst.relaxed.gpu.global.b64 [%0], t;\n}" ::"l"(p), "r"(lo), "r"(hi)
                 : "memory");
}
__device__ __forceinline__ uint2 ld_part(const unsigned long long* p) {
    uint2 r;
    asm volatile("{\n.reg .b64 t;\nld.relaxed.gpu.global.b64 t, [%2];\nmov.b64 {%0, %1}, t;\n}"
                 : "=r"(r.x), "=r"(r.y)
                 : "l"(p));
    return r;
}
__device__ __forceinline__ void proj_partials(const uint32_t (&a)[144], const Ctx& c, Ring& r, bool nine,
                                              unsigned long long* dst  , uint32_t tag) {
#pragma unroll 1
    for (int p = 0; p < 4; p++) {
        float d[64];
        gemm_n128(d, a, c, r, nine, 0);
#pragma unroll
        for (int j = 0; j < 16; j++) st_part(dst + (p * 16 + j) * 32, d[4 * j], d[4 * j + 1], d[4 * j + 2], d[4 * j + 3], tag);
    }
    float d[32];
    gemm_n64(d, a, c, r, nine);
#pragma unroll
    for (int j = 0; j < 8; j++) st_part(dst + (64 + j) * 32, d[4 * j], d[4 * j + 1], d[4 * j + 2], d[4 * j + 3], tag);
}

__device__ __forceinline__ void row_reduce(float& s0, float& s1, uint32_t red, int warp, int lane) {
    s0 += __shfl_xor_sync(0xffffffffu, s0, 1);
    s1 += __shfl_xor_sync(0xffffffffu, s1, 1);
    s0 += __shfl_xor_sync(0xffffffffu, s0, 2);
    s1 += __shfl_xor_sync(0xffffffffu, s1, 2);
    if ((lane & 3) == 0) {
        sts32f(red + (warp * 16 + (lane >> 2)) * 4, s0);
        sts32f(red + (warp * 16 + 8 + (lane >> 2)) * 4, s1);
    }
    bar_sync(3, 256);
    s0 = 0.f;
    s1 = 0.f;
#pragma unroll
    for (int w = 0; w < 8; w++) {
        s0 += lds32f(red + (w * 16 + (lane >> 2)) * 4);
        s1 += lds32f(red + (w * 16 + 8 + (lane >> 2)) * 4);
    }
}
__device__ __forceinline__ void layernorm_rows(float (&v)[36], uint32_t red, int warp, int lane) {
    float s0 = 0.f, s1 = 0.f;
#pragma unroll
    for (int j = 0; j < 9; j++) {
        s0 += v[4 * j] + v[4 * j + 1];
        s1 += v[4 * j + 2] + v[4 * j + 3];
    }
    row_reduce(s0, s1, red, warp, lane);
    const float m0 = s0 * (1.f / DM), m1 = s1 * (1.f / DM);
    s0 = 0.f;
    s1 = 0.f;
#pragma unroll
    for (int j = 0; j < 9; j++) {
        v[4 * j] -= m0;
        v[4 * j + 1] -= m0;
        v[4 * j + 2] -= m1;
        v[4 * j + 3] -= m1;
        s0 += v[4 * j] * v[4 * j] + v[4 * j + 1] * v[4 * j + 1];
        s1 += v[4 * j + 2] * v[4 * j + 2] + v[4 * j + 3] * v[4 * j + 3];
    }
    row_reduce(s0, s1, red + 512, warp, lane);
    const float r0 = rsqrtf(s0 * (1.f / DM) + 1e-5f), r1 = rsqrtf(s1 * (1.f / DM) + 1e-5f);
#pragma unroll
    for (int j = 0; j < 9; j++) {
        v[4 * j] *= r0;
        v[4 * j + 1] *= r0;
        v[4 * j + 2] *= r1;
        v[4 * j + 3] *= r1;
    }
}
__device__ __forceinline__ void load_mod0(float (&m)[3][18], const uint32_t* src, uint32_t tag) {
    const uint32_t t0 = clk32();
    while (true) {
        uint2 u[2][9];
#pragma unroll
        for (int n = 0; n < 2; n++)
#pragma unroll
            for (int j = 0; j < 9; j++)
                asm volatile("ld.relaxed.gpu.global.v2.u32 {%0,%1}, [%2];"
                             : "=r"(u[n][j].x), "=r"(u[n][j].y)
                             : "l"(src + n * DM + j * 64));
        uint32_t bad = 0;
#pragma unroll
        for (int n = 0; n < 2; n++)
#pragma unroll
            for (int j = 0; j < 9; j++) {
                bad |= (u[n][j].x ^ tag) | (u[n][j].y ^ tag);
                m[n + 1][2 * j] = __uint_as_float(u[n][j].x & 0xffff0000u);
                m[n + 1][2 * j + 1] = __uint_as_float(u[n][j].y & 0xffff0000u);
            }
        if (__all_sync(0xffffffffu, (bad & 0xffffu) == 0) || clk32() - t0 > WAIT_LIMIT) break;
    }
}
__device__ __forceinline__ void modulate_store(const float (&v)[36], const float (&shift)[18], const float (&scale)[18],
                                               uint4* hbuf  , int warp, int lane) {
    uint2* dst = reinterpret_cast<uint2*>(hbuf) + ((warp >> 1) * 32 + lane) * 2 + (warp & 1);
#pragma unroll
    for (int j = 0; j < 9; j++) {
        const float c0 = round_bf16(1.f + scale[2 * j]), c1 = round_bf16(1.f + scale[2 * j + 1]);
        uint2 o;
        o.x = pack_bf16(fmaf(v[4 * j], c0, shift[2 * j]), fmaf(v[4 * j + 1], c1, shift[2 * j + 1]));
        o.y = pack_bf16(fmaf(v[4 * j + 2], c0, shift[2 * j]), fmaf(v[4 * j + 3], c1, shift[2 * j + 1]));
        __stcg(dst + j * 256, o);
    }
}
__device__ __forceinline__ void sum_partials(float (&v)[36], const unsigned long long* src  ,
                                             uint32_t tag) {
    const uint32_t t0 = clk32();
    while (true) {
        uint2 t[8][8];
#pragma unroll
        for (int s = 0; s < 8; s++)
#pragma unroll
            for (int j = 0; j < 8; j++) t[s][j] = ld_part(src + (s * 72 + j * 8) * 32);
        uint32_t bad = 0;
#pragma unroll
        for (int s = 0; s < 8; s++)
#pragma unroll
            for (int j = 0; j < 8; j++) {
                bad |= t[s][j].x ^ tag;
                if (s == 0) {
                    v[4 * j] = bf_lo(t[s][j].x);
                    v[4 * j + 1] = bf_hi(t[s][j].x);
                    v[4 * j + 2] = bf_lo(t[s][j].y);
                    v[4 * j + 3] = bf_hi(t[s][j].y);
                } else {
                    v[4 * j] += bf_lo(t[s][j].x);
                    v[4 * j + 1] += bf_hi(t[s][j].x);
                    v[4 * j + 2] += bf_lo(t[s][j].y);
                    v[4 * j + 3] += bf_hi(t[s][j].y);
                }
            }
        if (__all_sync(0xffffffffu, (bad & 1u) == 0) || clk32() - t0 > WAIT_LIMIT) break;
    }
}
__device__ __forceinline__ void sum_tail(float (&v)[36], float (&m)[3][18], const unsigned long long* src, uint32_t tag,
                                         const uint32_t* gate, const uint32_t* shsc, uint32_t mtag) {
    const uint32_t t0 = clk32();
    while (true) {
        uint2 t[8], u[3][9];
#pragma unroll
        for (int s = 0; s < 8; s++) t[s] = ld_part(src + (s * 72 + 64) * 32);
#pragma unroll
        for (int n = 0; n < 3; n++)
#pragma unroll
            for (int j = 0; j < 9; j++)
                asm volatile("ld.relaxed.gpu.global.v2.u32 {%0,%1}, [%2];"
                             : "=r"(u[n][j].x), "=r"(u[n][j].y)
                             : "l"((n == 0 ? gate : shsc + (n - 1) * DM) + j * 64));
        uint32_t bad = 0, badm = 0;
        v[32] = v[33] = v[34] = v[35] = 0.f;
#pragma unroll
        for (int s = 0; s < 8; s++) {
            bad |= t[s].x ^ tag;
            v[32] += bf_lo(t[s].x);
            v[33] += bf_hi(t[s].x);
            v[34] += bf_lo(t[s].y);
            v[35] += bf_hi(t[s].y);
        }
#pragma unroll
        for (int n = 0; n < 3; n++)
#pragma unroll
            for (int j = 0; j < 9; j++) {
                badm |= (u[n][j].x ^ mtag) | (u[n][j].y ^ mtag);
                m[n][2 * j] = __uint_as_float(u[n][j].x & 0xffff0000u);
                m[n][2 * j + 1] = __uint_as_float(u[n][j].y & 0xffff0000u);
            }
        if (__all_sync(0xffffffffu, ((bad & 1u) | (badm & 0xffffu)) == 0) || clk32() - t0 > WAIT_LIMIT) break;
    }
}
__device__ __forceinline__ void load_frags(uint32_t (&a)[144], const uint4* src  ) {
#pragma unroll
    for (int k = 0; k < 36; k++) {
        uint4 t = __ldcg(src + k * 32);
        a[4 * k] = t.x;
        a[4 * k + 1] = t.y;
        a[4 * k + 2] = t.z;
        a[4 * k + 3] = t.w;
    }
}

constexpr float SM_SCALE = 0.08838834764831845f * 1.4426950408889634f;
constexpr float SM_HI = 1.2089258e24f;
constexpr float SM_LO = 9.0949470e-13f;
__device__ __forceinline__ void qk_step(float (&s)[32], const uint32_t (&q)[32], uint64_t dk) {
#pragma unroll
    for (int k = 0; k < 8; k++) {
        if (k == 0)
            wgmma_n64_z<0>(s, q[0], q[1], q[2], q[3], dk);
        else
            wgmma_n64<0>(s, q[4 * k], q[4 * k + 1], q[4 * k + 2], q[4 * k + 3], dk + (k >> 2) * 512 + (k & 3) * 2);
    }
}
__device__ __forceinline__ void pv_step(float (&o)[64], const uint32_t (&p)[16], uint64_t dv, int acc) {
#pragma unroll
    for (int k = 0; k < 4; k++)
        wgmma_n128<1>(o, p[4 * k], p[4 * k + 1], p[4 * k + 2], p[4 * k + 3], dv + k * 128, k != 0 ? 1 : acc);
}
template <bool SHIFT>
__device__ __forceinline__ void exp_step(const float (&s)[32], uint32_t (&p)[16], float n0, float n1, float& s0,
                                         float& s1) {
#pragma unroll
    for (int i = 0; i < 8; i++) {
        const float e0 = ex2(SHIFT ? s[4 * i] + n0 : s[4 * i]), e1 = ex2(SHIFT ? s[4 * i + 1] + n0 : s[4 * i + 1]);
        const float e2 = ex2(SHIFT ? s[4 * i + 2] + n1 : s[4 * i + 2]), e3 = ex2(SHIFT ? s[4 * i + 3] + n1 : s[4 * i + 3]);
        if (i == 0) {
            s0 = e0 + e1;
            s1 = e2 + e3;
        } else {
            s0 += e0 + e1;
            s1 += e2 + e3;
        }
        p[2 * i] = pack_bf16(e0, e1);
        p[2 * i + 1] = pack_bf16(e2, e3);
    }
}
__device__ __forceinline__ void row_max(const float (&sa)[32], const float (&sb)[32], float& x0, float& x1) {
    float xa[8];
#pragma unroll
    for (int i = 0; i < 8; i++) xa[i] = fmaxf(sa[i], sb[i]);
#pragma unroll
    for (int k = 1; k < 4; k++)
#pragma unroll
        for (int i = 0; i < 8; i++) xa[i] = fmaxf(xa[i], fmaxf(sa[8 * k + i], sb[8 * k + i]));
    x0 = fmaxf(fmaxf(xa[0], xa[1]), fmaxf(xa[4], xa[5]));
    x1 = fmaxf(fmaxf(xa[2], xa[3]), fmaxf(xa[6], xa[7]));
    x0 = fmaxf(x0, __shfl_xor_sync(0xffffffffu, x0, 1));
    x1 = fmaxf(x1, __shfl_xor_sync(0xffffffffu, x1, 1));
    x0 = fmaxf(x0, __shfl_xor_sync(0xffffffffu, x0, 2));
    x1 = fmaxf(x1, __shfl_xor_sync(0xffffffffu, x1, 2));
}
__device__ __forceinline__ void inv_row_sums(float l0, float l1, float& i0, float& i1) {
    l0 += __shfl_xor_sync(0xffffffffu, l0, 1);
    l1 += __shfl_xor_sync(0xffffffffu, l1, 1);
    l0 += __shfl_xor_sync(0xffffffffu, l0, 2);
    l1 += __shfl_xor_sync(0xffffffffu, l1, 2);
    i0 = rcp(l0);
    i1 = rcp(l1);
}

__device__ __forceinline__ uint32_t ld_epoch() {
    uint32_t e;
    asm volatile("ld.relaxed.gpu.global.u32 %0, [%1];" : "=r"(e) : "l"(&g_epoch) : "memory");
    return e;
}
__device__ __forceinline__ float silu_bf16(unsigned short c) {
    const float cv = bf_lo(c);
    return round_bf16(cv * rcp(1.f + ex2(-1.4426950408889634f * cv)));
}
__device__ __forceinline__ void st_mod(int idx, float v, uint32_t tag) {
    asm volatile("st.relaxed.gpu.global.u32 [%0], %1;" ::"l"(g_mod + idx), "r"(__float_as_uint(round_bf16(v)) | tag)
                 : "memory");
}
__device__ __forceinline__ void mod_block(const uint4 (&w)[5], const float (&sc)[5], int blk, uint32_t red, int warp,
                                          int lane, uint32_t tag) {
    float acc[8];
#pragma unroll
    for (int e = 0; e < 8; e++) acc[e] = 0.f;
#pragma unroll
    for (int i = 0; i < 5; i++) {
        acc[0] = fmaf(sc[i], bf_lo(w[i].x), acc[0]);
        acc[1] = fmaf(sc[i], bf_hi(w[i].x), acc[1]);
        acc[2] = fmaf(sc[i], bf_lo(w[i].y), acc[2]);
        acc[3] = fmaf(sc[i], bf_hi(w[i].y), acc[3]);
        acc[4] = fmaf(sc[i], bf_lo(w[i].z), acc[4]);
        acc[5] = fmaf(sc[i], bf_hi(w[i].z), acc[5]);
        acc[6] = fmaf(sc[i], bf_lo(w[i].w), acc[6]);
        acc[7] = fmaf(sc[i], bf_hi(w[i].w), acc[7]);
    }
#pragma unroll
    for (int o = 2; o < 32; o <<= 1)
#pragma unroll
        for (int e = 0; e < 8; e++) acc[e] += __shfl_xor_sync(0xffffffffu, acc[e], o);
    if (lane < 2) {
#pragma unroll
        for (int e = 0; e < 8; e++) sts32f(red + (warp * 16 + lane * 8 + e) * 4, acc[e]);
    }
    bar_sync(3, 256);
    if (warp == 0 && lane < 16) {
        float s = 0.f;
#pragma unroll
        for (int w8 = 0; w8 < 8; w8++) s += lds32f(red + (w8 * 16 + lane) * 4);
        if (blk < 72) st_mod(blk * 16 + lane, s, tag);
    }
}

__global__ void __cluster_dims__(2, 1, 1) __launch_bounds__(384, 1)
    fused_block_kernel(const __grid_constant__ Maps maps, const __nv_bfloat16* __restrict__ x,
                       const __nv_bfloat16* __restrict__ cvec, const __nv_bfloat16* __restrict__ wmod,
                       __nv_bfloat16* __restrict__ out) {
    extern __shared__ uint8_t smem_raw[];
    uint32_t sbase = (smem_u32(smem_raw) + 1023u) & ~1023u;
    asm volatile("" : "+r"(sbase));
    const int b = blockIdx.x;
    const int rank = b & 1;
    const int mt = ((b >> 1) & 7) * 2 + rank;
    const int g = b >> 4;
    const int warp = __shfl_sync(0xffffffffu, threadIdx.x >> 5, 0);
    const int lane = threadIdx.x & 31;

    if (warp >= 8) {
        asm volatile("setmaxnreg.dec.sync.aligned.u32 24;");
        if (warp == 8 && lane == 0) {
#pragma unroll
            for (int i = 0; i < 8; i++) {
                mbar_init(sbase + OFF_FULL + i * 8, 1);
                mbar_init(sbase + OFF_EMPTY + i * 8, 4);
            }
            asm volatile("fence.mbarrier_init.release.cluster;" ::: "memory");
            asm volatile("barrier.cluster.arrive.relaxed;\nbarrier.cluster.wait;" ::: "memory");
            uint32_t slot = 0, phase = 1;
            const uint32_t dst0 = sbase + rank * BOX_BYTES;
            auto acquire = [&](uint32_t bytes) {
                mbar_wait(sbase + OFF_EMPTY + slot * 8, phase);
                mbar_expect_tx(sbase + OFF_FULL + slot * 8, bytes);
            };
            auto adv8 = [&]() {
                if (++slot == 8) {
                    slot = 0;
                    phase ^= 1;
                }
            };
#pragma unroll 1
            for (int hq = 0; hq < 4; hq++) {
                const int col = (g * 4 + ((hq + 1) & 3)) * 128 + rank * 64;
#pragma unroll 1
                for (int kc = 0; kc < 9; kc++) {
                    acquire(SLOT_BYTES);
                    tma_mc(dst0 + slot * SLOT_BYTES, &maps.wq, col, kc * 64, sbase + OFF_FULL + slot * 8);
                    adv8();
                }
            }
            const int row0 = g * 4 * 2048;
#pragma unroll 1
            for (int n = 0; n < 128; n++) {
                if (n < 4) mbar_wait(sbase + OFF_EMPTY + (slot + 1) * 8, phase);
                acquire(2 * SLOT_BYTES);
                const uint32_t bar = sbase + OFF_FULL + slot * 8;
                const CUtensorMap* m = (n & 1) ? &maps.v : &maps.k;
                tma_mc(dst0 + slot * SLOT_BYTES, m, rank * 64, row0 + (n >> 1) * 128, bar);
                tma_mc(dst0 + (slot + 1) * SLOT_BYTES, m, rank * 64, row0 + (n >> 1) * 128 + 64, bar);
                adv8();
                adv8();
            }
#pragma unroll 1
            for (int p = 0; p < 4; p++)
#pragma unroll 1
                for (int kc = 0; kc < 8; kc++) {
                    acquire(SLOT_BYTES);
                    tma_mc(dst0 + slot * SLOT_BYTES, &maps.wo, p * 128 + rank * 64, g * 512 + kc * 64,
                           sbase + OFF_FULL + slot * 8);
                    adv8();
                }
#pragma unroll 1
            for (int kc = 0; kc < 4; kc++) {
                acquire(SLOT_BYTES);
                tma_mc(dst0 + slot * SLOT_BYTES, &maps.wo, 512, g * 512 + kc * 128 + rank * 64,
                       sbase + OFF_FULL + slot * 8);
                adv8();
            }
            const CUtensorMap* mg = rank ? &maps.wu : &maps.wg;
#pragma unroll 1
            for (int ch = 0; ch < 9; ch++)
#pragma unroll 1
                for (int kc = 0; kc < 9; kc++) {
                    acquire(SLOT_BYTES);
                    tma_mc(dst0 + slot * SLOT_BYTES, mg, g * 576 + ch * 64, kc * 64, sbase + OFF_FULL + slot * 8);
                    adv8();
                }
#pragma unroll 1
            for (int p = 0; p < 4; p++)
#pragma unroll 1
                for (int kc = 2; kc < 11; kc++) {
                    acquire(SLOT_BYTES);
                    tma_mc(dst0 + slot * SLOT_BYTES, &maps.wd, p * 128 + rank * 64, g * 576 + (kc < 9 ? kc : kc - 9) * 64,
                           sbase + OFF_FULL + slot * 8);
                    adv8();
                }
#pragma unroll 1
            for (int i = 0; i < 5; i++) {
                acquire(i < 4 ? SLOT_BYTES : BOX_BYTES);
                const int kc = 2 * i + rank + 2;
                if (i < 4 || rank == 0)
                    tma_mc(dst0 + slot * SLOT_BYTES, &maps.wd, 512, g * 576 + (kc < 9 ? kc : kc - 9) * 64,
                           sbase + OFF_FULL + slot * 8);
                adv8();
            }
        } else if (warp == 9 || warp == 10) {
            asm volatile("barrier.cluster.arrive.relaxed.aligned;" ::: "memory");
            const uint32_t tag = (ld_epoch() + 1) & 0xffffu;
            bar_sync(4, 320);
            const int blk = warp == 9 ? 72 + b : 200 + b;
            if (blk < 216) {
                float acc[8];
#pragma unroll
                for (int e = 0; e < 8; e++) acc[e] = 0.f;
                const uint4* wp = reinterpret_cast<const uint4*>(wmod + (size_t)(lane >> 1) * (6 * DM) + blk * 16) + (lane & 1);
                const unsigned short* cp = reinterpret_cast<const unsigned short*>(cvec) + (lane >> 1);
#pragma unroll 1
                for (int i = 0; i < 36; i++) {
                    const uint4 w = __ldg(wp + (size_t)i * (16 * 6 * DM / 8));
                    const float sc = silu_bf16(__ldg(cp + i * 16));
                    acc[0] = fmaf(sc, bf_lo(w.x), acc[0]);
                    acc[1] = fmaf(sc, bf_hi(w.x), acc[1]);
                    acc[2] = fmaf(sc, bf_lo(w.y), acc[2]);
                    acc[3] = fmaf(sc, bf_hi(w.y), acc[3]);
                    acc[4] = fmaf(sc, bf_lo(w.z), acc[4]);
                    acc[5] = fmaf(sc, bf_hi(w.z), acc[5]);
                    acc[6] = fmaf(sc, bf_lo(w.w), acc[6]);
                    acc[7] = fmaf(sc, bf_hi(w.w), acc[7]);
                }
#pragma unroll
                for (int o = 2; o < 32; o <<= 1)
#pragma unroll
                    for (int e = 0; e < 8; e++) acc[e] += __shfl_xor_sync(0xffffffffu, acc[e], o);
                if (lane < 2) {
#pragma unroll
                    for (int e = 0; e < 8; e++) st_mod(blk * 16 + lane * 8 + e, acc[e], tag);
                }
            }
        }
    } else {
        asm volatile("setmaxnreg.inc.sync.aligned.u32 240;");
        const int wg = warp >> 2;
        const int tid = threadIdx.x;
        Ctx cx;
        cx.sbase = sbase;
        cx.rel_cta = (lane == 0 && (warp & 3) < 2) ? (warp & 3) : 2;
        const uint32_t red = sbase + OFF_RED;
        const int own = mt * 8 + g;
        const int wown = mt * 8 + warp;
        PROF(0);
        PROFG(30);
        const uint32_t epoch = ld_epoch();
        {
            uint4 w1[5];
            unsigned short cu[5];
            const int half = tid & 1, r0 = tid >> 1;
            if (b < 72) {
#pragma unroll
                for (int i = 0; i < 5; i++) {
                    const int row = min(r0 + 128 * i, DM - 1);
                    cu[i] = __ldg(reinterpret_cast<const unsigned short*>(cvec) + row);
                    w1[i] = __ldg(reinterpret_cast<const uint4*>(wmod + (size_t)row * (6 * DM) + half * 8) + b * 2);
                }
            }
            if (warp == 0) {
                if (lane == 0) {
                    mbar_init(sbase + OFF_XBAR, 1);
                    asm volatile("fence.mbarrier_init.release.cluster;\nfence.proxy.async.shared::cta;" ::: "memory");
                    mbar_expect_tx(sbase + OFF_XBAR, 16 * DM * 2);
                }
                __syncwarp();
                if (lane < 16)
                    asm volatile(
                        "cp.async.bulk.shared::cluster.global.mbarrier::complete_tx::bytes [%0], [%1], %2, [%3];" ::"r"(
                            sbase + 8 * SLOT_BYTES + lane * XROW_STRIDE),
                        "l"(x + (size_t)(own * 16 + lane) * DM), "r"(DM * 2), "r"(sbase + OFF_XBAR)
                        : "memory");
                __syncwarp();
            }
            asm volatile("barrier.cluster.arrive.relaxed.aligned;" ::: "memory");
            if (b < 72) {
                float sc[5];
#pragma unroll
                for (int i = 0; i < 5; i++) sc[i] = (r0 + 128 * i < DM) ? silu_bf16(cu[i]) : 0.f;
                mod_block(w1, sc, b, red + 1024, warp, lane, (epoch + 1) & 0xffffu);
            } else {
                bar_sync(3, 256);
            }
            asm volatile("" ::"r"(epoch) : "memory");
            bar_arrive(4, 320);
        }

        Ring ring{0u, 0u};
        int stage = 0;
        asm volatile("" : "+r"(stage));
#pragma unroll 1
        for (;; stage++) {
            int tid, lane;
            asm volatile("mov.u32 %0, %%tid.x;" : "=r"(tid));
            lane = tid & 31;
            {
                float v[36], md[3][18];
                float4* x2buf = g_x2 + (size_t)b * 9 * 256 + tid;
                const uint32_t tag = (epoch + 1) & 0xffffu;
                const uint32_t* modp = g_mod + warp * 8 + (lane & 3) * 2;
                if (stage == 0) {
#pragma unroll
                    for (int i = 0; i < 18; i++) md[1][i] = md[2][i] = 0.f;
                    mbar_wait(sbase + OFF_XBAR, 0);
                    const uint32_t src = sbase + 8 * SLOT_BYTES + (lane >> 2) * XROW_STRIDE + warp * 16 + (lane & 3) * 4;
#pragma unroll
                    for (int j = 0; j < 9; j++) {
                        const uint32_t u0 = __float_as_uint(lds32f(src + j * 128));
                        const uint32_t u1 = __float_as_uint(lds32f(src + j * 128 + 8 * XROW_STRIDE));
                        v[4 * j] = bf_lo(u0);
                        v[4 * j + 1] = bf_hi(u0);
                        v[4 * j + 2] = bf_lo(u1);
                        v[4 * j + 3] = bf_hi(u1);
                    }
                } else {
                    const unsigned long long* psrc = g_part + (size_t)own * 8 * 72 * 32 + tid;
                    sum_partials(v, psrc, stage & 1);
                    PROF(stage == 1 ? 8 : 15);
                    float4 xr[9];
#pragma unroll
                    for (int j = 0; j < 9; j++) xr[j] = __ldcg(x2buf + j * 256);
                    sum_tail(v, md, psrc, stage & 1, modp + (stage * 3 - 1) * DM, modp + 3 * DM, tag);
                    const float gs = stage == 1 ? 1.f : 0.5f;
#pragma unroll
                    for (int j = 0; j < 9; j++) {
                        const float g0 = md[0][2 * j] * gs, g1 = md[0][2 * j + 1] * gs;
                        v[4 * j] = fmaf(g0, v[4 * j], xr[j].x);
                        v[4 * j + 1] = fmaf(g1, v[4 * j + 1], xr[j].y);
                        v[4 * j + 2] = fmaf(g0, v[4 * j + 2], xr[j].z);
                        v[4 * j + 3] = fmaf(g1, v[4 * j + 3], xr[j].w);
                    }
                    if (stage == 2) {
                        __nv_bfloat16* dst = out + (size_t)(own * 16 + (lane >> 2)) * DM + warp * 8 + (lane & 3) * 2;
#pragma unroll
                        for (int j = 0; j < 9; j++) {
                            *reinterpret_cast<uint32_t*>(dst + j * 64) = pack_bf16(v[4 * j], v[4 * j + 1]);
                            *reinterpret_cast<uint32_t*>(dst + j * 64 + 8 * DM) = pack_bf16(v[4 * j + 2], v[4 * j + 3]);
                        }
                        break;
                    }
                }
                PROF(stage == 0 ? 1 : 9);
                float keep[36];
#pragma unroll
                for (int i = 0; i < 36; i++) keep[i] = v[i];
                layernorm_rows(v, red, warp, lane);
                if (stage == 0) load_mod0(md, modp, tag);
                PROF(stage == 0 ? 2 : 10);
                modulate_store(v, md[1], md[2], g_h[stage] + (size_t)own * 36 * 32, warp, lane);
                __syncwarp();
                if (lane == 0) signal_cnt(stage * 128 + own);
#pragma unroll
                for (int j = 0; j < 9; j++)
                    __stcg(x2buf + j * 256, make_float4(keep[4 * j], keep[4 * j + 1], keep[4 * j + 2], keep[4 * j + 3]));
                if (stage == 0) asm volatile("barrier.cluster.wait.aligned;" ::: "memory");
            }

            const uint32_t spill = sbase + 8 * SLOT_BYTES + wg * 3 * SLOT_BYTES + (tid & 127) * 16;
            uint32_t a[144];
            PROF(stage == 0 ? 3 : 11);
            wait_cnt(stage * 128 + wown, (epoch + 1) * 8);
            PROF(stage == 0 ? 4 : 12);
            if (stage == 1) PROFG(25);
            load_frags(a, g_h[stage] + (size_t)wown * 36 * 32 + lane);
            uint4* hhbuf = g_hh + (size_t)b * 8 * 256 + tid;
            float d[64];
            if (wg == 1) bar_sync(5, 256);
#pragma unroll 1
            for (int ch = 0;; ch++) {
                gemm_n128(d, a, cx, ring, true, (ch == 0 && wg == 0) ? 5 : 0);
                if (stage == 0) {
#pragma unroll
                    for (int i = 0; i < 64; i++) d[i] *= SM_SCALE;
                    if (ch == 3) break;
#pragma unroll
                    for (int v = 0; v < 8; v++)
                        sts128(spill + (ch * 8 + v) * 2048, pack_bf16(d[8 * v], d[8 * v + 1]),
                               pack_bf16(d[8 * v + 2], d[8 * v + 3]), pack_bf16(d[8 * v + 4], d[8 * v + 5]),
                               pack_bf16(d[8 * v + 6], d[8 * v + 7]));
                } else {
#pragma unroll
                    for (int i = 0; i < 32; i++) {
                        const float gv = d[i], gu = gv * d[32 + i];
                        const float z = gv * fmaf(gv * gv, 0.7978845608028654f * 0.044715f, 0.7978845608028654f);
                        d[i] = fmaf(gu, tanh_fast(z), gu);
                    }
                    if (ch == 8) break;
#pragma unroll
                    for (int v = 0; v < 4; v++) {
                        const uint4 h4 = make_uint4(pack_bf16(d[8 * v], d[8 * v + 1]), pack_bf16(d[8 * v + 2], d[8 * v + 3]),
                                                    pack_bf16(d[8 * v + 4], d[8 * v + 5]), pack_bf16(d[8 * v + 6], d[8 * v + 7]));
                        if (ch < 2)
                            __stcg(hhbuf + (ch * 4 + v) * 256, h4);
                        else
                            sts128(spill + ((ch - 2) * 4 + v) * 2048, h4.x, h4.y, h4.z, h4.w);
                    }
                }
            }
            if (stage == 0) {
                uint32_t q[32];
#pragma unroll
                for (int i = 0; i < 32; i++) q[i] = pack_bf16(d[2 * i], d[2 * i + 1]);
                PROF(5);
                PROFG(23);
                {
                    float o[64], sa[32], sb[32];
                    uint32_t pa[16], pb[16];
#pragma unroll
                    for (int i = 0; i < 64; i++) o[i] = 0.f;
                    float n0 = 0.f, n1 = 0.f, l0 = 1.f, l1 = 1.f;
                    bool shifted = false;
                    const uint64_t dbase = desc_of(sbase);
                    const uint64_t dbk = dbase - (511u << 16);
                    const int my_bar = 1 + wg, other_bar = 2 - wg;

                    auto softmax_a = [&](bool first, float& s0, float& s1) {
                        if (first) {
                            shifted = false;
                            n0 = n1 = 0.f;
                            l0 = l1 = 0.f;
                        }
                        if (shifted)
                            exp_step<true>(sa, pa, n0, n1, s0, s1);
                        else
                            exp_step<false>(sa, pa, n0, n1, s0, s1);
                    };
                    auto softmax_b = [&](bool first, float s0, float s1) {
                        float u0, u1;
                        if (shifted)
                            exp_step<true>(sb, pb, n0, n1, u0, u1);
                        else
                            exp_step<false>(sb, pb, n0, n1, u0, u1);
                        s0 += u0;
                        s1 += u1;
                        bool bad = !(fmaxf(s0, s1) <= SM_HI);
                        if (first) {
                            float r0 = s0 + __shfl_xor_sync(0xffffffffu, s0, 1), r1 = s1 + __shfl_xor_sync(0xffffffffu, s1, 1);
                            r0 += __shfl_xor_sync(0xffffffffu, r0, 2);
                            r1 += __shfl_xor_sync(0xffffffffu, r1, 2);
                            bad = bad || !(fminf(r0, r1) >= SM_LO);
                        }
                        if (__any_sync(0xffffffffu, bad)) {
                            float x0, x1;
                            row_max(sa, sb, x0, x1);
                            x0 = -x0;
                            x1 = -x1;
                            if (!first) {
                                x0 = fminf(x0, n0);
                                x1 = fminf(x1, n1);
                                const float al0 = ex2(x0 - n0), al1 = ex2(x1 - n1);
                                l0 *= al0;
                                l1 *= al1;
#pragma unroll
                                for (int i = 0; i < 16; i++) {
                                    o[4 * i] *= al0;
                                    o[4 * i + 1] *= al0;
                                    o[4 * i + 2] *= al1;
                                    o[4 * i + 3] *= al1;
                                }
                            }
                            n0 = x0;
                            n1 = x1;
                            shifted = true;
                            exp_step<true>(sa, pa, n0, n1, s0, s1);
                            exp_step<true>(sb, pb, n0, n1, u0, u1);
                            s0 += u0;
                            s1 += u1;
                        }
                        l0 += s0;
                        l1 += s1;
                    };

                    cx.wait_full(4, 0);
                    if (wg == 1) bar_sync(my_bar, 256);
                    wg_fence();
                    qk_step(sa, q, dbk + 4 * 1024);
                    qk_step(sb, q, dbk + 5 * 1024);
                    wg_commit();
                    bar_arrive(other_bar, 256);
                    wg_wait<0>();
                    pin(sa);
                    pin(sb);
                    cx.release(4);
                    cx.wait_full(6, 0);
                    cx.wait_full(0, 1);
                    {
                        float s0, s1;
                        softmax_a(true, s0, s1);
                        softmax_b(true, s0, s1);
                    }
#pragma unroll 1
                    for (int t = 1; t < 64; t++) {
                        const int j = t & 15;
                        const uint32_t ks = 4 - 4 * (t & 1), vs = 2 + 4 * (t & 1);
                        TL(0);
                        bar_sync(my_bar, 256);
                        TL(2);
                        wg_fence();
                        const uint64_t dk = dbk + ks * 1024, dv = dbase + vs * 1024;
                        pv_step(o, pa, dv, j != 1);
                        pv_step(o, pb, dv + 1024, 1);
                        qk_step(sa, q, dk);
                        wg_commit();
                        qk_step(sb, q, dk + 1024);
                        wg_commit();
                        bar_arrive(other_bar, 256);
                        TL(3);
                        wg_wait<1>();
                        pin(o);
                        pin(sa);
                        pin(pa);
                        pin(pb);
                        TL(4);
                        cx.release(vs);
                        if (j == 0) {
                            float i0, i1;
                            inv_row_sums(l0, l1, i0, i1);
                            const uint32_t dst = spill + ((t >> 4) - 1) * 16384;
#pragma unroll
                            for (int v = 0; v < 8; v++)
                                sts128(dst + v * 2048, pack_bf16(o[8 * v] * i0, o[8 * v + 1] * i0),
                                       pack_bf16(o[8 * v + 2] * i1, o[8 * v + 3] * i1),
                                       pack_bf16(o[8 * v + 4] * i0, o[8 * v + 5] * i0),
                                       pack_bf16(o[8 * v + 6] * i1, o[8 * v + 7] * i1));
                        }
                        float s0, s1;
                        softmax_a(j == 0, s0, s1);
                        TL(5);
                        wg_wait<0>();
                        pin(sb);
                        TL(6);
                        cx.release(ks);
                        const uint32_t bv = sbase + OFF_FULL + (8 - vs) * 8, pv = ((38 + 4 * t) >> 3) & 1;
                        const uint32_t bk = t < 63 ? sbase + OFF_FULL + (4 - ks) * 8 : bv, pk = t < 63 ? ((40 + 4 * t) >> 3) & 1 : pv;
                        const bool okv = mbar_try(bv, pv), okk = mbar_try(bk, pk);
                        TL(1);
                        softmax_b(j == 0, s0, s1);
                        if (!(okv && okk) || j == 15) {
                            mbar_wait(bv, pv);
                            mbar_wait(bk, pk);
                            if (j == 15 && t < 63) {
                                const uint32_t src = spill + (t >> 4) * 16384;
#pragma unroll
                                for (int v = 0; v < 8; v++)
                                    lds128(src + v * 2048, q[4 * v], q[4 * v + 1], q[4 * v + 2], q[4 * v + 3]);
                            }
                        }
                        TL(7);
                    }
                    bar_sync(my_bar, 256);
                    wg_fence();
                    pv_step(o, pa, dbase + 2 * 1024, 1);
                    pv_step(o, pb, dbase + 3 * 1024, 1);
                    wg_commit();
                    if (wg == 0) bar_arrive(other_bar, 256);
                    float i0, i1;
                    inv_row_sums(l0, l1, i0, i1);
                    wg_wait<0>();
                    pin(o);
                    cx.release(2);
#pragma unroll
                    for (int i = 0; i < 16; i++) {
                        a[96 + 2 * i] = pack_bf16(o[4 * i] * i0, o[4 * i + 1] * i0);
                        a[96 + 2 * i + 1] = pack_bf16(o[4 * i + 2] * i1, o[4 * i + 3] * i1);
                    }
#pragma unroll
                    for (int i = 128; i < 144; i++) a[i] = 0;
                }
                ring.slot = 4;
                ring.phase = 0;
                PROF(6);
                PROFG(24);
            } else {
#pragma unroll
                for (int v = 0; v < 8; v++) {
                    const uint4 t = __ldcg(hhbuf + v * 256);
                    a[112 + 4 * v] = t.x;
                    a[113 + 4 * v] = t.y;
                    a[114 + 4 * v] = t.z;
                    a[115 + 4 * v] = t.w;
                }
#pragma unroll
                for (int i = 0; i < 16; i++) a[96 + i] = pack_bf16(d[2 * i], d[2 * i + 1]);
                PROF(13);
            }
#pragma unroll
            for (int v = 0; v < 24; v++) lds128(spill + v * 2048, a[4 * v], a[4 * v + 1], a[4 * v + 2], a[4 * v + 3]);

            proj_partials(a, cx, ring, stage != 0, g_part + ((size_t)wown * 8 + g) * 72 * 32 + lane, (stage + 1) & 1);
            PROF(stage == 0 ? 7 : 14);
            if (stage == 1) {
                PROFG(26);
                asm volatile("barrier.cluster.arrive.relaxed.aligned;" ::: "memory");
            }
        }
        PROF(16);
        PROFG(31);
        if (b == 0) {
            bar_sync(3, 256);
            if (tid == 0) g_epoch = epoch + 1;
        }
        asm volatile("barrier.cluster.wait.aligned;" ::: "memory");
    }
}

typedef CUresult (*EncodeFn)(CUtensorMap*, CUtensorMapDataType, cuuint32_t, void*, const cuuint64_t*, const cuuint64_t*,
                             const cuuint32_t*, const cuuint32_t*, CUtensorMapInterleave, CUtensorMapSwizzle,
                             CUtensorMapL2promotion, CUtensorMapFloatOOBfill);

void make_map(EncodeFn enc, CUtensorMap* m, const void* ptr, uint64_t rows, uint64_t cols) {
    cuuint64_t gdim[2] = {cols, rows};
    cuuint64_t gstr[1] = {cols * 2};
    cuuint32_t box[2] = {64, 64};
    cuuint32_t estr[2] = {1, 1};
    enc(m, CU_TENSOR_MAP_DATA_TYPE_BFLOAT16, 2, const_cast<void*>(ptr), gdim, gstr, box, estr,
        CU_TENSOR_MAP_INTERLEAVE_NONE, CU_TENSOR_MAP_SWIZZLE_128B, CU_TENSOR_MAP_L2_PROMOTION_L2_128B,
        CU_TENSOR_MAP_FLOAT_OOB_FILL_NONE);
}

}

extern "C" void kernel_launch(void* const* d_in, const int* in_sizes, int n_in, void* d_out, int out_size) {
    (void)in_sizes;
    (void)n_in;
    (void)out_size;
    void* fn = nullptr;
    cudaDriverEntryPointQueryResult qr;
    cudaGetDriverEntryPoint("cuTensorMapEncodeTiled", &fn, cudaEnableDefault, &qr);
    EncodeFn enc = (EncodeFn)fn;
    Maps maps;
    make_map(enc, &maps.k, d_in[1], 32 * 2048, 128);
    make_map(enc, &maps.v, d_in[2], 32 * 2048, 128);
    make_map(enc, &maps.wq, d_in[3], 576, 4096);
    make_map(enc, &maps.wo, d_in[4], 4096, 576);
    make_map(enc, &maps.wg, d_in[6], 576, 4608);
    make_map(enc, &maps.wu, d_in[7], 576, 4608);
    make_map(enc, &maps.wd, d_in[8], 4608, 576);
    cudaFuncSetAttribute(fused_block_kernel, cudaFuncAttributeMaxDynamicSharedMemorySize, SMEM_BYTES);
    fused_block_kernel<<<128, 384, SMEM_BYTES>>>(maps, (const __nv_bfloat16*)d_in[0], (const __nv_bfloat16*)d_in[9],
                                                 (const __nv_bfloat16*)d_in[10], (__nv_bfloat16*)d_out);
}
```

```cpp
#include <cuda_runtime.h>
#include <cuda_bf16.h>
#include <cuda.h>
#include <stdint.h>

namespace {

constexpr int DM = 576;
constexpr int SLOT_BYTES = 16384;
constexpr int BOX_BYTES = 8192;
constexpr int NUNITS = 14;
constexpr int SMEM_TAIL = NUNITS * SLOT_BYTES;
constexpr int SMEM_BYTES = SMEM_TAIL + 2048 + 1024;
constexpr int OFF_FULL = SMEM_TAIL;
constexpr int OFF_EMPTY = SMEM_TAIL + 64;
constexpr int OFF_RED = SMEM_TAIL + 128;

constexpr int OFF_XBAR = SMEM_TAIL + 1792;
constexpr int XROW_STRIDE = DM * 2 + 16;

__device__ unsigned g_epoch;
__device__ __align__(16) uint32_t g_mod[6 * DM];
__device__ uint4 g_h[2][128 * 36 * 32];
__device__ unsigned long long g_part[128 * 8 * 72 * 32];
__device__ float4 g_x2[128 * 9 * 256];
__device__ uint4 g_hh[128 * 8 * 256];
__device__ unsigned g_cnt[256 * 32];

#define TL(i)
#define PROFR(i)
#define PROF(i)
#define PROFG(i)

struct Maps {
    CUtensorMap k, v, wq, wo, wg, wu, wd;
};

__device__ __forceinline__ uint32_t smem_u32(const void* p) { return (uint32_t)__cvta_generic_to_shared(p); }
__device__ __forceinline__ void mbar_init(uint32_t a, uint32_t c) {
    asm volatile("mbarrier.init.shared::cta.b64 [%0], %1;" ::"r"(a), "r"(c) : "memory");
}
__device__ __forceinline__ void mbar_expect_tx(uint32_t a, uint32_t bytes) {
    asm volatile("mbarrier.arrive.expect_tx.shared::cta.b64 _, [%0], %1;" ::"r"(a), "r"(bytes) : "memory");
}
__device__ __forceinline__ bool mbar_try(uint32_t a, uint32_t ph) {
    uint32_t ok;
    asm volatile(
        "{\n.reg .pred p;\nmbarrier.try_wait.parity.shared::cta.b64 p, [%1], %2;\nselp.u32 %0, 1, 0, p;\n}"
        : "=r"(ok)
        : "r"(a), "r"(ph)
        : "memory");
    return ok != 0;
}
__device__ __forceinline__ uint32_t clk32() {
    uint32_t c;
    asm volatile("mov.u32 %0, %%clock;" : "=r"(c));
    return c;
}
constexpr uint32_t WAIT_LIMIT = 1u << 30;
__device__ __forceinline__ void mbar_wait(uint32_t a, uint32_t ph) {
    if (mbar_try(a, ph)) return;
    uint32_t t0 = clk32();
    while (!mbar_try(a, ph)) {
        if (clk32() - t0 > WAIT_LIMIT) break;
    }
}
__device__ __forceinline__ void mbar_arrive_cluster(uint32_t a, uint32_t cta) {
    asm volatile(
        "{\n.reg .b32 ra;\nmapa.shared::cluster.u32 ra, %0, %1;\nmbarrier.arrive.shared::cluster.b64 _, [ra];\n}" ::"r"(a),
        "r"(cta)
        : "memory");
}
__device__ __forceinline__ void tma_mc(uint32_t dst, const CUtensorMap* m, int c0, int c1, uint32_t bar) {
    asm volatile(
        "cp.async.bulk.tensor.2d.shared::cluster.global.mbarrier::complete_tx::bytes.multicast::cluster"
        " [%0], [%1, {%3, %4}], [%2], %5;" ::"r"(dst),
        "l"(m), "r"(bar), "r"(c0), "r"(c1), "h"((uint16_t)3)
        : "memory");
}
__device__ __forceinline__ void bar_sync(int id, int n) { asm volatile("bar.sync %0, %1;" ::"r"(id), "r"(n) : "memory"); }
__device__ __forceinline__ void bar_arrive(int id, int n) {
    asm volatile("bar.arrive %0, %1;" ::"r"(id), "r"(n) : "memory");
}
__device__ __forceinline__ void wg_fence() { asm volatile("wgmma.fence.sync.aligned;" ::: "memory"); }
__device__ __forceinline__ void wg_commit() { asm volatile("wgmma.commit_group.sync.aligned;" ::: "memory"); }
template <int N>
__device__ __forceinline__ void wg_wait() {
    asm volatile("wgmma.wait_group.sync.aligned %0;" ::"n"(N) : "memory");
}
template <int N>
__device__ __forceinline__ void pin(float (&d)[N]) {
#pragma unroll
    for (int i = 0; i < N; i++) asm volatile("" : "+f"(d[i])::"memory");
}
template <int N>
__device__ __forceinline__ void pin(uint32_t (&d)[N]) {
#pragma unroll
    for (int i = 0; i < N; i++) asm volatile("" : "+r"(d[i])::"memory");
}
__device__ __forceinline__ uint32_t pack_bf16(float lo, float hi) {
    uint32_t r;
    asm("cvt.rn.bf16x2.f32 %0, %1, %2;" : "=r"(r) : "f"(hi), "f"(lo));
    return r;
}
__device__ __forceinline__ float bf_lo(uint32_t v) { return __uint_as_float(v << 16); }
__device__ __forceinline__ float bf_hi(uint32_t v) { return __uint_as_float(v & 0xffff0000u); }
__device__ __forceinline__ float round_bf16(float v) { return __bfloat162float(__float2bfloat16_rn(v)); }
__device__ __forceinline__ float ex2(float x) {
    float y;
    asm("ex2.approx.ftz.f32 %0, %1;" : "=f"(y) : "f"(x));
    return y;
}
__device__ __forceinline__ float rcp(float x) {
    float y;
    asm("rcp.approx.ftz.f32 %0, %1;" : "=f"(y) : "f"(x));
    return y;
}
__device__ __forceinline__ float tanh_fast(float x) {
    float y;
    asm("tanh.approx.f32 %0, %1;" : "=f"(y) : "f"(x));
    return y;
}
__device__ __forceinline__ void sts128(uint32_t a, uint32_t x, uint32_t y, uint32_t z, uint32_t w) {
    asm volatile("st.shared.v4.b32 [%0], {%1,%2,%3,%4};" ::"r"(a), "r"(x), "r"(y), "r"(z), "r"(w) : "memory");
}
__device__ __forceinline__ void lds128(uint32_t a, uint32_t& x, uint32_t& y, uint32_t& z, uint32_t& w) {
    asm volatile("ld.shared.v4.b32 {%0,%1,%2,%3}, [%4];" : "=r"(x), "=r"(y), "=r"(z), "=r"(w) : "r"(a) : "memory");
}
__device__ __forceinline__ void sts32f(uint32_t a, float v) {
    asm volatile("st.shared.f32 [%0], %1;" ::"r"(a), "f"(v) : "memory");
}
__device__ __forceinline__ float lds32f(uint32_t a) {
    float v;
    asm volatile("ld.shared.f32 %0, [%1];" : "=f"(v) : "r"(a) : "memory");
    return v;
}
__device__ __forceinline__ void signal_cnt(int idx) {
    asm volatile("red.release.gpu.global.add.u32 [%0], 1;" ::"l"(&g_cnt[idx * 32]) : "memory");
}
__device__ __forceinline__ void wait_cnt(int idx, unsigned target) {
    if ((threadIdx.x & 31) == 0) {
        uint32_t t0 = clk32();
        while (true) {
            unsigned v;
            asm volatile("ld.acquire.gpu.global.u32 %0, [%1];" : "=r"(v) : "l"(&g_cnt[idx * 32]) : "memory");
            if ((int)(v - target) >= 0) break;
            if (clk32() - t0 > WAIT_LIMIT) break;
        }
    }
    __syncwarp();
}

#define F8(d, b) \
    "+f"(d[b]), "+f"(d[b + 1]), "+f"(d[b + 2]), "+f"(d[b + 3]), "+f"(d[b + 4]), "+f"(d[b + 5]), "+f"(d[b + 6]), "+f"(d[b + 7])

template <int TB>
__device__ __forceinline__ void wgmma_n128(float (&d)[64], uint32_t a0, uint32_t a1, uint32_t a2, uint32_t a3,
                                           uint64_t db, int sc) {
    asm volatile(
        "{\n.reg .pred p;\nsetp.ne.b32 p, %69, 0;\n"
        "wgmma.mma_async.sync.aligned.m64n128k16.f32.bf16.bf16 "
        "{%0,%1,%2,%3,%4,%5,%6,%7,%8,%9,%10,%11,%12,%13,%14,%15,%16,%17,%18,%19,%20,%21,%22,%23,%24,%25,%26,%27,%28,%29,%30,%31,"
        "%32,%33,%34,%35,%36,%37,%38,%39,%40,%41,%42,%43,%44,%45,%46,%47,%48,%49,%50,%51,%52,%53,%54,%55,%56,%57,%58,%59,%60,%61,%62,%63},"
        "{%64,%65,%66,%67}, %68, p, 1, 1, %70;\n}"
        : F8(d, 0), F8(d, 8), F8(d, 16), F8(d, 24), F8(d, 32), F8(d, 40), F8(d, 48), F8(d, 56)
        : "r"(a0), "r"(a1), "r"(a2), "r"(a3), "l"(db), "r"(sc), "n"(TB));
}
#define O8(d, b) \
    "=f"(d[b]), "=f"(d[b + 1]), "=f"(d[b + 2]), "=f"(d[b + 3]), "=f"(d[b + 4]), "=f"(d[b + 5]), "=f"(d[b + 6]), "=f"(d[b + 7])
template <int TB>
__device__ __forceinline__ void wgmma_n128_z(float (&d)[64], uint32_t a0, uint32_t a1, uint32_t a2, uint32_t a3,
                                             uint64_t db) {
    asm volatile(
        "wgmma.mma_async.sync.aligned.m64n128k16.f32.bf16.bf16 "
        "{%0,%1,%2,%3,%4,%5,%6,%7,%8,%9,%10,%11,%12,%13,%14,%15,%16,%17,%18,%19,%20,%21,%22,%23,%24,%25,%26,%27,%28,%29,%30,%31,"
        "%32,%33,%34,%35,%36,%37,%38,%39,%40,%41,%42,%43,%44,%45,%46,%47,%48,%49,%50,%51,%52,%53,%54,%55,%56,%57,%58,%59,%60,%61,%62,%63},"
        "{%64,%65,%66,%67}, %68, 0, 1, 1, %69;"
        : O8(d, 0), O8(d, 8), O8(d, 16), O8(d, 24), O8(d, 32), O8(d, 40), O8(d, 48), O8(d, 56)
        : "r"(a0), "r"(a1), "r"(a2), "r"(a3), "l"(db), "n"(TB));
}
template <int TB>
__device__ __forceinline__ void wgmma_n64_z(float (&d)[32], uint32_t a0, uint32_t a1, uint32_t a2, uint32_t a3,
                                            uint64_t db) {
    asm volatile(
        "wgmma.mma_async.sync.aligned.m64n64k16.f32.bf16.bf16 "
        "{%0,%1,%2,%3,%4,%5,%6,%7,%8,%9,%10,%11,%12,%13,%14,%15,%16,%17,%18,%19,%20,%21,%22,%23,%24,%25,%26,%27,%28,%29,%30,%31},"
        "{%32,%33,%34,%35}, %36, 0, 1, 1, %37;"
        : O8(d, 0), O8(d, 8), O8(d, 16), O8(d, 24)
        : "r"(a0), "r"(a1), "r"(a2), "r"(a3), "l"(db), "n"(TB));
}
template <int TB>
__device__ __forceinline__ void wgmma_n64(float (&d)[32], uint32_t a0, uint32_t a1, uint32_t a2, uint32_t a3,
                                          uint64_t db) {
    asm volatile(
        "wgmma.mma_async.sync.aligned.m64n64k16.f32.bf16.bf16 "
        "{%0,%1,%2,%3,%4,%5,%6,%7,%8,%9,%10,%11,%12,%13,%14,%15,%16,%17,%18,%19,%20,%21,%22,%23,%24,%25,%26,%27,%28,%29,%30,%31},"
        "{%32,%33,%34,%35}, %36, 1, 1, 1, %37;"
        : F8(d, 0), F8(d, 8), F8(d, 16), F8(d, 24)
        : "r"(a0), "r"(a1), "r"(a2), "r"(a3), "l"(db), "n"(TB));
}

__device__ __forceinline__ uint64_t desc_of(uint32_t saddr) {
    return (uint64_t)(((saddr >> 4) & 0x3FFFu) | (512u << 16)) | ((uint64_t)(64u | (1u << 30)) << 32);
}

struct Ring {
    uint32_t slot;
    uint32_t phase;
    __device__ __forceinline__ void next() {
        if (++slot == 8) {
            slot = 0;
            phase ^= 1;
        }
    }
};

struct Ctx {
    uint32_t sbase;
    uint32_t rel_cta;
    __device__ __forceinline__ void wait_full(uint32_t slot, uint32_t phase) const {
        mbar_wait(sbase + OFF_FULL + slot * 8, phase);
    }
    __device__ __forceinline__ void release(uint32_t slot) const {
        if (rel_cta < 2) mbar_arrive_cluster(sbase + OFF_EMPTY + slot * 8, rel_cta);
    }
};

__device__ __forceinline__ void gemm_n128(float (&d)[64], const uint32_t (&a)[144], const Ctx& c, Ring& r, bool nine,
                                          int kick) {
    uint32_t prev = 0;
#pragma unroll
    for (int s = 0; s < 9; s++) {
        if (s < 8 || nine) {
            c.wait_full(r.slot, r.phase);
            uint64_t db = desc_of(c.sbase + r.slot * SLOT_BYTES);
            wg_fence();
#pragma unroll
            for (int k = 0; k < 4; k++) {
                if ((s | k) == 0)
                    wgmma_n128_z<1>(d, a[0], a[1], a[2], a[3], db);
                else
                    wgmma_n128<1>(d, a[s * 16 + k * 4], a[s * 16 + k * 4 + 1], a[s * 16 + k * 4 + 2],
                                  a[s * 16 + k * 4 + 3], db + k * 128, 1);
            }
            wg_commit();
            if (s == 3 && kick) bar_arrive(kick, 256);
            if (s > 0) {
                wg_wait<1>();
                c.release(prev);
            }
            prev = r.slot;
            r.next();
        }
    }
    wg_wait<0>();
    c.release(prev);
    pin(d);
}
__device__ __forceinline__ void gemm_n64(float (&d)[32], const uint32_t (&a)[144], const Ctx& c, Ring& r, bool nine) {
    uint32_t prev = 0;
#pragma unroll
    for (int s = 0; s < 5; s++) {
        if (s < 4 || nine) {
            c.wait_full(r.slot, r.phase);
            uint64_t db = desc_of(c.sbase + r.slot * SLOT_BYTES);
            wg_fence();
#pragma unroll
            for (int k = 0; k < 8; k++) {
                if ((s | k) == 0)
                    wgmma_n64_z<1>(d, a[0], a[1], a[2], a[3], db);
                else if (s * 8 + k < 36)
                    wgmma_n64<1>(d, a[s * 32 + k * 4], a[s * 32 + k * 4 + 1], a[s * 32 + k * 4 + 2],
                                 a[s * 32 + k * 4 + 3], db + k * 128);
            }
            wg_commit();
            if (s > 0) {
                wg_wait<1>();
                c.release(prev);
            }
            prev = r.slot;
            r.next();
        }
    }
    wg_wait<0>();
    c.release(prev);
    pin(d);
}
__device__ __forceinline__ void st_part(unsigned long long* p, float a, float b, float c, float d, uint32_t tag) {
    const uint32_t lo = (pack_bf16(a, b) & ~1u) | tag, hi = pack_bf16(c, d);
    asm volatile("{\n.reg .b64 t;\nmov.b64 t, {%1, %2};\nst.relaxed.gpu.global.b64 [%0], t;\n}" ::"l"(p), "r"(lo), "r"(hi)
                 : "memory");
}
__device__ __forceinline__ uint2 ld_part(const unsigned long long* p) {
    uint2 r;
    asm volatile("{\n.reg .b64 t;\nld.relaxed.gpu.global.b64 t, [%2];\nmov.b64 {%0, %1}, t;\n}"
                 : "=r"(r.x), "=r"(r.y)
                 : "l"(p));
    return r;
}
__device__ __forceinline__ void proj_partials(const uint32_t (&a)[144], const Ctx& c, Ring& r, bool nine,
                                              unsigned long long* dst  , uint32_t tag) {
#pragma unroll 1
    for (int p = 0; p < 4; p++) {
        float d[64];
        gemm_n128(d, a, c, r, nine, 0);
#pragma unroll
        for (int j = 0; j < 16; j++) st_part(dst + (p * 16 + j) * 32, d[4 * j], d[4 * j + 1], d[4 * j + 2], d[4 * j + 3], tag);
    }
    float d[32];
    gemm_n64(d, a, c, r, nine);
#pragma unroll
    for (int j = 0; j < 8; j++) st_part(dst + (64 + j) * 32, d[4 * j], d[4 * j + 1], d[4 * j + 2], d[4 * j + 3], tag);
}

__device__ __forceinline__ void row_reduce(float& s0, float& s1, uint32_t red, int warp, int lane) {
    s0 += __shfl_xor_sync(0xffffffffu, s0, 1);
    s1 += __shfl_xor_sync(0xffffffffu, s1, 1);
    s0 += __shfl_xor_sync(0xffffffffu, s0, 2);
    s1 += __shfl_xor_sync(0xffffffffu, s1, 2);
    if ((lane & 3) == 0) {
        sts32f(red + (warp * 16 + (lane >> 2)) * 4, s0);
        sts32f(red + (warp * 16 + 8 + (lane >> 2)) * 4, s1);
    }
    bar_sync(3, 256);
    s0 = 0.f;
    s1 = 0.f;
#pragma unroll
    for (int w = 0; w < 8; w++) {
        s0 += lds32f(red + (w * 16 + (lane >> 2)) * 4);
        s1 += lds32f(red + (w * 16 + 8 + (lane >> 2)) * 4);
    }
}
__device__ __forceinline__ void layernorm_rows(float (&v)[36], uint32_t red, int warp, int lane) {
    float s0 = 0.f, s1 = 0.f;
#pragma unroll
    for (int j = 0; j < 9; j++) {
        s0 += v[4 * j] + v[4 * j + 1];
        s1 += v[4 * j + 2] + v[4 * j + 3];
    }
    row_reduce(s0, s1, red, warp, lane);
    const float m0 = s0 * (1.f / DM), m1 = s1 * (1.f / DM);
    s0 = 0.f;
    s1 = 0.f;
#pragma unroll
    for (int j = 0; j < 9; j++) {
        v[4 * j] -= m0;
        v[4 * j + 1] -= m0;
        v[4 * j + 2] -= m1;
        v[4 * j + 3] -= m1;
        s0 += v[4 * j] * v[4 * j] + v[4 * j + 1] * v[4 * j + 1];
        s1 += v[4 * j + 2] * v[4 * j + 2] + v[4 * j + 3] * v[4 * j + 3];
    }
    row_reduce(s0, s1, red + 512, warp, lane);
    const float r0 = rsqrtf(s0 * (1.f / DM) + 1e-5f), r1 = rsqrtf(s1 * (1.f / DM) + 1e-5f);
#pragma unroll
    for (int j = 0; j < 9; j++) {
        v[4 * j] *= r0;
        v[4 * j + 1] *= r0;
        v[4 * j + 2] *= r1;
        v[4 * j + 3] *= r1;
    }
}
__device__ __forceinline__ void load_mod0(float (&m)[3][18], const uint32_t* src, uint32_t tag) {
    const uint32_t t0 = clk32();
    while (true) {
        uint2 u[2][9];
#pragma unroll
        for (int n = 0; n < 2; n++)
#pragma unroll
            for (int j = 0; j < 9; j++)
                asm volatile("ld.relaxed.gpu.global.v2.u32 {%0,%1}, [%2];"
                             : "=r"(u[n][j].x), "=r"(u[n][j].y)
                             : "l"(src + n * DM + j * 64));
        uint32_t bad = 0;
#pragma unroll
        for (int n = 0; n < 2; n++)
#pragma unroll
            for (int j = 0; j < 9; j++) {
                bad |= (u[n][j].x ^ tag) | (u[n][j].y ^ tag);
                m[n + 1][2 * j] = __uint_as_float(u[n][j].x & 0xffff0000u);
                m[n + 1][2 * j + 1] = __uint_as_float(u[n][j].y & 0xffff0000u);
            }
        if (__all_sync(0xffffffffu, (bad & 0xffffu) == 0) || clk32() - t0 > WAIT_LIMIT) break;
    }
}
__device__ __forceinline__ void modulate_store(const float (&v)[36], const float (&shift)[18], const float (&scale)[18],
                                               uint4* hbuf  , int warp, int lane) {
    uint2* dst = reinterpret_cast<uint2*>(hbuf) + ((warp >> 1) * 32 + lane) * 2 + (warp & 1);
#pragma unroll
    for (int j = 0; j < 9; j++) {
        const float c0 = round_bf16(1.f + scale[2 * j]), c1 = round_bf16(1.f + scale[2 * j + 1]);
        uint2 o;
        o.x = pack_bf16(fmaf(v[4 * j], c0, shift[2 * j]), fmaf(v[4 * j + 1], c1, shift[2 * j + 1]));
        o.y = pack_bf16(fmaf(v[4 * j + 2], c0, shift[2 * j]), fmaf(v[4 * j + 3], c1, shift[2 * j + 1]));
        __stcg(dst + j * 256, o);
    }
}
__device__ __forceinline__ void sum_partials(float (&v)[36], const unsigned long long* src  ,
                                             uint32_t tag) {
    const uint32_t t0 = clk32();
    while (true) {
        uint2 t[8][8];
#pragma unroll
        for (int s = 0; s < 8; s++)
#pragma unroll
            for (int j = 0; j < 8; j++) t[s][j] = ld_part(src + (s * 72 + j * 8) * 32);
        uint32_t bad = 0;
#pragma unroll
        for (int s = 0; s < 8; s++)
#pragma unroll
            for (int j = 0; j < 8; j++) {
                bad |= t[s][j].x ^ tag;
                if (s == 0) {
                    v[4 * j] = bf_lo(t[s][j].x);
                    v[4 * j + 1] = bf_hi(t[s][j].x);
                    v[4 * j + 2] = bf_lo(t[s][j].y);
                    v[4 * j + 3] = bf_hi(t[s][j].y);
                } else {
                    v[4 * j] += bf_lo(t[s][j].x);
                    v[4 * j + 1] += bf_hi(t[s][j].x);
                    v[4 * j + 2] += bf_lo(t[s][j].y);
                    v[4 * j + 3] += bf_hi(t[s][j].y);
                }
            }
        if (__all_sync(0xffffffffu, (bad & 1u) == 0) || clk32() - t0 > WAIT_LIMIT) break;
    }
}
__device__ __forceinline__ void sum_tail(float (&v)[36], float (&m)[3][18], const unsigned long long* src, uint32_t tag,
                                         const uint32_t* gate, const uint32_t* shsc, uint32_t mtag) {
    const uint32_t t0 = clk32();
    while (true) {
        uint2 t[8], u[3][9];
#pragma unroll
        for (int s = 0; s < 8; s++) t[s] = ld_part(src + (s * 72 + 64) * 32);
#pragma unroll
        for (int n = 0; n < 3; n++)
#pragma unroll
            for (int j = 0; j < 9; j++)
                asm volatile("ld.relaxed.gpu.global.v2.u32 {%0,%1}, [%2];"
                             : "=r"(u[n][j].x), "=r"(u[n][j].y)
                             : "l"((n == 0 ? gate : shsc + (n - 1) * DM) + j * 64));
        uint32_t bad = 0, badm = 0;
        v[32] = v[33] = v[34] = v[35] = 0.f;
#pragma unroll
        for (int s = 0; s < 8; s++) {
            bad |= t[s].x ^ tag;
            v[32] += bf_lo(t[s].x);
            v[33] += bf_hi(t[s].x);
            v[34] += bf_lo(t[s].y);
            v[35] += bf_hi(t[s].y);
        }
#pragma unroll
        for (int n = 0; n < 3; n++)
#pragma unroll
            for (int j = 0; j < 9; j++) {
                badm |= (u[n][j].x ^ mtag) | (u[n][j].y ^ mtag);
                m[n][2 * j] = __uint_as_float(u[n][j].x & 0xffff0000u);
                m[n][2 * j + 1] = __uint_as_float(u[n][j].y & 0xffff0000u);
            }
        if (__all_sync(0xffffffffu, ((bad & 1u) | (badm & 0xffffu)) == 0) || clk32() - t0 > WAIT_LIMIT) break;
    }
}
__device__ __forceinline__ void load_frags(uint32_t (&a)[144], const uint4* src  ) {
#pragma unroll
    for (int k = 0; k < 36; k++) {
        uint4 t = __ldcg(src + k * 32);
        a[4 * k] = t.x;
        a[4 * k + 1] = t.y;
        a[4 * k + 2] = t.z;
        a[4 * k + 3] = t.w;
    }
}

constexpr float SM_SCALE = 0.08838834764831845f * 1.4426950408889634f;
constexpr float SM_HI = 1.2089258e24f;
constexpr float SM_LO = 9.0949470e-13f;
__device__ __forceinline__ void qk_step(float (&s)[32], const uint32_t (&q)[32], uint64_t dk) {
#pragma unroll
    for (int k = 0; k < 8; k++) {
        if (k == 0)
            wgmma_n64_z<0>(s, q[0], q[1], q[2], q[3], dk);
        else
            wgmma_n64<0>(s, q[4 * k], q[4 * k + 1], q[4 * k + 2], q[4 * k + 3], dk + (k >> 2) * 512 + (k & 3) * 2);
    }
}
__device__ __forceinline__ void pv_step(float (&o)[64], const uint32_t (&p)[16], uint64_t dv, int acc) {
#pragma unroll
    for (int k = 0; k < 4; k++)
        wgmma_n128<1>(o, p[4 * k], p[4 * k + 1], p[4 * k + 2], p[4 * k + 3], dv + k * 128, k != 0 ? 1 : acc);
}
template <bool SHIFT>
__device__ __forceinline__ void exp_step(const float (&s)[32], uint32_t (&p)[16], float n0, float n1, float& s0,
                                         float& s1) {
#pragma unroll
    for (int i = 0; i < 8; i++) {
        const float e0 = ex2(SHIFT ? s[4 * i] + n0 : s[4 * i]), e1 = ex2(SHIFT ? s[4 * i + 1] + n0 : s[4 * i + 1]);
        const float e2 = ex2(SHIFT ? s[4 * i + 2] + n1 : s[4 * i + 2]), e3 = ex2(SHIFT ? s[4 * i + 3] + n1 : s[4 * i + 3]);
        if (i == 0) {
            s0 = e0 + e1;
            s1 = e2 + e3;
        } else {
            s0 += e0 + e1;
            s1 += e2 + e3;
        }
        p[2 * i] = pack_bf16(e0, e1);
        p[2 * i + 1] = pack_bf16(e2, e3);
    }
}
__device__ __forceinline__ void row_max(const float (&sa)[32], const float (&sb)[32], float& x0, float& x1) {
    float xa[8];
#pragma unroll
    for (int i = 0; i < 8; i++) xa[i] = fmaxf(sa[i], sb[i]);
#pragma unroll
    for (int k = 1; k < 4; k++)
#pragma unroll
        for (int i = 0; i < 8; i++) xa[i] = fmaxf(xa[i], fmaxf(sa[8 * k + i], sb[8 * k + i]));
    x0 = fmaxf(fmaxf(xa[0], xa[1]), fmaxf(xa[4], xa[5]));
    x1 = fmaxf(fmaxf(xa[2], xa[3]), fmaxf(xa[6], xa[7]));
    x0 = fmaxf(x0, __shfl_xor_sync(0xffffffffu, x0, 1));
    x1 = fmaxf(x1, __shfl_xor_sync(0xffffffffu, x1, 1));
    x0 = fmaxf(x0, __shfl_xor_sync(0xffffffffu, x0, 2));
    x1 = fmaxf(x1, __shfl_xor_sync(0xffffffffu, x1, 2));
}
__device__ __forceinline__ void inv_row_sums(float l0, float l1, float& i0, float& i1) {
    l0 += __shfl_xor_sync(0xffffffffu, l0, 1);
    l1 += __shfl_xor_sync(0xffffffffu, l1, 1);
    l0 += __shfl_xor_sync(0xffffffffu, l0, 2);
    l1 += __shfl_xor_sync(0xffffffffu, l1, 2);
    i0 = rcp(l0);
    i1 = rcp(l1);
}

__device__ __forceinline__ uint32_t ld_epoch() {
    uint32_t e;
    asm volatile("ld.relaxed.gpu.global.u32 %0, [%1];" : "=r"(e) : "l"(&g_epoch) : "memory");
    return e;
}
__device__ __forceinline__ float silu_bf16(unsigned short c) {
    const float cv = bf_lo(c);
    return round_bf16(cv * rcp(1.f + ex2(-1.4426950408889634f * cv)));
}
__device__ __forceinline__ void st_mod(int idx, float v, uint32_t tag) {
    asm volatile("st.relaxed.gpu.global.u32 [%0], %1;" ::"l"(g_mod + idx), "r"(__float_as_uint(round_bf16(v)) | tag)
                 : "memory");
}
__device__ __forceinline__ void mod_block(const uint4 (&w)[5], const float (&sc)[5], int blk, uint32_t red, int warp,
                                          int lane, uint32_t tag) {
    float acc[8];
#pragma unroll
    for (int e = 0; e < 8; e++) acc[e] = 0.f;
#pragma unroll
    for (int i = 0; i < 5; i++) {
        acc[0] = fmaf(sc[i], bf_lo(w[i].x), acc[0]);
        acc[1] = fmaf(sc[i], bf_hi(w[i].x), acc[1]);
        acc[2] = fmaf(sc[i], bf_lo(w[i].y), acc[2]);
        acc[3] = fmaf(sc[i], bf_hi(w[i].y), acc[3]);
        acc[4] = fmaf(sc[i], bf_lo(w[i].z), acc[4]);
        acc[5] = fmaf(sc[i], bf_hi(w[i].z), acc[5]);
        acc[6] = fmaf(sc[i], bf_lo(w[i].w), acc[6]);
        acc[7] = fmaf(sc[i], bf_hi(w[i].w), acc[7]);
    }
#pragma unroll
    for (int o = 2; o < 32; o <<= 1)
#pragma unroll
        for (int e = 0; e < 8; e++) acc[e] += __shfl_xor_sync(0xffffffffu, acc[e], o);
    if (lane < 2) {
#pragma unroll
        for (int e = 0; e < 8; e++) sts32f(red + (warp * 16 + lane * 8 + e) * 4, acc[e]);
    }
    bar_sync(3, 256);
    if (warp == 0 && lane < 16) {
        float s = 0.f;
#pragma unroll
        for (int w8 = 0; w8 < 8; w8++) s += lds32f(red + (w8 * 16 + lane) * 4);
        if (blk < 72) st_mod(blk * 16 + lane, s, tag);
    }
}

__global__ void __cluster_dims__(2, 1, 1) __launch_bounds__(384, 1)
    fused_block_kernel(const __grid_constant__ Maps maps, const __nv_bfloat16* __restrict__ x,
                       const __nv_bfloat16* __restrict__ cvec, const __nv_bfloat16* __restrict__ wmod,
                       __nv_bfloat16* __restrict__ out) {
    extern __shared__ uint8_t smem_raw[];
    uint32_t sbase = (smem_u32(smem_raw) + 1023u) & ~1023u;
    asm volatile("" : "+r"(sbase));
    const int b = blockIdx.x;
    const int rank = b & 1;
    const int mt = ((b >> 1) & 7) * 2 + rank;
    const int g = b >> 4;
    const int warp = __shfl_sync(0xffffffffu, threadIdx.x >> 5, 0);
    const int lane = threadIdx.x & 31;

    if (warp >= 8) {
        asm volatile("setmaxnreg.dec.sync.aligned.u32 24;");
        if (warp == 8 && lane == 0) {
#pragma unroll
            for (int i = 0; i < 8; i++) {
                mbar_init(sbase + OFF_FULL + i * 8, 1);
                mbar_init(sbase + OFF_EMPTY + i * 8, 4);
            }
            asm volatile("fence.mbarrier_init.release.cluster;" ::: "memory");
            asm volatile("barrier.cluster.arrive.relaxed;\nbarrier.cluster.wait;" ::: "memory");
            uint32_t slot = 0, phase = 1;
            const uint32_t dst0 = sbase + rank * BOX_BYTES;
            auto acquire = [&](uint32_t bytes) {
                mbar_wait(sbase + OFF_EMPTY + slot * 8, phase);
                mbar_expect_tx(sbase + OFF_FULL + slot * 8, bytes);
            };
            auto adv8 = [&]() {
                if (++slot == 8) {
                    slot = 0;
                    phase ^= 1;
                }
            };
#pragma unroll 1
            for (int hq = 0; hq < 4; hq++) {
                const int col = (g * 4 + ((hq + 1) & 3)) * 128 + rank * 64;
#pragma unroll 1
                for (int kc = 0; kc < 9; kc++) {
                    acquire(SLOT_BYTES);
                    tma_mc(dst0 + slot * SLOT_BYTES, &maps.wq, col, kc * 64, sbase + OFF_FULL + slot * 8);
                    adv8();
                }
            }
            const int row0 = g * 4 * 2048;
#pragma unroll 1
            for (int n = 0; n < 128; n++) {
                if (n < 4) mbar_wait(sbase + OFF_EMPTY + (slot + 1) * 8, phase);
                acquire(2 * SLOT_BYTES);
                const uint32_t bar = sbase + OFF_FULL + slot * 8;
                const CUtensorMap* m = (n & 1) ? &maps.v : &maps.k;
                tma_mc(dst0 + slot * SLOT_BYTES, m, rank * 64, row0 + (n >> 1) * 128, bar);
                tma_mc(dst0 + (slot + 1) * SLOT_BYTES, m, rank * 64, row0 + (n >> 1) * 128 + 64, bar);
                adv8();
                adv8();
            }
#pragma unroll 1
            for (int p = 0; p < 4; p++)
#pragma unroll 1
                for (int kc = 0; kc < 8; kc++) {
                    acquire(SLOT_BYTES);
                    tma_mc(dst0 + slot * SLOT_BYTES, &maps.wo, p * 128 + rank * 64, g * 512 + kc * 64,
                           sbase + OFF_FULL + slot * 8);
                    adv8();
                }
#pragma unroll 1
            for (int kc = 0; kc < 4; kc++) {
                acquire(SLOT_BYTES);
                tma_mc(dst0 + slot * SLOT_BYTES, &maps.wo, 512, g * 512 + kc * 128 + rank * 64,
                       sbase + OFF_FULL + slot * 8);
                adv8();
            }
            const CUtensorMap* mg = rank ? &maps.wu : &maps.wg;
#pragma unroll 1
            for (int ch = 0; ch < 9; ch++)
#pragma unroll 1
                for (int kc = 0; kc < 9; kc++) {
                    acquire(SLOT_BYTES);
                    tma_mc(dst0 + slot * SLOT_BYTES, mg, g * 576 + ch * 64, kc * 64, sbase + OFF_FULL + slot * 8);
                    adv8();
                }
#pragma unroll 1
            for (int p = 0; p < 4; p++)
#pragma unroll 1
                for (int kc = 2; kc < 11; kc++) {
                    acquire(SLOT_BYTES);
                    tma_mc(dst0 + slot * SLOT_BYTES, &maps.wd, p * 128 + rank * 64, g * 576 + (kc < 9 ? kc : kc - 9) * 64,
                           sbase + OFF_FULL + slot * 8);
                    adv8();
                }
#pragma unroll 1
            for (int i = 0; i < 5; i++) {
                acquire(i < 4 ? SLOT_BYTES : BOX_BYTES);
                const int kc = 2 * i + rank + 2;
                if (i < 4 || rank == 0)
                    tma_mc(dst0 + slot * SLOT_BYTES, &maps.wd, 512, g * 576 + (kc < 9 ? kc : kc - 9) * 64,
                           sbase + OFF_FULL + slot * 8);
                adv8();
            }
        } else if (warp == 9 || warp == 10) {
            asm volatile("barrier.cluster.arrive.relaxed.aligned;" ::: "memory");
            const uint32_t tag = (ld_epoch() + 1) & 0xffffu;
            bar_sync(4, 320);
            const int blk = warp == 9 ? 72 + b : 200 + b;
            if (blk < 216) {
                float acc[8];
#pragma unroll
                for (int e = 0; e < 8; e++) acc[e] = 0.f;
                const uint4* wp = reinterpret_cast<const uint4*>(wmod + (size_t)(lane >> 1) * (6 * DM) + blk * 16) + (lane & 1);
                const unsigned short* cp = reinterpret_cast<const unsigned short*>(cvec) + (lane >> 1);
#pragma unroll 1
                for (int i = 0; i < 36; i++) {
                    const uint4 w = __ldg(wp + (size_t)i * (16 * 6 * DM / 8));
                    const float sc = silu_bf16(__ldg(cp + i * 16));
                    acc[0] = fmaf(sc, bf_lo(w.x), acc[0]);
                    acc[1] = fmaf(sc, bf_hi(w.x), acc[1]);
                    acc[2] = fmaf(sc, bf_lo(w.y), acc[2]);
                    acc[3] = fmaf(sc, bf_hi(w.y), acc[3]);
                    acc[4] = fmaf(sc, bf_lo(w.z), acc[4]);
                    acc[5] = fmaf(sc, bf_hi(w.z), acc[5]);
                    acc[6] = fmaf(sc, bf_lo(w.w), acc[6]);
                    acc[7] = fmaf(sc, bf_hi(w.w), acc[7]);
                }
#pragma unroll
                for (int o = 2; o < 32; o <<= 1)
#pragma unroll
                    for (int e = 0; e < 8; e++) acc[e] += __shfl_xor_sync(0xffffffffu, acc[e], o);
                if (lane < 2) {
#pragma unroll
                    for (int e = 0; e < 8; e++) st_mod(blk * 16 + lane * 8 + e, acc[e], tag);
                }
            }
        }
    } else {
        asm volatile("setmaxnreg.inc.sync.aligned.u32 240;");
        const int wg = warp >> 2;
        const int tid = threadIdx.x;
        Ctx cx;
        cx.sbase = sbase;
        cx.rel_cta = (lane == 0 && (warp & 3) < 2) ? (warp & 3) : 2;
        const uint32_t red = sbase + OFF_RED;
        const int own = mt * 8 + g;
        const int wown = mt * 8 + warp;
        PROF(0);
        PROFG(30);
        const uint32_t epoch = ld_epoch();
        {
            uint4 w1[5];
            unsigned short cu[5];
            const int half = tid & 1, r0 = tid >> 1;
            if (b < 72) {
#pragma unroll
                for (int i = 0; i < 5; i++) {
                    const int row = min(r0 + 128 * i, DM - 1);
                    cu[i] = __ldg(reinterpret_cast<const unsigned short*>(cvec) + row);
                    w1[i] = __ldg(reinterpret_cast<const uint4*>(wmod + (size_t)row * (6 * DM) + half * 8) + b * 2);
                }
            }
            if (warp == 0) {
                if (lane == 0) {
                    mbar_init(sbase + OFF_XBAR, 1);
                    asm volatile("fence.mbarrier_init.release.cluster;\nfence.proxy.async.shared::cta;" ::: "memory");
                    mbar_expect_tx(sbase + OFF_XBAR, 16 * DM * 2);
                }
                __syncwarp();
                if (lane < 16)
                    asm volatile(
                        "cp.async.bulk.shared::cluster.global.mbarrier::complete_tx::bytes [%0], [%1], %2, [%3];" ::"r"(
                            sbase + 8 * SLOT_BYTES + lane * XROW_STRIDE),
                        "l"(x + (size_t)(own * 16 + lane) * DM), "r"(DM * 2), "r"(sbase + OFF_XBAR)
                        : "memory");
                __syncwarp();
            }
            asm volatile("barrier.cluster.arrive.relaxed.aligned;" ::: "memory");
            if (b < 72) {
                float sc[5];
#pragma unroll
                for (int i = 0; i < 5; i++) sc[i] = (r0 + 128 * i < DM) ? silu_bf16(cu[i]) : 0.f;
                mod_block(w1, sc, b, red + 1024, warp, lane, (epoch + 1) & 0xffffu);
            } else {
                bar_sync(3, 256);
            }
            asm volatile("" ::"r"(epoch) : "memory");
            bar_arrive(4, 320);
        }

        Ring ring{0u, 0u};
        int stage = 0;
        asm volatile("" : "+r"(stage));
#pragma unroll 1
        for (;; stage++) {
            int tid, lane;
            asm volatile("mov.u32 %0, %%tid.x;" : "=r"(tid));
            lane = tid & 31;
            {
                float v[36], md[3][18];
                float4* x2buf = g_x2 + (size_t)b * 9 * 256 + tid;
                const uint32_t tag = (epoch + 1) & 0xffffu;
                const uint32_t* modp = g_mod + warp * 8 + (lane & 3) * 2;
                if (stage == 0) {
#pragma unroll
                    for (int i = 0; i < 18; i++) md[1][i] = md[2][i] = 0.f;
                    mbar_wait(sbase + OFF_XBAR, 0);
                    const uint32_t src = sbase + 8 * SLOT_BYTES + (lane >> 2) * XROW_STRIDE + warp * 16 + (lane & 3) * 4;
#pragma unroll
                    for (int j = 0; j < 9; j++) {
                        const uint32_t u0 = __float_as_uint(lds32f(src + j * 128));
                        const uint32_t u1 = __float_as_uint(lds32f(src + j * 128 + 8 * XROW_STRIDE));
                        v[4 * j] = bf_lo(u0);
                        v[4 * j + 1] = bf_hi(u0);
                        v[4 * j + 2] = bf_lo(u1);
                        v[4 * j + 3] = bf_hi(u1);
                    }
                } else {
                    const unsigned long long* psrc = g_part + (size_t)own * 8 * 72 * 32 + tid;
                    sum_partials(v, psrc, stage & 1);
                    PROF(stage == 1 ? 8 : 15);
                    float4 xr[9];
#pragma unroll
                    for (int j = 0; j < 9; j++) xr[j] = __ldcg(x2buf + j * 256);
                    sum_tail(v, md, psrc, stage & 1, modp + (stage * 3 - 1) * DM, modp + 3 * DM, tag);
                    const float gs = stage == 1 ? 1.f : 0.5f;
#pragma unroll
                    for (int j = 0; j < 9; j++) {
                        const float g0 = md[0][2 * j] * gs, g1 = md[0][2 * j + 1] * gs;
                        v[4 * j] = fmaf(g0, v[4 * j], xr[j].x);
                        v[4 * j + 1] = fmaf(g1, v[4 * j + 1], xr[j].y);
                        v[4 * j + 2] = fmaf(g0, v[4 * j + 2], xr[j].z);
                        v[4 * j + 3] = fmaf(g1, v[4 * j + 3], xr[j].w);
                    }
                    if (stage == 2) {
                        __nv_bfloat16* dst = out + (size_t)(own * 16 + (lane >> 2)) * DM + warp * 8 + (lane & 3) * 2;
#pragma unroll
                        for (int j = 0; j < 9; j++) {
                            *reinterpret_cast<uint32_t*>(dst + j * 64) = pack_bf16(v[4 * j], v[4 * j + 1]);
                            *reinterpret_cast<uint32_t*>(dst + j * 64 + 8 * DM) = pack_bf16(v[4 * j + 2], v[4 * j + 3]);
                        }
                        break;
                    }
                }
                PROF(stage == 0 ? 1 : 9);
                float keep[36];
#pragma unroll
                for (int i = 0; i < 36; i++) keep[i] = v[i];
                layernorm_rows(v, red, warp, lane);
                if (stage == 0) load_mod0(md, modp, tag);
                PROF(stage == 0 ? 2 : 10);
                modulate_store(v, md[1], md[2], g_h[stage] + (size_t)own * 36 * 32, warp, lane);
                __syncwarp();
                if (lane == 0) signal_cnt(stage * 128 + own);
#pragma unroll
                for (int j = 0; j < 9; j++)
                    __stcg(x2buf + j * 256, make_float4(keep[4 * j], keep[4 * j + 1], keep[4 * j + 2], keep[4 * j + 3]));
                if (stage == 0) asm volatile("barrier.cluster.wait.aligned;" ::: "memory");
            }

            const uint32_t spill = sbase + 8 * SLOT_BYTES + wg * 3 * SLOT_BYTES + (tid & 127) * 16;
            uint32_t a[144];
            PROF(stage == 0 ? 3 : 11);
            wait_cnt(stage * 128 + wown, (epoch + 1) * 8);
            PROF(stage == 0 ? 4 : 12);
            if (stage == 1) PROFG(25);
            load_frags(a, g_h[stage] + (size_t)wown * 36 * 32 + lane);
            uint4* hhbuf = g_hh + (size_t)b * 8 * 256 + tid;
            float d[64];
            if (wg == 1) bar_sync(5, 256);
#pragma unroll 1
            for (int ch = 0;; ch++) {
                gemm_n128(d, a, cx, ring, true, (ch == 0 && wg == 0) ? 5 : 0);
                if (stage == 0) {
#pragma unroll
                    for (int i = 0; i < 64; i++) d[i] *= SM_SCALE;
                    if (ch == 3) break;
#pragma unroll
                    for (int v = 0; v < 8; v++)
                        sts128(spill + (ch * 8 + v) * 2048, pack_bf16(d[8 * v], d[8 * v + 1]),
                               pack_bf16(d[8 * v + 2], d[8 * v + 3]), pack_bf16(d[8 * v + 4], d[8 * v + 5]),
                               pack_bf16(d[8 * v + 6], d[8 * v + 7]));
                } else {
#pragma unroll
                    for (int i = 0; i < 32; i++) {
                        const float gv = d[i], gu = gv * d[32 + i];
                        const float z = gv * fmaf(gv * gv, 0.7978845608028654f * 0.044715f, 0.7978845608028654f);
                        d[i] = fmaf(gu, tanh_fast(z), gu);
                    }
                    if (ch == 8) break;
#pragma unroll
                    for (int v = 0; v < 4; v++) {
                        const uint4 h4 = make_uint4(pack_bf16(d[8 * v], d[8 * v + 1]), pack_bf16(d[8 * v + 2], d[8 * v + 3]),
                                                    pack_bf16(d[8 * v + 4], d[8 * v + 5]), pack_bf16(d[8 * v + 6], d[8 * v + 7]));
                        if (ch < 2)
                            __stcg(hhbuf + (ch * 4 + v) * 256, h4);
                        else
                            sts128(spill + ((ch - 2) * 4 + v) * 2048, h4.x, h4.y, h4.z, h4.w);
                    }
                }
            }
            if (stage == 0) {
                uint32_t q[32];
#pragma unroll
                for (int i = 0; i < 32; i++) q[i] = pack_bf16(d[2 * i], d[2 * i + 1]);
                PROF(5);
                PROFG(23);
                {
                    float o[64], sa[32], sb[32];
                    uint32_t pa[16], pb[16];
#pragma unroll
                    for (int i = 0; i < 64; i++) o[i] = 0.f;
                    float n0 = 0.f, n1 = 0.f, l0 = 1.f, l1 = 1.f;
                    bool shifted = false;
                    const uint64_t dbase = desc_of(sbase);
                    const uint64_t dbk = dbase - (511u << 16);
                    const int my_bar = 1 + wg, other_bar = 2 - wg;

                    auto softmax_a = [&](bool first, float& s0, float& s1) {
                        if (first) {
                            shifted = false;
                            n0 = n1 = 0.f;
                            l0 = l1 = 0.f;
                        }
                        if (shifted)
                            exp_step<true>(sa, pa, n0, n1, s0, s1);
                        else
                            exp_step<false>(sa, pa, n0, n1, s0, s1);
                    };
                    auto softmax_b = [&](bool first, float s0, float s1) {
                        float u0, u1;
                        if (shifted)
                            exp_step<true>(sb, pb, n0, n1, u0, u1);
                        else
                            exp_step<false>(sb, pb, n0, n1, u0, u1);
                        s0 += u0;
                        s1 += u1;
                        bool bad = !(fmaxf(s0, s1) <= SM_HI);
                        if (first) {
                            float r0 = s0 + __shfl_xor_sync(0xffffffffu, s0, 1), r1 = s1 + __shfl_xor_sync(0xffffffffu, s1, 1);
                            r0 += __shfl_xor_sync(0xffffffffu, r0, 2);
                            r1 += __shfl_xor_sync(0xffffffffu, r1, 2);
                            bad = bad || !(fminf(r0, r1) >= SM_LO);
                        }
                        if (__any_sync(0xffffffffu, bad)) {
                            float x0, x1;
                            row_max(sa, sb, x0, x1);
                            x0 = -x0;
                            x1 = -x1;
                            if (!first) {
                                x0 = fminf(x0, n0);
                                x1 = fminf(x1, n1);
                                const float al0 = ex2(x0 - n0), al1 = ex2(x1 - n1);
                                l0 *= al0;
                                l1 *= al1;
#pragma unroll
                                for (int i = 0; i < 16; i++) {
                                    o[4 * i] *= al0;
                                    o[4 * i + 1] *= al0;
                                    o[4 * i + 2] *= al1;
                                    o[4 * i + 3] *= al1;
                                }
                            }
                            n0 = x0;
                            n1 = x1;
                            shifted = true;
                            exp_step<true>(sa, pa, n0, n1, s0, s1);
                            exp_step<true>(sb, pb, n0, n1, u0, u1);
                            s0 += u0;
                            s1 += u1;
                        }
                        l0 += s0;
                        l1 += s1;
                    };

                    cx.wait_full(4, 0);
                    if (wg == 1) bar_sync(my_bar, 256);
                    wg_fence();
                    qk_step(sa, q, dbk + 4 * 1024);
                    qk_step(sb, q, dbk + 5 * 1024);
                    wg_commit();
                    bar_arrive(other_bar, 256);
                    wg_wait<0>();
                    pin(sa);
                    pin(sb);
                    cx.release(4);
                    cx.wait_full(6, 0);
                    cx.wait_full(0, 1);
                    {
                        float s0, s1;
                        softmax_a(true, s0, s1);
                        softmax_b(true, s0, s1);
                    }
                    uint32_t klo = (uint32_t)dbk, vlo = (uint32_t)dbase + 6 * 1024;
                    const uint32_t dhi = (uint32_t)(dbase >> 32);
#pragma unroll 1
                    for (int t = 1; t < 64; t++) {
                        const int j = t & 15;
                        const uint32_t ks = 4 - 4 * (t & 1), vs = 2 + 4 * (t & 1);
                        const uint64_t dk = ((uint64_t)dhi << 32) | klo, dv = ((uint64_t)dhi << 32) | vlo;
                        TL(0);
                        bar_sync(my_bar, 256);
                        TL(2);
                        wg_fence();
                        pv_step(o, pa, dv, j != 1);
                        qk_step(sa, q, dk);
                        wg_commit();
                        qk_step(sb, q, dk + 1024);
                        pv_step(o, pb, dv + 1024, 1);
                        wg_commit();
                        bar_arrive(other_bar, 256);
                        klo ^= 4096;
                        vlo ^= 4096;
                        asm volatile("" : "+r"(klo), "+r"(vlo));
                        TL(3);
                        wg_wait<1>();
                        pin(sa);
                        pin(pa);
                        TL(4);
                        const float lp0 = l0, lp1 = l1;
                        float s0, s1;
                        softmax_a(j == 0, s0, s1);
                        TL(5);
                        wg_wait<0>();
                        pin(o);
                        pin(sb);
                        pin(pb);
                        TL(6);
                        cx.release(vs);
                        cx.release(ks);
                        if (j == 0) {
                            float i0, i1;
                            inv_row_sums(lp0, lp1, i0, i1);
                            const uint32_t dst = spill + ((t >> 4) - 1) * 16384;
#pragma unroll
                            for (int v = 0; v < 8; v++)
                                sts128(dst + v * 2048, pack_bf16(o[8 * v] * i0, o[8 * v + 1] * i0),
                                       pack_bf16(o[8 * v + 2] * i1, o[8 * v + 3] * i1),
                                       pack_bf16(o[8 * v + 4] * i0, o[8 * v + 5] * i0),
                                       pack_bf16(o[8 * v + 6] * i1, o[8 * v + 7] * i1));
                        }
                        const uint32_t bv = sbase + OFF_FULL + (8 - vs) * 8, pv = ((38 + 4 * t) >> 3) & 1;
                        const uint32_t bk = t < 63 ? sbase + OFF_FULL + (4 - ks) * 8 : bv,
                                       pk = t < 63 ? ((40 + 4 * t) >> 3) & 1 : pv;
                        const bool okv = mbar_try(bv, pv), okk = mbar_try(bk, pk);
                        TL(1);
                        softmax_b(j == 0, s0, s1);
                        if (!(okv && okk) || j == 15) {
                            mbar_wait(bv, pv);
                            mbar_wait(bk, pk);
                            if (j == 15 && t < 63) {
                                const uint32_t src = spill + (t >> 4) * 16384;
#pragma unroll
                                for (int v = 0; v < 8; v++)
                                    lds128(src + v * 2048, q[4 * v], q[4 * v + 1], q[4 * v + 2], q[4 * v + 3]);
                            }
                        }
                        TL(7);
                    }
                    bar_sync(my_bar, 256);
                    wg_fence();
                    pv_step(o, pa, dbase + 2 * 1024, 1);
                    pv_step(o, pb, dbase + 3 * 1024, 1);
                    wg_commit();
                    if (wg == 0) bar_arrive(other_bar, 256);
                    float i0, i1;
                    inv_row_sums(l0, l1, i0, i1);
                    wg_wait<0>();
                    pin(o);
                    cx.release(2);
#pragma unroll
                    for (int i = 0; i < 16; i++) {
                        a[96 + 2 * i] = pack_bf16(o[4 * i] * i0, o[4 * i + 1] * i0);
                        a[96 + 2 * i + 1] = pack_bf16(o[4 * i + 2] * i1, o[4 * i + 3] * i1);
                    }
#pragma unroll
                    for (int i = 128; i < 144; i++) a[i] = 0;
                }
                ring.slot = 4;
                ring.phase = 0;
                PROF(6);
                PROFG(24);
            } else {
#pragma unroll
                for (int v = 0; v < 8; v++) {
                    const uint4 t = __ldcg(hhbuf + v * 256);
                    a[112 + 4 * v] = t.x;
                    a[113 + 4 * v] = t.y;
                    a[114 + 4 * v] = t.z;
                    a[115 + 4 * v] = t.w;
                }
#pragma unroll
                for (int i = 0; i < 16; i++) a[96 + i] = pack_bf16(d[2 * i], d[2 * i + 1]);
                PROF(13);
            }
#pragma unroll
            for (int v = 0; v < 24; v++) lds128(spill + v * 2048, a[4 * v], a[4 * v + 1], a[4 * v + 2], a[4 * v + 3]);

            proj_partials(a, cx, ring, stage != 0, g_part + ((size_t)wown * 8 + g) * 72 * 32 + lane, (stage + 1) & 1);
            PROF(stage == 0 ? 7 : 14);
            if (stage == 1) {
                PROFG(26);
                asm volatile("barrier.cluster.arrive.relaxed.aligned;" ::: "memory");
            }
        }
        PROF(16);
        PROFG(31);
        if (b == 0) {
            bar_sync(3, 256);
            if (tid == 0) g_epoch = epoch + 1;
        }
        asm volatile("barrier.cluster.wait.aligned;" ::: "memory");
    }
}

typedef CUresult (*EncodeFn)(CUtensorMap*, CUtensorMapDataType, cuuint32_t, void*, const cuuint64_t*, const cuuint64_t*,
                             const cuuint32_t*, const cuuint32_t*, CUtensorMapInterleave, CUtensorMapSwizzle,
                             CUtensorMapL2promotion, CUtensorMapFloatOOBfill);

void make_map(EncodeFn enc, CUtensorMap* m, const void* ptr, uint64_t rows, uint64_t cols) {
    cuuint64_t gdim[2] = {cols, rows};
    cuuint64_t gstr[1] = {cols * 2};
    cuuint32_t box[2] = {64, 64};
    cuuint32_t estr[2] = {1, 1};
    enc(m, CU_TENSOR_MAP_DATA_TYPE_BFLOAT16, 2, const_cast<void*>(ptr), gdim, gstr, box, estr,
        CU_TENSOR_MAP_INTERLEAVE_NONE, CU_TENSOR_MAP_SWIZZLE_128B, CU_TENSOR_MAP_L2_PROMOTION_L2_128B,
        CU_TENSOR_MAP_FLOAT_OOB_FILL_NONE);
}

}

extern "C" void kernel_launch(void* const* d_in, const int* in_sizes, int n_in, void* d_out, int out_size) {
    (void)in_sizes;
    (void)n_in;
    (void)out_size;
    void* fn = nullptr;
    cudaDriverEntryPointQueryResult qr;
    cudaGetDriverEntryPoint("cuTensorMapEncodeTiled", &fn, cudaEnableDefault, &qr);
    EncodeFn enc = (EncodeFn)fn;
    Maps maps;
    make_map(enc, &maps.k, d_in[1], 32 * 2048, 128);
    make_map(enc, &maps.v, d_in[2], 32 * 2048, 128);
    make_map(enc, &maps.wq, d_in[3], 576, 4096);
    make_map(enc, &maps.wo, d_in[4], 4096, 576);
    make_map(enc, &maps.wg, d_in[6], 576, 4608);
    make_map(enc, &maps.wu, d_in[7], 576, 4608);
    make_map(enc, &maps.wd, d_in[8], 4608, 576);
    cudaFuncSetAttribute(fused_block_kernel, cudaFuncAttributeMaxDynamicSharedMemorySize, SMEM_BYTES);
    fused_block_kernel<<<128, 384, SMEM_BYTES>>>(maps, (const __nv_bfloat16*)d_in[0], (const __nv_bfloat16*)d_in[9],
                                                 (const __nv_bfloat16*)d_in[10], (__nv_bfloat16*)d_out);
}
```

```cpp
#include <cuda_runtime.h>
#include <cuda_bf16.h>
#include <cuda.h>
#include <stdint.h>

namespace {

constexpr int DM = 576;
constexpr int SLOT_BYTES = 16384;
constexpr int BOX_BYTES = 8192;
constexpr int NUNITS = 14;
constexpr int SMEM_TAIL = NUNITS * SLOT_BYTES;
constexpr int SMEM_BYTES = SMEM_TAIL + 2048 + 1024;
constexpr int OFF_FULL = SMEM_TAIL;
constexpr int OFF_EMPTY = SMEM_TAIL + 64;
constexpr int OFF_RED = SMEM_TAIL + 128;

constexpr int KV_AHEAD = 16;
constexpr int OFF_XBAR = SMEM_TAIL + 1792;
constexpr int XROW_STRIDE = DM * 2 + 16;

__device__ unsigned g_epoch;
__device__ __align__(16) uint32_t g_mod[6 * DM];
__device__ uint4 g_h[2][128 * 36 * 32];
__device__ unsigned long long g_part[128 * 8 * 72 * 32];
__device__ float4 g_x2[128 * 9 * 256];
__device__ uint4 g_hh[128 * 8 * 256];
__device__ unsigned g_cnt[256 * 32];

#define TL(i)
#define PROFR(i)
#define PROF(i)
#define PROFG(i)

struct Maps {
    CUtensorMap k, v, wq, wo, wg, wu, wd;
};

__device__ __forceinline__ uint32_t smem_u32(const void* p) { return (uint32_t)__cvta_generic_to_shared(p); }
__device__ __forceinline__ void mbar_init(uint32_t a, uint32_t c) {
    asm volatile("mbarrier.init.shared::cta.b64 [%0], %1;" ::"r"(a), "r"(c) : "memory");
}
__device__ __forceinline__ void mbar_expect_tx(uint32_t a, uint32_t bytes) {
    asm volatile("mbarrier.arrive.expect_tx.shared::cta.b64 _, [%0], %1;" ::"r"(a), "r"(bytes) : "memory");
}
__device__ __forceinline__ bool mbar_try(uint32_t a, uint32_t ph) {
    uint32_t ok;
    asm volatile(
        "{\n.reg .pred p;\nmbarrier.try_wait.parity.shared::cta.b64 p, [%1], %2;\nselp.u32 %0, 1, 0, p;\n}"
        : "=r"(ok)
        : "r"(a), "r"(ph)
        : "memory");
    return ok != 0;
}
__device__ __forceinline__ uint32_t clk32() {
    uint32_t c;
    asm volatile("mov.u32 %0, %%clock;" : "=r"(c));
    return c;
}
constexpr uint32_t WAIT_LIMIT = 1u << 30;
__device__ __forceinline__ void mbar_wait(uint32_t a, uint32_t ph) {
    if (mbar_try(a, ph)) return;
    uint32_t t0 = clk32();
    while (!mbar_try(a, ph)) {
        if (clk32() - t0 > WAIT_LIMIT) break;
    }
}
__device__ __forceinline__ void mbar_arrive_cluster(uint32_t a, uint32_t cta) {
    asm volatile(
        "{\n.reg .b32 ra;\nmapa.shared::cluster.u32 ra, %0, %1;\nmbarrier.arrive.shared::cluster.b64 _, [ra];\n}" ::"r"(a),
        "r"(cta)
        : "memory");
}
__device__ __forceinline__ void tma_mc(uint32_t dst, const CUtensorMap* m, int c0, int c1, uint32_t bar) {
    asm volatile(
        "cp.async.bulk.tensor.2d.shared::cluster.global.mbarrier::complete_tx::bytes.multicast::cluster"
        " [%0], [%1, {%3, %4}], [%2], %5;" ::"r"(dst),
        "l"(m), "r"(bar), "r"(c0), "r"(c1), "h"((uint16_t)3)
        : "memory");
}
__device__ __forceinline__ void l2_prefetch(const void* p, uint32_t bytes) {
    asm volatile("cp.async.bulk.prefetch.L2.global [%0], %1;" ::"l"(p), "r"(bytes) : "memory");
}
__device__ __forceinline__ void bar_sync(int id, int n) { asm volatile("bar.sync %0, %1;" ::"r"(id), "r"(n) : "memory"); }
__device__ __forceinline__ void bar_arrive(int id, int n) {
    asm volatile("bar.arrive %0, %1;" ::"r"(id), "r"(n) : "memory");
}
__device__ __forceinline__ void wg_fence() { asm volatile("wgmma.fence.sync.aligned;" ::: "memory"); }
__device__ __forceinline__ void wg_commit() { asm volatile("wgmma.commit_group.sync.aligned;" ::: "memory"); }
template <int N>
__device__ __forceinline__ void wg_wait() {
    asm volatile("wgmma.wait_group.sync.aligned %0;" ::"n"(N) : "memory");
}
template <int N>
__device__ __forceinline__ void pin(float (&d)[N]) {
#pragma unroll
    for (int i = 0; i < N; i++) asm volatile("" : "+f"(d[i])::"memory");
}
template <int N>
__device__ __forceinline__ void pin(uint32_t (&d)[N]) {
#pragma unroll
    for (int i = 0; i < N; i++) asm volatile("" : "+r"(d[i])::"memory");
}
__device__ __forceinline__ uint32_t pack_bf16(float lo, float hi) {
    uint32_t r;
    asm("cvt.rn.bf16x2.f32 %0, %1, %2;" : "=r"(r) : "f"(hi), "f"(lo));
    return r;
}
__device__ __forceinline__ float bf_lo(uint32_t v) { return __uint_as_float(v << 16); }
__device__ __forceinline__ float bf_hi(uint32_t v) { return __uint_as_float(v & 0xffff0000u); }
__device__ __forceinline__ float round_bf16(float v) { return __bfloat162float(__float2bfloat16_rn(v)); }
__device__ __forceinline__ float ex2(float x) {
    float y;
    asm("ex2.approx.ftz.f32 %0, %1;" : "=f"(y) : "f"(x));
    return y;
}
__device__ __forceinline__ float rcp(float x) {
    float y;
    asm("rcp.approx.ftz.f32 %0, %1;" : "=f"(y) : "f"(x));
    return y;
}
__device__ __forceinline__ float tanh_fast(float x) {
    float y;
    asm("tanh.approx.f32 %0, %1;" : "=f"(y) : "f"(x));
    return y;
}
__device__ __forceinline__ void sts128(uint32_t a, uint32_t x, uint32_t y, uint32_t z, uint32_t w) {
    asm volatile("st.shared.v4.b32 [%0], {%1,%2,%3,%4};" ::"r"(a), "r"(x), "r"(y), "r"(z), "r"(w) : "memory");
}
__device__ __forceinline__ void lds128(uint32_t a, uint32_t& x, uint32_t& y, uint32_t& z, uint32_t& w) {
    asm volatile("ld.shared.v4.b32 {%0,%1,%2,%3}, [%4];" : "=r"(x), "=r"(y), "=r"(z), "=r"(w) : "r"(a) : "memory");
}
__device__ __forceinline__ void sts32f(uint32_t a, float v) {
    asm volatile("st.shared.f32 [%0], %1;" ::"r"(a), "f"(v) : "memory");
}
__device__ __forceinline__ float lds32f(uint32_t a) {
    float v;
    asm volatile("ld.shared.f32 %0, [%1];" : "=f"(v) : "r"(a) : "memory");
    return v;
}
__device__ __forceinline__ void signal_cnt(int idx) {
    asm volatile("red.release.gpu.global.add.u32 [%0], 1;" ::"l"(&g_cnt[idx * 32]) : "memory");
}
__device__ __forceinline__ void wait_cnt(int idx, unsigned target) {
    if ((threadIdx.x & 31) == 0) {
        uint32_t t0 = clk32();
        while (true) {
            unsigned v;
            asm volatile("ld.acquire.gpu.global.u32 %0, [%1];" : "=r"(v) : "l"(&g_cnt[idx * 32]) : "memory");
            if ((int)(v - target) >= 0) break;
            if (clk32() - t0 > WAIT_LIMIT) break;
        }
    }
    __syncwarp();
}

#define F8(d, b) \
    "+f"(d[b]), "+f"(d[b + 1]), "+f"(d[b + 2]), "+f"(d[b + 3]), "+f"(d[b + 4]), "+f"(d[b + 5]), "+f"(d[b + 6]), "+f"(d[b + 7])

template <int TB>
__device__ __forceinline__ void wgmma_n128(float (&d)[64], uint32_t a0, uint32_t a1, uint32_t a2, uint32_t a3,
                                           uint64_t db, int sc) {
    asm volatile(
        "{\n.reg .pred p;\nsetp.ne.b32 p, %69, 0;\n"
        "wgmma.mma_async.sync.aligned.m64n128k16.f32.bf16.bf16 "
        "{%0,%1,%2,%3,%4,%5,%6,%7,%8,%9,%10,%11,%12,%13,%14,%15,%16,%17,%18,%19,%20,%21,%22,%23,%24,%25,%26,%27,%28,%29,%30,%31,"
        "%32,%33,%34,%35,%36,%37,%38,%39,%40,%41,%42,%43,%44,%45,%46,%47,%48,%49,%50,%51,%52,%53,%54,%55,%56,%57,%58,%59,%60,%61,%62,%63},"
        "{%64,%65,%66,%67}, %68, p, 1, 1, %70;\n}"
        : F8(d, 0), F8(d, 8), F8(d, 16), F8(d, 24), F8(d, 32), F8(d, 40), F8(d, 48), F8(d, 56)
        : "r"(a0), "r"(a1), "r"(a2), "r"(a3), "l"(db), "r"(sc), "n"(TB));
}
#define O8(d, b) \
    "=f"(d[b]), "=f"(d[b + 1]), "=f"(d[b + 2]), "=f"(d[b + 3]), "=f"(d[b + 4]), "=f"(d[b + 5]), "=f"(d[b + 6]), "=f"(d[b + 7])
template <int TB>
__device__ __forceinline__ void wgmma_n128_z(float (&d)[64], uint32_t a0, uint32_t a1, uint32_t a2, uint32_t a3,
                                             uint64_t db) {
    asm volatile(
        "wgmma.mma_async.sync.aligned.m64n128k16.f32.bf16.bf16 "
        "{%0,%1,%2,%3,%4,%5,%6,%7,%8,%9,%10,%11,%12,%13,%14,%15,%16,%17,%18,%19,%20,%21,%22,%23,%24,%25,%26,%27,%28,%29,%30,%31,"
        "%32,%33,%34,%35,%36,%37,%38,%39,%40,%41,%42,%43,%44,%45,%46,%47,%48,%49,%50,%51,%52,%53,%54,%55,%56,%57,%58,%59,%60,%61,%62,%63},"
        "{%64,%65,%66,%67}, %68, 0, 1, 1, %69;"
        : O8(d, 0), O8(d, 8), O8(d, 16), O8(d, 24), O8(d, 32), O8(d, 40), O8(d, 48), O8(d, 56)
        : "r"(a0), "r"(a1), "r"(a2), "r"(a3), "l"(db), "n"(TB));
}
template <int TB>
__device__ __forceinline__ void wgmma_n64_z(float (&d)[32], uint32_t a0, uint32_t a1, uint32_t a2, uint32_t a3,
                                            uint64_t db) {
    asm volatile(
        "wgmma.mma_async.sync.aligned.m64n64k16.f32.bf16.bf16 "
        "{%0,%1,%2,%3,%4,%5,%6,%7,%8,%9,%10,%11,%12,%13,%14,%15,%16,%17,%18,%19,%20,%21,%22,%23,%24,%25,%26,%27,%28,%29,%30,%31},"
        "{%32,%33,%34,%35}, %36, 0, 1, 1, %37;"
        : O8(d, 0), O8(d, 8), O8(d, 16), O8(d, 24)
        : "r"(a0), "r"(a1), "r"(a2), "r"(a3), "l"(db), "n"(TB));
}
template <int TB>
__device__ __forceinline__ void wgmma_n64(float (&d)[32], uint32_t a0, uint32_t a1, uint32_t a2, uint32_t a3,
                                          uint64_t db) {
    asm volatile(
        "wgmma.mma_async.sync.aligned.m64n64k16.f32.bf16.bf16 "
        "{%0,%1,%2,%3,%4,%5,%6,%7,%8,%9,%10,%11,%12,%13,%14,%15,%16,%17,%18,%19,%20,%21,%22,%23,%24,%25,%26,%27,%28,%29,%30,%31},"
        "{%32,%33,%34,%35}, %36, 1, 1, 1, %37;"
        : F8(d, 0), F8(d, 8), F8(d, 16), F8(d, 24)
        : "r"(a0), "r"(a1), "r"(a2), "r"(a3), "l"(db), "n"(TB));
}

__device__ __forceinline__ uint64_t desc_of(uint32_t saddr) {
    return (uint64_t)(((saddr >> 4) & 0x3FFFu) | (512u << 16)) | ((uint64_t)(64u | (1u << 30)) << 32);
}

struct Ring {
    uint32_t slot;
    uint32_t phase;
    __device__ __forceinline__ void next() {
        if (++slot == 8) {
            slot = 0;
            phase ^= 1;
        }
    }
};

struct Ctx {
    uint32_t sbase;
    uint32_t rel_cta;
    __device__ __forceinline__ void wait_full(uint32_t slot, uint32_t phase) const {
        mbar_wait(sbase + OFF_FULL + slot * 8, phase);
    }
    __device__ __forceinline__ void release(uint32_t slot) const {
        if (rel_cta < 2) mbar_arrive_cluster(sbase + OFF_EMPTY + slot * 8, rel_cta);
    }
};

__device__ __forceinline__ void gemm_n128(float (&d)[64], const uint32_t (&a)[144], const Ctx& c, Ring& r, bool nine,
                                          int kick) {
    uint32_t prev = 0;
#pragma unroll
    for (int s = 0; s < 9; s++) {
        if (s < 8 || nine) {
            c.wait_full(r.slot, r.phase);
            uint64_t db = desc_of(c.sbase + r.slot * SLOT_BYTES);
            wg_fence();
#pragma unroll
            for (int k = 0; k < 4; k++) {
                if ((s | k) == 0)
                    wgmma_n128_z<1>(d, a[0], a[1], a[2], a[3], db);
                else
                    wgmma_n128<1>(d, a[s * 16 + k * 4], a[s * 16 + k * 4 + 1], a[s * 16 + k * 4 + 2],
                                  a[s * 16 + k * 4 + 3], db + k * 128, 1);
            }
            wg_commit();
            if (s == 3 && kick) bar_arrive(kick, 256);
            if (s > 0) {
                wg_wait<1>();
                c.release(prev);
            }
            prev = r.slot;
            r.next();
        }
    }
    wg_wait<0>();
    c.release(prev);
    pin(d);
}
__device__ __forceinline__ void gemm_n64(float (&d)[32], const uint32_t (&a)[144], const Ctx& c, Ring& r, bool nine) {
    uint32_t prev = 0;
#pragma unroll
    for (int s = 0; s < 5; s++) {
        if (s < 4 || nine) {
            c.wait_full(r.slot, r.phase);
            uint64_t db = desc_of(c.sbase + r.slot * SLOT_BYTES);
            wg_fence();
#pragma unroll
            for (int k = 0; k < 8; k++) {
                if ((s | k) == 0)
                    wgmma_n64_z<1>(d, a[0], a[1], a[2], a[3], db);
                else if (s * 8 + k < 36)
                    wgmma_n64<1>(d, a[s * 32 + k * 4], a[s * 32 + k * 4 + 1], a[s * 32 + k * 4 + 2],
                                 a[s * 32 + k * 4 + 3], db + k * 128);
            }
            wg_commit();
            if (s > 0) {
                wg_wait<1>();
                c.release(prev);
            }
            prev = r.slot;
            r.next();
        }
    }
    wg_wait<0>();
    c.release(prev);
    pin(d);
}
__device__ __forceinline__ void st_part(unsigned long long* p, float a, float b, float c, float d, uint32_t tag) {
    const uint32_t lo = (pack_bf16(a, b) & ~1u) | tag, hi = pack_bf16(c, d);
    asm volatile("{\n.reg .b64 t;\nmov.b64 t, {%1, %2};\nst.relaxed.gpu.global.b64 [%0], t;\n}" ::"l"(p), "r"(lo), "r"(hi)
                 : "memory");
}
__device__ __forceinline__ uint2 ld_part(const unsigned long long* p) {
    uint2 r;
    asm volatile("{\n.reg .b64 t;\nld.relaxed.gpu.global.b64 t, [%2];\nmov.b64 {%0, %1}, t;\n}"
                 : "=r"(r.x), "=r"(r.y)
                 : "l"(p));
    return r;
}
__device__ __forceinline__ void proj_partials(const uint32_t (&a)[144], const Ctx& c, Ring& r, bool nine,
                                              unsigned long long* dst  , uint32_t tag) {
#pragma unroll 1
    for (int p = 0; p < 4; p++) {
        float d[64];
        gemm_n128(d, a, c, r, nine, 0);
#pragma unroll
        for (int j = 0; j < 16; j++) st_part(dst + (p * 16 + j) * 32, d[4 * j], d[4 * j + 1], d[4 * j + 2], d[4 * j + 3], tag);
    }
    float d[32];
    gemm_n64(d, a, c, r, nine);
#pragma unroll
    for (int j = 0; j < 8; j++) st_part(dst + (64 + j) * 32, d[4 * j], d[4 * j + 1], d[4 * j + 2], d[4 * j + 3], tag);
}

__device__ __forceinline__ void row_reduce(float& s0, float& s1, uint32_t red, int warp, int lane) {
    s0 += __shfl_xor_sync(0xffffffffu, s0, 1);
    s1 += __shfl_xor_sync(0xffffffffu, s1, 1);
    s0 += __shfl_xor_sync(0xffffffffu, s0, 2);
    s1 += __shfl_xor_sync(0xffffffffu, s1, 2);
    if ((lane & 3) == 0) {
        sts32f(red + (warp * 16 + (lane >> 2)) * 4, s0);
        sts32f(red + (warp * 16 + 8 + (lane >> 2)) * 4, s1);
    }
    bar_sync(3, 256);
    s0 = 0.f;
    s1 = 0.f;
#pragma unroll
    for (int w = 0; w < 8; w++) {
        s0 += lds32f(red + (w * 16 + (lane >> 2)) * 4);
        s1 += lds32f(red + (w * 16 + 8 + (lane >> 2)) * 4);
    }
}
__device__ __forceinline__ void layernorm_rows(float (&v)[36], uint32_t red, int warp, int lane) {
    float s0 = 0.f, s1 = 0.f;
#pragma unroll
    for (int j = 0; j < 9; j++) {
        s0 += v[4 * j] + v[4 * j + 1];
        s1 += v[4 * j + 2] + v[4 * j + 3];
    }
    row_reduce(s0, s1, red, warp, lane);
    const float m0 = s0 * (1.f / DM), m1 = s1 * (1.f / DM);
    s0 = 0.f;
    s1 = 0.f;
#pragma unroll
    for (int j = 0; j < 9; j++) {
        v[4 * j] -= m0;
        v[4 * j + 1] -= m0;
        v[4 * j + 2] -= m1;
        v[4 * j + 3] -= m1;
        s0 += v[4 * j] * v[4 * j] + v[4 * j + 1] * v[4 * j + 1];
        s1 += v[4 * j + 2] * v[4 * j + 2] + v[4 * j + 3] * v[4 * j + 3];
    }
    row_reduce(s0, s1, red + 512, warp, lane);
    const float r0 = rsqrtf(s0 * (1.f / DM) + 1e-5f), r1 = rsqrtf(s1 * (1.f / DM) + 1e-5f);
#pragma unroll
    for (int j = 0; j < 9; j++) {
        v[4 * j] *= r0;
        v[4 * j + 1] *= r0;
        v[4 * j + 2] *= r1;
        v[4 * j + 3] *= r1;
    }
}
__device__ __forceinline__ void load_mod0(float (&m)[3][18], const uint32_t* src, uint32_t tag) {
    const uint32_t t0 = clk32();
    while (true) {
        uint2 u[2][9];
#pragma unroll
        for (int n = 0; n < 2; n++)
#pragma unroll
            for (int j = 0; j < 9; j++)
                asm volatile("ld.relaxed.gpu.global.v2.u32 {%0,%1}, [%2];"
                             : "=r"(u[n][j].x), "=r"(u[n][j].y)
                             : "l"(src + n * DM + j * 64));
        uint32_t bad = 0;
#pragma unroll
        for (int n = 0; n < 2; n++)
#pragma unroll
            for (int j = 0; j < 9; j++) {
                bad |= (u[n][j].x ^ tag) | (u[n][j].y ^ tag);
                m[n + 1][2 * j] = __uint_as_float(u[n][j].x & 0xffff0000u);
                m[n + 1][2 * j + 1] = __uint_as_float(u[n][j].y & 0xffff0000u);
            }
        if (__all_sync(0xffffffffu, (bad & 0xffffu) == 0) || clk32() - t0 > WAIT_LIMIT) break;
    }
}
__device__ __forceinline__ void modulate_store(const float (&v)[36], const float (&shift)[18], const float (&scale)[18],
                                               uint4* hbuf  , int warp, int lane) {
    uint2* dst = reinterpret_cast<uint2*>(hbuf) + ((warp >> 1) * 32 + lane) * 2 + (warp & 1);
#pragma unroll
    for (int j = 0; j < 9; j++) {
        const float c0 = round_bf16(1.f + scale[2 * j]), c1 = round_bf16(1.f + scale[2 * j + 1]);
        uint2 o;
        o.x = pack_bf16(fmaf(v[4 * j], c0, shift[2 * j]), fmaf(v[4 * j + 1], c1, shift[2 * j + 1]));
        o.y = pack_bf16(fmaf(v[4 * j + 2], c0, shift[2 * j]), fmaf(v[4 * j + 3], c1, shift[2 * j + 1]));
        __stcg(dst + j * 256, o);
    }
}
__device__ __forceinline__ void sum_partials(float (&v)[36], const unsigned long long* src  ,
                                             uint32_t tag) {
    const uint32_t t0 = clk32();
    while (true) {
        uint2 t[8][8];
#pragma unroll
        for (int s = 0; s < 8; s++)
#pragma unroll
            for (int j = 0; j < 8; j++) t[s][j] = ld_part(src + (s * 72 + j * 8) * 32);
        uint32_t bad = 0;
#pragma unroll
        for (int s = 0; s < 8; s++)
#pragma unroll
            for (int j = 0; j < 8; j++) {
                bad |= t[s][j].x ^ tag;
                if (s == 0) {
                    v[4 * j] = bf_lo(t[s][j].x);
                    v[4 * j + 1] = bf_hi(t[s][j].x);
                    v[4 * j + 2] = bf_lo(t[s][j].y);
                    v[4 * j + 3] = bf_hi(t[s][j].y);
                } else {
                    v[4 * j] += bf_lo(t[s][j].x);
                    v[4 * j + 1] += bf_hi(t[s][j].x);
                    v[4 * j + 2] += bf_lo(t[s][j].y);
                    v[4 * j + 3] += bf_hi(t[s][j].y);
                }
            }
        if (__all_sync(0xffffffffu, (bad & 1u) == 0) || clk32() - t0 > WAIT_LIMIT) break;
    }
}
__device__ __forceinline__ void sum_tail(float (&v)[36], float (&m)[3][18], const unsigned long long* src, uint32_t tag,
                                         const uint32_t* gate, const uint32_t* shsc, uint32_t mtag) {
    const uint32_t t0 = clk32();
    while (true) {
        uint2 t[8], u[3][9];
#pragma unroll
        for (int s = 0; s < 8; s++) t[s] = ld_part(src + (s * 72 + 64) * 32);
#pragma unroll
        for (int n = 0; n < 3; n++)
#pragma unroll
            for (int j = 0; j < 9; j++)
                asm volatile("ld.relaxed.gpu.global.v2.u32 {%0,%1}, [%2];"
                             : "=r"(u[n][j].x), "=r"(u[n][j].y)
                             : "l"((n == 0 ? gate : shsc + (n - 1) * DM) + j * 64));
        uint32_t bad = 0, badm = 0;
        v[32] = v[33] = v[34] = v[35] = 0.f;
#pragma unroll
        for (int s = 0; s < 8; s++) {
            bad |= t[s].x ^ tag;
            v[32] += bf_lo(t[s].x);
            v[33] += bf_hi(t[s].x);
            v[34] += bf_lo(t[s].y);
            v[35] += bf_hi(t[s].y);
        }
#pragma unroll
        for (int n = 0; n < 3; n++)
#pragma unroll
            for (int j = 0; j < 9; j++) {
                badm |= (u[n][j].x ^ mtag) | (u[n][j].y ^ mtag);
                m[n][2 * j] = __uint_as_float(u[n][j].x & 0xffff0000u);
                m[n][2 * j + 1] = __uint_as_float(u[n][j].y & 0xffff0000u);
            }
        if (__all_sync(0xffffffffu, ((bad & 1u) | (badm & 0xffffu)) == 0) || clk32() - t0 > WAIT_LIMIT) break;
    }
}
__device__ __forceinline__ void load_frags(uint32_t (&a)[144], const uint4* src  ) {
#pragma unroll
    for (int k = 0; k < 36; k++) {
        uint4 t = __ldcg(src + k * 32);
        a[4 * k] = t.x;
        a[4 * k + 1] = t.y;
        a[4 * k + 2] = t.z;
        a[4 * k + 3] = t.w;
    }
}

constexpr float SM_SCALE = 0.08838834764831845f * 1.4426950408889634f;
constexpr float SM_HI = 1.2089258e24f;
constexpr float SM_LO = 9.0949470e-13f;
__device__ __forceinline__ void qk_step(float (&s)[32], const uint32_t (&q)[32], uint64_t dk) {
#pragma unroll
    for (int k = 0; k < 8; k++) {
        if (k == 0)
            wgmma_n64_z<0>(s, q[0], q[1], q[2], q[3], dk);
        else
            wgmma_n64<0>(s, q[4 * k], q[4 * k + 1], q[4 * k + 2], q[4 * k + 3], dk + (k >> 2) * 512 + (k & 3) * 2);
    }
}
__device__ __forceinline__ void pv_step(float (&o)[64], const uint32_t (&p)[16], uint64_t dv, int acc) {
#pragma unroll
    for (int k = 0; k < 4; k++)
        wgmma_n128<1>(o, p[4 * k], p[4 * k + 1], p[4 * k + 2], p[4 * k + 3], dv + k * 128, k != 0 ? 1 : acc);
}
template <bool SHIFT>
__device__ __forceinline__ void exp_step(const float (&s)[32], uint32_t (&p)[16], float n0, float n1, float& s0,
                                         float& s1) {
#pragma unroll
    for (int i = 0; i < 8; i++) {
        const float e0 = ex2(SHIFT ? s[4 * i] + n0 : s[4 * i]), e1 = ex2(SHIFT ? s[4 * i + 1] + n0 : s[4 * i + 1]);
        const float e2 = ex2(SHIFT ? s[4 * i + 2] + n1 : s[4 * i + 2]), e3 = ex2(SHIFT ? s[4 * i + 3] + n1 : s[4 * i + 3]);
        if (i == 0) {
            s0 = e0 + e1;
            s1 = e2 + e3;
        } else {
            s0 += e0 + e1;
            s1 += e2 + e3;
        }
        p[2 * i] = pack_bf16(e0, e1);
        p[2 * i + 1] = pack_bf16(e2, e3);
    }
}
__device__ __forceinline__ void row_max(const float (&sa)[32], const float (&sb)[32], float& x0, float& x1) {
    float xa[8];
#pragma unroll
    for (int i = 0; i < 8; i++) xa[i] = fmaxf(sa[i], sb[i]);
#pragma unroll
    for (int k = 1; k < 4; k++)
#pragma unroll
        for (int i = 0; i < 8; i++) xa[i] = fmaxf(xa[i], fmaxf(sa[8 * k + i], sb[8 * k + i]));
    x0 = fmaxf(fmaxf(xa[0], xa[1]), fmaxf(xa[4], xa[5]));
    x1 = fmaxf(fmaxf(xa[2], xa[3]), fmaxf(xa[6], xa[7]));
    x0 = fmaxf(x0, __shfl_xor_sync(0xffffffffu, x0, 1));
    x1 = fmaxf(x1, __shfl_xor_sync(0xffffffffu, x1, 1));
    x0 = fmaxf(x0, __shfl_xor_sync(0xffffffffu, x0, 2));
    x1 = fmaxf(x1, __shfl_xor_sync(0xffffffffu, x1, 2));
}
__device__ __forceinline__ void inv_row_sums(float l0, float l1, float& i0, float& i1) {
    l0 += __shfl_xor_sync(0xffffffffu, l0, 1);
    l1 += __shfl_xor_sync(0xffffffffu, l1, 1);
    l0 += __shfl_xor_sync(0xffffffffu, l0, 2);
    l1 += __shfl_xor_sync(0xffffffffu, l1, 2);
    i0 = rcp(l0);
    i1 = rcp(l1);
}

__device__ __forceinline__ uint32_t ld_epoch() {
    uint32_t e;
    asm volatile("ld.relaxed.gpu.global.u32 %0, [%1];" : "=r"(e) : "l"(&g_epoch) : "memory");
    return e;
}
__device__ __forceinline__ float silu_bf16(unsigned short c) {
    const float cv = bf_lo(c);
    return round_bf16(cv * rcp(1.f + ex2(-1.4426950408889634f * cv)));
}
__device__ __forceinline__ void st_mod(int idx, float v, uint32_t tag) {
    asm volatile("st.relaxed.gpu.global.u32 [%0], %1;" ::"l"(g_mod + idx), "r"(__float_as_uint(round_bf16(v)) | tag)
                 : "memory");
}
__device__ __forceinline__ void mod_block(const uint4 (&w)[5], const float (&sc)[5], int blk, uint32_t red, int warp,
                                          int lane, uint32_t tag) {
    float acc[8];
#pragma unroll
    for (int e = 0; e < 8; e++) acc[e] = 0.f;
#pragma unroll
    for (int i = 0; i < 5; i++) {
        acc[0] = fmaf(sc[i], bf_lo(w[i].x), acc[0]);
        acc[1] = fmaf(sc[i], bf_hi(w[i].x), acc[1]);
        acc[2] = fmaf(sc[i], bf_lo(w[i].y), acc[2]);
        acc[3] = fmaf(sc[i], bf_hi(w[i].y), acc[3]);
        acc[4] = fmaf(sc[i], bf_lo(w[i].z), acc[4]);
        acc[5] = fmaf(sc[i], bf_hi(w[i].z), acc[5]);
        acc[6] = fmaf(sc[i], bf_lo(w[i].w), acc[6]);
        acc[7] = fmaf(sc[i], bf_hi(w[i].w), acc[7]);
    }
#pragma unroll
    for (int o = 2; o < 32; o <<= 1)
#pragma unroll
        for (int e = 0; e < 8; e++) acc[e] += __shfl_xor_sync(0xffffffffu, acc[e], o);
    if (lane < 2) {
#pragma unroll
        for (int e = 0; e < 8; e++) sts32f(red + (warp * 16 + lane * 8 + e) * 4, acc[e]);
    }
    bar_sync(3, 256);
    if (warp == 0 && lane < 16) {
        float s = 0.f;
#pragma unroll
        for (int w8 = 0; w8 < 8; w8++) s += lds32f(red + (w8 * 16 + lane) * 4);
        if (blk < 72) st_mod(blk * 16 + lane, s, tag);
    }
}

__global__ void __cluster_dims__(2, 1, 1) __launch_bounds__(384, 1)
    fused_block_kernel(const __grid_constant__ Maps maps, const __nv_bfloat16* __restrict__ x,
                       const __nv_bfloat16* __restrict__ cvec, const __nv_bfloat16* __restrict__ wmod,
                       __nv_bfloat16* __restrict__ out, const __nv_bfloat16* __restrict__ kc_ptr,
                       const __nv_bfloat16* __restrict__ vc_ptr) {
    extern __shared__ uint8_t smem_raw[];
    uint32_t sbase = (smem_u32(smem_raw) + 1023u) & ~1023u;
    asm volatile("" : "+r"(sbase));
    const int b = blockIdx.x;
    const int rank = b & 1;
    const int mt = ((b >> 1) & 7) * 2 + rank;
    const int g = b >> 4;
    const int warp = __shfl_sync(0xffffffffu, threadIdx.x >> 5, 0);
    const int lane = threadIdx.x & 31;

    if (warp >= 8) {
        asm volatile("setmaxnreg.dec.sync.aligned.u32 24;");
        if (warp == 8 && lane == 0) {
#pragma unroll
            for (int i = 0; i < 8; i++) {
                mbar_init(sbase + OFF_FULL + i * 8, 1);
                mbar_init(sbase + OFF_EMPTY + i * 8, 4);
            }
            asm volatile("fence.mbarrier_init.release.cluster;" ::: "memory");
            asm volatile("barrier.cluster.arrive.relaxed;\nbarrier.cluster.wait;" ::: "memory");
            uint32_t slot = 0, phase = 1;
            const uint32_t dst0 = sbase + rank * BOX_BYTES;
            auto acquire = [&](uint32_t bytes) {
                mbar_wait(sbase + OFF_EMPTY + slot * 8, phase);
                mbar_expect_tx(sbase + OFF_FULL + slot * 8, bytes);
            };
            auto adv8 = [&]() {
                if (++slot == 8) {
                    slot = 0;
                    phase ^= 1;
                }
            };
            {
                const int u = b & 15;
                l2_prefetch(kc_ptr + (size_t)(g * 4 * 2048 + u * 64) * 128, SLOT_BYTES);
                l2_prefetch(vc_ptr + (size_t)(g * 4 * 2048 + u * 64) * 128, SLOT_BYTES);
            }
#pragma unroll 1
            for (int hq = 0; hq < 4; hq++) {
                const int col = (g * 4 + ((hq + 1) & 3)) * 128 + rank * 64;
#pragma unroll 1
                for (int kc = 0; kc < 9; kc++) {
                    acquire(SLOT_BYTES);
                    tma_mc(dst0 + slot * SLOT_BYTES, &maps.wq, col, kc * 64, sbase + OFF_FULL + slot * 8);
                    adv8();
                }
            }
            const int row0 = g * 4 * 2048;
#pragma unroll 1
            for (int n = 0; n < 128; n++) {
                if (n < 4) mbar_wait(sbase + OFF_EMPTY + (slot + 1) * 8, phase);
                acquire(2 * SLOT_BYTES);
                const uint32_t bar = sbase + OFF_FULL + slot * 8;
                const int r0 = n == 0 ? 0 : (n == 127 ? 126 : n + 1);
                const int r1 = n == 0 ? 1 : (n == 127 ? 127 : n - 1);
                tma_mc(dst0 + slot * SLOT_BYTES, n == 127 ? &maps.v : &maps.k, rank * 64, row0 + r0 * 64, bar);
                tma_mc(dst0 + (slot + 1) * SLOT_BYTES, n == 0 ? &maps.k : &maps.v, rank * 64, row0 + r1 * 64, bar);
                adv8();
                adv8();
                const int u = n + KV_AHEAD;
                if (u < 128 && (u & 15) == (b & 15)) {
                    l2_prefetch(kc_ptr + (size_t)(row0 + u * 64) * 128, SLOT_BYTES);
                    l2_prefetch(vc_ptr + (size_t)(row0 + u * 64) * 128, SLOT_BYTES);
                }
            }
#pragma unroll 1
            for (int p = 0; p < 4; p++)
#pragma unroll 1
                for (int kc = 0; kc < 8; kc++) {
                    acquire(SLOT_BYTES);
                    tma_mc(dst0 + slot * SLOT_BYTES, &maps.wo, p * 128 + rank * 64, g * 512 + kc * 64,
                           sbase + OFF_FULL + slot * 8);
                    adv8();
                }
#pragma unroll 1
            for (int kc = 0; kc < 4; kc++) {
                acquire(SLOT_BYTES);
                tma_mc(dst0 + slot * SLOT_BYTES, &maps.wo, 512, g * 512 + kc * 128 + rank * 64,
                       sbase + OFF_FULL + slot * 8);
                adv8();
            }
            const CUtensorMap* mg = rank ? &maps.wu : &maps.wg;
#pragma unroll 1
            for (int ch = 0; ch < 9; ch++)
#pragma unroll 1
                for (int kc = 0; kc < 9; kc++) {
                    acquire(SLOT_BYTES);
                    tma_mc(dst0 + slot * SLOT_BYTES, mg, g * 576 + ch * 64, kc * 64, sbase + OFF_FULL + slot * 8);
                    adv8();
                }
#pragma unroll 1
            for (int p = 0; p < 4; p++)
#pragma unroll 1
                for (int kc = 2; kc < 11; kc++) {
                    acquire(SLOT_BYTES);
                    tma_mc(dst0 + slot * SLOT_BYTES, &maps.wd, p * 128 + rank * 64, g * 576 + (kc < 9 ? kc : kc - 9) * 64,
                           sbase + OFF_FULL + slot * 8);
                    adv8();
                }
#pragma unroll 1
            for (int i = 0; i < 5; i++) {
                acquire(i < 4 ? SLOT_BYTES : BOX_BYTES);
                const int kc = 2 * i + rank + 2;
                if (i < 4 || rank == 0)
                    tma_mc(dst0 + slot * SLOT_BYTES, &maps.wd, 512, g * 576 + (kc < 9 ? kc : kc - 9) * 64,
                           sbase + OFF_FULL + slot * 8);
                adv8();
            }
        } else if (warp == 9 || warp == 10) {
            asm volatile("barrier.cluster.arrive.relaxed.aligned;" ::: "memory");
            const uint32_t tag = (ld_epoch() + 1) & 0xffffu;
            bar_sync(4, 320);
            const int blk = warp == 9 ? 72 + b : 200 + b;
            if (blk < 216) {
                float acc[8];
#pragma unroll
                for (int e = 0; e < 8; e++) acc[e] = 0.f;
                const uint4* wp = reinterpret_cast<const uint4*>(wmod + (size_t)(lane >> 1) * (6 * DM) + blk * 16) + (lane & 1);
                const unsigned short* cp = reinterpret_cast<const unsigned short*>(cvec) + (lane >> 1);
#pragma unroll 1
                for (int i = 0; i < 36; i++) {
                    const uint4 w = __ldg(wp + (size_t)i * (16 * 6 * DM / 8));
                    const float sc = silu_bf16(__ldg(cp + i * 16));
                    acc[0] = fmaf(sc, bf_lo(w.x), acc[0]);
                    acc[1] = fmaf(sc, bf_hi(w.x), acc[1]);
                    acc[2] = fmaf(sc, bf_lo(w.y), acc[2]);
                    acc[3] = fmaf(sc, bf_hi(w.y), acc[3]);
                    acc[4] = fmaf(sc, bf_lo(w.z), acc[4]);
                    acc[5] = fmaf(sc, bf_hi(w.z), acc[5]);
                    acc[6] = fmaf(sc, bf_lo(w.w), acc[6]);
                    acc[7] = fmaf(sc, bf_hi(w.w), acc[7]);
                }
#pragma unroll
                for (int o = 2; o < 32; o <<= 1)
#pragma unroll
                    for (int e = 0; e < 8; e++) acc[e] += __shfl_xor_sync(0xffffffffu, acc[e], o);
                if (lane < 2) {
#pragma unroll
                    for (int e = 0; e < 8; e++) st_mod(blk * 16 + lane * 8 + e, acc[e], tag);
                }
            }
        }
    } else {
        asm volatile("setmaxnreg.inc.sync.aligned.u32 240;");
        const int wg = warp >> 2;
        const int tid = threadIdx.x;
        Ctx cx;
        cx.sbase = sbase;
        cx.rel_cta = (lane == 0 && (warp & 3) < 2) ? (warp & 3) : 2;
        const uint32_t red = sbase + OFF_RED;
        const int own = mt * 8 + g;
        const int wown = mt * 8 + warp;
        PROF(0);
        PROFG(30);
        const uint32_t epoch = ld_epoch();
        {
            uint4 w1[5];
            unsigned short cu[5];
            const int half = tid & 1, r0 = tid >> 1;
            if (b < 72) {
#pragma unroll
                for (int i = 0; i < 5; i++) {
                    const int row = min(r0 + 128 * i, DM - 1);
                    cu[i] = __ldg(reinterpret_cast<const unsigned short*>(cvec) + row);
                    w1[i] = __ldg(reinterpret_cast<const uint4*>(wmod + (size_t)row * (6 * DM) + half * 8) + b * 2);
                }
            }
            if (warp == 0) {
                if (lane == 0) {
                    mbar_init(sbase + OFF_XBAR, 1);
                    asm volatile("fence.mbarrier_init.release.cluster;\nfence.proxy.async.shared::cta;" ::: "memory");
                    mbar_expect_tx(sbase + OFF_XBAR, 16 * DM * 2);
                }
                __syncwarp();
                if (lane < 16)
                    asm volatile(
                        "cp.async.bulk.shared::cluster.global.mbarrier::complete_tx::bytes [%0], [%1], %2, [%3];" ::"r"(
                            sbase + 8 * SLOT_BYTES + lane * XROW_STRIDE),
                        "l"(x + (size_t)(own * 16 + lane) * DM), "r"(DM * 2), "r"(sbase + OFF_XBAR)
                        : "memory");
                __syncwarp();
            }
            asm volatile("barrier.cluster.arrive.relaxed.aligned;" ::: "memory");
            if (b < 72) {
                float sc[5];
#pragma unroll
                for (int i = 0; i < 5; i++) sc[i] = (r0 + 128 * i < DM) ? silu_bf16(cu[i]) : 0.f;
                mod_block(w1, sc, b, red + 1024, warp, lane, (epoch + 1) & 0xffffu);
            } else {
                bar_sync(3, 256);
            }
            asm volatile("" ::"r"(epoch) : "memory");
            bar_arrive(4, 320);
        }

        Ring ring{0u, 0u};
        int stage = 0;
        asm volatile("" : "+r"(stage));
#pragma unroll 1
        for (;; stage++) {
            int tid, lane;
            asm volatile("mov.u32 %0, %%tid.x;" : "=r"(tid));
            lane = tid & 31;
            {
                float v[36], md[3][18];
                float4* x2buf = g_x2 + (size_t)b * 9 * 256 + tid;
                const uint32_t tag = (epoch + 1) & 0xffffu;
                const uint32_t* modp = g_mod + warp * 8 + (lane & 3) * 2;
                if (stage == 0) {
#pragma unroll
                    for (int i = 0; i < 18; i++) md[1][i] = md[2][i] = 0.f;
                    mbar_wait(sbase + OFF_XBAR, 0);
                    const uint32_t src = sbase + 8 * SLOT_BYTES + (lane >> 2) * XROW_STRIDE + warp * 16 + (lane & 3) * 4;
#pragma unroll
                    for (int j = 0; j < 9; j++) {
                        const uint32_t u0 = __float_as_uint(lds32f(src + j * 128));
                        const uint32_t u1 = __float_as_uint(lds32f(src + j * 128 + 8 * XROW_STRIDE));
                        v[4 * j] = bf_lo(u0);
                        v[4 * j + 1] = bf_hi(u0);
                        v[4 * j + 2] = bf_lo(u1);
                        v[4 * j + 3] = bf_hi(u1);
                    }
                } else {
                    const unsigned long long* psrc = g_part + (size_t)own * 8 * 72 * 32 + tid;
                    sum_partials(v, psrc, stage & 1);
                    PROF(stage == 1 ? 8 : 15);
                    float4 xr[9];
#pragma unroll
                    for (int j = 0; j < 9; j++) xr[j] = __ldcg(x2buf + j * 256);
                    sum_tail(v, md, psrc, stage & 1, modp + (stage * 3 - 1) * DM, modp + 3 * DM, tag);
                    const float gs = stage == 1 ? 1.f : 0.5f;
#pragma unroll
                    for (int j = 0; j < 9; j++) {
                        const float g0 = md[0][2 * j] * gs, g1 = md[0][2 * j + 1] * gs;
                        v[4 * j] = fmaf(g0, v[4 * j], xr[j].x);
                        v[4 * j + 1] = fmaf(g1, v[4 * j + 1], xr[j].y);
                        v[4 * j + 2] = fmaf(g0, v[4 * j + 2], xr[j].z);
                        v[4 * j + 3] = fmaf(g1, v[4 * j + 3], xr[j].w);
                    }
                    if (stage == 2) {
                        __nv_bfloat16* dst = out + (size_t)(own * 16 + (lane >> 2)) * DM + warp * 8 + (lane & 3) * 2;
#pragma unroll
                        for (int j = 0; j < 9; j++) {
                            *reinterpret_cast<uint32_t*>(dst + j * 64) = pack_bf16(v[4 * j], v[4 * j + 1]);
                            *reinterpret_cast<uint32_t*>(dst + j * 64 + 8 * DM) = pack_bf16(v[4 * j + 2], v[4 * j + 3]);
                        }
                        break;
                    }
                }
                PROF(stage == 0 ? 1 : 9);
                float keep[36];
#pragma unroll
                for (int i = 0; i < 36; i++) keep[i] = v[i];
                layernorm_rows(v, red, warp, lane);
                if (stage == 0) load_mod0(md, modp, tag);
                PROF(stage == 0 ? 2 : 10);
                modulate_store(v, md[1], md[2], g_h[stage] + (size_t)own * 36 * 32, warp, lane);
                __syncwarp();
                if (lane == 0) signal_cnt(stage * 128 + own);
#pragma unroll
                for (int j = 0; j < 9; j++)
                    __stcg(x2buf + j * 256, make_float4(keep[4 * j], keep[4 * j + 1], keep[4 * j + 2], keep[4 * j + 3]));
                if (stage == 0) asm volatile("barrier.cluster.wait.aligned;" ::: "memory");
            }

            const uint32_t spill = sbase + 8 * SLOT_BYTES + wg * 3 * SLOT_BYTES + (tid & 127) * 16;
            uint32_t a[144];
            PROF(stage == 0 ? 3 : 11);
            wait_cnt(stage * 128 + wown, (epoch + 1) * 8);
            PROF(stage == 0 ? 4 : 12);
            if (stage == 1) PROFG(25);
            load_frags(a, g_h[stage] + (size_t)wown * 36 * 32 + lane);
            uint4* hhbuf = g_hh + (size_t)b * 8 * 256 + tid;
            float d[64];
            if (wg == 1) bar_sync(5, 256);
#pragma unroll 1
            for (int ch = 0;; ch++) {
                gemm_n128(d, a, cx, ring, true, (ch == 0 && wg == 0) ? 5 : 0);
                if (stage == 0) {
#pragma unroll
                    for (int i = 0; i < 64; i++) d[i] *= SM_SCALE;
                    if (ch == 3) break;
#pragma unroll
                    for (int v = 0; v < 8; v++)
                        sts128(spill + (ch * 8 + v) * 2048, pack_bf16(d[8 * v], d[8 * v + 1]),
                               pack_bf16(d[8 * v + 2], d[8 * v + 3]), pack_bf16(d[8 * v + 4], d[8 * v + 5]),
                               pack_bf16(d[8 * v + 6], d[8 * v + 7]));
                } else {
#pragma unroll
                    for (int i = 0; i < 32; i++) {
                        const float gv = d[i], gu = gv * d[32 + i];
                        const float z = gv * fmaf(gv * gv, 0.7978845608028654f * 0.044715f, 0.7978845608028654f);
                        d[i] = fmaf(gu, tanh_fast(z), gu);
                    }
                    if (ch == 8) break;
#pragma unroll
                    for (int v = 0; v < 4; v++) {
                        const uint4 h4 = make_uint4(pack_bf16(d[8 * v], d[8 * v + 1]), pack_bf16(d[8 * v + 2], d[8 * v + 3]),
                                                    pack_bf16(d[8 * v + 4], d[8 * v + 5]), pack_bf16(d[8 * v + 6], d[8 * v + 7]));
                        if (ch < 2)
                            __stcg(hhbuf + (ch * 4 + v) * 256, h4);
                        else
                            sts128(spill + ((ch - 2) * 4 + v) * 2048, h4.x, h4.y, h4.z, h4.w);
                    }
                }
            }
            if (stage == 0) {
                uint32_t q[32];
#pragma unroll
                for (int i = 0; i < 32; i++) q[i] = pack_bf16(d[2 * i], d[2 * i + 1]);
                PROF(5);
                PROFG(23);
                {
                    float o[64], sa[32], sb[32];
                    uint32_t pa[16], pb[16];
#pragma unroll
                    for (int i = 0; i < 64; i++) o[i] = 0.f;
                    float n0 = 0.f, n1 = 0.f, l0 = 1.f, l1 = 1.f;
                    bool shifted = false;
                    const uint64_t dbase = desc_of(sbase);
                    const uint64_t dbk = dbase - (511u << 16);
                    const int my_bar = 1 + wg, other_bar = 2 - wg;

                    auto softmax_a = [&](bool first, float& s0, float& s1) {
                        if (first) {
                            shifted = false;
                            n0 = n1 = 0.f;
                            l0 = l1 = 0.f;
                        }
                        if (shifted)
                            exp_step<true>(sa, pa, n0, n1, s0, s1);
                        else
                            exp_step<false>(sa, pa, n0, n1, s0, s1);
                    };
                    auto softmax_b = [&](bool first, float s0, float s1) {
                        float u0, u1;
                        if (shifted)
                            exp_step<true>(sb, pb, n0, n1, u0, u1);
                        else
                            exp_step<false>(sb, pb, n0, n1, u0, u1);
                        s0 += u0;
                        s1 += u1;
                        bool bad = !(fmaxf(s0, s1) <= SM_HI);
                        if (first) {
                            float r0 = s0 + __shfl_xor_sync(0xffffffffu, s0, 1), r1 = s1 + __shfl_xor_sync(0xffffffffu, s1, 1);
                            r0 += __shfl_xor_sync(0xffffffffu, r0, 2);
                            r1 += __shfl_xor_sync(0xffffffffu, r1, 2);
                            bad = bad || !(fminf(r0, r1) >= SM_LO);
                        }
                        if (__any_sync(0xffffffffu, bad)) {
                            float x0, x1;
                            row_max(sa, sb, x0, x1);
                            x0 = -x0;
                            x1 = -x1;
                            if (!first) {
                                x0 = fminf(x0, n0);
                                x1 = fminf(x1, n1);
                                const float al0 = ex2(x0 - n0), al1 = ex2(x1 - n1);
                                l0 *= al0;
                                l1 *= al1;
#pragma unroll
                                for (int i = 0; i < 16; i++) {
                                    o[4 * i] *= al0;
                                    o[4 * i + 1] *= al0;
                                    o[4 * i + 2] *= al1;
                                    o[4 * i + 3] *= al1;
                                }
                            }
                            n0 = x0;
                            n1 = x1;
                            shifted = true;
                            exp_step<true>(sa, pa, n0, n1, s0, s1);
                            exp_step<true>(sb, pb, n0, n1, u0, u1);
                            s0 += u0;
                            s1 += u1;
                        }
                        l0 += s0;
                        l1 += s1;
                    };

                    cx.wait_full(4, 0);
                    if (wg == 1) bar_sync(my_bar, 256);
                    wg_fence();
                    qk_step(sa, q, dbk + 4 * 1024);
                    qk_step(sb, q, dbk + 5 * 1024);
                    wg_commit();
                    bar_arrive(other_bar, 256);
                    wg_wait<0>();
                    pin(sa);
                    pin(sb);
                    cx.release(4);
                    cx.wait_full(6, 0);
                    {
                        float s0, s1;
                        softmax_a(true, s0, s1);
                        softmax_b(true, s0, s1);
                    }
                    uint32_t alo = (uint32_t)dbase + 6 * 1024, blo = (uint32_t)dbase;
                    const uint32_t dhi = (uint32_t)(dbase >> 32);
#pragma unroll 1
                    for (int t = 1; t < 64; t++) {
                        const int j = t & 15;
                        const uint32_t sA = 2 + 4 * (t & 1), sB = 4 - 4 * (t & 1);
                        const uint64_t da = ((uint64_t)dhi << 32) | alo, db = ((uint64_t)dhi << 32) | blo;
                        TL(0);
                        bar_sync(my_bar, 256);
                        TL(2);
                        wg_fence();
                        pv_step(o, pa, da + 1024, j != 1);
                        qk_step(sa, q, da - (511u << 16));
                        wg_commit();
                        cx.wait_full(sB, ((36 + 4 * t) >> 3) & 1);
                        wg_fence();
                        qk_step(sb, q, db - (511u << 16));
                        pv_step(o, pb, db + 1024, 1);
                        wg_commit();
                        bar_arrive(other_bar, 256);
                        alo ^= 4096;
                        blo ^= 4096;
                        asm volatile("" : "+r"(alo), "+r"(blo));
                        TL(3);
                        wg_wait<1>();
                        pin(sa);
                        pin(pa);
                        TL(4);
                        cx.release(sA);
                        const float lp0 = l0, lp1 = l1;
                        float s0, s1;
                        softmax_a(j == 0, s0, s1);
                        TL(5);
                        wg_wait<0>();
                        pin(o);
                        pin(sb);
                        pin(pb);
                        TL(6);
                        cx.release(sB);
                        if (j == 0) {
                            float i0, i1;
                            inv_row_sums(lp0, lp1, i0, i1);
                            const uint32_t dst = spill + ((t >> 4) - 1) * 16384;
#pragma unroll
                            for (int v = 0; v < 8; v++)
                                sts128(dst + v * 2048, pack_bf16(o[8 * v] * i0, o[8 * v + 1] * i0),
                                       pack_bf16(o[8 * v + 2] * i1, o[8 * v + 3] * i1),
                                       pack_bf16(o[8 * v + 4] * i0, o[8 * v + 5] * i0),
                                       pack_bf16(o[8 * v + 6] * i1, o[8 * v + 7] * i1));
                        }
                        const uint32_t bn = sbase + OFF_FULL + (8 - sA) * 8, pn = ((38 + 4 * t) >> 3) & 1;
                        const bool okn = mbar_try(bn, pn);
                        TL(1);
                        softmax_b(j == 0, s0, s1);
                        if (!okn || j == 15) {
                            mbar_wait(bn, pn);
                            if (j == 15 && t < 63) {
                                const uint32_t src = spill + (t >> 4) * 16384;
#pragma unroll
                                for (int v = 0; v < 8; v++)
                                    lds128(src + v * 2048, q[4 * v], q[4 * v + 1], q[4 * v + 2], q[4 * v + 3]);
                            }
                        }
                        TL(7);
                    }
                    bar_sync(my_bar, 256);
                    wg_fence();
                    pv_step(o, pa, dbase + 2 * 1024, 1);
                    pv_step(o, pb, dbase + 3 * 1024, 1);
                    wg_commit();
                    if (wg == 0) bar_arrive(other_bar, 256);
                    float i0, i1;
                    inv_row_sums(l0, l1, i0, i1);
                    wg_wait<0>();
                    pin(o);
                    cx.release(2);
#pragma unroll
                    for (int i = 0; i < 16; i++) {
                        a[96 + 2 * i] = pack_bf16(o[4 * i] * i0, o[4 * i + 1] * i0);
                        a[96 + 2 * i + 1] = pack_bf16(o[4 * i + 2] * i1, o[4 * i + 3] * i1);
                    }
#pragma unroll
                    for (int i = 128; i < 144; i++) a[i] = 0;
                }
                ring.slot = 4;
                ring.phase = 0;
                PROF(6);
                PROFG(24);
            } else {
#pragma unroll
                for (int v = 0; v < 8; v++) {
                    const uint4 t = __ldcg(hhbuf + v * 256);
                    a[112 + 4 * v] = t.x;
                    a[113 + 4 * v] = t.y;
                    a[114 + 4 * v] = t.z;
                    a[115 + 4 * v] = t.w;
                }
#pragma unroll
                for (int i = 0; i < 16; i++) a[96 + i] = pack_bf16(d[2 * i], d[2 * i + 1]);
                PROF(13);
            }
#pragma unroll
            for (int v = 0; v < 24; v++) lds128(spill + v * 2048, a[4 * v], a[4 * v + 1], a[4 * v + 2], a[4 * v + 3]);

            proj_partials(a, cx, ring, stage != 0, g_part + ((size_t)wown * 8 + g) * 72 * 32 + lane, (stage + 1) & 1);
            PROF(stage == 0 ? 7 : 14);
            if (stage == 1) {
                PROFG(26);
                asm volatile("barrier.cluster.arrive.relaxed.aligned;" ::: "memory");
            }
        }
        PROF(16);
        PROFG(31);
        if (b == 0) {
            bar_sync(3, 256);
            if (tid == 0) g_epoch = epoch + 1;
        }
        asm volatile("barrier.cluster.wait.aligned;" ::: "memory");
    }
}

typedef CUresult (*EncodeFn)(CUtensorMap*, CUtensorMapDataType, cuuint32_t, void*, const cuuint64_t*, const cuuint64_t*,
                             const cuuint32_t*, const cuuint32_t*, CUtensorMapInterleave, CUtensorMapSwizzle,
                             CUtensorMapL2promotion, CUtensorMapFloatOOBfill);

void make_map(EncodeFn enc, CUtensorMap* m, const void* ptr, uint64_t rows, uint64_t cols) {
    cuuint64_t gdim[2] = {cols, rows};
    cuuint64_t gstr[1] = {cols * 2};
    cuuint32_t box[2] = {64, 64};
    cuuint32_t estr[2] = {1, 1};
    enc(m, CU_TENSOR_MAP_DATA_TYPE_BFLOAT16, 2, const_cast<void*>(ptr), gdim, gstr, box, estr,
        CU_TENSOR_MAP_INTERLEAVE_NONE, CU_TENSOR_MAP_SWIZZLE_128B, CU_TENSOR_MAP_L2_PROMOTION_L2_128B,
        CU_TENSOR_MAP_FLOAT_OOB_FILL_NONE);
}

}

extern "C" void kernel_launch(void* const* d_in, const int* in_sizes, int n_in, void* d_out, int out_size) {
    (void)in_sizes;
    (void)n_in;
    (void)out_size;
    void* fn = nullptr;
    cudaDriverEntryPointQueryResult qr;
    cudaGetDriverEntryPoint("cuTensorMapEncodeTiled", &fn, cudaEnableDefault, &qr);
    EncodeFn enc = (EncodeFn)fn;
    Maps maps;
    make_map(enc, &maps.k, d_in[1], 32 * 2048, 128);
    make_map(enc, &maps.v, d_in[2], 32 * 2048, 128);
    make_map(enc, &maps.wq, d_in[3], 576, 4096);
    make_map(enc, &maps.wo, d_in[4], 4096, 576);
    make_map(enc, &maps.wg, d_in[6], 576, 4608);
    make_map(enc, &maps.wu, d_in[7], 576, 4608);
    make_map(enc, &maps.wd, d_in[8], 4608, 576);
    cudaFuncSetAttribute(fused_block_kernel, cudaFuncAttributeMaxDynamicSharedMemorySize, SMEM_BYTES);
    fused_block_kernel<<<128, 384, SMEM_BYTES>>>(maps, (const __nv_bfloat16*)d_in[0], (const __nv_bfloat16*)d_in[9],
                                                 (const __nv_bfloat16*)d_in[10], (__nv_bfloat16*)d_out,
                                                 (const __nv_bfloat16*)d_in[1], (const __nv_bfloat16*)d_in[2]);
}
```

```cpp
#include <cuda_runtime.h>
#include <cuda_bf16.h>
#include <cuda.h>
#include <stdint.h>

namespace {

constexpr int DM = 576;
constexpr int SLOT_BYTES = 16384;
constexpr int BOX_BYTES = 8192;
constexpr int NUNITS = 14;
constexpr int SMEM_TAIL = NUNITS * SLOT_BYTES;
constexpr int SMEM_BYTES = SMEM_TAIL + 2048 + 1024;
constexpr int OFF_FULL = SMEM_TAIL;
constexpr int OFF_EMPTY = SMEM_TAIL + 64;
constexpr int OFF_RED = SMEM_TAIL + 128;

constexpr int KV_AHEAD = 16;
constexpr int OFF_XBAR = SMEM_TAIL + 1792;
constexpr int XROW_STRIDE = DM * 2 + 16;

struct Scratch {
    unsigned epoch;
    unsigned pad[31];
    uint32_t mod[6 * DM];
    uint4 h[2][128 * 36 * 32];
    unsigned long long part[128 * 8 * 72 * 32];
    float4 x2[128 * 9 * 256];
    uint4 hh[128 * 8 * 256];
};
__device__ Scratch g_scratch;

#define TL(i)
#define PROFR(i)
#define PROF(i)
#define PROFG(i)

struct Params {
    const __nv_bfloat16 *x, *cvec, *wmod, *kc, *vc;
    __nv_bfloat16* out;
    Scratch* sc;
    CUtensorMap k, v, wq, wo, wg, wu, wd;
};

__device__ __forceinline__ uint32_t smem_u32(const void* p) { return (uint32_t)__cvta_generic_to_shared(p); }
__device__ __forceinline__ void mbar_init(uint32_t a, uint32_t c) {
    asm volatile("mbarrier.init.shared::cta.b64 [%0], %1;" ::"r"(a), "r"(c) : "memory");
}
__device__ __forceinline__ void mbar_expect_tx(uint32_t a, uint32_t bytes) {
    asm volatile("mbarrier.arrive.expect_tx.shared::cta.b64 _, [%0], %1;" ::"r"(a), "r"(bytes) : "memory");
}
__device__ __forceinline__ bool mbar_try(uint32_t a, uint32_t ph) {
    uint32_t ok;
    asm volatile(
        "{\n.reg .pred p;\nmbarrier.try_wait.parity.shared::cta.b64 p, [%1], %2;\nselp.u32 %0, 1, 0, p;\n}"
        : "=r"(ok)
        : "r"(a), "r"(ph)
        : "memory");
    return ok != 0;
}
__device__ __forceinline__ uint32_t clk32() {
    uint32_t c;
    asm volatile("mov.u32 %0, %%clock;" : "=r"(c));
    return c;
}
constexpr uint32_t WAIT_LIMIT = 1u << 30;
__device__ __forceinline__ void mbar_wait(uint32_t a, uint32_t ph) {
    if (mbar_try(a, ph)) return;
    uint32_t t0 = clk32();
    while (!mbar_try(a, ph)) {
        if (clk32() - t0 > WAIT_LIMIT) break;
    }
}
__device__ __forceinline__ void mbar_arrive_cluster(uint32_t a, uint32_t cta) {
    asm volatile(
        "{\n.reg .b32 ra;\nmapa.shared::cluster.u32 ra, %0, %1;\nmbarrier.arrive.shared::cluster.b64 _, [ra];\n}" ::"r"(a),
        "r"(cta)
        : "memory");
}
__device__ __forceinline__ void tma_mc(uint32_t dst, const CUtensorMap* m, int c0, int c1, uint32_t bar) {
    asm volatile(
        "cp.async.bulk.tensor.2d.shared::cluster.global.mbarrier::complete_tx::bytes.multicast::cluster"
        " [%0], [%1, {%3, %4}], [%2], %5;" ::"r"(dst),
        "l"(m), "r"(bar), "r"(c0), "r"(c1), "h"((uint16_t)3)
        : "memory");
}
__device__ __forceinline__ void l2_prefetch(const void* p, uint32_t bytes) {
    asm volatile("cp.async.bulk.prefetch.L2.global [%0], %1;" ::"l"(p), "r"(bytes) : "memory");
}
__device__ __forceinline__ void bar_sync(int id, int n) { asm volatile("bar.sync %0, %1;" ::"r"(id), "r"(n) : "memory"); }
__device__ __forceinline__ void bar_arrive(int id, int n) {
    asm volatile("bar.arrive %0, %1;" ::"r"(id), "r"(n) : "memory");
}
__device__ __forceinline__ void wg_fence() { asm volatile("wgmma.fence.sync.aligned;" ::: "memory"); }
__device__ __forceinline__ void wg_commit() { asm volatile("wgmma.commit_group.sync.aligned;" ::: "memory"); }
template <int N>
__device__ __forceinline__ void wg_wait() {
    asm volatile("wgmma.wait_group.sync.aligned %0;" ::"n"(N) : "memory");
}
template <int N>
__device__ __forceinline__ void pin(float (&d)[N]) {
#pragma unroll
    for (int i = 0; i < N; i++) asm volatile("" : "+f"(d[i])::"memory");
}
template <int N>
__device__ __forceinline__ void pin(uint32_t (&d)[N]) {
#pragma unroll
    for (int i = 0; i < N; i++) asm volatile("" : "+r"(d[i])::"memory");
}
__device__ __forceinline__ uint32_t pack_bf16(float lo, float hi) {
    uint32_t r;
    asm("cvt.rn.bf16x2.f32 %0, %1, %2;" : "=r"(r) : "f"(hi), "f"(lo));
    return r;
}
__device__ __forceinline__ float bf_lo(uint32_t v) { return __uint_as_float(v << 16); }
__device__ __forceinline__ float bf_hi(uint32_t v) { return __uint_as_float(v & 0xffff0000u); }
__device__ __forceinline__ float round_bf16(float v) { return __bfloat162float(__float2bfloat16_rn(v)); }
__device__ __forceinline__ float ex2(float x) {
    float y;
    asm("ex2.approx.ftz.f32 %0, %1;" : "=f"(y) : "f"(x));
    return y;
}
__device__ __forceinline__ float rcp(float x) {
    float y;
    asm("rcp.approx.ftz.f32 %0, %1;" : "=f"(y) : "f"(x));
    return y;
}
__device__ __forceinline__ float tanh_fast(float x) {
    float y;
    asm("tanh.approx.f32 %0, %1;" : "=f"(y) : "f"(x));
    return y;
}
__device__ __forceinline__ void sts128(uint32_t a, uint32_t x, uint32_t y, uint32_t z, uint32_t w) {
    asm volatile("st.shared.v4.b32 [%0], {%1,%2,%3,%4};" ::"r"(a), "r"(x), "r"(y), "r"(z), "r"(w) : "memory");
}
__device__ __forceinline__ void lds128(uint32_t a, uint32_t& x, uint32_t& y, uint32_t& z, uint32_t& w) {
    asm volatile("ld.shared.v4.b32 {%0,%1,%2,%3}, [%4];" : "=r"(x), "=r"(y), "=r"(z), "=r"(w) : "r"(a) : "memory");
}
__device__ __forceinline__ void sts32f(uint32_t a, float v) {
    asm volatile("st.shared.f32 [%0], %1;" ::"r"(a), "f"(v) : "memory");
}
__device__ __forceinline__ float lds32f(uint32_t a) {
    float v;
    asm volatile("ld.shared.f32 %0, [%1];" : "=f"(v) : "r"(a) : "memory");
    return v;
}
#define F8(d, b) \
    "+f"(d[b]), "+f"(d[b + 1]), "+f"(d[b + 2]), "+f"(d[b + 3]), "+f"(d[b + 4]), "+f"(d[b + 5]), "+f"(d[b + 6]), "+f"(d[b + 7])

template <int TB>
__device__ __forceinline__ void wgmma_n128(float (&d)[64], uint32_t a0, uint32_t a1, uint32_t a2, uint32_t a3,
                                           uint64_t db, int sc) {
    asm volatile(
        "{\n.reg .pred p;\nsetp.ne.b32 p, %69, 0;\n"
        "wgmma.mma_async.sync.aligned.m64n128k16.f32.bf16.bf16 "
        "{%0,%1,%2,%3,%4,%5,%6,%7,%8,%9,%10,%11,%12,%13,%14,%15,%16,%17,%18,%19,%20,%21,%22,%23,%24,%25,%26,%27,%28,%29,%30,%31,"
        "%32,%33,%34,%35,%36,%37,%38,%39,%40,%41,%42,%43,%44,%45,%46,%47,%48,%49,%50,%51,%52,%53,%54,%55,%56,%57,%58,%59,%60,%61,%62,%63},"
        "{%64,%65,%66,%67}, %68, p, 1, 1, %70;\n}"
        : F8(d, 0), F8(d, 8), F8(d, 16), F8(d, 24), F8(d, 32), F8(d, 40), F8(d, 48), F8(d, 56)
        : "r"(a0), "r"(a1), "r"(a2), "r"(a3), "l"(db), "r"(sc), "n"(TB));
}
#define O8(d, b) \
    "=f"(d[b]), "=f"(d[b + 1]), "=f"(d[b + 2]), "=f"(d[b + 3]), "=f"(d[b + 4]), "=f"(d[b + 5]), "=f"(d[b + 6]), "=f"(d[b + 7])
template <int TB>
__device__ __forceinline__ void wgmma_n128_z(float (&d)[64], uint32_t a0, uint32_t a1, uint32_t a2, uint32_t a3,
                                             uint64_t db) {
    asm volatile(
        "wgmma.mma_async.sync.aligned.m64n128k16.f32.bf16.bf16 "
        "{%0,%1,%2,%3,%4,%5,%6,%7,%8,%9,%10,%11,%12,%13,%14,%15,%16,%17,%18,%19,%20,%21,%22,%23,%24,%25,%26,%27,%28,%29,%30,%31,"
        "%32,%33,%34,%35,%36,%37,%38,%39,%40,%41,%42,%43,%44,%45,%46,%47,%48,%49,%50,%51,%52,%53,%54,%55,%56,%57,%58,%59,%60,%61,%62,%63},"
        "{%64,%65,%66,%67}, %68, 0, 1, 1, %69;"
        : O8(d, 0), O8(d, 8), O8(d, 16), O8(d, 24), O8(d, 32), O8(d, 40), O8(d, 48), O8(d, 56)
        : "r"(a0), "r"(a1), "r"(a2), "r"(a3), "l"(db), "n"(TB));
}
template <int TB>
__device__ __forceinline__ void wgmma_n64_z(float (&d)[32], uint32_t a0, uint32_t a1, uint32_t a2, uint32_t a3,
                                            uint64_t db) {
    asm volatile(
        "wgmma.mma_async.sync.aligned.m64n64k16.f32.bf16.bf16 "
        "{%0,%1,%2,%3,%4,%5,%6,%7,%8,%9,%10,%11,%12,%13,%14,%15,%16,%17,%18,%19,%20,%21,%22,%23,%24,%25,%26,%27,%28,%29,%30,%31},"
        "{%32,%33,%34,%35}, %36, 0, 1, 1, %37;"
        : O8(d, 0), O8(d, 8), O8(d, 16), O8(d, 24)
        : "r"(a0), "r"(a1), "r"(a2), "r"(a3), "l"(db), "n"(TB));
}
template <int TB>
__device__ __forceinline__ void wgmma_n64(float (&d)[32], uint32_t a0, uint32_t a1, uint32_t a2, uint32_t a3,
                                          uint64_t db) {
    asm volatile(
        "wgmma.mma_async.sync.aligned.m64n64k16.f32.bf16.bf16 "
        "{%0,%1,%2,%3,%4,%5,%6,%7,%8,%9,%10,%11,%12,%13,%14,%15,%16,%17,%18,%19,%20,%21,%22,%23,%24,%25,%26,%27,%28,%29,%30,%31},"
        "{%32,%33,%34,%35}, %36, 1, 1, 1, %37;"
        : F8(d, 0), F8(d, 8), F8(d, 16), F8(d, 24)
        : "r"(a0), "r"(a1), "r"(a2), "r"(a3), "l"(db), "n"(TB));
}

__device__ __forceinline__ uint64_t desc_of(uint32_t saddr) {
    return (uint64_t)(((saddr >> 4) & 0x3FFFu) | (512u << 16)) | ((uint64_t)(64u | (1u << 30)) << 32);
}

struct Ring {
    uint32_t slot;
    uint32_t phase;
    __device__ __forceinline__ void next() {
        if (++slot == 8) {
            slot = 0;
            phase ^= 1;
        }
    }
};

struct Ctx {
    uint32_t sbase;
    uint32_t rel_cta;
    __device__ __forceinline__ void wait_full(uint32_t slot, uint32_t phase) const {
        mbar_wait(sbase + OFF_FULL + slot * 8, phase);
    }
    __device__ __forceinline__ void release(uint32_t slot) const {
        if (rel_cta < 2) mbar_arrive_cluster(sbase + OFF_EMPTY + slot * 8, rel_cta);
    }
};

__device__ __forceinline__ void gemm_n128(float (&d)[64], const uint32_t (&a)[144], const Ctx& c, Ring& r, bool nine,
                                          int kick) {
    uint32_t prev = 0;
#pragma unroll
    for (int s = 0; s < 9; s++) {
        if (s < 8 || nine) {
            c.wait_full(r.slot, r.phase);
            uint64_t db = desc_of(c.sbase + r.slot * SLOT_BYTES);
            wg_fence();
#pragma unroll
            for (int k = 0; k < 4; k++) {
                if ((s | k) == 0)
                    wgmma_n128_z<1>(d, a[0], a[1], a[2], a[3], db);
                else
                    wgmma_n128<1>(d, a[s * 16 + k * 4], a[s * 16 + k * 4 + 1], a[s * 16 + k * 4 + 2],
                                  a[s * 16 + k * 4 + 3], db + k * 128, 1);
            }
            wg_commit();
            if (s == 3 && kick) bar_arrive(kick, 256);
            if (s > 0) {
                wg_wait<1>();
                c.release(prev);
            }
            prev = r.slot;
            r.next();
        }
    }
    wg_wait<0>();
    c.release(prev);
    pin(d);
}
__device__ __forceinline__ void gemm_n64(float (&d)[32], const uint32_t (&a)[144], const Ctx& c, Ring& r, bool nine) {
    uint32_t prev = 0;
#pragma unroll
    for (int s = 0; s < 5; s++) {
        if (s < 4 || nine) {
            c.wait_full(r.slot, r.phase);
            uint64_t db = desc_of(c.sbase + r.slot * SLOT_BYTES);
            wg_fence();
#pragma unroll
            for (int k = 0; k < 8; k++) {
                if ((s | k) == 0)
                    wgmma_n64_z<1>(d, a[0], a[1], a[2], a[3], db);
                else if (s * 8 + k < 36)
                    wgmma_n64<1>(d, a[s * 32 + k * 4], a[s * 32 + k * 4 + 1], a[s * 32 + k * 4 + 2],
                                 a[s * 32 + k * 4 + 3], db + k * 128);
            }
            wg_commit();
            if (s > 0) {
                wg_wait<1>();
                c.release(prev);
            }
            prev = r.slot;
            r.next();
        }
    }
    wg_wait<0>();
    c.release(prev);
    pin(d);
}
__device__ __forceinline__ void st_part(unsigned long long* p, float a, float b, float c, float d, uint32_t tag) {
    const uint32_t lo = (pack_bf16(a, b) & ~1u) | tag, hi = pack_bf16(c, d);
    asm volatile("{\n.reg .b64 t;\nmov.b64 t, {%1, %2};\nst.relaxed.gpu.global.b64 [%0], t;\n}" ::"l"(p), "r"(lo), "r"(hi)
                 : "memory");
}
__device__ __forceinline__ uint2 ld_part(const unsigned long long* p) {
    uint2 r;
    asm volatile("{\n.reg .b64 t;\nld.relaxed.gpu.global.b64 t, [%2];\nmov.b64 {%0, %1}, t;\n}"
                 : "=r"(r.x), "=r"(r.y)
                 : "l"(p));
    return r;
}
__device__ __forceinline__ void proj_partials(const uint32_t (&a)[144], const Ctx& c, Ring& r, bool nine,
                                              unsigned long long* dst  , uint32_t tag) {
#pragma unroll 1
    for (int p = 0; p < 4; p++) {
        float d[64];
        gemm_n128(d, a, c, r, nine, 0);
#pragma unroll
        for (int j = 0; j < 16; j++) st_part(dst + (p * 16 + j) * 32, d[4 * j], d[4 * j + 1], d[4 * j + 2], d[4 * j + 3], tag);
    }
    float d[32];
    gemm_n64(d, a, c, r, nine);
#pragma unroll
    for (int j = 0; j < 8; j++) st_part(dst + (64 + j) * 32, d[4 * j], d[4 * j + 1], d[4 * j + 2], d[4 * j + 3], tag);
}

__device__ __forceinline__ void row_reduce(float& s0, float& s1, uint32_t red, int warp, int lane) {
    s0 += __shfl_xor_sync(0xffffffffu, s0, 1);
    s1 += __shfl_xor_sync(0xffffffffu, s1, 1);
    s0 += __shfl_xor_sync(0xffffffffu, s0, 2);
    s1 += __shfl_xor_sync(0xffffffffu, s1, 2);
    if ((lane & 3) == 0) {
        sts32f(red + (warp * 16 + (lane >> 2)) * 4, s0);
        sts32f(red + (warp * 16 + 8 + (lane >> 2)) * 4, s1);
    }
    bar_sync(3, 256);
    s0 = 0.f;
    s1 = 0.f;
#pragma unroll
    for (int w = 0; w < 8; w++) {
        s0 += lds32f(red + (w * 16 + (lane >> 2)) * 4);
        s1 += lds32f(red + (w * 16 + 8 + (lane >> 2)) * 4);
    }
}
__device__ __forceinline__ void layernorm_rows(float (&v)[36], uint32_t red, int warp, int lane) {
    float s0 = 0.f, s1 = 0.f;
#pragma unroll
    for (int j = 0; j < 9; j++) {
        s0 += v[4 * j] + v[4 * j + 1];
        s1 += v[4 * j + 2] + v[4 * j + 3];
    }
    row_reduce(s0, s1, red, warp, lane);
    const float m0 = s0 * (1.f / DM), m1 = s1 * (1.f / DM);
    s0 = 0.f;
    s1 = 0.f;
#pragma unroll
    for (int j = 0; j < 9; j++) {
        v[4 * j] -= m0;
        v[4 * j + 1] -= m0;
        v[4 * j + 2] -= m1;
        v[4 * j + 3] -= m1;
        s0 += v[4 * j] * v[4 * j] + v[4 * j + 1] * v[4 * j + 1];
        s1 += v[4 * j + 2] * v[4 * j + 2] + v[4 * j + 3] * v[4 * j + 3];
    }
    row_reduce(s0, s1, red + 512, warp, lane);
    const float r0 = rsqrtf(s0 * (1.f / DM) + 1e-5f), r1 = rsqrtf(s1 * (1.f / DM) + 1e-5f);
#pragma unroll
    for (int j = 0; j < 9; j++) {
        v[4 * j] *= r0;
        v[4 * j + 1] *= r0;
        v[4 * j + 2] *= r1;
        v[4 * j + 3] *= r1;
    }
}
__device__ __forceinline__ void load_mod0(float (&m)[3][18], const uint32_t* src, uint32_t tag) {
    const uint32_t t0 = clk32();
    while (true) {
        uint2 u[2][9];
#pragma unroll
        for (int n = 0; n < 2; n++)
#pragma unroll
            for (int j = 0; j < 9; j++)
                asm volatile("ld.relaxed.gpu.global.v2.u32 {%0,%1}, [%2];"
                             : "=r"(u[n][j].x), "=r"(u[n][j].y)
                             : "l"(src + n * DM + j * 64));
        uint32_t bad = 0;
#pragma unroll
        for (int n = 0; n < 2; n++)
#pragma unroll
            for (int j = 0; j < 9; j++) {
                bad |= (u[n][j].x ^ tag) | (u[n][j].y ^ tag);
                m[n + 1][2 * j] = __uint_as_float(u[n][j].x & 0xffff0000u);
                m[n + 1][2 * j + 1] = __uint_as_float(u[n][j].y & 0xffff0000u);
            }
        if (__all_sync(0xffffffffu, (bad & 0xffffu) == 0) || clk32() - t0 > WAIT_LIMIT) break;
    }
}
__device__ __forceinline__ void st_relaxed2(uint2* p, uint32_t x, uint32_t y) {
    asm volatile("st.relaxed.gpu.global.v2.u32 [%0], {%1, %2};" ::"l"(p), "r"(x), "r"(y) : "memory");
}
__device__ __forceinline__ void modulate_store(const float (&v)[36], const float (&shift)[18], const float (&scale)[18],
                                               uint4* hbuf  , int warp, int lane) {
    uint2* dst = reinterpret_cast<uint2*>(hbuf) + ((warp >> 1) * 32 + lane) * 2 + (warp & 1);
#pragma unroll
    for (int j = 0; j < 9; j++) {
        const float c0 = round_bf16(1.f + scale[2 * j]), c1 = round_bf16(1.f + scale[2 * j + 1]);
        uint2 o;
        o.x = pack_bf16(fmaf(v[4 * j], c0, shift[2 * j]), fmaf(v[4 * j + 1], c1, shift[2 * j + 1]));
        o.y = pack_bf16(fmaf(v[4 * j + 2], c0, shift[2 * j]), fmaf(v[4 * j + 3], c1, shift[2 * j + 1]));
        st_relaxed2(dst + j * 256, max(o.x, 1u), max(o.y, 1u));
    }
}
__device__ __forceinline__ void clear_h(uint4* hbuf, int warp, int lane) {
    uint2* dst = reinterpret_cast<uint2*>(hbuf) + ((warp >> 1) * 32 + lane) * 2 + (warp & 1);
#pragma unroll
    for (int j = 0; j < 9; j++) st_relaxed2(dst + j * 256, 0u, 0u);
}
__device__ __forceinline__ void sum_partials(float (&v)[36], const unsigned long long* src  ,
                                             uint32_t tag) {
    const uint32_t t0 = clk32();
    while (true) {
        uint2 t[8][8];
#pragma unroll
        for (int s = 0; s < 8; s++)
#pragma unroll
            for (int j = 0; j < 8; j++) t[s][j] = ld_part(src + (s * 72 + j * 8) * 32);
        uint32_t bad = 0;
#pragma unroll
        for (int s = 0; s < 8; s++)
#pragma unroll
            for (int j = 0; j < 8; j++) {
                bad |= t[s][j].x ^ tag;
                if (s == 0) {
                    v[4 * j] = bf_lo(t[s][j].x);
                    v[4 * j + 1] = bf_hi(t[s][j].x);
                    v[4 * j + 2] = bf_lo(t[s][j].y);
                    v[4 * j + 3] = bf_hi(t[s][j].y);
                } else {
                    v[4 * j] += bf_lo(t[s][j].x);
                    v[4 * j + 1] += bf_hi(t[s][j].x);
                    v[4 * j + 2] += bf_lo(t[s][j].y);
                    v[4 * j + 3] += bf_hi(t[s][j].y);
                }
            }
        if (__all_sync(0xffffffffu, (bad & 1u) == 0) || clk32() - t0 > WAIT_LIMIT) break;
    }
}
__device__ __forceinline__ void sum_tail(float (&v)[36], float (&m)[3][18], const unsigned long long* src, uint32_t tag,
                                         const uint32_t* gate, const uint32_t* shsc, uint32_t mtag) {
    const uint32_t t0 = clk32();
    while (true) {
        uint2 t[8], u[3][9];
#pragma unroll
        for (int s = 0; s < 8; s++) t[s] = ld_part(src + (s * 72 + 64) * 32);
#pragma unroll
        for (int n = 0; n < 3; n++)
#pragma unroll
            for (int j = 0; j < 9; j++)
                asm volatile("ld.relaxed.gpu.global.v2.u32 {%0,%1}, [%2];"
                             : "=r"(u[n][j].x), "=r"(u[n][j].y)
                             : "l"((n == 0 ? gate : shsc + (n - 1) * DM) + j * 64));
        uint32_t bad = 0, badm = 0;
        v[32] = v[33] = v[34] = v[35] = 0.f;
#pragma unroll
        for (int s = 0; s < 8; s++) {
            bad |= t[s].x ^ tag;
            v[32] += bf_lo(t[s].x);
            v[33] += bf_hi(t[s].x);
            v[34] += bf_lo(t[s].y);
            v[35] += bf_hi(t[s].y);
        }
#pragma unroll
        for (int n = 0; n < 3; n++)
#pragma unroll
            for (int j = 0; j < 9; j++) {
                badm |= (u[n][j].x ^ mtag) | (u[n][j].y ^ mtag);
                m[n][2 * j] = __uint_as_float(u[n][j].x & 0xffff0000u);
                m[n][2 * j + 1] = __uint_as_float(u[n][j].y & 0xffff0000u);
            }
        if (__all_sync(0xffffffffu, ((bad & 1u) | (badm & 0xffffu)) == 0) || clk32() - t0 > WAIT_LIMIT) break;
    }
}
template <int K0, int K1>
__device__ __forceinline__ void poll_frags(uint32_t (&a)[144], const uint4* src  ) {
    const uint32_t t0 = clk32();
    while (true) {
#pragma unroll
        for (int k = K0; k < K1; k++)
            asm volatile("ld.relaxed.gpu.global.v4.u32 {%0,%1,%2,%3}, [%4];"
                         : "=r"(a[4 * k]), "=r"(a[4 * k + 1]), "=r"(a[4 * k + 2]), "=r"(a[4 * k + 3])
                         : "l"(src + k * 32));
        uint32_t m0 = a[4 * K0], m1 = a[4 * K0 + 1];
#pragma unroll
        for (int i = 4 * K0 + 2; i < 4 * K1; i += 2) {
            m0 = min(m0, a[i]);
            m1 = min(m1, a[i + 1]);
        }
        if (__all_sync(0xffffffffu, min(m0, m1) != 0) || clk32() - t0 > WAIT_LIMIT) break;
    }
}

constexpr float SM_SCALE = 0.08838834764831845f * 1.4426950408889634f;
constexpr float SM_HI = 1.2089258e24f;
constexpr float SM_LO = 9.0949470e-13f;
__device__ __forceinline__ void qk_step(float (&s)[32], const uint32_t (&q)[32], uint64_t dk) {
#pragma unroll
    for (int k = 0; k < 8; k++) {
        if (k == 0)
            wgmma_n64_z<0>(s, q[0], q[1], q[2], q[3], dk);
        else
            wgmma_n64<0>(s, q[4 * k], q[4 * k + 1], q[4 * k + 2], q[4 * k + 3], dk + (k >> 2) * 512 + (k & 3) * 2);
    }
}
__device__ __forceinline__ void pv_step(float (&o)[64], const uint32_t (&p)[16], uint64_t dv, int acc) {
#pragma unroll
    for (int k = 0; k < 4; k++)
        wgmma_n128<1>(o, p[4 * k], p[4 * k + 1], p[4 * k + 2], p[4 * k + 3], dv + k * 128, k != 0 ? 1 : acc);
}
template <bool SHIFT>
__device__ __forceinline__ void exp_step(const float (&s)[32], uint32_t (&p)[16], float n0, float n1, float& s0,
                                         float& s1) {
#pragma unroll
    for (int i = 0; i < 8; i++) {
        const float e0 = ex2(SHIFT ? s[4 * i] + n0 : s[4 * i]), e1 = ex2(SHIFT ? s[4 * i + 1] + n0 : s[4 * i + 1]);
        const float e2 = ex2(SHIFT ? s[4 * i + 2] + n1 : s[4 * i + 2]), e3 = ex2(SHIFT ? s[4 * i + 3] + n1 : s[4 * i + 3]);
        if (i == 0) {
            s0 = e0 + e1;
            s1 = e2 + e3;
        } else {
            s0 += e0 + e1;
            s1 += e2 + e3;
        }
        p[2 * i] = pack_bf16(e0, e1);
        p[2 * i + 1] = pack_bf16(e2, e3);
    }
}
__device__ __forceinline__ void row_max(const float (&sa)[32], const float (&sb)[32], float& x0, float& x1) {
    float xa[8];
#pragma unroll
    for (int i = 0; i < 8; i++) xa[i] = fmaxf(sa[i], sb[i]);
#pragma unroll
    for (int k = 1; k < 4; k++)
#pragma unroll
        for (int i = 0; i < 8; i++) xa[i] = fmaxf(xa[i], fmaxf(sa[8 * k + i], sb[8 * k + i]));
    x0 = fmaxf(fmaxf(xa[0], xa[1]), fmaxf(xa[4], xa[5]));
    x1 = fmaxf(fmaxf(xa[2], xa[3]), fmaxf(xa[6], xa[7]));
    x0 = fmaxf(x0, __shfl_xor_sync(0xffffffffu, x0, 1));
    x1 = fmaxf(x1, __shfl_xor_sync(0xffffffffu, x1, 1));
    x0 = fmaxf(x0, __shfl_xor_sync(0xffffffffu, x0, 2));
    x1 = fmaxf(x1, __shfl_xor_sync(0xffffffffu, x1, 2));
}
__device__ __forceinline__ void inv_row_sums(float l0, float l1, float& i0, float& i1) {
    l0 += __shfl_xor_sync(0xffffffffu, l0, 1);
    l1 += __shfl_xor_sync(0xffffffffu, l1, 1);
    l0 += __shfl_xor_sync(0xffffffffu, l0, 2);
    l1 += __shfl_xor_sync(0xffffffffu, l1, 2);
    i0 = rcp(l0);
    i1 = rcp(l1);
}

__device__ __forceinline__ uint32_t ld_epoch(const Scratch* sc) {
    uint32_t e;
    asm volatile("ld.relaxed.gpu.global.u32 %0, [%1];" : "=r"(e) : "l"(&sc->epoch) : "memory");
    return e;
}
__device__ __forceinline__ float silu_bf16(unsigned short c) {
    const float cv = bf_lo(c);
    return round_bf16(cv * rcp(1.f + ex2(-1.4426950408889634f * cv)));
}
__device__ __forceinline__ void st_mod(uint32_t* p, float v, uint32_t tag) {
    asm volatile("st.relaxed.gpu.global.u32 [%0], %1;" ::"l"(p), "r"(__float_as_uint(round_bf16(v)) | tag)
                 : "memory");
}
__device__ __forceinline__ void mod_block(const uint4 (&w)[5], const float (&sc)[5], uint32_t* dst, uint32_t red,
                                          int warp, int lane, uint32_t tag) {
    float acc[8];
#pragma unroll
    for (int e = 0; e < 8; e++) acc[e] = 0.f;
#pragma unroll
    for (int i = 0; i < 5; i++) {
        acc[0] = fmaf(sc[i], bf_lo(w[i].x), acc[0]);
        acc[1] = fmaf(sc[i], bf_hi(w[i].x), acc[1]);
        acc[2] = fmaf(sc[i], bf_lo(w[i].y), acc[2]);
        acc[3] = fmaf(sc[i], bf_hi(w[i].y), acc[3]);
        acc[4] = fmaf(sc[i], bf_lo(w[i].z), acc[4]);
        acc[5] = fmaf(sc[i], bf_hi(w[i].z), acc[5]);
        acc[6] = fmaf(sc[i], bf_lo(w[i].w), acc[6]);
        acc[7] = fmaf(sc[i], bf_hi(w[i].w), acc[7]);
    }
#pragma unroll
    for (int o = 2; o < 32; o <<= 1)
#pragma unroll
        for (int e = 0; e < 8; e++) acc[e] += __shfl_xor_sync(0xffffffffu, acc[e], o);
    if (lane < 2) {
#pragma unroll
        for (int e = 0; e < 8; e++) sts32f(red + (warp * 16 + lane * 8 + e) * 4, acc[e]);
    }
    bar_sync(3, 256);
    if (warp == 0 && lane < 16) {
        float s = 0.f;
#pragma unroll
        for (int w8 = 0; w8 < 8; w8++) s += lds32f(red + (w8 * 16 + lane) * 4);
        st_mod(dst + lane, s, tag);
    }
}

__global__ void __cluster_dims__(2, 1, 1) __launch_bounds__(384, 1)
    fused_block_kernel(const __grid_constant__ Params maps) {
    extern __shared__ uint8_t smem_raw[];
    uint32_t sbase = (smem_u32(smem_raw) + 1023u) & ~1023u;
    asm volatile("" : "+r"(sbase));
    const int b = blockIdx.x;
    const int rank = b & 1;
    const int mt = ((b >> 1) & 7) * 2 + rank;
    const int g = b >> 4;
    const int warp = __shfl_sync(0xffffffffu, threadIdx.x >> 5, 0);
    const int lane = threadIdx.x & 31;
    Scratch* const sc_ = maps.sc;
    const __nv_bfloat16* const wmod = maps.wmod;
    const __nv_bfloat16* const cvec = maps.cvec;

    if (warp >= 8) {
        asm volatile("setmaxnreg.dec.sync.aligned.u32 24;");
        if (warp == 8 && lane == 0) {
#pragma unroll
            for (int i = 0; i < 8; i++) {
                mbar_init(sbase + OFF_FULL + i * 8, 1);
                mbar_init(sbase + OFF_EMPTY + i * 8, 4);
            }
            asm volatile("fence.mbarrier_init.release.cluster;" ::: "memory");
            asm volatile("barrier.cluster.arrive.relaxed;\nbarrier.cluster.wait;" ::: "memory");
            uint32_t slot = 0, phase = 1;
            const uint32_t dst0 = sbase + rank * BOX_BYTES;
            auto acquire = [&](uint32_t bytes) {
                mbar_wait(sbase + OFF_EMPTY + slot * 8, phase);
                mbar_expect_tx(sbase + OFF_FULL + slot * 8, bytes);
            };
            auto adv8 = [&]() {
                if (++slot == 8) {
                    slot = 0;
                    phase ^= 1;
                }
            };
#pragma unroll 1
            for (int hq = 0; hq < 4; hq++) {
                const int col = (g * 4 + ((hq + 1) & 3)) * 128 + rank * 64;
                if (hq == 2) {
                    l2_prefetch(maps.kc + (size_t)(g * 4 * 2048 + (b & 15) * 64) * 128, SLOT_BYTES);
                    l2_prefetch(maps.vc + (size_t)(g * 4 * 2048 + (b & 15) * 64) * 128, SLOT_BYTES);
                }
#pragma unroll 1
                for (int kc = 0; kc < 9; kc++) {
                    acquire(SLOT_BYTES);
                    tma_mc(dst0 + slot * SLOT_BYTES, &maps.wq, col, kc * 64, sbase + OFF_FULL + slot * 8);
                    adv8();
                }
            }
            const int row0 = g * 4 * 2048;
#pragma unroll 1
            for (int n = 0; n < 128; n++) {
                if (n < 4) mbar_wait(sbase + OFF_EMPTY + (slot + 1) * 8, phase);
                acquire(2 * SLOT_BYTES);
                const uint32_t bar = sbase + OFF_FULL + slot * 8;
                const int r0 = n == 0 ? 0 : (n == 127 ? 126 : n + 1);
                const int r1 = n == 0 ? 1 : (n == 127 ? 127 : n - 1);
                tma_mc(dst0 + slot * SLOT_BYTES, n == 127 ? &maps.v : &maps.k, rank * 64, row0 + r0 * 64, bar);
                tma_mc(dst0 + (slot + 1) * SLOT_BYTES, n == 0 ? &maps.k : &maps.v, rank * 64, row0 + r1 * 64, bar);
                adv8();
                adv8();
                const int u = n + KV_AHEAD;
                if (u < 128 && (u & 15) == (b & 15)) {
                    l2_prefetch(maps.kc + (size_t)(row0 + u * 64) * 128, SLOT_BYTES);
                    l2_prefetch(maps.vc + (size_t)(row0 + u * 64) * 128, SLOT_BYTES);
                }
            }
#pragma unroll 1
            for (int p = 0; p < 4; p++)
#pragma unroll 1
                for (int kc = 0; kc < 8; kc++) {
                    acquire(SLOT_BYTES);
                    tma_mc(dst0 + slot * SLOT_BYTES, &maps.wo, p * 128 + rank * 64, g * 512 + kc * 64,
                           sbase + OFF_FULL + slot * 8);
                    adv8();
                }
#pragma unroll 1
            for (int kc = 0; kc < 4; kc++) {
                acquire(SLOT_BYTES);
                tma_mc(dst0 + slot * SLOT_BYTES, &maps.wo, 512, g * 512 + kc * 128 + rank * 64,
                       sbase + OFF_FULL + slot * 8);
                adv8();
            }
            const CUtensorMap* mg = rank ? &maps.wu : &maps.wg;
#pragma unroll 1
            for (int ch = 0; ch < 9; ch++)
#pragma unroll 1
                for (int kc = 0; kc < 9; kc++) {
                    acquire(SLOT_BYTES);
                    tma_mc(dst0 + slot * SLOT_BYTES, mg, g * 576 + ch * 64, kc * 64, sbase + OFF_FULL + slot * 8);
                    adv8();
                }
#pragma unroll 1
            for (int p = 0; p < 4; p++)
#pragma unroll 1
                for (int kc = 2; kc < 11; kc++) {
                    acquire(SLOT_BYTES);
                    tma_mc(dst0 + slot * SLOT_BYTES, &maps.wd, p * 128 + rank * 64, g * 576 + (kc < 9 ? kc : kc - 9) * 64,
                           sbase + OFF_FULL + slot * 8);
                    adv8();
                }
#pragma unroll 1
            for (int i = 0; i < 5; i++) {
                acquire(i < 4 ? SLOT_BYTES : BOX_BYTES);
                const int kc = 2 * i + rank + 2;
                if (i < 4 || rank == 0)
                    tma_mc(dst0 + slot * SLOT_BYTES, &maps.wd, 512, g * 576 + (kc < 9 ? kc : kc - 9) * 64,
                           sbase + OFF_FULL + slot * 8);
                adv8();
            }
        } else if (warp == 11) {
            const int row = b * 5 + lane;
            if (lane < 5 && row < DM) l2_prefetch(wmod + (size_t)row * (6 * DM), 2 * DM * 2);
        } else if (warp == 9 || warp == 10) {
            asm volatile("barrier.cluster.arrive.relaxed.aligned;" ::: "memory");
            const uint32_t tag = (ld_epoch(sc_) + 1) & 0xffffu;
            bar_sync(4, 320);
            const int blk = warp == 9 ? 72 + b : 200 + b;
            if (blk < 216) {
                float acc[8];
#pragma unroll
                for (int e = 0; e < 8; e++) acc[e] = 0.f;
                const uint4* wp = reinterpret_cast<const uint4*>(wmod + (size_t)(lane >> 1) * (6 * DM) + blk * 16) + (lane & 1);
                const unsigned short* cp = reinterpret_cast<const unsigned short*>(cvec) + (lane >> 1);
#pragma unroll 1
                for (int i = 0; i < 36; i++) {
                    const uint4 w = __ldg(wp + (size_t)i * (16 * 6 * DM / 8));
                    const float sc = silu_bf16(__ldg(cp + i * 16));
                    acc[0] = fmaf(sc, bf_lo(w.x), acc[0]);
                    acc[1] = fmaf(sc, bf_hi(w.x), acc[1]);
                    acc[2] = fmaf(sc, bf_lo(w.y), acc[2]);
                    acc[3] = fmaf(sc, bf_hi(w.y), acc[3]);
                    acc[4] = fmaf(sc, bf_lo(w.z), acc[4]);
                    acc[5] = fmaf(sc, bf_hi(w.z), acc[5]);
                    acc[6] = fmaf(sc, bf_lo(w.w), acc[6]);
                    acc[7] = fmaf(sc, bf_hi(w.w), acc[7]);
                }
#pragma unroll
                for (int o = 2; o < 32; o <<= 1)
#pragma unroll
                    for (int e = 0; e < 8; e++) acc[e] += __shfl_xor_sync(0xffffffffu, acc[e], o);
                if (lane < 2) {
#pragma unroll
                    for (int e = 0; e < 8; e++) st_mod(sc_->mod + blk * 16 + lane * 8 + e, acc[e], tag);
                }
            }
        }
    } else {
        asm volatile("setmaxnreg.inc.sync.aligned.u32 240;");
        const int wg = warp >> 2;
        const int tid = threadIdx.x;
        Ctx cx;
        cx.sbase = sbase;
        cx.rel_cta = (lane == 0 && (warp & 3) < 2) ? (warp & 3) : 2;
        const uint32_t red = sbase + OFF_RED;
        const int own = mt * 8 + g;
        const int wown = mt * 8 + warp;
        PROF(0);
        PROFG(30);
        PROFR(17);
        const uint32_t epoch = ld_epoch(sc_);
        {
            uint4 w1[5];
            unsigned short cu[5];
            const int half = tid & 1, r0 = tid >> 1;
            if (b < 72) {
#pragma unroll
                for (int i = 0; i < 5; i++) {
                    const int row = min(r0 + 128 * i, DM - 1);
                    cu[i] = __ldg(reinterpret_cast<const unsigned short*>(cvec) + row);
                    w1[i] = __ldg(reinterpret_cast<const uint4*>(wmod + (size_t)row * (6 * DM) + half * 8) + b * 2);
                }
            }
            if (warp == 0) {
                if (lane == 0) {
                    mbar_init(sbase + OFF_XBAR, 1);
                    asm volatile("fence.mbarrier_init.release.cluster;\nfence.proxy.async.shared::cta;" ::: "memory");
                    mbar_expect_tx(sbase + OFF_XBAR, 16 * DM * 2);
                }
                __syncwarp();
                if (lane < 16)
                    asm volatile(
                        "cp.async.bulk.shared::cluster.global.mbarrier::complete_tx::bytes [%0], [%1], %2, [%3];" ::"r"(
                            sbase + 8 * SLOT_BYTES + lane * XROW_STRIDE),
                        "l"(maps.x + (size_t)(own * 16 + lane) * DM), "r"(DM * 2), "r"(sbase + OFF_XBAR)
                        : "memory");
                __syncwarp();
            }
            PROFR(18);
            asm volatile("barrier.cluster.arrive.relaxed.aligned;" ::: "memory");
            if (b < 72) {
                float sc[5];
#pragma unroll
                for (int i = 0; i < 5; i++) sc[i] = (r0 + 128 * i < DM) ? silu_bf16(cu[i]) : 0.f;
                mod_block(w1, sc, sc_->mod + b * 16, red + 1024, warp, lane, (epoch + 1) & 0xffffu);
            } else {
                bar_sync(3, 256);
            }
            asm volatile("" ::"r"(epoch) : "memory");
            bar_arrive(4, 320);
            PROFR(21);
        }

        Ring ring{0u, 0u};
        int stage = 0;
        asm volatile("" : "+r"(stage));
#pragma unroll 1
        for (;; stage++) {
            int tid, lane;
            asm volatile("mov.u32 %0, %%tid.x;" : "=r"(tid));
            lane = tid & 31;
            {
                float v[36], md[3][18];
                float4* x2buf = sc_->x2 + (size_t)b * 9 * 256 + tid;
                const uint32_t tag = (epoch + 1) & 0xffffu;
                const uint32_t* modp = sc_->mod + warp * 8 + (lane & 3) * 2;
                if (stage == 0) {
#pragma unroll
                    for (int i = 0; i < 18; i++) md[1][i] = md[2][i] = 0.f;
                    mbar_wait(sbase + OFF_XBAR, 0);
                    PROFR(22);
                    const uint32_t src = sbase + 8 * SLOT_BYTES + (lane >> 2) * XROW_STRIDE + warp * 16 + (lane & 3) * 4;
#pragma unroll
                    for (int j = 0; j < 9; j++) {
                        const uint32_t u0 = __float_as_uint(lds32f(src + j * 128));
                        const uint32_t u1 = __float_as_uint(lds32f(src + j * 128 + 8 * XROW_STRIDE));
                        v[4 * j] = bf_lo(u0);
                        v[4 * j + 1] = bf_hi(u0);
                        v[4 * j + 2] = bf_lo(u1);
                        v[4 * j + 3] = bf_hi(u1);
                    }
                } else {
                    const unsigned long long* psrc = sc_->part + (size_t)own * 8 * 72 * 32 + tid;
                    sum_partials(v, psrc, stage & 1);
                    PROF(stage == 1 ? 8 : 15);
                    float4 xr[9];
#pragma unroll
                    for (int j = 0; j < 9; j++) xr[j] = __ldcg(x2buf + j * 256);
                    sum_tail(v, md, psrc, stage & 1, modp + (stage * 3 - 1) * DM, modp + 3 * DM, tag);
                    const float gs = stage == 1 ? 1.f : 0.5f;
#pragma unroll
                    for (int j = 0; j < 9; j++) {
                        const float g0 = md[0][2 * j] * gs, g1 = md[0][2 * j + 1] * gs;
                        v[4 * j] = fmaf(g0, v[4 * j], xr[j].x);
                        v[4 * j + 1] = fmaf(g1, v[4 * j + 1], xr[j].y);
                        v[4 * j + 2] = fmaf(g0, v[4 * j + 2], xr[j].z);
                        v[4 * j + 3] = fmaf(g1, v[4 * j + 3], xr[j].w);
                    }
                    clear_h(sc_->h[stage - 1] + (size_t)own * 36 * 32, warp, lane);
                    if (stage == 2) {
                        __nv_bfloat16* dst = maps.out + (size_t)(own * 16 + (lane >> 2)) * DM + warp * 8 + (lane & 3) * 2;
#pragma unroll
                        for (int j = 0; j < 9; j++) {
                            *reinterpret_cast<uint32_t*>(dst + j * 64) = pack_bf16(v[4 * j], v[4 * j + 1]);
                            *reinterpret_cast<uint32_t*>(dst + j * 64 + 8 * DM) = pack_bf16(v[4 * j + 2], v[4 * j + 3]);
                        }
                        break;
                    }
                }
                PROF(stage == 0 ? 1 : 9);
                float keep[36];
#pragma unroll
                for (int i = 0; i < 36; i++) keep[i] = v[i];
                layernorm_rows(v, red, warp, lane);
                if (stage == 0) PROFR(27);
                if (stage == 0) load_mod0(md, modp, tag);
                if (stage == 0) PROFR(28);
                PROF(stage == 0 ? 2 : 10);
                modulate_store(v, md[1], md[2], sc_->h[stage] + (size_t)own * 36 * 32, warp, lane);
#pragma unroll
                for (int j = 0; j < 9; j++)
                    __stcg(x2buf + j * 256, make_float4(keep[4 * j], keep[4 * j + 1], keep[4 * j + 2], keep[4 * j + 3]));
                if (stage == 0) asm volatile("barrier.cluster.wait.aligned;" ::: "memory");
            }

            const uint32_t spill = sbase + 8 * SLOT_BYTES + wg * 3 * SLOT_BYTES + (tid & 127) * 16;
            uint32_t a[144];
            PROF(stage == 0 ? 3 : 11);
            poll_frags<32, 36>(a, sc_->h[stage] + (size_t)wown * 36 * 32 + lane);
            PROF(stage == 0 ? 4 : 12);
            if (stage == 1) PROFG(25);
            poll_frags<0, 32>(a, sc_->h[stage] + (size_t)wown * 36 * 32 + lane);
            uint4* hhbuf = sc_->hh + (size_t)b * 8 * 256 + tid;
            float d[64];
            if (wg == 1) bar_sync(5, 256);
#pragma unroll 1
            for (int ch = 0;; ch++) {
                gemm_n128(d, a, cx, ring, true, (ch == 0 && wg == 0) ? 5 : 0);
                if (stage == 0) {
#pragma unroll
                    for (int i = 0; i < 64; i++) d[i] *= SM_SCALE;
                    if (ch == 3) break;
#pragma unroll
                    for (int v = 0; v < 8; v++)
                        sts128(spill + (ch * 8 + v) * 2048, pack_bf16(d[8 * v], d[8 * v + 1]),
                               pack_bf16(d[8 * v + 2], d[8 * v + 3]), pack_bf16(d[8 * v + 4], d[8 * v + 5]),
                               pack_bf16(d[8 * v + 6], d[8 * v + 7]));
                } else {
#pragma unroll
                    for (int i = 0; i < 32; i++) {
                        const float gv = d[i], gu = gv * d[32 + i];
                        const float z = gv * fmaf(gv * gv, 0.7978845608028654f * 0.044715f, 0.7978845608028654f);
                        d[i] = fmaf(gu, tanh_fast(z), gu);
                    }
                    if (ch == 8) break;
#pragma unroll
                    for (int v = 0; v < 4; v++) {
                        const uint4 h4 = make_uint4(pack_bf16(d[8 * v], d[8 * v + 1]), pack_bf16(d[8 * v + 2], d[8 * v + 3]),
                                                    pack_bf16(d[8 * v + 4], d[8 * v + 5]), pack_bf16(d[8 * v + 6], d[8 * v + 7]));
                        if (ch < 2)
                            __stcg(hhbuf + (ch * 4 + v) * 256, h4);
                        else
                            sts128(spill + ((ch - 2) * 4 + v) * 2048, h4.x, h4.y, h4.z, h4.w);
                    }
                }
            }
            if (stage == 0) {
                uint32_t q[32];
#pragma unroll
                for (int i = 0; i < 32; i++) q[i] = pack_bf16(d[2 * i], d[2 * i + 1]);
                PROF(5);
                PROFG(23);
                {
                    float o[64], sa[32], sb[32];
                    uint32_t pa[16], pb[16];
#pragma unroll
                    for (int i = 0; i < 64; i++) o[i] = 0.f;
                    float n0 = 0.f, n1 = 0.f, l0 = 1.f, l1 = 1.f;
                    bool shifted = false;
                    const uint64_t dbase = desc_of(sbase);
                    const uint64_t dbk = dbase - (511u << 16);
                    const int my_bar = 1 + wg, other_bar = 2 - wg;

                    auto softmax_a = [&](bool first, float& s0, float& s1) {
                        if (first) {
                            shifted = false;
                            n0 = n1 = 0.f;
                            l0 = l1 = 0.f;
                        }
                        if (shifted)
                            exp_step<true>(sa, pa, n0, n1, s0, s1);
                        else
                            exp_step<false>(sa, pa, n0, n1, s0, s1);
                    };
                    auto softmax_b = [&](bool first, float s0, float s1) {
                        float u0, u1;
                        if (shifted)
                            exp_step<true>(sb, pb, n0, n1, u0, u1);
                        else
                            exp_step<false>(sb, pb, n0, n1, u0, u1);
                        s0 += u0;
                        s1 += u1;
                        bool bad = !(fmaxf(s0, s1) <= SM_HI);
                        if (first) {
                            float r0 = s0 + __shfl_xor_sync(0xffffffffu, s0, 1), r1 = s1 + __shfl_xor_sync(0xffffffffu, s1, 1);
                            r0 += __shfl_xor_sync(0xffffffffu, r0, 2);
                            r1 += __shfl_xor_sync(0xffffffffu, r1, 2);
                            bad = bad || !(fminf(r0, r1) >= SM_LO);
                        }
                        if (__any_sync(0xffffffffu, bad)) {
                            float x0, x1;
                            row_max(sa, sb, x0, x1);
                            x0 = -x0;
                            x1 = -x1;
                            if (!first) {
                                x0 = fminf(x0, n0);
                                x1 = fminf(x1, n1);
                                const float al0 = ex2(x0 - n0), al1 = ex2(x1 - n1);
                                l0 *= al0;
                                l1 *= al1;
#pragma unroll
                                for (int i = 0; i < 16; i++) {
                                    o[4 * i] *= al0;
                                    o[4 * i + 1] *= al0;
                                    o[4 * i + 2] *= al1;
                                    o[4 * i + 3] *= al1;
                                }
                            }
                            n0 = x0;
                            n1 = x1;
                            shifted = true;
                            exp_step<true>(sa, pa, n0, n1, s0, s1);
                            exp_step<true>(sb, pb, n0, n1, u0, u1);
                            s0 += u0;
                            s1 += u1;
                        }
                        l0 += s0;
                        l1 += s1;
                    };

                    cx.wait_full(4, 0);
                    if (wg == 1) bar_sync(my_bar, 256);
                    wg_fence();
                    qk_step(sa, q, dbk + 4 * 1024);
                    qk_step(sb, q, dbk + 5 * 1024);
                    wg_commit();
                    bar_arrive(other_bar, 256);
                    wg_wait<0>();
                    pin(sa);
                    pin(sb);
                    cx.release(4);
                    cx.wait_full(6, 0);
                    {
                        float s0, s1;
                        softmax_a(true, s0, s1);
                        softmax_b(true, s0, s1);
                    }
                    uint32_t alo = (uint32_t)dbase + 6 * 1024, blo = (uint32_t)dbase;
                    const uint32_t dhi = (uint32_t)(dbase >> 32);
#pragma unroll 1
                    for (int t = 1; t < 64; t++) {
                        const int j = t & 15;
                        const uint32_t sA = 2 + 4 * (t & 1), sB = 4 - 4 * (t & 1);
                        const uint64_t da = ((uint64_t)dhi << 32) | alo, db = ((uint64_t)dhi << 32) | blo;
                        TL(0);
                        bar_sync(my_bar, 256);
                        TL(2);
                        wg_fence();
                        pv_step(o, pa, da + 1024, j != 1);
                        qk_step(sa, q, da - (511u << 16));
                        wg_commit();
                        cx.wait_full(sB, ((36 + 4 * t) >> 3) & 1);
                        wg_fence();
                        qk_step(sb, q, db - (511u << 16));
                        pv_step(o, pb, db + 1024, 1);
                        wg_commit();
                        bar_arrive(other_bar, 256);
                        alo ^= 4096;
                        blo ^= 4096;
                        asm volatile("" : "+r"(alo), "+r"(blo));
                        TL(3);
                        wg_wait<1>();
                        pin(sa);
                        pin(pa);
                        TL(4);
                        cx.release(sA);
                        const float lp0 = l0, lp1 = l1;
                        float s0, s1;
                        softmax_a(j == 0, s0, s1);
                        TL(5);
                        wg_wait<0>();
                        pin(o);
                        pin(sb);
                        pin(pb);
                        TL(6);
                        cx.release(sB);
                        if (j == 0) {
                            float i0, i1;
                            inv_row_sums(lp0, lp1, i0, i1);
                            const uint32_t dst = spill + ((t >> 4) - 1) * 16384;
#pragma unroll
                            for (int v = 0; v < 8; v++)
                                sts128(dst + v * 2048, pack_bf16(o[8 * v] * i0, o[8 * v + 1] * i0),
                                       pack_bf16(o[8 * v + 2] * i1, o[8 * v + 3] * i1),
                                       pack_bf16(o[8 * v + 4] * i0, o[8 * v + 5] * i0),
                                       pack_bf16(o[8 * v + 6] * i1, o[8 * v + 7] * i1));
                        }
                        const uint32_t bn = sbase + OFF_FULL + (8 - sA) * 8, pn = ((38 + 4 * t) >> 3) & 1;
                        const bool okn = mbar_try(bn, pn);
                        TL(1);
                        softmax_b(j == 0, s0, s1);
                        if (!okn || j == 15) {
                            mbar_wait(bn, pn);
                            if (j == 15 && t < 63) {
                                const uint32_t src = spill + (t >> 4) * 16384;
#pragma unroll
                                for (int v = 0; v < 8; v++)
                                    lds128(src + v * 2048, q[4 * v], q[4 * v + 1], q[4 * v + 2], q[4 * v + 3]);
                            }
                        }
                        TL(7);
                    }
                    bar_sync(my_bar, 256);
                    wg_fence();
                    pv_step(o, pa, dbase + 2 * 1024, 1);
                    pv_step(o, pb, dbase + 3 * 1024, 1);
                    wg_commit();
                    if (wg == 0) bar_arrive(other_bar, 256);
                    float i0, i1;
                    inv_row_sums(l0, l1, i0, i1);
                    wg_wait<0>();
                    pin(o);
                    cx.release(2);
#pragma unroll
                    for (int i = 0; i < 16; i++) {
                        a[96 + 2 * i] = pack_bf16(o[4 * i] * i0, o[4 * i + 1] * i0);
                        a[96 + 2 * i + 1] = pack_bf16(o[4 * i + 2] * i1, o[4 * i + 3] * i1);
                    }
#pragma unroll
                    for (int i = 128; i < 144; i++) a[i] = 0;
                }
                ring.slot = 4;
                ring.phase = 0;
                PROF(6);
                PROFG(24);
            } else {
#pragma unroll
                for (int v = 0; v < 8; v++) {
                    const uint4 t = __ldcg(hhbuf + v * 256);
                    a[112 + 4 * v] = t.x;
                    a[113 + 4 * v] = t.y;
                    a[114 + 4 * v] = t.z;
                    a[115 + 4 * v] = t.w;
                }
#pragma unroll
                for (int i = 0; i < 16; i++) a[96 + i] = pack_bf16(d[2 * i], d[2 * i + 1]);
                PROF(13);
            }
#pragma unroll
            for (int v = 0; v < 24; v++) lds128(spill + v * 2048, a[4 * v], a[4 * v + 1], a[4 * v + 2], a[4 * v + 3]);

            proj_partials(a, cx, ring, stage != 0, sc_->part + ((size_t)wown * 8 + g) * 72 * 32 + lane, (stage + 1) & 1);
            PROF(stage == 0 ? 7 : 14);
            if (stage == 1) {
                PROFG(26);
                asm volatile("barrier.cluster.arrive.relaxed.aligned;" ::: "memory");
            }
        }
        PROF(16);
        PROFG(31);
        if (b == 0) {
            bar_sync(3, 256);
            if (tid == 0) sc_->epoch = epoch + 1;
        }
        asm volatile("barrier.cluster.wait.aligned;" ::: "memory");
    }
}

typedef CUresult (*EncodeFn)(CUtensorMap*, CUtensorMapDataType, cuuint32_t, void*, const cuuint64_t*, const cuuint64_t*,
                             const cuuint32_t*, const cuuint32_t*, CUtensorMapInterleave, CUtensorMapSwizzle,
                             CUtensorMapL2promotion, CUtensorMapFloatOOBfill);

void make_map(EncodeFn enc, CUtensorMap* m, const void* ptr, uint64_t rows, uint64_t cols) {
    cuuint64_t gdim[2] = {cols, rows};
    cuuint64_t gstr[1] = {cols * 2};
    cuuint32_t box[2] = {64, 64};
    cuuint32_t estr[2] = {1, 1};
    enc(m, CU_TENSOR_MAP_DATA_TYPE_BFLOAT16, 2, const_cast<void*>(ptr), gdim, gstr, box, estr,
        CU_TENSOR_MAP_INTERLEAVE_NONE, CU_TENSOR_MAP_SWIZZLE_128B, CU_TENSOR_MAP_L2_PROMOTION_L2_128B,
        CU_TENSOR_MAP_FLOAT_OOB_FILL_NONE);
}

}

extern "C" void kernel_launch(void* const* d_in, const int* in_sizes, int n_in, void* d_out, int out_size) {
    (void)in_sizes;
    (void)n_in;
    (void)out_size;
    void* fn = nullptr;
    cudaDriverEntryPointQueryResult qr;
    cudaGetDriverEntryPoint("cuTensorMapEncodeTiled", &fn, cudaEnableDefault, &qr);
    EncodeFn enc = (EncodeFn)fn;
    Params maps;
    maps.x = (const __nv_bfloat16*)d_in[0];
    maps.cvec = (const __nv_bfloat16*)d_in[9];
    maps.wmod = (const __nv_bfloat16*)d_in[10];
    maps.kc = (const __nv_bfloat16*)d_in[1];
    maps.vc = (const __nv_bfloat16*)d_in[2];
    maps.out = (__nv_bfloat16*)d_out;
    void* scp = nullptr;
    cudaGetSymbolAddress(&scp, g_scratch);
    maps.sc = (Scratch*)scp;
    make_map(enc, &maps.k, d_in[1], 32 * 2048, 128);
    make_map(enc, &maps.v, d_in[2], 32 * 2048, 128);
    make_map(enc, &maps.wq, d_in[3], 576, 4096);
    make_map(enc, &maps.wo, d_in[4], 4096, 576);
    make_map(enc, &maps.wg, d_in[6], 576, 4608);
    make_map(enc, &maps.wu, d_in[7], 576, 4608);
    make_map(enc, &maps.wd, d_in[8], 4608, 576);
    cudaFuncSetAttribute(fused_block_kernel, cudaFuncAttributeMaxDynamicSharedMemorySize, SMEM_BYTES);
    fused_block_kernel<<<128, 384, SMEM_BYTES>>>(maps);
}
```

```cpp
#include <cuda_runtime.h>
#include <cuda_bf16.h>
#include <cuda.h>
#include <stdint.h>

namespace {

constexpr int DM = 576;
constexpr int SLOT_BYTES = 16384;
constexpr int BOX_BYTES = 8192;
constexpr int NUNITS = 14;
constexpr int SMEM_TAIL = NUNITS * SLOT_BYTES;
constexpr int SMEM_BYTES = SMEM_TAIL + 2048 + 1024;
constexpr int OFF_FULL = SMEM_TAIL;
constexpr int OFF_EMPTY = SMEM_TAIL + 64;
constexpr int OFF_RED = SMEM_TAIL + 128;

constexpr int KV_AHEAD = 16;
constexpr int OFF_XBAR = SMEM_TAIL + 1792;
constexpr int OFF_ROWS = 8 * SLOT_BYTES;
constexpr int XROW_STRIDE = DM * 2 + 16;

struct Scratch {
    unsigned epoch;
    unsigned pad[31];
    uint32_t mod[6 * DM];
    uint4 h[2][2][128 * 36 * 32];
    uint4 part[128 * 8 * 36 * 32];
    uint4 hh[128 * 8 * 256];
    __nv_bfloat16 x2[2048 * DM];
};
__device__ Scratch g_scratch;

#define TL(i)
#define PROFR(i)
#define PROF(i)
#define PROFG(i)

struct Params {
    const __nv_bfloat16 *x, *cvec, *wmod, *kc, *vc;
    __nv_bfloat16* out;
    Scratch* sc;
    CUtensorMap k, v, wq, wo, wg, wu, wd;
};

__device__ __forceinline__ uint32_t smem_u32(const void* p) { return (uint32_t)__cvta_generic_to_shared(p); }
__device__ __forceinline__ void mbar_init(uint32_t a, uint32_t c) {
    asm volatile("mbarrier.init.shared::cta.b64 [%0], %1;" ::"r"(a), "r"(c) : "memory");
}
__device__ __forceinline__ void mbar_expect_tx(uint32_t a, uint32_t bytes) {
    asm volatile("mbarrier.arrive.expect_tx.shared::cta.b64 _, [%0], %1;" ::"r"(a), "r"(bytes) : "memory");
}
__device__ __forceinline__ bool mbar_try(uint32_t a, uint32_t ph) {
    uint32_t ok;
    asm volatile(
        "{\n.reg .pred p;\nmbarrier.try_wait.parity.shared::cta.b64 p, [%1], %2;\nselp.u32 %0, 1, 0, p;\n}"
        : "=r"(ok)
        : "r"(a), "r"(ph)
        : "memory");
    return ok != 0;
}
__device__ __forceinline__ uint32_t clk32() {
    uint32_t c;
    asm volatile("mov.u32 %0, %%clock;" : "=r"(c));
    return c;
}
constexpr uint32_t WAIT_LIMIT = 1u << 30;
__device__ __forceinline__ void mbar_wait(uint32_t a, uint32_t ph) {
    if (mbar_try(a, ph)) return;
    uint32_t t0 = clk32();
    while (!mbar_try(a, ph)) {
        if (clk32() - t0 > WAIT_LIMIT) break;
    }
}
__device__ __forceinline__ void mbar_arrive_cluster(uint32_t a, uint32_t cta) {
    asm volatile(
        "{\n.reg .b32 ra;\nmapa.shared::cluster.u32 ra, %0, %1;\nmbarrier.arrive.shared::cluster.b64 _, [ra];\n}" ::"r"(a),
        "r"(cta)
        : "memory");
}
__device__ __forceinline__ void tma_mc(uint32_t dst, const CUtensorMap* m, int c0, int c1, uint32_t bar) {
    asm volatile(
        "cp.async.bulk.tensor.2d.shared::cluster.global.mbarrier::complete_tx::bytes.multicast::cluster"
        " [%0], [%1, {%3, %4}], [%2], %5;" ::"r"(dst),
        "l"(m), "r"(bar), "r"(c0), "r"(c1), "h"((uint16_t)3)
        : "memory");
}
__device__ __forceinline__ void l2_prefetch(const void* p, uint32_t bytes) {
    asm volatile("cp.async.bulk.prefetch.L2.global [%0], %1;" ::"l"(p), "r"(bytes) : "memory");
}
__device__ __forceinline__ void bar_sync(int id, int n) { asm volatile("bar.sync %0, %1;" ::"r"(id), "r"(n) : "memory"); }
__device__ __forceinline__ void bar_arrive(int id, int n) {
    asm volatile("bar.arrive %0, %1;" ::"r"(id), "r"(n) : "memory");
}
__device__ __forceinline__ void wg_fence() { asm volatile("wgmma.fence.sync.aligned;" ::: "memory"); }
__device__ __forceinline__ void wg_commit() { asm volatile("wgmma.commit_group.sync.aligned;" ::: "memory"); }
template <int N>
__device__ __forceinline__ void wg_wait() {
    asm volatile("wgmma.wait_group.sync.aligned %0;" ::"n"(N) : "memory");
}
template <int N>
__device__ __forceinline__ void pin(float (&d)[N]) {
#pragma unroll
    for (int i = 0; i < N; i++) asm volatile("" : "+f"(d[i])::"memory");
}
template <int N>
__device__ __forceinline__ void pin(uint32_t (&d)[N]) {
#pragma unroll
    for (int i = 0; i < N; i++) asm volatile("" : "+r"(d[i])::"memory");
}
__device__ __forceinline__ uint32_t pack_bf16(float lo, float hi) {
    uint32_t r;
    asm("cvt.rn.bf16x2.f32 %0, %1, %2;" : "=r"(r) : "f"(hi), "f"(lo));
    return r;
}
__device__ __forceinline__ float bf_lo(uint32_t v) { return __uint_as_float(v << 16); }
__device__ __forceinline__ float bf_hi(uint32_t v) { return __uint_as_float(v & 0xffff0000u); }
__device__ __forceinline__ float round_bf16(float v) { return __bfloat162float(__float2bfloat16_rn(v)); }
__device__ __forceinline__ float ex2(float x) {
    float y;
    asm("ex2.approx.ftz.f32 %0, %1;" : "=f"(y) : "f"(x));
    return y;
}
__device__ __forceinline__ float rcp(float x) {
    float y;
    asm("rcp.approx.ftz.f32 %0, %1;" : "=f"(y) : "f"(x));
    return y;
}
__device__ __forceinline__ float tanh_fast(float x) {
    float y;
    asm("tanh.approx.f32 %0, %1;" : "=f"(y) : "f"(x));
    return y;
}
__device__ __forceinline__ void sts128(uint32_t a, uint32_t x, uint32_t y, uint32_t z, uint32_t w) {
    asm volatile("st.shared.v4.b32 [%0], {%1,%2,%3,%4};" ::"r"(a), "r"(x), "r"(y), "r"(z), "r"(w) : "memory");
}
__device__ __forceinline__ void lds128(uint32_t a, uint32_t& x, uint32_t& y, uint32_t& z, uint32_t& w) {
    asm volatile("ld.shared.v4.b32 {%0,%1,%2,%3}, [%4];" : "=r"(x), "=r"(y), "=r"(z), "=r"(w) : "r"(a) : "memory");
}
__device__ __forceinline__ void sts32f(uint32_t a, float v) {
    asm volatile("st.shared.f32 [%0], %1;" ::"r"(a), "f"(v) : "memory");
}
__device__ __forceinline__ float lds32f(uint32_t a) {
    float v;
    asm volatile("ld.shared.f32 %0, [%1];" : "=f"(v) : "r"(a) : "memory");
    return v;
}
#define F8(d, b) \
    "+f"(d[b]), "+f"(d[b + 1]), "+f"(d[b + 2]), "+f"(d[b + 3]), "+f"(d[b + 4]), "+f"(d[b + 5]), "+f"(d[b + 6]), "+f"(d[b + 7])

template <int TB>
__device__ __forceinline__ void wgmma_n128(float (&d)[64], uint32_t a0, uint32_t a1, uint32_t a2, uint32_t a3,
                                           uint64_t db, int sc) {
    asm volatile(
        "{\n.reg .pred p;\nsetp.ne.b32 p, %69, 0;\n"
        "wgmma.mma_async.sync.aligned.m64n128k16.f32.bf16.bf16 "
        "{%0,%1,%2,%3,%4,%5,%6,%7,%8,%9,%10,%11,%12,%13,%14,%15,%16,%17,%18,%19,%20,%21,%22,%23,%24,%25,%26,%27,%28,%29,%30,%31,"
        "%32,%33,%34,%35,%36,%37,%38,%39,%40,%41,%42,%43,%44,%45,%46,%47,%48,%49,%50,%51,%52,%53,%54,%55,%56,%57,%58,%59,%60,%61,%62,%63},"
        "{%64,%65,%66,%67}, %68, p, 1, 1, %70;\n}"
        : F8(d, 0), F8(d, 8), F8(d, 16), F8(d, 24), F8(d, 32), F8(d, 40), F8(d, 48), F8(d, 56)
        : "r"(a0), "r"(a1), "r"(a2), "r"(a3), "l"(db), "r"(sc), "n"(TB));
}
#define O8(d, b) \
    "=f"(d[b]), "=f"(d[b + 1]), "=f"(d[b + 2]), "=f"(d[b + 3]), "=f"(d[b + 4]), "=f"(d[b + 5]), "=f"(d[b + 6]), "=f"(d[b + 7])
template <int TB>
__device__ __forceinline__ void wgmma_n128_z(float (&d)[64], uint32_t a0, uint32_t a1, uint32_t a2, uint32_t a3,
                                             uint64_t db) {
    asm volatile(
        "wgmma.mma_async.sync.aligned.m64n128k16.f32.bf16.bf16 "
        "{%0,%1,%2,%3,%4,%5,%6,%7,%8,%9,%10,%11,%12,%13,%14,%15,%16,%17,%18,%19,%20,%21,%22,%23,%24,%25,%26,%27,%28,%29,%30,%31,"
        "%32,%33,%34,%35,%36,%37,%38,%39,%40,%41,%42,%43,%44,%45,%46,%47,%48,%49,%50,%51,%52,%53,%54,%55,%56,%57,%58,%59,%60,%61,%62,%63},"
        "{%64,%65,%66,%67}, %68, 0, 1, 1, %69;"
        : O8(d, 0), O8(d, 8), O8(d, 16), O8(d, 24), O8(d, 32), O8(d, 40), O8(d, 48), O8(d, 56)
        : "r"(a0), "r"(a1), "r"(a2), "r"(a3), "l"(db), "n"(TB));
}
template <int TB>
__device__ __forceinline__ void wgmma_n64_z(float (&d)[32], uint32_t a0, uint32_t a1, uint32_t a2, uint32_t a3,
                                            uint64_t db) {
    asm volatile(
        "wgmma.mma_async.sync.aligned.m64n64k16.f32.bf16.bf16 "
        "{%0,%1,%2,%3,%4,%5,%6,%7,%8,%9,%10,%11,%12,%13,%14,%15,%16,%17,%18,%19,%20,%21,%22,%23,%24,%25,%26,%27,%28,%29,%30,%31},"
        "{%32,%33,%34,%35}, %36, 0, 1, 1, %37;"
        : O8(d, 0), O8(d, 8), O8(d, 16), O8(d, 24)
        : "r"(a0), "r"(a1), "r"(a2), "r"(a3), "l"(db), "n"(TB));
}
template <int TB>
__device__ __forceinline__ void wgmma_n64(float (&d)[32], uint32_t a0, uint32_t a1, uint32_t a2, uint32_t a3,
                                          uint64_t db) {
    asm volatile(
        "wgmma.mma_async.sync.aligned.m64n64k16.f32.bf16.bf16 "
        "{%0,%1,%2,%3,%4,%5,%6,%7,%8,%9,%10,%11,%12,%13,%14,%15,%16,%17,%18,%19,%20,%21,%22,%23,%24,%25,%26,%27,%28,%29,%30,%31},"
        "{%32,%33,%34,%35}, %36, 1, 1, 1, %37;"
        : F8(d, 0), F8(d, 8), F8(d, 16), F8(d, 24)
        : "r"(a0), "r"(a1), "r"(a2), "r"(a3), "l"(db), "n"(TB));
}

__device__ __forceinline__ uint64_t desc_of(uint32_t saddr) {
    return (uint64_t)(((saddr >> 4) & 0x3FFFu) | (512u << 16)) | ((uint64_t)(64u | (1u << 30)) << 32);
}

struct Ring {
    uint32_t slot;
    uint32_t phase;
    __device__ __forceinline__ void next() {
        if (++slot == 8) {
            slot = 0;
            phase ^= 1;
        }
    }
};

struct Ctx {
    uint32_t sbase;
    uint32_t rel_cta;
    __device__ __forceinline__ void wait_full(uint32_t slot, uint32_t phase) const {
        mbar_wait(sbase + OFF_FULL + slot * 8, phase);
    }
    __device__ __forceinline__ void release(uint32_t slot) const {
        if (rel_cta < 2) mbar_arrive_cluster(sbase + OFF_EMPTY + slot * 8, rel_cta);
    }
};

__device__ __forceinline__ void gemm_n128(float (&d)[64], const uint32_t (&a)[144], const Ctx& c, Ring& r, bool nine) {
    uint32_t prev = 0;
#pragma unroll
    for (int s = 0; s < 9; s++) {
        if (s < 8 || nine) {
            c.wait_full(r.slot, r.phase);
            uint64_t db = desc_of(c.sbase + r.slot * SLOT_BYTES);
            wg_fence();
#pragma unroll
            for (int k = 0; k < 4; k++) {
                if ((s | k) == 0)
                    wgmma_n128_z<1>(d, a[0], a[1], a[2], a[3], db);
                else
                    wgmma_n128<1>(d, a[s * 16 + k * 4], a[s * 16 + k * 4 + 1], a[s * 16 + k * 4 + 2],
                                  a[s * 16 + k * 4 + 3], db + k * 128, 1);
            }
            wg_commit();
            if (s > 0) {
                wg_wait<1>();
                c.release(prev);
            }
            prev = r.slot;
            r.next();
        }
    }
    wg_wait<0>();
    c.release(prev);
    pin(d);
}
__device__ __forceinline__ void gemm_n64(float (&d)[32], const uint32_t (&a)[144], const Ctx& c, Ring& r, bool nine) {
    uint32_t prev = 0;
#pragma unroll
    for (int s = 0; s < 5; s++) {
        if (s < 4 || nine) {
            c.wait_full(r.slot, r.phase);
            uint64_t db = desc_of(c.sbase + r.slot * SLOT_BYTES);
            wg_fence();
#pragma unroll
            for (int k = 0; k < 8; k++) {
                if ((s | k) == 0)
                    wgmma_n64_z<1>(d, a[0], a[1], a[2], a[3], db);
                else if (s * 8 + k < 36)
                    wgmma_n64<1>(d, a[s * 32 + k * 4], a[s * 32 + k * 4 + 1], a[s * 32 + k * 4 + 2],
                                 a[s * 32 + k * 4 + 3], db + k * 128);
            }
            wg_commit();
            if (s > 0) {
                wg_wait<1>();
                c.release(prev);
            }
            prev = r.slot;
            r.next();
        }
    }
    wg_wait<0>();
    c.release(prev);
    pin(d);
}
__device__ __forceinline__ void st128(uint4* p, uint32_t x, uint32_t y, uint32_t z, uint32_t w) {
    asm volatile(
        "{\n.reg .b64 lo, hi;\n.reg .b128 t;\nmov.b64 lo, {%1, %2};\nmov.b64 hi, {%3, %4};\nmov.b128 t, {lo, hi};\n"
        "st.relaxed.gpu.global.b128 [%0], t;\n}" ::"l"(p),
        "r"(x), "r"(y), "r"(z), "r"(w)
        : "memory");
}
__device__ __forceinline__ uint4 ld128(const uint4* p) {
    uint4 r;
    asm volatile(
        "{\n.reg .b64 lo, hi;\n.reg .b128 t;\nld.relaxed.gpu.global.b128 t, [%4];\nmov.b128 {lo, hi}, t;\n"
        "mov.b64 {%0, %1}, lo;\nmov.b64 {%2, %3}, hi;\n}"
        : "=r"(r.x), "=r"(r.y), "=r"(r.z), "=r"(r.w)
        : "l"(p));
    return r;
}
__device__ __forceinline__ void st64(void* p, uint32_t x, uint32_t y) {
    asm volatile("{\n.reg .b64 t;\nmov.b64 t, {%1, %2};\nst.relaxed.gpu.global.b64 [%0], t;\n}" ::"l"(p), "r"(x), "r"(y)
                 : "memory");
}
__device__ __forceinline__ uint2 ld64(const void* p) {
    uint2 r;
    asm volatile("{\n.reg .b64 t;\nld.relaxed.gpu.global.b64 t, [%2];\nmov.b64 {%0, %1}, t;\n}"
                 : "=r"(r.x), "=r"(r.y)
                 : "l"(p));
    return r;
}
__device__ __forceinline__ void rows_load(uint32_t sbase, const __nv_bfloat16* src, int lane) {
    if (lane == 0) mbar_expect_tx(sbase + OFF_XBAR, 16 * DM * 2);
    __syncwarp();
    if (lane < 16)
        asm volatile("cp.async.bulk.shared::cluster.global.mbarrier::complete_tx::bytes [%0], [%1], %2, [%3];" ::"r"(
                         sbase + OFF_ROWS + lane * XROW_STRIDE),
                     "l"(src + lane * DM), "r"(DM * 2), "r"(sbase + OFF_XBAR)
                     : "memory");
    __syncwarp();
}
__device__ __forceinline__ void rows_store(uint32_t sbase, __nv_bfloat16* dst, int lane) {
    if (lane < 16) {
        asm volatile("cp.async.bulk.global.shared::cta.bulk_group [%0], [%1], %2;" ::"l"(dst + lane * DM),
                     "r"(sbase + OFF_ROWS + lane * XROW_STRIDE), "r"(DM * 2)
                     : "memory");
        asm volatile("cp.async.bulk.commit_group;" ::: "memory");
    }
    __syncwarp();
}
__device__ __forceinline__ void rows_store_wait() { asm volatile("cp.async.bulk.wait_group 0;" ::: "memory"); }

__device__ __forceinline__ constexpr int own_col(int j) { return j < 8 ? (j >> 1) * 128 + (j & 1) * 8 : 512; }
__device__ __forceinline__ void row_reduce(float& s0, float& s1, uint32_t red, int warp, int lane) {
    s0 += __shfl_xor_sync(0xffffffffu, s0, 1);
    s1 += __shfl_xor_sync(0xffffffffu, s1, 1);
    s0 += __shfl_xor_sync(0xffffffffu, s0, 2);
    s1 += __shfl_xor_sync(0xffffffffu, s1, 2);
    if ((lane & 3) == 0) {
        sts32f(red + (warp * 16 + (lane >> 2)) * 4, s0);
        sts32f(red + (warp * 16 + 8 + (lane >> 2)) * 4, s1);
    }
    bar_sync(3, 256);
    s0 = 0.f;
    s1 = 0.f;
#pragma unroll
    for (int w = 0; w < 8; w++) {
        s0 += lds32f(red + (w * 16 + (lane >> 2)) * 4);
        s1 += lds32f(red + (w * 16 + 8 + (lane >> 2)) * 4);
    }
}
__device__ __forceinline__ void layernorm_rows(float (&v)[36], uint32_t red, int warp, int lane) {
    float s0 = 0.f, s1 = 0.f;
#pragma unroll
    for (int j = 0; j < 9; j++) {
        s0 += v[4 * j] + v[4 * j + 1];
        s1 += v[4 * j + 2] + v[4 * j + 3];
    }
    row_reduce(s0, s1, red, warp, lane);
    const float m0 = s0 * (1.f / DM), m1 = s1 * (1.f / DM);
    s0 = 0.f;
    s1 = 0.f;
#pragma unroll
    for (int j = 0; j < 9; j++) {
        v[4 * j] -= m0;
        v[4 * j + 1] -= m0;
        v[4 * j + 2] -= m1;
        v[4 * j + 3] -= m1;
        s0 += v[4 * j] * v[4 * j] + v[4 * j + 1] * v[4 * j + 1];
        s1 += v[4 * j + 2] * v[4 * j + 2] + v[4 * j + 3] * v[4 * j + 3];
    }
    row_reduce(s0, s1, red + 512, warp, lane);
    const float r0 = rsqrtf(s0 * (1.f / DM) + 1e-5f), r1 = rsqrtf(s1 * (1.f / DM) + 1e-5f);
#pragma unroll
    for (int j = 0; j < 9; j++) {
        v[4 * j] *= r0;
        v[4 * j + 1] *= r0;
        v[4 * j + 2] *= r1;
        v[4 * j + 3] *= r1;
    }
}
__device__ __forceinline__ void load_mod0(float (&m)[3][18], const uint32_t* src, int warp, uint32_t tag) {
    const uint32_t t0 = clk32();
    while (true) {
        uint2 u[2][9];
#pragma unroll
        for (int n = 0; n < 2; n++)
#pragma unroll
            for (int j = 0; j < 9; j++) u[n][j] = ld64(src + n * DM + own_col(j) - (j == 8 ? warp * 8 : 0));
        uint32_t bad = 0;
#pragma unroll
        for (int n = 0; n < 2; n++)
#pragma unroll
            for (int j = 0; j < 9; j++) {
                bad |= (u[n][j].x ^ tag) | (u[n][j].y ^ tag);
                m[n + 1][2 * j] = __uint_as_float(u[n][j].x & 0xffff0000u);
                m[n + 1][2 * j + 1] = __uint_as_float(u[n][j].y & 0xffff0000u);
            }
        if (__all_sync(0xffffffffu, (bad & 0xffffu) == 0) || clk32() - t0 > WAIT_LIMIT) break;
    }
}
__device__ __forceinline__ void modulate_store(const float (&v)[36], const float (&shift)[18], const float (&scale)[18],
                                               uint4* hbuf  , int warp, int lane) {
    uint32_t o[18];
#pragma unroll
    for (int j = 0; j < 9; j++) {
        const uint32_t cc = pack_bf16(1.f + scale[2 * j], 1.f + scale[2 * j + 1]);
        const float c0 = bf_lo(cc), c1 = bf_hi(cc);
        o[2 * j] = max(pack_bf16(fmaf(v[4 * j], c0, shift[2 * j]), fmaf(v[4 * j + 1], c1, shift[2 * j + 1])), 1u);
        o[2 * j + 1] = max(pack_bf16(fmaf(v[4 * j + 2], c0, shift[2 * j]), fmaf(v[4 * j + 3], c1, shift[2 * j + 1])), 1u);
    }
#pragma unroll
    for (int i = 0; i < 4; i++) st128(hbuf + (i * 8 + warp) * 32 + lane, o[4 * i], o[4 * i + 1], o[4 * i + 2], o[4 * i + 3]);
    st64(reinterpret_cast<uint2*>(hbuf + (32 + (warp >> 1)) * 32 + lane) + (warp & 1), o[16], o[17]);
}
__device__ __forceinline__ void sum_partials(float (&v)[36], const uint4* src  , uint32_t tag) {
    const uint32_t t0 = clk32();
    while (true) {
        uint4 t[8][4];
#pragma unroll
        for (int s = 0; s < 8; s++)
#pragma unroll
            for (int i = 0; i < 4; i++) t[s][i] = ld128(src + (s * 36 + i * 8) * 32);
        uint32_t bad = 0;
#pragma unroll
        for (int i = 0; i < 32; i++) v[i] = 0.f;
#pragma unroll
        for (int s = 0; s < 8; s++)
#pragma unroll
            for (int i = 0; i < 4; i++) {
                bad |= t[s][i].x ^ tag;
                v[8 * i] += bf_lo(t[s][i].x);
                v[8 * i + 1] += bf_hi(t[s][i].x);
                v[8 * i + 2] += bf_lo(t[s][i].y);
                v[8 * i + 3] += bf_hi(t[s][i].y);
                v[8 * i + 4] += bf_lo(t[s][i].z);
                v[8 * i + 5] += bf_hi(t[s][i].z);
                v[8 * i + 6] += bf_lo(t[s][i].w);
                v[8 * i + 7] += bf_hi(t[s][i].w);
            }
        if (__all_sync(0xffffffffu, (bad & 1u) == 0) || clk32() - t0 > WAIT_LIMIT) break;
    }
}
__device__ __forceinline__ void sum_tail(float (&v)[36], float (&m)[3][18], const uint2* src  ,
                                         uint32_t tag, const uint32_t* gate, const uint32_t* shsc, int warp,
                                         uint32_t mtag) {
    const uint32_t t0 = clk32();
    while (true) {
        uint2 t[8], u[3][9];
#pragma unroll
        for (int s = 0; s < 8; s++) t[s] = ld64(src + s * 72 * 32);
#pragma unroll
        for (int n = 0; n < 3; n++)
#pragma unroll
            for (int j = 0; j < 9; j++)
                u[n][j] = ld64((n == 0 ? gate : shsc + (n - 1) * DM) + own_col(j) - (j == 8 ? warp * 8 : 0));
        uint32_t bad = 0, badm = 0;
        v[32] = v[33] = v[34] = v[35] = 0.f;
#pragma unroll
        for (int s = 0; s < 8; s++) {
            bad |= t[s].x ^ tag;
            v[32] += bf_lo(t[s].x);
            v[33] += bf_hi(t[s].x);
            v[34] += bf_lo(t[s].y);
            v[35] += bf_hi(t[s].y);
        }
#pragma unroll
        for (int n = 0; n < 3; n++)
#pragma unroll
            for (int j = 0; j < 9; j++) {
                badm |= (u[n][j].x ^ mtag) | (u[n][j].y ^ mtag);
                m[n][2 * j] = __uint_as_float(u[n][j].x & 0xffff0000u);
                m[n][2 * j + 1] = __uint_as_float(u[n][j].y & 0xffff0000u);
            }
        if (__all_sync(0xffffffffu, ((bad & 1u) | (badm & 0xffffu)) == 0) || clk32() - t0 > WAIT_LIMIT) break;
    }
}
template <int K0, int K1>
__device__ __forceinline__ void poll_frags(uint32_t (&a)[144], const uint4* src  ) {
    const uint32_t t0 = clk32();
    while (true) {
#pragma unroll
        for (int k = K0; k < K1; k++)
            asm volatile("ld.relaxed.gpu.global.v4.u32 {%0,%1,%2,%3}, [%4];"
                         : "=r"(a[4 * k]), "=r"(a[4 * k + 1]), "=r"(a[4 * k + 2]), "=r"(a[4 * k + 3])
                         : "l"(src + k * 32));
        uint32_t m0 = a[4 * K0], m1 = a[4 * K0 + 1];
#pragma unroll
        for (int i = 4 * K0 + 2; i < 4 * K1; i += 2) {
            m0 = min(m0, a[i]);
            m1 = min(m1, a[i + 1]);
        }
        if (__all_sync(0xffffffffu, min(m0, m1) != 0) || clk32() - t0 > WAIT_LIMIT) break;
    }
}

constexpr float SM_SCALE = 0.08838834764831845f * 1.4426950408889634f;
constexpr float SM_HI = 1.2089258e24f;
constexpr float SM_LO = 9.0949470e-13f;
__device__ __forceinline__ void qk_step(float (&s)[32], const uint32_t (&q)[32], uint64_t dk) {
#pragma unroll
    for (int k = 0; k < 8; k++) {
        if (k == 0)
            wgmma_n64_z<0>(s, q[0], q[1], q[2], q[3], dk);
        else
            wgmma_n64<0>(s, q[4 * k], q[4 * k + 1], q[4 * k + 2], q[4 * k + 3], dk + (k >> 2) * 512 + (k & 3) * 2);
    }
}
__device__ __forceinline__ void pv_step(float (&o)[64], const uint32_t (&p)[16], uint64_t dv, int acc) {
#pragma unroll
    for (int k = 0; k < 4; k++)
        wgmma_n128<1>(o, p[4 * k], p[4 * k + 1], p[4 * k + 2], p[4 * k + 3], dv + k * 128, k != 0 ? 1 : acc);
}
template <bool SHIFT>
__device__ __forceinline__ void exp_step(const float (&s)[32], uint32_t (&p)[16], float n0, float n1, float& s0,
                                         float& s1) {
#pragma unroll
    for (int i = 0; i < 8; i++) {
        const float e0 = ex2(SHIFT ? s[4 * i] + n0 : s[4 * i]), e1 = ex2(SHIFT ? s[4 * i + 1] + n0 : s[4 * i + 1]);
        const float e2 = ex2(SHIFT ? s[4 * i + 2] + n1 : s[4 * i + 2]), e3 = ex2(SHIFT ? s[4 * i + 3] + n1 : s[4 * i + 3]);
        if (i == 0) {
            s0 = e0 + e1;
            s1 = e2 + e3;
        } else {
            s0 += e0 + e1;
            s1 += e2 + e3;
        }
        p[2 * i] = pack_bf16(e0, e1);
        p[2 * i + 1] = pack_bf16(e2, e3);
    }
}
__device__ __forceinline__ void row_max(const float (&sa)[32], const float (&sb)[32], float& x0, float& x1) {
    float xa[8];
#pragma unroll
    for (int i = 0; i < 8; i++) xa[i] = fmaxf(sa[i], sb[i]);
#pragma unroll
    for (int k = 1; k < 4; k++)
#pragma unroll
        for (int i = 0; i < 8; i++) xa[i] = fmaxf(xa[i], fmaxf(sa[8 * k + i], sb[8 * k + i]));
    x0 = fmaxf(fmaxf(xa[0], xa[1]), fmaxf(xa[4], xa[5]));
    x1 = fmaxf(fmaxf(xa[2], xa[3]), fmaxf(xa[6], xa[7]));
    x0 = fmaxf(x0, __shfl_xor_sync(0xffffffffu, x0, 1));
    x1 = fmaxf(x1, __shfl_xor_sync(0xffffffffu, x1, 1));
    x0 = fmaxf(x0, __shfl_xor_sync(0xffffffffu, x0, 2));
    x1 = fmaxf(x1, __shfl_xor_sync(0xffffffffu, x1, 2));
}
__device__ __forceinline__ void inv_row_sums(float l0, float l1, float& i0, float& i1) {
    l0 += __shfl_xor_sync(0xffffffffu, l0, 1);
    l1 += __shfl_xor_sync(0xffffffffu, l1, 1);
    l0 += __shfl_xor_sync(0xffffffffu, l0, 2);
    l1 += __shfl_xor_sync(0xffffffffu, l1, 2);
    i0 = rcp(l0);
    i1 = rcp(l1);
}

__device__ __forceinline__ uint32_t ld_epoch(const Scratch* sc) {
    uint32_t e;
    asm volatile("ld.relaxed.gpu.global.u32 %0, [%1];" : "=r"(e) : "l"(&sc->epoch) : "memory");
    return e;
}
__device__ __forceinline__ float silu_bf16(unsigned short c) {
    const float cv = bf_lo(c);
    return round_bf16(cv * rcp(1.f + ex2(-1.4426950408889634f * cv)));
}
__device__ __forceinline__ void st_mod(uint32_t* p, float v, uint32_t tag) {
    asm volatile("st.relaxed.gpu.global.u32 [%0], %1;" ::"l"(p), "r"(__float_as_uint(round_bf16(v)) | tag)
                 : "memory");
}
__device__ __forceinline__ void mod_block(const uint4 (&w)[5], const float (&sc)[5], uint32_t* dst, uint32_t red,
                                          int warp, int lane, uint32_t tag) {
    float acc[8];
#pragma unroll
    for (int e = 0; e < 8; e++) acc[e] = 0.f;
#pragma unroll
    for (int i = 0; i < 5; i++) {
        acc[0] = fmaf(sc[i], bf_lo(w[i].x), acc[0]);
        acc[1] = fmaf(sc[i], bf_hi(w[i].x), acc[1]);
        acc[2] = fmaf(sc[i], bf_lo(w[i].y), acc[2]);
        acc[3] = fmaf(sc[i], bf_hi(w[i].y), acc[3]);
        acc[4] = fmaf(sc[i], bf_lo(w[i].z), acc[4]);
        acc[5] = fmaf(sc[i], bf_hi(w[i].z), acc[5]);
        acc[6] = fmaf(sc[i], bf_lo(w[i].w), acc[6]);
        acc[7] = fmaf(sc[i], bf_hi(w[i].w), acc[7]);
    }
#pragma unroll
    for (int o = 2; o < 32; o <<= 1)
#pragma unroll
        for (int e = 0; e < 8; e++) acc[e] += __shfl_xor_sync(0xffffffffu, acc[e], o);
    if (lane < 2) {
#pragma unroll
        for (int e = 0; e < 8; e++) sts32f(red + (warp * 16 + lane * 8 + e) * 4, acc[e]);
    }
    bar_sync(3, 256);
    if (warp == 0 && lane < 16) {
        float s = 0.f;
#pragma unroll
        for (int w8 = 0; w8 < 8; w8++) s += lds32f(red + (w8 * 16 + lane) * 4);
        st_mod(dst + lane, s, tag);
    }
}

__global__ void __cluster_dims__(2, 1, 1) __launch_bounds__(384, 1)
    fused_block_kernel(const __grid_constant__ Params maps) {
    extern __shared__ uint8_t smem_raw[];
    uint32_t sbase = (smem_u32(smem_raw) + 1023u) & ~1023u;
    asm volatile("" : "+r"(sbase));
    const int b = blockIdx.x;
    const int rank = b & 1;
    const int mt = ((b >> 1) & 7) * 2 + rank;
    const int g = b >> 4;
    const int warp = __shfl_sync(0xffffffffu, threadIdx.x >> 5, 0);
    const int lane = threadIdx.x & 31;
    Scratch* const sc_ = maps.sc;
    const __nv_bfloat16* const wmod = maps.wmod;
    const __nv_bfloat16* const cvec = maps.cvec;

    if (warp >= 8) {
        asm volatile("setmaxnreg.dec.sync.aligned.u32 24;");
        if (warp == 8 && lane == 0) {
#pragma unroll
            for (int i = 0; i < 8; i++) {
                mbar_init(sbase + OFF_FULL + i * 8, 1);
                mbar_init(sbase + OFF_EMPTY + i * 8, 4);
            }
            asm volatile("fence.mbarrier_init.release.cluster;" ::: "memory");
            asm volatile("barrier.cluster.arrive.relaxed;\nbarrier.cluster.wait;" ::: "memory");
            uint32_t slot = 0, phase = 1;
            const uint32_t dst0 = sbase + rank * BOX_BYTES;
            auto acquire = [&](uint32_t bytes) {
                mbar_wait(sbase + OFF_EMPTY + slot * 8, phase);
                mbar_expect_tx(sbase + OFF_FULL + slot * 8, bytes);
            };
            auto adv8 = [&]() {
                if (++slot == 8) {
                    slot = 0;
                    phase ^= 1;
                }
            };
#pragma unroll 1
            for (int hq = 0; hq < 4; hq++) {
                const int col = (g * 4 + ((hq + 1) & 3)) * 128 + rank * 64;
                if (hq == 2) {
                    l2_prefetch(maps.kc + (size_t)(g * 4 * 2048 + (b & 15) * 64) * 128, SLOT_BYTES);
                    l2_prefetch(maps.vc + (size_t)(g * 4 * 2048 + (b & 15) * 64) * 128, SLOT_BYTES);
                }
#pragma unroll 1
                for (int kc = 0; kc < 9; kc++) {
                    acquire(SLOT_BYTES);
                    tma_mc(dst0 + slot * SLOT_BYTES, &maps.wq, col, kc * 64, sbase + OFF_FULL + slot * 8);
                    adv8();
                }
            }
            const int row0 = g * 4 * 2048;
#pragma unroll 1
            for (int n = 0; n < 128; n++) {
                if (n < 4) mbar_wait(sbase + OFF_EMPTY + (slot + 1) * 8, phase);
                acquire(2 * SLOT_BYTES);
                const uint32_t bar = sbase + OFF_FULL + slot * 8;
                const int r0 = n == 0 ? 0 : (n == 127 ? 126 : n + 1);
                const int r1 = n == 0 ? 1 : (n == 127 ? 127 : n - 1);
                tma_mc(dst0 + slot * SLOT_BYTES, n == 127 ? &maps.v : &maps.k, rank * 64, row0 + r0 * 64, bar);
                tma_mc(dst0 + (slot + 1) * SLOT_BYTES, n == 0 ? &maps.k : &maps.v, rank * 64, row0 + r1 * 64, bar);
                adv8();
                adv8();
                const int u = n + KV_AHEAD;
                if (u < 128 && (u & 15) == (b & 15)) {
                    l2_prefetch(maps.kc + (size_t)(row0 + u * 64) * 128, SLOT_BYTES);
                    l2_prefetch(maps.vc + (size_t)(row0 + u * 64) * 128, SLOT_BYTES);
                }
            }
#pragma unroll 1
            for (int p = 0; p < 4; p++)
#pragma unroll 1
                for (int kc = 0; kc < 8; kc++) {
                    acquire(SLOT_BYTES);
                    tma_mc(dst0 + slot * SLOT_BYTES, &maps.wo, p * 128 + rank * 64, g * 512 + kc * 64,
                           sbase + OFF_FULL + slot * 8);
                    adv8();
                }
#pragma unroll 1
            for (int kc = 0; kc < 4; kc++) {
                acquire(SLOT_BYTES);
                tma_mc(dst0 + slot * SLOT_BYTES, &maps.wo, 512, g * 512 + kc * 128 + rank * 64,
                       sbase + OFF_FULL + slot * 8);
                adv8();
            }
            const CUtensorMap* mg = rank ? &maps.wu : &maps.wg;
#pragma unroll 1
            for (int ch = 0; ch < 9; ch++)
#pragma unroll 1
                for (int kc = 0; kc < 9; kc++) {
                    acquire(SLOT_BYTES);
                    tma_mc(dst0 + slot * SLOT_BYTES, mg, g * 576 + ch * 64, kc * 64, sbase + OFF_FULL + slot * 8);
                    adv8();
                }
#pragma unroll 1
            for (int p = 0; p < 4; p++)
#pragma unroll 1
                for (int kc = 2; kc < 11; kc++) {
                    acquire(SLOT_BYTES);
                    tma_mc(dst0 + slot * SLOT_BYTES, &maps.wd, p * 128 + rank * 64, g * 576 + (kc < 9 ? kc : kc - 9) * 64,
                           sbase + OFF_FULL + slot * 8);
                    adv8();
                }
#pragma unroll 1
            for (int i = 0; i < 5; i++) {
                acquire(i < 4 ? SLOT_BYTES : BOX_BYTES);
                const int kc = 2 * i + rank + 2;
                if (i < 4 || rank == 0)
                    tma_mc(dst0 + slot * SLOT_BYTES, &maps.wd, 512, g * 576 + (kc < 9 ? kc : kc - 9) * 64,
                           sbase + OFF_FULL + slot * 8);
                adv8();
            }
        } else if (warp == 11) {
            const int row = b * 5 + lane;
            if (lane < 5 && row < DM) l2_prefetch(wmod + (size_t)row * (6 * DM), 2 * DM * 2);
            asm volatile("barrier.cluster.arrive.relaxed.aligned;" ::: "memory");
            uint4* hz = sc_->h[(ld_epoch(sc_) & 1) ^ 1][0] + (size_t)b * 72 * 32 + lane;
            bar_sync(6, 160);
#pragma unroll 1
            for (int i = 0; i < 72; i++) {
                hz[i * 32] = make_uint4(0, 0, 0, 0);
                __nanosleep(200);
            }
        } else if (warp == 9 || warp == 10) {
            asm volatile("barrier.cluster.arrive.relaxed.aligned;" ::: "memory");
            const uint32_t tag = (ld_epoch(sc_) + 1) & 0xffffu;
            bar_sync(4, 320);
            const int blk = warp == 9 ? 72 + b : 200 + b;
            if (blk < 216) {
                float acc[8];
#pragma unroll
                for (int e = 0; e < 8; e++) acc[e] = 0.f;
                const uint4* wp = reinterpret_cast<const uint4*>(wmod + (size_t)(lane >> 1) * (6 * DM) + blk * 16) + (lane & 1);
                const unsigned short* cp = reinterpret_cast<const unsigned short*>(cvec) + (lane >> 1);
#pragma unroll 1
                for (int i = 0; i < 36; i++) {
                    const uint4 w = __ldg(wp + (size_t)i * (16 * 6 * DM / 8));
                    const float sc = silu_bf16(__ldg(cp + i * 16));
                    acc[0] = fmaf(sc, bf_lo(w.x), acc[0]);
                    acc[1] = fmaf(sc, bf_hi(w.x), acc[1]);
                    acc[2] = fmaf(sc, bf_lo(w.y), acc[2]);
                    acc[3] = fmaf(sc, bf_hi(w.y), acc[3]);
                    acc[4] = fmaf(sc, bf_lo(w.z), acc[4]);
                    acc[5] = fmaf(sc, bf_hi(w.z), acc[5]);
                    acc[6] = fmaf(sc, bf_lo(w.w), acc[6]);
                    acc[7] = fmaf(sc, bf_hi(w.w), acc[7]);
                }
#pragma unroll
                for (int o = 2; o < 32; o <<= 1)
#pragma unroll
                    for (int e = 0; e < 8; e++) acc[e] += __shfl_xor_sync(0xffffffffu, acc[e], o);
                if (lane < 2) {
#pragma unroll
                    for (int e = 0; e < 8; e++) st_mod(sc_->mod + blk * 16 + lane * 8 + e, acc[e], tag);
                }
            }
        }
    } else {
        asm volatile("setmaxnreg.inc.sync.aligned.u32 240;");
        const int wg = warp >> 2;
        const int tid = threadIdx.x;
        Ctx cx;
        cx.sbase = sbase;
        cx.rel_cta = (lane == 0 && (warp & 3) < 2) ? (warp & 3) : 2;
        const uint32_t red = sbase + OFF_RED;
        const int own = mt * 8 + g;
        const int wown = mt * 8 + warp;
        PROF(0);
        PROFG(30);
        PROFR(17);
        const uint32_t epoch = ld_epoch(sc_);
        {
            uint4 w1[5];
            unsigned short cu[5];
            const int half = tid & 1, r0 = tid >> 1;
            if (b < 72) {
#pragma unroll
                for (int i = 0; i < 5; i++) {
                    const int row = min(r0 + 128 * i, DM - 1);
                    cu[i] = __ldg(reinterpret_cast<const unsigned short*>(cvec) + row);
                    w1[i] = __ldg(reinterpret_cast<const uint4*>(wmod + (size_t)row * (6 * DM) + half * 8) + b * 2);
                }
            }
            if (warp == 0) {
                if (lane == 0) {
                    mbar_init(sbase + OFF_XBAR, 1);
                    asm volatile("fence.mbarrier_init.release.cluster;\nfence.proxy.async.shared::cta;" ::: "memory");
                }
                rows_load(sbase, maps.x + (size_t)own * 16 * DM, lane);
            }
            PROFR(18);
            asm volatile("barrier.cluster.arrive.relaxed.aligned;" ::: "memory");
            if (b < 72) {
                float sc[5];
#pragma unroll
                for (int i = 0; i < 5; i++) sc[i] = (r0 + 128 * i < DM) ? silu_bf16(cu[i]) : 0.f;
                mod_block(w1, sc, sc_->mod + b * 16, red + 1024, warp, lane, (epoch + 1) & 0xffffu);
            } else {
                bar_sync(3, 256);
            }
            asm volatile("" ::"r"(epoch) : "memory");
            bar_arrive(4, 320);
            PROFR(21);
        }

        Ring ring{0u, 0u};
        int stage = 0;
        asm volatile("" : "+r"(stage));
#pragma unroll 1
        for (;; stage++) {
            int tid, lane;
            asm volatile("mov.u32 %0, %%tid.x;" : "=r"(tid));
            lane = tid & 31;
            {
                float v[36], md[3][18];
                const uint32_t tag = (epoch + 1) & 0xffffu;
                const uint32_t* modp = sc_->mod + warp * 16 + (lane & 3) * 2;
                if (stage == 0) {
#pragma unroll
                    for (int i = 0; i < 18; i++) md[0][i] = md[1][i] = md[2][i] = 0.f;
#pragma unroll
                    for (int i = 0; i < 36; i++) v[i] = 0.f;
                } else {
                    const uint4* psrc = sc_->part + (size_t)own * 8 * 36 * 32;
                    sum_partials(v, psrc + tid, stage & 1);
                    PROF(stage == 1 ? 8 : 15);
                    sum_tail(v, md, reinterpret_cast<const uint2*>(psrc + 32 * 32) + tid, stage & 1,
                             modp + (stage * 3 - 1) * DM, modp + 3 * DM, warp, tag);
                }
                mbar_wait(sbase + OFF_XBAR, stage & 1);
                if (stage == 0) PROFR(22);
                {
                    const float gs = stage == 2 ? 0.5f : 1.f;
                    const uint32_t rows = sbase + OFF_ROWS + (lane >> 2) * XROW_STRIDE + warp * 32 + (lane & 3) * 4;
#pragma unroll
                    for (int j = 0; j < 9; j++) {
                        const uint32_t ad = rows + own_col(j) * 2 - (j == 8 ? warp * 16 : 0);
                        const uint32_t u0 = __float_as_uint(lds32f(ad)), u1 = __float_as_uint(lds32f(ad + 8 * XROW_STRIDE));
                        const float g0 = md[0][2 * j] * gs, g1 = md[0][2 * j + 1] * gs;
                        v[4 * j] = fmaf(g0, v[4 * j], bf_lo(u0));
                        v[4 * j + 1] = fmaf(g1, v[4 * j + 1], bf_hi(u0));
                        v[4 * j + 2] = fmaf(g0, v[4 * j + 2], bf_lo(u1));
                        v[4 * j + 3] = fmaf(g1, v[4 * j + 3], bf_hi(u1));
                        sts32f(ad, __uint_as_float(pack_bf16(v[4 * j], v[4 * j + 1])));
                        sts32f(ad + 8 * XROW_STRIDE, __uint_as_float(pack_bf16(v[4 * j + 2], v[4 * j + 3])));
                    }
                    asm volatile("fence.proxy.async.shared::cta;" ::: "memory");
                }
                if (stage == 2) break;
                PROF(stage == 0 ? 1 : 9);
                layernorm_rows(v, red, warp, lane);
                if (stage == 0) PROFR(27);
                if (stage == 0) load_mod0(md, modp, warp, tag);
                if (stage == 0) PROFR(28);
                PROF(stage == 0 ? 2 : 10);
                modulate_store(v, md[1], md[2], sc_->h[epoch & 1][stage] + (size_t)own * 36 * 32, warp, lane);
                if (stage == 0) asm volatile("barrier.cluster.wait.aligned;" ::: "memory");
            }

            const uint32_t spill = sbase + 8 * SLOT_BYTES + wg * 3 * SLOT_BYTES + (tid & 127) * 16;
            uint32_t a[144];
            PROF(stage == 0 ? 3 : 11);
            {
                const uint4* hsrc = sc_->h[epoch & 1][stage] + (size_t)wown * 36 * 32 + lane;
                poll_frags<32, 36>(a, hsrc);
                PROF(stage == 0 ? 4 : 12);
                if (stage == 1) PROFG(25);
                if (wg == 1) bar_sync(5, 256);
                poll_frags<0, 32>(a, hsrc);
                if (wg == 0) bar_arrive(5, 256);
            }
            uint4* hhbuf = sc_->hh + (size_t)b * 8 * 256 + tid;
            float d[64];
#pragma unroll 1
            for (int ch = 0;; ch++) {
                gemm_n128(d, a, cx, ring, true);
                if (stage == 0) {
#pragma unroll
                    for (int i = 0; i < 64; i++) d[i] *= SM_SCALE;
                    if (ch == 3) break;
#pragma unroll
                    for (int v = 0; v < 8; v++)
                        sts128(spill + (ch * 8 + v) * 2048, pack_bf16(d[8 * v], d[8 * v + 1]),
                               pack_bf16(d[8 * v + 2], d[8 * v + 3]), pack_bf16(d[8 * v + 4], d[8 * v + 5]),
                               pack_bf16(d[8 * v + 6], d[8 * v + 7]));
                } else {
#pragma unroll
                    for (int i = 0; i < 32; i++) {
                        const float gv = d[i], gu = gv * d[32 + i];
                        const float z = gv * fmaf(gv * gv, 0.7978845608028654f * 0.044715f, 0.7978845608028654f);
                        d[i] = fmaf(gu, tanh_fast(z), gu);
                    }
                    if (ch == 8) break;
                    if (warp == 0) {
                        if (ch == 0) rows_store(sbase, sc_->x2 + (size_t)own * 16 * DM, lane);
                        if (ch == 1) rows_store_wait();
                    }
#pragma unroll
                    for (int v = 0; v < 4; v++) {
                        const uint4 h4 = make_uint4(pack_bf16(d[8 * v], d[8 * v + 1]), pack_bf16(d[8 * v + 2], d[8 * v + 3]),
                                                    pack_bf16(d[8 * v + 4], d[8 * v + 5]), pack_bf16(d[8 * v + 6], d[8 * v + 7]));
                        if (ch < 2)
                            __stcg(hhbuf + (ch * 4 + v) * 256, h4);
                        else
                            sts128(spill + ((ch - 2) * 4 + v) * 2048, h4.x, h4.y, h4.z, h4.w);
                    }
                }
            }
            if (stage == 0) {
                uint32_t q[32];
#pragma unroll
                for (int i = 0; i < 32; i++) q[i] = pack_bf16(d[2 * i], d[2 * i + 1]);
                PROF(5);
                PROFG(23);
                if (wg == 0) bar_arrive(6, 160);
                {
                    float o[64], sa[32], sb[32];
                    uint32_t pa[16], pb[16];
#pragma unroll
                    for (int i = 0; i < 64; i++) o[i] = 0.f;
                    float n0 = 0.f, n1 = 0.f, l0 = 1.f, l1 = 1.f;
                    bool shifted = false;
                    const uint64_t dbase = desc_of(sbase);
                    const uint64_t dbk = dbase - (511u << 16);
                    const int my_bar = 1 + wg, other_bar = 2 - wg;

                    auto softmax_a = [&](bool first, float& s0, float& s1) {
                        if (first) {
                            shifted = false;
                            n0 = n1 = 0.f;
                            l0 = l1 = 0.f;
                        }
                        if (shifted)
                            exp_step<true>(sa, pa, n0, n1, s0, s1);
                        else
                            exp_step<false>(sa, pa, n0, n1, s0, s1);
                    };
                    auto softmax_b = [&](bool first, float s0, float s1) {
                        float u0, u1;
                        if (shifted)
                            exp_step<true>(sb, pb, n0, n1, u0, u1);
                        else
                            exp_step<false>(sb, pb, n0, n1, u0, u1);
                        s0 += u0;
                        s1 += u1;
                        bool bad = !(fmaxf(s0, s1) <= SM_HI);
                        if (first) {
                            float r0 = s0 + __shfl_xor_sync(0xffffffffu, s0, 1), r1 = s1 + __shfl_xor_sync(0xffffffffu, s1, 1);
                            r0 += __shfl_xor_sync(0xffffffffu, r0, 2);
                            r1 += __shfl_xor_sync(0xffffffffu, r1, 2);
                            bad = bad || !(fminf(r0, r1) >= SM_LO);
                        }
                        if (__any_sync(0xffffffffu, bad)) {
                            float x0, x1;
                            row_max(sa, sb, x0, x1);
                            x0 = -x0;
                            x1 = -x1;
                            if (!first) {
                                x0 = fminf(x0, n0);
                                x1 = fminf(x1, n1);
                                const float al0 = ex2(x0 - n0), al1 = ex2(x1 - n1);
                                l0 *= al0;
                                l1 *= al1;
#pragma unroll
                                for (int i = 0; i < 16; i++) {
                                    o[4 * i] *= al0;
                                    o[4 * i + 1] *= al0;
                                    o[4 * i + 2] *= al1;
                                    o[4 * i + 3] *= al1;
                                }
                            }
                            n0 = x0;
                            n1 = x1;
                            shifted = true;
                            exp_step<true>(sa, pa, n0, n1, s0, s1);
                            exp_step<true>(sb, pb, n0, n1, u0, u1);
                            s0 += u0;
                            s1 += u1;
                        }
                        l0 += s0;
                        l1 += s1;
                    };

                    cx.wait_full(4, 0);
                    if (wg == 1) bar_sync(my_bar, 256);
                    wg_fence();
                    qk_step(sa, q, dbk + 4 * 1024);
                    qk_step(sb, q, dbk + 5 * 1024);
                    wg_commit();
                    bar_arrive(other_bar, 256);
                    wg_wait<0>();
                    pin(sa);
                    pin(sb);
                    cx.release(4);
                    cx.wait_full(6, 0);
                    {
                        float s0, s1;
                        softmax_a(true, s0, s1);
                        softmax_b(true, s0, s1);
                    }
                    uint32_t alo = (uint32_t)dbase + 6 * 1024, blo = (uint32_t)dbase;
                    const uint32_t dhi = (uint32_t)(dbase >> 32);
#pragma unroll 1
                    for (int t = 1; t < 64; t++) {
                        const int j = t & 15;
                        const uint32_t sA = 2 + 4 * (t & 1), sB = 4 - 4 * (t & 1);
                        const uint64_t da = ((uint64_t)dhi << 32) | alo, db = ((uint64_t)dhi << 32) | blo;
                        TL(0);
                        bar_sync(my_bar, 256);
                        TL(2);
                        wg_fence();
                        pv_step(o, pa, da + 1024, j != 1);
                        qk_step(sa, q, da - (511u << 16));
                        wg_commit();
                        cx.wait_full(sB, ((36 + 4 * t) >> 3) & 1);
                        wg_fence();
                        qk_step(sb, q, db - (511u << 16));
                        pv_step(o, pb, db + 1024, 1);
                        wg_commit();
                        bar_arrive(other_bar, 256);
                        alo ^= 4096;
                        blo ^= 4096;
                        asm volatile("" : "+r"(alo), "+r"(blo));
                        TL(3);
                        wg_wait<1>();
                        pin(sa);
                        pin(pa);
                        TL(4);
                        cx.release(sA);
                        const float lp0 = l0, lp1 = l1;
                        float s0, s1;
                        softmax_a(j == 0, s0, s1);
                        TL(5);
                        wg_wait<0>();
                        pin(o);
                        pin(sb);
                        pin(pb);
                        TL(6);
                        cx.release(sB);
                        if (j == 0) {
                            float i0, i1;
                            inv_row_sums(lp0, lp1, i0, i1);
                            const uint32_t dst = spill + ((t >> 4) - 1) * 16384;
#pragma unroll
                            for (int v = 0; v < 8; v++)
                                sts128(dst + v * 2048, pack_bf16(o[8 * v] * i0, o[8 * v + 1] * i0),
                                       pack_bf16(o[8 * v + 2] * i1, o[8 * v + 3] * i1),
                                       pack_bf16(o[8 * v + 4] * i0, o[8 * v + 5] * i0),
                                       pack_bf16(o[8 * v + 6] * i1, o[8 * v + 7] * i1));
                        }
                        const uint32_t bn = sbase + OFF_FULL + (8 - sA) * 8, pn = ((38 + 4 * t) >> 3) & 1;
                        const bool okn = mbar_try(bn, pn);
                        TL(1);
                        softmax_b(j == 0, s0, s1);
                        if (!okn || j == 15) {
                            mbar_wait(bn, pn);
                            if (j == 15 && t < 63) {
                                const uint32_t src = spill + (t >> 4) * 16384;
#pragma unroll
                                for (int v = 0; v < 8; v++)
                                    lds128(src + v * 2048, q[4 * v], q[4 * v + 1], q[4 * v + 2], q[4 * v + 3]);
                            }
                        }
                        TL(7);
                    }
                    bar_sync(my_bar, 256);
                    wg_fence();
                    pv_step(o, pa, dbase + 2 * 1024, 1);
                    pv_step(o, pb, dbase + 3 * 1024, 1);
                    wg_commit();
                    if (wg == 0) bar_arrive(other_bar, 256);
                    float i0, i1;
                    inv_row_sums(l0, l1, i0, i1);
                    wg_wait<0>();
                    pin(o);
                    cx.release(2);
#pragma unroll
                    for (int i = 0; i < 16; i++) {
                        a[96 + 2 * i] = pack_bf16(o[4 * i] * i0, o[4 * i + 1] * i0);
                        a[96 + 2 * i + 1] = pack_bf16(o[4 * i + 2] * i1, o[4 * i + 3] * i1);
                    }
#pragma unroll
                    for (int i = 128; i < 144; i++) a[i] = 0;
                }
                ring.slot = 4;
                ring.phase = 0;
                PROF(6);
                PROFG(24);
            } else {
#pragma unroll
                for (int v = 0; v < 8; v++) {
                    const uint4 t = __ldcg(hhbuf + v * 256);
                    a[112 + 4 * v] = t.x;
                    a[113 + 4 * v] = t.y;
                    a[114 + 4 * v] = t.z;
                    a[115 + 4 * v] = t.w;
                }
#pragma unroll
                for (int i = 0; i < 16; i++) a[96 + i] = pack_bf16(d[2 * i], d[2 * i + 1]);
                PROF(13);
            }
#pragma unroll
            for (int v = 0; v < 24; v++) lds128(spill + v * 2048, a[4 * v], a[4 * v + 1], a[4 * v + 2], a[4 * v + 3]);

            {
                uint4* dst = sc_->part + ((size_t)wown * 8 + g) * 36 * 32 + lane;
                const uint32_t ptag = (stage + 1) & 1;
#pragma unroll 1
                for (int p = 0; p < 4; p++) {
                    gemm_n128(d, a, cx, ring, stage != 0);
#pragma unroll
                    for (int u = 0; u < 8; u++)
                        st128(dst + (p * 8 + u) * 32, (pack_bf16(d[8 * u], d[8 * u + 1]) & ~1u) | ptag,
                              pack_bf16(d[8 * u + 2], d[8 * u + 3]), pack_bf16(d[8 * u + 4], d[8 * u + 5]),
                              pack_bf16(d[8 * u + 6], d[8 * u + 7]));
                    if (p == 0 && warp == 0) rows_load(sbase, (stage == 0 ? maps.x : sc_->x2) + (size_t)own * 16 * DM, lane);
                }
                float e[32];
                gemm_n64(e, a, cx, ring, stage != 0);
                uint2* dst2 = reinterpret_cast<uint2*>(dst - lane + 32 * 32) + lane;
#pragma unroll
                for (int j = 0; j < 8; j++)
                    st64(dst2 + j * 32, (pack_bf16(e[4 * j], e[4 * j + 1]) & ~1u) | ptag, pack_bf16(e[4 * j + 2], e[4 * j + 3]));
            }
            PROF(stage == 0 ? 7 : 14);
            if (stage == 1) {
                PROFG(26);
                asm volatile("barrier.cluster.arrive.relaxed.aligned;" ::: "memory");
            }
        }
        bar_sync(3, 256);
        if (warp == 0) {
            rows_store(sbase, maps.out + (size_t)own * 16 * DM, lane);
            if (b == 0 && lane == 0) sc_->epoch = epoch + 1;
            rows_store_wait();
        }
        PROF(16);
        PROFG(31);
        asm volatile("barrier.cluster.wait.aligned;" ::: "memory");
    }
}

typedef CUresult (*EncodeFn)(CUtensorMap*, CUtensorMapDataType, cuuint32_t, void*, const cuuint64_t*, const cuuint64_t*,
                             const cuuint32_t*, const cuuint32_t*, CUtensorMapInterleave, CUtensorMapSwizzle,
                             CUtensorMapL2promotion, CUtensorMapFloatOOBfill);

void make_map(EncodeFn enc, CUtensorMap* m, const void* ptr, uint64_t rows, uint64_t cols) {
    cuuint64_t gdim[2] = {cols, rows};
    cuuint64_t gstr[1] = {cols * 2};
    cuuint32_t box[2] = {64, 64};
    cuuint32_t estr[2] = {1, 1};
    enc(m, CU_TENSOR_MAP_DATA_TYPE_BFLOAT16, 2, const_cast<void*>(ptr), gdim, gstr, box, estr,
        CU_TENSOR_MAP_INTERLEAVE_NONE, CU_TENSOR_MAP_SWIZZLE_128B, CU_TENSOR_MAP_L2_PROMOTION_L2_128B,
        CU_TENSOR_MAP_FLOAT_OOB_FILL_NONE);
}

}

extern "C" void kernel_launch(void* const* d_in, const int* in_sizes, int n_in, void* d_out, int out_size) {
    (void)in_sizes;
    (void)n_in;
    (void)out_size;
    void* fn = nullptr;
    cudaDriverEntryPointQueryResult qr;
    cudaGetDriverEntryPoint("cuTensorMapEncodeTiled", &fn, cudaEnableDefault, &qr);
    EncodeFn enc = (EncodeFn)fn;
    Params maps;
    maps.x = (const __nv_bfloat16*)d_in[0];
    maps.cvec = (const __nv_bfloat16*)d_in[9];
    maps.wmod = (const __nv_bfloat16*)d_in[10];
    maps.kc = (const __nv_bfloat16*)d_in[1];
    maps.vc = (const __nv_bfloat16*)d_in[2];
    maps.out = (__nv_bfloat16*)d_out;
    void* scp = nullptr;
    cudaGetSymbolAddress(&scp, g_scratch);
    maps.sc = (Scratch*)scp;
    make_map(enc, &maps.k, d_in[1], 32 * 2048, 128);
    make_map(enc, &maps.v, d_in[2], 32 * 2048, 128);
    make_map(enc, &maps.wq, d_in[3], 576, 4096);
    make_map(enc, &maps.wo, d_in[4], 4096, 576);
    make_map(enc, &maps.wg, d_in[6], 576, 4608);
    make_map(enc, &maps.wu, d_in[7], 576, 4608);
    make_map(enc, &maps.wd, d_in[8], 4608, 576);
    cudaFuncSetAttribute(fused_block_kernel, cudaFuncAttributeMaxDynamicSharedMemorySize, SMEM_BYTES);
    fused_block_kernel<<<128, 384, SMEM_BYTES>>>(maps);
}
```

```cpp
#include <cuda_runtime.h>
#include <cuda_bf16.h>
#include <cuda.h>
#include <stdint.h>

namespace {

constexpr int DM = 576;
constexpr int SLOT_BYTES = 16384;
constexpr int BOX_BYTES = 8192;
constexpr int NUNITS = 14;
constexpr int SMEM_TAIL = NUNITS * SLOT_BYTES;
constexpr int SMEM_BYTES = SMEM_TAIL + 2048 + 1024;
constexpr int OFF_FULL = SMEM_TAIL;
constexpr int OFF_EMPTY = SMEM_TAIL + 64;
constexpr int OFF_RED = SMEM_TAIL + 128;

constexpr int KV_AHEAD = 16;
constexpr int OFF_XBAR = SMEM_TAIL + 1792;
constexpr int OFF_ROWS = 8 * SLOT_BYTES;
constexpr int OFF_MODT = OFF_ROWS + 20480;
constexpr int XROW_STRIDE = DM * 2 + 16;

struct Scratch {
    unsigned epoch;
    unsigned pad[31];
    uint32_t mod[6 * DM];
    uint4 h[2][2][128 * 36 * 32];
    uint4 part[128 * 8 * 36 * 32];
    uint4 hh[128 * 8 * 256];
    __nv_bfloat16 x2[2048 * DM];
};
__device__ Scratch g_scratch;

#define TL(i)
#define PROFR(i)
#define PROF(i)
#define PROFG(i)

struct Params {
    const __nv_bfloat16 *x, *cvec, *wmod, *kc, *vc;
    __nv_bfloat16* out;
    Scratch* sc;
    CUtensorMap k, v, wq, wo, wg, wu, wd;
};

__device__ __forceinline__ uint32_t smem_u32(const void* p) { return (uint32_t)__cvta_generic_to_shared(p); }
__device__ __forceinline__ void mbar_init(uint32_t a, uint32_t c) {
    asm volatile("mbarrier.init.shared::cta.b64 [%0], %1;" ::"r"(a), "r"(c) : "memory");
}
__device__ __forceinline__ void mbar_expect_tx(uint32_t a, uint32_t bytes) {
    asm volatile("mbarrier.arrive.expect_tx.shared::cta.b64 _, [%0], %1;" ::"r"(a), "r"(bytes) : "memory");
}
__device__ __forceinline__ bool mbar_try(uint32_t a, uint32_t ph) {
    uint32_t ok;
    asm volatile(
        "{\n.reg .pred p;\nmbarrier.try_wait.parity.shared::cta.b64 p, [%1], %2;\nselp.u32 %0, 1, 0, p;\n}"
        : "=r"(ok)
        : "r"(a), "r"(ph)
        : "memory");
    return ok != 0;
}
__device__ __forceinline__ uint32_t clk32() {
    uint32_t c;
    asm volatile("mov.u32 %0, %%clock;" : "=r"(c));
    return c;
}
constexpr uint32_t WAIT_LIMIT = 1u << 30;
__device__ __forceinline__ void mbar_wait(uint32_t a, uint32_t ph) {
    if (mbar_try(a, ph)) return;
    uint32_t t0 = clk32();
    while (!mbar_try(a, ph)) {
        if (clk32() - t0 > WAIT_LIMIT) break;
    }
}
__device__ __forceinline__ void mbar_arrive_cluster(uint32_t a, uint32_t cta) {
    asm volatile(
        "{\n.reg .b32 ra;\nmapa.shared::cluster.u32 ra, %0, %1;\nmbarrier.arrive.shared::cluster.b64 _, [ra];\n}" ::"r"(a),
        "r"(cta)
        : "memory");
}
__device__ __forceinline__ void tma_mc(uint32_t dst, const CUtensorMap* m, int c0, int c1, uint32_t bar) {
    asm volatile(
        "cp.async.bulk.tensor.2d.shared::cluster.global.mbarrier::complete_tx::bytes.multicast::cluster"
        " [%0], [%1, {%3, %4}], [%2], %5;" ::"r"(dst),
        "l"(m), "r"(bar), "r"(c0), "r"(c1), "h"((uint16_t)3)
        : "memory");
}
__device__ __forceinline__ void l2_prefetch(const void* p, uint32_t bytes) {
    asm volatile("cp.async.bulk.prefetch.L2.global [%0], %1;" ::"l"(p), "r"(bytes) : "memory");
}
__device__ __forceinline__ void bar_sync(int id, int n) { asm volatile("bar.sync %0, %1;" ::"r"(id), "r"(n) : "memory"); }
__device__ __forceinline__ void bar_arrive(int id, int n) {
    asm volatile("bar.arrive %0, %1;" ::"r"(id), "r"(n) : "memory");
}
__device__ __forceinline__ void wg_fence() { asm volatile("wgmma.fence.sync.aligned;" ::: "memory"); }
__device__ __forceinline__ void wg_commit() { asm volatile("wgmma.commit_group.sync.aligned;" ::: "memory"); }
template <int N>
__device__ __forceinline__ void wg_wait() {
    asm volatile("wgmma.wait_group.sync.aligned %0;" ::"n"(N) : "memory");
}
template <int N>
__device__ __forceinline__ void pin(float (&d)[N]) {
#pragma unroll
    for (int i = 0; i < N; i++) asm volatile("" : "+f"(d[i])::"memory");
}
template <int N>
__device__ __forceinline__ void pin(uint32_t (&d)[N]) {
#pragma unroll
    for (int i = 0; i < N; i++) asm volatile("" : "+r"(d[i])::"memory");
}
__device__ __forceinline__ uint32_t pack_bf16(float lo, float hi) {
    uint32_t r;
    asm("cvt.rn.bf16x2.f32 %0, %1, %2;" : "=r"(r) : "f"(hi), "f"(lo));
    return r;
}
__device__ __forceinline__ float bf_lo(uint32_t v) { return __uint_as_float(v << 16); }
__device__ __forceinline__ float bf_hi(uint32_t v) { return __uint_as_float(v & 0xffff0000u); }
__device__ __forceinline__ float round_bf16(float v) { return __bfloat162float(__float2bfloat16_rn(v)); }
__device__ __forceinline__ float ex2(float x) {
    float y;
    asm("ex2.approx.ftz.f32 %0, %1;" : "=f"(y) : "f"(x));
    return y;
}
__device__ __forceinline__ float rcp(float x) {
    float y;
    asm("rcp.approx.ftz.f32 %0, %1;" : "=f"(y) : "f"(x));
    return y;
}
__device__ __forceinline__ float tanh_fast(float x) {
    float y;
    asm("tanh.approx.f32 %0, %1;" : "=f"(y) : "f"(x));
    return y;
}
__device__ __forceinline__ void sts128(uint32_t a, uint32_t x, uint32_t y, uint32_t z, uint32_t w) {
    asm volatile("st.shared.v4.b32 [%0], {%1,%2,%3,%4};" ::"r"(a), "r"(x), "r"(y), "r"(z), "r"(w) : "memory");
}
__device__ __forceinline__ void lds128(uint32_t a, uint32_t& x, uint32_t& y, uint32_t& z, uint32_t& w) {
    asm volatile("ld.shared.v4.b32 {%0,%1,%2,%3}, [%4];" : "=r"(x), "=r"(y), "=r"(z), "=r"(w) : "r"(a) : "memory");
}
__device__ __forceinline__ void sts32f(uint32_t a, float v) {
    asm volatile("st.shared.f32 [%0], %1;" ::"r"(a), "f"(v) : "memory");
}
__device__ __forceinline__ float lds32f(uint32_t a) {
    float v;
    asm volatile("ld.shared.f32 %0, [%1];" : "=f"(v) : "r"(a) : "memory");
    return v;
}
#define F8(d, b) \
    "+f"(d[b]), "+f"(d[b + 1]), "+f"(d[b + 2]), "+f"(d[b + 3]), "+f"(d[b + 4]), "+f"(d[b + 5]), "+f"(d[b + 6]), "+f"(d[b + 7])

template <int TB>
__device__ __forceinline__ void wgmma_n128(float (&d)[64], uint32_t a0, uint32_t a1, uint32_t a2, uint32_t a3,
                                           uint64_t db, int sc) {
    asm volatile(
        "{\n.reg .pred p;\nsetp.ne.b32 p, %69, 0;\n"
        "wgmma.mma_async.sync.aligned.m64n128k16.f32.bf16.bf16 "
        "{%0,%1,%2,%3,%4,%5,%6,%7,%8,%9,%10,%11,%12,%13,%14,%15,%16,%17,%18,%19,%20,%21,%22,%23,%24,%25,%26,%27,%28,%29,%30,%31,"
        "%32,%33,%34,%35,%36,%37,%38,%39,%40,%41,%42,%43,%44,%45,%46,%47,%48,%49,%50,%51,%52,%53,%54,%55,%56,%57,%58,%59,%60,%61,%62,%63},"
        "{%64,%65,%66,%67}, %68, p, 1, 1, %70;\n}"
        : F8(d, 0), F8(d, 8), F8(d, 16), F8(d, 24), F8(d, 32), F8(d, 40), F8(d, 48), F8(d, 56)
        : "r"(a0), "r"(a1), "r"(a2), "r"(a3), "l"(db), "r"(sc), "n"(TB));
}
#define O8(d, b) \
    "=f"(d[b]), "=f"(d[b + 1]), "=f"(d[b + 2]), "=f"(d[b + 3]), "=f"(d[b + 4]), "=f"(d[b + 5]), "=f"(d[b + 6]), "=f"(d[b + 7])
template <int TB>
__device__ __forceinline__ void wgmma_n128_z(float (&d)[64], uint32_t a0, uint32_t a1, uint32_t a2, uint32_t a3,
                                             uint64_t db) {
    asm volatile(
        "wgmma.mma_async.sync.aligned.m64n128k16.f32.bf16.bf16 "
        "{%0,%1,%2,%3,%4,%5,%6,%7,%8,%9,%10,%11,%12,%13,%14,%15,%16,%17,%18,%19,%20,%21,%22,%23,%24,%25,%26,%27,%28,%29,%30,%31,"
        "%32,%33,%34,%35,%36,%37,%38,%39,%40,%41,%42,%43,%44,%45,%46,%47,%48,%49,%50,%51,%52,%53,%54,%55,%56,%57,%58,%59,%60,%61,%62,%63},"
        "{%64,%65,%66,%67}, %68, 0, 1, 1, %69;"
        : O8(d, 0), O8(d, 8), O8(d, 16), O8(d, 24), O8(d, 32), O8(d, 40), O8(d, 48), O8(d, 56)
        : "r"(a0), "r"(a1), "r"(a2), "r"(a3), "l"(db), "n"(TB));
}
template <int TB>
__device__ __forceinline__ void wgmma_n64_z(float (&d)[32], uint32_t a0, uint32_t a1, uint32_t a2, uint32_t a3,
                                            uint64_t db) {
    asm volatile(
        "wgmma.mma_async.sync.aligned.m64n64k16.f32.bf16.bf16 "
        "{%0,%1,%2,%3,%4,%5,%6,%7,%8,%9,%10,%11,%12,%13,%14,%15,%16,%17,%18,%19,%20,%21,%22,%23,%24,%25,%26,%27,%28,%29,%30,%31},"
        "{%32,%33,%34,%35}, %36, 0, 1, 1, %37;"
        : O8(d, 0), O8(d, 8), O8(d, 16), O8(d, 24)
        : "r"(a0), "r"(a1), "r"(a2), "r"(a3), "l"(db), "n"(TB));
}
template <int TB>
__device__ __forceinline__ void wgmma_n64(float (&d)[32], uint32_t a0, uint32_t a1, uint32_t a2, uint32_t a3,
                                          uint64_t db) {
    asm volatile(
        "wgmma.mma_async.sync.aligned.m64n64k16.f32.bf16.bf16 "
        "{%0,%1,%2,%3,%4,%5,%6,%7,%8,%9,%10,%11,%12,%13,%14,%15,%16,%17,%18,%19,%20,%21,%22,%23,%24,%25,%26,%27,%28,%29,%30,%31},"
        "{%32,%33,%34,%35}, %36, 1, 1, 1, %37;"
        : F8(d, 0), F8(d, 8), F8(d, 16), F8(d, 24)
        : "r"(a0), "r"(a1), "r"(a2), "r"(a3), "l"(db), "n"(TB));
}

__device__ __forceinline__ uint64_t desc_of(uint32_t saddr) {
    return (uint64_t)(((saddr >> 4) & 0x3FFFu) | (512u << 16)) | ((uint64_t)(64u | (1u << 30)) << 32);
}

struct Ring {
    uint32_t slot;
    uint32_t phase;
    __device__ __forceinline__ void next() {
        if (++slot == 8) {
            slot = 0;
            phase ^= 1;
        }
    }
};

struct Ctx {
    uint32_t sbase;
    uint32_t rel_cta;
    __device__ __forceinline__ void wait_full(uint32_t slot, uint32_t phase) const {
        mbar_wait(sbase + OFF_FULL + slot * 8, phase);
    }
    __device__ __forceinline__ void release(uint32_t slot) const {
        if (rel_cta < 2) mbar_arrive_cluster(sbase + OFF_EMPTY + slot * 8, rel_cta);
    }
};

__device__ __forceinline__ void gemm_n128(float (&d)[64], const uint32_t (&a)[144], const Ctx& c, Ring& r, bool nine) {
    uint32_t prev = 0;
#pragma unroll
    for (int s = 0; s < 9; s++) {
        if (s < 8 || nine) {
            c.wait_full(r.slot, r.phase);
            uint64_t db = desc_of(c.sbase + r.slot * SLOT_BYTES);
            wg_fence();
#pragma unroll
            for (int k = 0; k < 4; k++) {
                if ((s | k) == 0)
                    wgmma_n128_z<1>(d, a[0], a[1], a[2], a[3], db);
                else
                    wgmma_n128<1>(d, a[s * 16 + k * 4], a[s * 16 + k * 4 + 1], a[s * 16 + k * 4 + 2],
                                  a[s * 16 + k * 4 + 3], db + k * 128, 1);
            }
            wg_commit();
            if (s > 0) {
                wg_wait<1>();
                c.release(prev);
            }
            prev = r.slot;
            r.next();
        }
    }
    wg_wait<0>();
    c.release(prev);
    pin(d);
}
__device__ __forceinline__ void gemm_n64(float (&d)[32], const uint32_t (&a)[144], const Ctx& c, Ring& r, bool nine) {
    uint32_t prev = 0;
#pragma unroll
    for (int s = 0; s < 5; s++) {
        if (s < 4 || nine) {
            c.wait_full(r.slot, r.phase);
            uint64_t db = desc_of(c.sbase + r.slot * SLOT_BYTES);
            wg_fence();
#pragma unroll
            for (int k = 0; k < 8; k++) {
                if ((s | k) == 0)
                    wgmma_n64_z<1>(d, a[0], a[1], a[2], a[3], db);
                else if (s * 8 + k < 36)
                    wgmma_n64<1>(d, a[s * 32 + k * 4], a[s * 32 + k * 4 + 1], a[s * 32 + k * 4 + 2],
                                 a[s * 32 + k * 4 + 3], db + k * 128);
            }
            wg_commit();
            if (s > 0) {
                wg_wait<1>();
                c.release(prev);
            }
            prev = r.slot;
            r.next();
        }
    }
    wg_wait<0>();
    c.release(prev);
    pin(d);
}
__device__ __forceinline__ void st128(uint4* p, uint32_t x, uint32_t y, uint32_t z, uint32_t w) {
    asm volatile(
        "{\n.reg .b64 lo, hi;\n.reg .b128 t;\nmov.b64 lo, {%1, %2};\nmov.b64 hi, {%3, %4};\nmov.b128 t, {lo, hi};\n"
        "st.relaxed.gpu.global.b128 [%0], t;\n}" ::"l"(p),
        "r"(x), "r"(y), "r"(z), "r"(w)
        : "memory");
}
__device__ __forceinline__ uint4 ld128(const uint4* p) {
    uint4 r;
    asm volatile(
        "{\n.reg .b64 lo, hi;\n.reg .b128 t;\nld.relaxed.gpu.global.b128 t, [%4];\nmov.b128 {lo, hi}, t;\n"
        "mov.b64 {%0, %1}, lo;\nmov.b64 {%2, %3}, hi;\n}"
        : "=r"(r.x), "=r"(r.y), "=r"(r.z), "=r"(r.w)
        : "l"(p));
    return r;
}
__device__ __forceinline__ void st64(void* p, uint32_t x, uint32_t y) {
    asm volatile("{\n.reg .b64 t;\nmov.b64 t, {%1, %2};\nst.relaxed.gpu.global.b64 [%0], t;\n}" ::"l"(p), "r"(x), "r"(y)
                 : "memory");
}
__device__ __forceinline__ uint2 ld64(const void* p) {
    uint2 r;
    asm volatile("{\n.reg .b64 t;\nld.relaxed.gpu.global.b64 t, [%2];\nmov.b64 {%0, %1}, t;\n}"
                 : "=r"(r.x), "=r"(r.y)
                 : "l"(p));
    return r;
}
__device__ __forceinline__ void rows_load(uint32_t sbase, const __nv_bfloat16* src, int lane) {
    if (lane == 0) mbar_expect_tx(sbase + OFF_XBAR, 16 * DM * 2);
    __syncwarp();
    if (lane < 16)
        asm volatile("cp.async.bulk.shared::cluster.global.mbarrier::complete_tx::bytes [%0], [%1], %2, [%3];" ::"r"(
                         sbase + OFF_ROWS + lane * XROW_STRIDE),
                     "l"(src + lane * DM), "r"(DM * 2), "r"(sbase + OFF_XBAR)
                     : "memory");
    __syncwarp();
}
__device__ __forceinline__ void rows_store(uint32_t sbase, __nv_bfloat16* dst, int lane) {
    if (lane < 16) {
        asm volatile("cp.async.bulk.global.shared::cta.bulk_group [%0], [%1], %2;" ::"l"(dst + lane * DM),
                     "r"(sbase + OFF_ROWS + lane * XROW_STRIDE), "r"(DM * 2)
                     : "memory");
        asm volatile("cp.async.bulk.commit_group;" ::: "memory");
    }
    __syncwarp();
}
__device__ __forceinline__ void rows_store_wait() { asm volatile("cp.async.bulk.wait_group 0;" ::: "memory"); }

__device__ __forceinline__ constexpr int own_col(int j) { return j < 8 ? (j >> 1) * 128 + (j & 1) * 8 : 512; }
__device__ __forceinline__ void row_reduce(float& s0, float& s1, uint32_t red, int warp, int lane) {
    s0 += __shfl_xor_sync(0xffffffffu, s0, 1);
    s1 += __shfl_xor_sync(0xffffffffu, s1, 1);
    s0 += __shfl_xor_sync(0xffffffffu, s0, 2);
    s1 += __shfl_xor_sync(0xffffffffu, s1, 2);
    if ((lane & 3) == 0) {
        sts32f(red + (warp * 16 + (lane >> 2)) * 4, s0);
        sts32f(red + (warp * 16 + 8 + (lane >> 2)) * 4, s1);
    }
    bar_sync(3, 256);
    s0 = 0.f;
    s1 = 0.f;
#pragma unroll
    for (int w = 0; w < 8; w++) {
        s0 += lds32f(red + (w * 16 + (lane >> 2)) * 4);
        s1 += lds32f(red + (w * 16 + 8 + (lane >> 2)) * 4);
    }
}
__device__ __forceinline__ void layernorm_rows(float (&v)[36], uint32_t red, int warp, int lane) {
    float s0 = 0.f, s1 = 0.f;
#pragma unroll
    for (int j = 0; j < 9; j++) {
        s0 += v[4 * j] + v[4 * j + 1];
        s1 += v[4 * j + 2] + v[4 * j + 3];
    }
    row_reduce(s0, s1, red, warp, lane);
    const float m0 = s0 * (1.f / DM), m1 = s1 * (1.f / DM);
    s0 = 0.f;
    s1 = 0.f;
#pragma unroll
    for (int j = 0; j < 9; j++) {
        v[4 * j] -= m0;
        v[4 * j + 1] -= m0;
        v[4 * j + 2] -= m1;
        v[4 * j + 3] -= m1;
        s0 += v[4 * j] * v[4 * j] + v[4 * j + 1] * v[4 * j + 1];
        s1 += v[4 * j + 2] * v[4 * j + 2] + v[4 * j + 3] * v[4 * j + 3];
    }
    row_reduce(s0, s1, red + 512, warp, lane);
    const float r0 = rsqrtf(s0 * (1.f / DM) + 1e-5f), r1 = rsqrtf(s1 * (1.f / DM) + 1e-5f);
#pragma unroll
    for (int j = 0; j < 9; j++) {
        v[4 * j] *= r0;
        v[4 * j + 1] *= r0;
        v[4 * j + 2] *= r1;
        v[4 * j + 3] *= r1;
    }
}
__device__ __forceinline__ void mod_to_smem(uint32_t dst, const uint32_t* src, uint32_t tag) {
    const uint32_t t0 = clk32();
    uint4 u;
    while (true) {
        u = ld128(reinterpret_cast<const uint4*>(src));
        const uint32_t bad = ((u.x ^ tag) | (u.y ^ tag) | (u.z ^ tag) | (u.w ^ tag)) & 0xffffu;
        if (__all_sync(0xffffffffu, bad == 0) || clk32() - t0 > WAIT_LIMIT) break;
        __nanosleep(64);
    }
    sts128(dst, u.x & 0xffff0000u, u.y & 0xffff0000u, u.z & 0xffff0000u, u.w & 0xffff0000u);
}
__device__ __forceinline__ void lds_mod(float (&m)[18], uint32_t src  , int warp) {
#pragma unroll
    for (int j = 0; j < 9; j++)
        asm volatile("ld.shared.v2.f32 {%0,%1}, [%2];"
                     : "=f"(m[2 * j]), "=f"(m[2 * j + 1])
                     : "r"(src + own_col(j) * 4 - (j == 8 ? warp * 32 : 0))
                     : "memory");
}
__device__ __forceinline__ void modulate_store(const float (&v)[36], const float (&shift)[18], const float (&scale)[18],
                                               uint4* hbuf  , int warp, int lane) {
    uint32_t o[18];
#pragma unroll
    for (int j = 0; j < 9; j++) {
        const uint32_t cc = pack_bf16(1.f + scale[2 * j], 1.f + scale[2 * j + 1]);
        const float c0 = bf_lo(cc), c1 = bf_hi(cc);
        o[2 * j] = max(pack_bf16(fmaf(v[4 * j], c0, shift[2 * j]), fmaf(v[4 * j + 1], c1, shift[2 * j + 1])), 1u);
        o[2 * j + 1] = max(pack_bf16(fmaf(v[4 * j + 2], c0, shift[2 * j]), fmaf(v[4 * j + 3], c1, shift[2 * j + 1])), 1u);
    }
#pragma unroll
    for (int i = 0; i < 4; i++) st128(hbuf + (i * 8 + warp) * 32 + lane, o[4 * i], o[4 * i + 1], o[4 * i + 2], o[4 * i + 3]);
    st64(reinterpret_cast<uint2*>(hbuf + (32 + (warp >> 1)) * 32 + lane) + (warp & 1), o[16], o[17]);
}
__device__ __forceinline__ void sum_partials(float (&v)[36], const uint4* src  , uint32_t tag) {
    const uint32_t t0 = clk32();
    while (true) {
        uint4 t[8][4];
#pragma unroll
        for (int s = 0; s < 8; s++)
#pragma unroll
            for (int i = 0; i < 4; i++) t[s][i] = ld128(src + (s * 36 + i * 8) * 32);
        uint32_t bad = 0;
#pragma unroll
        for (int i = 0; i < 32; i++) v[i] = 0.f;
#pragma unroll
        for (int s = 0; s < 8; s++)
#pragma unroll
            for (int i = 0; i < 4; i++) {
                bad |= t[s][i].x ^ tag;
                v[8 * i] += bf_lo(t[s][i].x);
                v[8 * i + 1] += bf_hi(t[s][i].x);
                v[8 * i + 2] += bf_lo(t[s][i].y);
                v[8 * i + 3] += bf_hi(t[s][i].y);
                v[8 * i + 4] += bf_lo(t[s][i].z);
                v[8 * i + 5] += bf_hi(t[s][i].z);
                v[8 * i + 6] += bf_lo(t[s][i].w);
                v[8 * i + 7] += bf_hi(t[s][i].w);
            }
        if (__all_sync(0xffffffffu, (bad & 1u) == 0) || clk32() - t0 > WAIT_LIMIT) break;
    }
}
__device__ __forceinline__ void sum_tail(float (&v)[36], const uint2* src  , uint32_t tag) {
    const uint32_t t0 = clk32();
    while (true) {
        uint2 t[8];
#pragma unroll
        for (int s = 0; s < 8; s++) t[s] = ld64(src + s * 72 * 32);
        uint32_t bad = 0;
        v[32] = v[33] = v[34] = v[35] = 0.f;
#pragma unroll
        for (int s = 0; s < 8; s++) {
            bad |= t[s].x ^ tag;
            v[32] += bf_lo(t[s].x);
            v[33] += bf_hi(t[s].x);
            v[34] += bf_lo(t[s].y);
            v[35] += bf_hi(t[s].y);
        }
        if (__all_sync(0xffffffffu, (bad & 1u) == 0) || clk32() - t0 > WAIT_LIMIT) break;
    }
}
template <int K0, int K1>
__device__ __forceinline__ void poll_frags(uint32_t (&a)[144], const uint4* src  ) {
    const uint32_t t0 = clk32();
    while (true) {
#pragma unroll
        for (int k = K0; k < K1; k++)
            asm volatile("ld.relaxed.gpu.global.v4.u32 {%0,%1,%2,%3}, [%4];"
                         : "=r"(a[4 * k]), "=r"(a[4 * k + 1]), "=r"(a[4 * k + 2]), "=r"(a[4 * k + 3])
                         : "l"(src + k * 32));
        uint32_t m0 = a[4 * K0], m1 = a[4 * K0 + 1];
#pragma unroll
        for (int i = 4 * K0 + 2; i < 4 * K1; i += 2) {
            m0 = min(m0, a[i]);
            m1 = min(m1, a[i + 1]);
        }
        if (__all_sync(0xffffffffu, min(m0, m1) != 0) || clk32() - t0 > WAIT_LIMIT) break;
    }
}

constexpr float SM_SCALE = 0.08838834764831845f * 1.4426950408889634f;
constexpr float SM_HI = 1.2089258e24f;
constexpr float SM_LO = 9.0949470e-13f;
__device__ __forceinline__ void qk_step(float (&s)[32], const uint32_t (&q)[32], uint64_t dk) {
#pragma unroll
    for (int k = 0; k < 8; k++) {
        if (k == 0)
            wgmma_n64_z<0>(s, q[0], q[1], q[2], q[3], dk);
        else
            wgmma_n64<0>(s, q[4 * k], q[4 * k + 1], q[4 * k + 2], q[4 * k + 3], dk + (k >> 2) * 512 + (k & 3) * 2);
    }
}
__device__ __forceinline__ void pv_step(float (&o)[64], const uint32_t (&p)[16], uint64_t dv, int acc) {
#pragma unroll
    for (int k = 0; k < 4; k++)
        wgmma_n128<1>(o, p[4 * k], p[4 * k + 1], p[4 * k + 2], p[4 * k + 3], dv + k * 128, k != 0 ? 1 : acc);
}
template <bool SHIFT>
__device__ __forceinline__ void exp_step(const float (&s)[32], uint32_t (&p)[16], float n0, float n1, float& s0,
                                         float& s1) {
#pragma unroll
    for (int i = 0; i < 8; i++) {
        const float e0 = ex2(SHIFT ? s[4 * i] + n0 : s[4 * i]), e1 = ex2(SHIFT ? s[4 * i + 1] + n0 : s[4 * i + 1]);
        const float e2 = ex2(SHIFT ? s[4 * i + 2] + n1 : s[4 * i + 2]), e3 = ex2(SHIFT ? s[4 * i + 3] + n1 : s[4 * i + 3]);
        if (i == 0) {
            s0 = e0 + e1;
            s1 = e2 + e3;
        } else {
            s0 += e0 + e1;
            s1 += e2 + e3;
        }
        p[2 * i] = pack_bf16(e0, e1);
        p[2 * i + 1] = pack_bf16(e2, e3);
    }
}
__device__ __forceinline__ void row_max(const float (&sa)[32], const float (&sb)[32], float& x0, float& x1) {
    float xa[8];
#pragma unroll
    for (int i = 0; i < 8; i++) xa[i] = fmaxf(sa[i], sb[i]);
#pragma unroll
    for (int k = 1; k < 4; k++)
#pragma unroll
        for (int i = 0; i < 8; i++) xa[i] = fmaxf(xa[i], fmaxf(sa[8 * k + i], sb[8 * k + i]));
    x0 = fmaxf(fmaxf(xa[0], xa[1]), fmaxf(xa[4], xa[5]));
    x1 = fmaxf(fmaxf(xa[2], xa[3]), fmaxf(xa[6], xa[7]));
    x0 = fmaxf(x0, __shfl_xor_sync(0xffffffffu, x0, 1));
    x1 = fmaxf(x1, __shfl_xor_sync(0xffffffffu, x1, 1));
    x0 = fmaxf(x0, __shfl_xor_sync(0xffffffffu, x0, 2));
    x1 = fmaxf(x1, __shfl_xor_sync(0xffffffffu, x1, 2));
}
__device__ __forceinline__ void inv_row_sums(float l0, float l1, float& i0, float& i1) {
    l0 += __shfl_xor_sync(0xffffffffu, l0, 1);
    l1 += __shfl_xor_sync(0xffffffffu, l1, 1);
    l0 += __shfl_xor_sync(0xffffffffu, l0, 2);
    l1 += __shfl_xor_sync(0xffffffffu, l1, 2);
    i0 = rcp(l0);
    i1 = rcp(l1);
}

__device__ __forceinline__ uint32_t ld_epoch(const Scratch* sc) {
    uint32_t e;
    asm volatile("ld.relaxed.gpu.global.u32 %0, [%1];" : "=r"(e) : "l"(&sc->epoch) : "memory");
    return e;
}
__device__ __forceinline__ float silu_bf16(unsigned short c) {
    const float cv = bf_lo(c);
    return round_bf16(cv * rcp(1.f + ex2(-1.4426950408889634f * cv)));
}
__device__ __forceinline__ void st_mod(uint32_t* p, float v, uint32_t tag) {
    asm volatile("st.relaxed.gpu.global.u32 [%0], %1;" ::"l"(p), "r"(__float_as_uint(round_bf16(v)) | tag)
                 : "memory");
}
__device__ __forceinline__ void mod_block(const uint4 (&w)[5], const float (&sc)[5], uint32_t* dst, uint32_t red,
                                          int warp, int lane, uint32_t tag) {
    float acc[8];
#pragma unroll
    for (int e = 0; e < 8; e++) acc[e] = 0.f;
#pragma unroll
    for (int i = 0; i < 5; i++) {
        acc[0] = fmaf(sc[i], bf_lo(w[i].x), acc[0]);
        acc[1] = fmaf(sc[i], bf_hi(w[i].x), acc[1]);
        acc[2] = fmaf(sc[i], bf_lo(w[i].y), acc[2]);
        acc[3] = fmaf(sc[i], bf_hi(w[i].y), acc[3]);
        acc[4] = fmaf(sc[i], bf_lo(w[i].z), acc[4]);
        acc[5] = fmaf(sc[i], bf_hi(w[i].z), acc[5]);
        acc[6] = fmaf(sc[i], bf_lo(w[i].w), acc[6]);
        acc[7] = fmaf(sc[i], bf_hi(w[i].w), acc[7]);
    }
#pragma unroll
    for (int o = 2; o < 32; o <<= 1)
#pragma unroll
        for (int e = 0; e < 8; e++) acc[e] += __shfl_xor_sync(0xffffffffu, acc[e], o);
    if (lane < 2) {
#pragma unroll
        for (int e = 0; e < 8; e++) sts32f(red + (warp * 16 + lane * 8 + e) * 4, acc[e]);
    }
    bar_sync(3, 256);
    if (warp == 0 && lane < 16) {
        float s = 0.f;
#pragma unroll
        for (int w8 = 0; w8 < 8; w8++) s += lds32f(red + (w8 * 16 + lane) * 4);
        st_mod(dst + lane, s, tag);
    }
}

__global__ void __cluster_dims__(2, 1, 1) __launch_bounds__(384, 1)
    fused_block_kernel(const __grid_constant__ Params maps) {
    extern __shared__ uint8_t smem_raw[];
    uint32_t sbase = (smem_u32(smem_raw) + 1023u) & ~1023u;
    asm volatile("" : "+r"(sbase));
    const int b = blockIdx.x;
    const int rank = b & 1;
    const int mt = ((b >> 1) & 7) * 2 + rank;
    const int g = b >> 4;
    const int warp = __shfl_sync(0xffffffffu, threadIdx.x >> 5, 0);
    const int lane = threadIdx.x & 31;
    Scratch* const sc_ = maps.sc;
    const __nv_bfloat16* const wmod = maps.wmod;
    const __nv_bfloat16* const cvec = maps.cvec;

    if (warp >= 8) {
        asm volatile("setmaxnreg.dec.sync.aligned.u32 24;");
        if (warp == 8 && lane == 0) {
#pragma unroll
            for (int i = 0; i < 8; i++) {
                mbar_init(sbase + OFF_FULL + i * 8, 1);
                mbar_init(sbase + OFF_EMPTY + i * 8, 4);
            }
            asm volatile("fence.mbarrier_init.release.cluster;" ::: "memory");
            asm volatile("barrier.cluster.arrive.relaxed;\nbarrier.cluster.wait;" ::: "memory");
            uint32_t slot = 0, phase = 1;
            const uint32_t dst0 = sbase + rank * BOX_BYTES;
            auto acquire = [&](uint32_t bytes) {
                mbar_wait(sbase + OFF_EMPTY + slot * 8, phase);
                mbar_expect_tx(sbase + OFF_FULL + slot * 8, bytes);
            };
            auto adv8 = [&]() {
                if (++slot == 8) {
                    slot = 0;
                    phase ^= 1;
                }
            };
#pragma unroll 1
            for (int hq = 0; hq < 4; hq++) {
                const int col = (g * 4 + ((hq + 1) & 3)) * 128 + rank * 64;
                if (hq == 2) {
                    l2_prefetch(maps.kc + (size_t)(g * 4 * 2048 + (b & 15) * 64) * 128, SLOT_BYTES);
                    l2_prefetch(maps.vc + (size_t)(g * 4 * 2048 + (b & 15) * 64) * 128, SLOT_BYTES);
                }
#pragma unroll 1
                for (int kc = 0; kc < 9; kc++) {
                    acquire(SLOT_BYTES);
                    tma_mc(dst0 + slot * SLOT_BYTES, &maps.wq, col, kc * 64, sbase + OFF_FULL + slot * 8);
                    adv8();
                }
            }
            const int row0 = g * 4 * 2048;
#pragma unroll 1
            for (int n = 0; n < 128; n++) {
                if (n < 4) mbar_wait(sbase + OFF_EMPTY + (slot + 1) * 8, phase);
                acquire(2 * SLOT_BYTES);
                const uint32_t bar = sbase + OFF_FULL + slot * 8;
                const int r0 = n == 0 ? 0 : (n == 127 ? 126 : n + 1);
                const int r1 = n == 0 ? 1 : (n == 127 ? 127 : n - 1);
                tma_mc(dst0 + slot * SLOT_BYTES, n == 127 ? &maps.v : &maps.k, rank * 64, row0 + r0 * 64, bar);
                tma_mc(dst0 + (slot + 1) * SLOT_BYTES, n == 0 ? &maps.k : &maps.v, rank * 64, row0 + r1 * 64, bar);
                adv8();
                adv8();
                const int u = n + KV_AHEAD;
                if (u < 128 && (u & 15) == (b & 15)) {
                    l2_prefetch(maps.kc + (size_t)(row0 + u * 64) * 128, SLOT_BYTES);
                    l2_prefetch(maps.vc + (size_t)(row0 + u * 64) * 128, SLOT_BYTES);
                }
            }
#pragma unroll 1
            for (int p = 0; p < 4; p++)
#pragma unroll 1
                for (int kc = 0; kc < 8; kc++) {
                    acquire(SLOT_BYTES);
                    tma_mc(dst0 + slot * SLOT_BYTES, &maps.wo, p * 128 + rank * 64, g * 512 + kc * 64,
                           sbase + OFF_FULL + slot * 8);
                    adv8();
                }
#pragma unroll 1
            for (int kc = 0; kc < 4; kc++) {
                acquire(SLOT_BYTES);
                tma_mc(dst0 + slot * SLOT_BYTES, &maps.wo, 512, g * 512 + kc * 128 + rank * 64,
                       sbase + OFF_FULL + slot * 8);
                adv8();
            }
            const CUtensorMap* mg = rank ? &maps.wu : &maps.wg;
#pragma unroll 1
            for (int ch = 0; ch < 9; ch++)
#pragma unroll 1
                for (int kc = 0; kc < 9; kc++) {
                    acquire(SLOT_BYTES);
                    tma_mc(dst0 + slot * SLOT_BYTES, mg, g * 576 + ch * 64, kc * 64, sbase + OFF_FULL + slot * 8);
                    adv8();
                }
#pragma unroll 1
            for (int p = 0; p < 4; p++)
#pragma unroll 1
                for (int kc = 2; kc < 11; kc++) {
                    acquire(SLOT_BYTES);
                    tma_mc(dst0 + slot * SLOT_BYTES, &maps.wd, p * 128 + rank * 64, g * 576 + (kc < 9 ? kc : kc - 9) * 64,
                           sbase + OFF_FULL + slot * 8);
                    adv8();
                }
#pragma unroll 1
            for (int i = 0; i < 5; i++) {
                acquire(i < 4 ? SLOT_BYTES : BOX_BYTES);
                const int kc = 2 * i + rank + 2;
                if (i < 4 || rank == 0)
                    tma_mc(dst0 + slot * SLOT_BYTES, &maps.wd, 512, g * 576 + (kc < 9 ? kc : kc - 9) * 64,
                           sbase + OFF_FULL + slot * 8);
                adv8();
            }
        } else if (warp == 11) {
            const int row = b * 5 + lane;
            if (lane < 5 && row < DM) l2_prefetch(wmod + (size_t)row * (6 * DM), 2 * DM * 2);
            asm volatile("barrier.cluster.arrive.relaxed.aligned;" ::: "memory");
            uint4* hz = sc_->h[(ld_epoch(sc_) & 1) ^ 1][0] + (size_t)b * 72 * 32 + lane;
            bar_sync(6, 160);
#pragma unroll 1
            for (int i = 0; i < 72; i++) {
                hz[i * 32] = make_uint4(0, 0, 0, 0);
                __nanosleep(200);
            }
        } else if (warp == 9 || warp == 10) {
            asm volatile("barrier.cluster.arrive.relaxed.aligned;" ::: "memory");
            const uint32_t tag = (ld_epoch(sc_) + 1) & 0xffffu;
            bar_sync(4, 320);
            const int blk = warp == 9 ? 72 + b : 200 + b;
            if (blk < 216) {
                float acc[8];
#pragma unroll
                for (int e = 0; e < 8; e++) acc[e] = 0.f;
                const uint4* wp = reinterpret_cast<const uint4*>(wmod + (size_t)(lane >> 1) * (6 * DM) + blk * 16) + (lane & 1);
                const unsigned short* cp = reinterpret_cast<const unsigned short*>(cvec) + (lane >> 1);
#pragma unroll 1
                for (int i = 0; i < 36; i++) {
                    const uint4 w = __ldg(wp + (size_t)i * (16 * 6 * DM / 8));
                    const float sc = silu_bf16(__ldg(cp + i * 16));
                    acc[0] = fmaf(sc, bf_lo(w.x), acc[0]);
                    acc[1] = fmaf(sc, bf_hi(w.x), acc[1]);
                    acc[2] = fmaf(sc, bf_lo(w.y), acc[2]);
                    acc[3] = fmaf(sc, bf_hi(w.y), acc[3]);
                    acc[4] = fmaf(sc, bf_lo(w.z), acc[4]);
                    acc[5] = fmaf(sc, bf_hi(w.z), acc[5]);
                    acc[6] = fmaf(sc, bf_lo(w.w), acc[6]);
                    acc[7] = fmaf(sc, bf_hi(w.w), acc[7]);
                }
#pragma unroll
                for (int o = 2; o < 32; o <<= 1)
#pragma unroll
                    for (int e = 0; e < 8; e++) acc[e] += __shfl_xor_sync(0xffffffffu, acc[e], o);
                if (lane < 2) {
#pragma unroll
                    for (int e = 0; e < 8; e++) st_mod(sc_->mod + blk * 16 + lane * 8 + e, acc[e], tag);
                }
            }
            if (warp == 9) {
#pragma unroll 1
                for (int st = 1; st <= 2; st++) {
                    bar_sync(7, 160);
                    const uint32_t* src = sc_->mod + (st * 3 - 1) * DM;
                    const int n = st == 1 ? 3 * DM : DM;
#pragma unroll 1
                    for (int i = lane * 4; i < n + 127 - ((n + 127) & 127); i += 128)
                        mod_to_smem(sbase + OFF_MODT + min(i, n - 4) * 4, src + min(i, n - 4), tag);
                    __syncwarp();
                    rows_load(sbase, (st == 1 ? maps.x : sc_->x2) + (size_t)(mt * 8 + g) * 16 * DM, lane);
                }
            }
        }
    } else {
        asm volatile("setmaxnreg.inc.sync.aligned.u32 240;");
        const int wg = warp >> 2;
        const int tid = threadIdx.x;
        Ctx cx;
        cx.sbase = sbase;
        cx.rel_cta = (lane == 0 && (warp & 3) < 2) ? (warp & 3) : 2;
        const uint32_t red = sbase + OFF_RED;
        const int own = mt * 8 + g;
        const int wown = mt * 8 + warp;
        PROF(0);
        PROFG(30);
        PROFR(17);
        const uint32_t epoch = ld_epoch(sc_);
        {
            uint4 w1[5];
            unsigned short cu[5];
            const int half = tid & 1, r0 = tid >> 1;
            if (b < 72) {
#pragma unroll
                for (int i = 0; i < 5; i++) {
                    const int row = min(r0 + 128 * i, DM - 1);
                    cu[i] = __ldg(reinterpret_cast<const unsigned short*>(cvec) + row);
                    w1[i] = __ldg(reinterpret_cast<const uint4*>(wmod + (size_t)row * (6 * DM) + half * 8) + b * 2);
                }
            }
            if (warp == 0) {
                if (lane == 0) {
                    mbar_init(sbase + OFF_XBAR, 1);
                    asm volatile("fence.mbarrier_init.release.cluster;\nfence.proxy.async.shared::cta;" ::: "memory");
                }
                rows_load(sbase, maps.x + (size_t)own * 16 * DM, lane);
            }
            PROFR(18);
            asm volatile("barrier.cluster.arrive.relaxed.aligned;" ::: "memory");
            if (b < 72) {
                float sc[5];
#pragma unroll
                for (int i = 0; i < 5; i++) sc[i] = (r0 + 128 * i < DM) ? silu_bf16(cu[i]) : 0.f;
                mod_block(w1, sc, sc_->mod + b * 16, red + 1024, warp, lane, (epoch + 1) & 0xffffu);
            } else {
                bar_sync(3, 256);
            }
            asm volatile("" ::"r"(epoch) : "memory");
            bar_arrive(4, 320);
            PROFR(21);
        }

        Ring ring{0u, 0u};
        int stage = 0;
        asm volatile("" : "+r"(stage));
#pragma unroll 1
        for (;; stage++) {
            int tid, lane;
            asm volatile("mov.u32 %0, %%tid.x;" : "=r"(tid));
            lane = tid & 31;
            {
                float v[36];
                const uint32_t modt = sbase + OFF_MODT + (warp * 16 + (lane & 3) * 2) * 4;
                if (stage == 0) {
#pragma unroll
                    for (int i = 0; i < 36; i++) v[i] = 0.f;
                } else {
                    const uint4* psrc = sc_->part + (size_t)own * 8 * 36 * 32;
                    sum_partials(v, psrc + tid, stage & 1);
                    PROF(stage == 1 ? 8 : 15);
                    sum_tail(v, reinterpret_cast<const uint2*>(psrc + 32 * 32) + tid, stage & 1);
                }
                mbar_wait(sbase + OFF_XBAR, stage & 1);
                if (stage == 0) PROFR(22);
                {
                    const float gs = stage == 2 ? 0.5f : 1.f;
                    float gate[18];
                    lds_mod(gate, modt, warp);
                    const uint32_t rows = sbase + OFF_ROWS + (lane >> 2) * XROW_STRIDE + warp * 32 + (lane & 3) * 4;
#pragma unroll
                    for (int j = 0; j < 9; j++) {
                        const uint32_t ad = rows + own_col(j) * 2 - (j == 8 ? warp * 16 : 0);
                        const uint32_t u0 = __float_as_uint(lds32f(ad)), u1 = __float_as_uint(lds32f(ad + 8 * XROW_STRIDE));
                        const float g0 = stage ? gate[2 * j] * gs : 0.f, g1 = stage ? gate[2 * j + 1] * gs : 0.f;
                        v[4 * j] = fmaf(g0, v[4 * j], bf_lo(u0));
                        v[4 * j + 1] = fmaf(g1, v[4 * j + 1], bf_hi(u0));
                        v[4 * j + 2] = fmaf(g0, v[4 * j + 2], bf_lo(u1));
                        v[4 * j + 3] = fmaf(g1, v[4 * j + 3], bf_hi(u1));
                        sts32f(ad, __uint_as_float(pack_bf16(v[4 * j], v[4 * j + 1])));
                        sts32f(ad + 8 * XROW_STRIDE, __uint_as_float(pack_bf16(v[4 * j + 2], v[4 * j + 3])));
                    }
                    asm volatile("fence.proxy.async.shared::cta;" ::: "memory");
                }
                if (stage == 2) break;
                PROF(stage == 0 ? 1 : 9);
                layernorm_rows(v, red, warp, lane);
                if (stage == 0) PROFR(27);
                if (stage == 0) {
                    const uint32_t tag = (epoch + 1) & 0xffffu;
                    mod_to_smem(sbase + OFF_MODT + (DM + tid * 4) * 4, sc_->mod + tid * 4, tag);
                    if (warp == 7) mod_to_smem(sbase + OFF_MODT + (DM + 1024 + lane * 4) * 4, sc_->mod + 1024 + lane * 4, tag);
                    bar_sync(3, 256);
                }
                float shift[18], scale[18];
                lds_mod(shift, modt + DM * 4, warp);
                lds_mod(scale, modt + 2 * DM * 4, warp);
                if (stage == 0) PROFR(28);
                PROF(stage == 0 ? 2 : 10);
                modulate_store(v, shift, scale, sc_->h[epoch & 1][stage] + (size_t)own * 36 * 32, warp, lane);
                if (stage == 0) asm volatile("barrier.cluster.wait.aligned;" ::: "memory");
            }

            const uint32_t spill = sbase + 8 * SLOT_BYTES + wg * 3 * SLOT_BYTES + (tid & 127) * 16;
            uint32_t a[144];
            PROF(stage == 0 ? 3 : 11);
            {
                const uint4* hsrc = sc_->h[epoch & 1][stage] + (size_t)wown * 36 * 32 + lane;
                poll_frags<32, 36>(a, hsrc);
                PROF(stage == 0 ? 4 : 12);
                if (stage == 1) PROFG(25);
                if (wg == 1) bar_sync(5, 256);
                poll_frags<0, 32>(a, hsrc);
                if (wg == 0) bar_arrive(5, 256);
            }
            uint4* hhbuf = sc_->hh + (size_t)b * 8 * 256 + tid;
            float d[64];
#pragma unroll 1
            for (int ch = 0;; ch++) {
                gemm_n128(d, a, cx, ring, true);
                if (stage == 0) {
#pragma unroll
                    for (int i = 0; i < 64; i++) d[i] *= SM_SCALE;
                    if (ch == 3) break;
#pragma unroll
                    for (int v = 0; v < 8; v++)
                        sts128(spill + (ch * 8 + v) * 2048, pack_bf16(d[8 * v], d[8 * v + 1]),
                               pack_bf16(d[8 * v + 2], d[8 * v + 3]), pack_bf16(d[8 * v + 4], d[8 * v + 5]),
                               pack_bf16(d[8 * v + 6], d[8 * v + 7]));
                } else {
#pragma unroll
                    for (int i = 0; i < 32; i++) {
                        const float gv = d[i], gu = gv * d[32 + i];
                        const float z = gv * fmaf(gv * gv, 0.7978845608028654f * 0.044715f, 0.7978845608028654f);
                        d[i] = fmaf(gu, tanh_fast(z), gu);
                    }
                    if (ch == 8) break;
                    if (warp == 0) {
                        if (ch == 0) rows_store(sbase, sc_->x2 + (size_t)own * 16 * DM, lane);
                        if (ch == 1) rows_store_wait();
                    }
#pragma unroll
                    for (int v = 0; v < 4; v++) {
                        const uint4 h4 = make_uint4(pack_bf16(d[8 * v], d[8 * v + 1]), pack_bf16(d[8 * v + 2], d[8 * v + 3]),
                                                    pack_bf16(d[8 * v + 4], d[8 * v + 5]), pack_bf16(d[8 * v + 6], d[8 * v + 7]));
                        if (ch < 2)
                            __stcg(hhbuf + (ch * 4 + v) * 256, h4);
                        else
                            sts128(spill + ((ch - 2) * 4 + v) * 2048, h4.x, h4.y, h4.z, h4.w);
                    }
                }
            }
            if (stage == 0) {
                uint32_t q[32];
#pragma unroll
                for (int i = 0; i < 32; i++) q[i] = pack_bf16(d[2 * i], d[2 * i + 1]);
                PROF(5);
                PROFG(23);
                if (wg == 0) bar_arrive(6, 160);
                {
                    float o[64], sa[32], sb[32];
                    uint32_t pa[16], pb[16];
#pragma unroll
                    for (int i = 0; i < 64; i++) o[i] = 0.f;
                    float n0 = 0.f, n1 = 0.f, l0 = 1.f, l1 = 1.f;
                    bool shifted = false;
                    const uint64_t dbase = desc_of(sbase);
                    const uint64_t dbk = dbase - (511u << 16);
                    const int my_bar = 1 + wg, other_bar = 2 - wg;

                    auto softmax_a = [&](bool first, float& s0, float& s1) {
                        if (first) {
                            shifted = false;
                            n0 = n1 = 0.f;
                            l0 = l1 = 0.f;
                        }
                        if (shifted)
                            exp_step<true>(sa, pa, n0, n1, s0, s1);
                        else
                            exp_step<false>(sa, pa, n0, n1, s0, s1);
                    };
                    auto softmax_b = [&](bool first, float s0, float s1) {
                        float u0, u1;
                        if (shifted)
                            exp_step<true>(sb, pb, n0, n1, u0, u1);
                        else
                            exp_step<false>(sb, pb, n0, n1, u0, u1);
                        s0 += u0;
                        s1 += u1;
                        bool bad = !(fmaxf(s0, s1) <= SM_HI);
                        if (first) {
                            float r0 = s0 + __shfl_xor_sync(0xffffffffu, s0, 1), r1 = s1 + __shfl_xor_sync(0xffffffffu, s1, 1);
                            r0 += __shfl_xor_sync(0xffffffffu, r0, 2);
                            r1 += __shfl_xor_sync(0xffffffffu, r1, 2);
                            bad = bad || !(fminf(r0, r1) >= SM_LO);
                        }
                        if (__any_sync(0xffffffffu, bad)) {
                            float x0, x1;
                            row_max(sa, sb, x0, x1);
                            x0 = -x0;
                            x1 = -x1;
                            if (!first) {
                                x0 = fminf(x0, n0);
                                x1 = fminf(x1, n1);
                                const float al0 = ex2(x0 - n0), al1 = ex2(x1 - n1);
                                l0 *= al0;
                                l1 *= al1;
#pragma unroll
                                for (int i = 0; i < 16; i++) {
                                    o[4 * i] *= al0;
                                    o[4 * i + 1] *= al0;
                                    o[4 * i + 2] *= al1;
                                    o[4 * i + 3] *= al1;
                                }
                            }
                            n0 = x0;
                            n1 = x1;
                            shifted = true;
                            exp_step<true>(sa, pa, n0, n1, s0, s1);
                            exp_step<true>(sb, pb, n0, n1, u0, u1);
                            s0 += u0;
                            s1 += u1;
                        }
                        l0 += s0;
                        l1 += s1;
                    };

                    cx.wait_full(4, 0);
                    if (wg == 1) bar_sync(my_bar, 256);
                    wg_fence();
                    qk_step(sa, q, dbk + 4 * 1024);
                    qk_step(sb, q, dbk + 5 * 1024);
                    wg_commit();
                    bar_arrive(other_bar, 256);
                    wg_wait<0>();
                    pin(sa);
                    pin(sb);
                    cx.release(4);
                    cx.wait_full(6, 0);
                    {
                        float s0, s1;
                        softmax_a(true, s0, s1);
                        softmax_b(true, s0, s1);
                    }
                    uint32_t alo = (uint32_t)dbase + 6 * 1024, blo = (uint32_t)dbase;
                    const uint32_t dhi = (uint32_t)(dbase >> 32);
#pragma unroll 1
                    for (int t = 1; t < 64; t++) {
                        const int j = t & 15;
                        const uint32_t sA = 2 + 4 * (t & 1), sB = 4 - 4 * (t & 1);
                        const uint64_t da = ((uint64_t)dhi << 32) | alo, db = ((uint64_t)dhi << 32) | blo;
                        TL(0);
                        bar_sync(my_bar, 256);
                        TL(2);
                        wg_fence();
                        pv_step(o, pa, da + 1024, j != 1);
                        qk_step(sa, q, da - (511u << 16));
                        wg_commit();
                        cx.wait_full(sB, ((36 + 4 * t) >> 3) & 1);
                        wg_fence();
                        qk_step(sb, q, db - (511u << 16));
                        pv_step(o, pb, db + 1024, 1);
                        wg_commit();
                        bar_arrive(other_bar, 256);
                        alo ^= 4096;
                        blo ^= 4096;
                        asm volatile("" : "+r"(alo), "+r"(blo));
                        TL(3);
                        wg_wait<1>();
                        pin(sa);
                        pin(pa);
                        TL(4);
                        cx.release(sA);
                        const float lp0 = l0, lp1 = l1;
                        float s0, s1;
                        softmax_a(j == 0, s0, s1);
                        TL(5);
                        wg_wait<0>();
                        pin(o);
                        pin(sb);
                        pin(pb);
                        TL(6);
                        cx.release(sB);
                        if (j == 0) {
                            float i0, i1;
                            inv_row_sums(lp0, lp1, i0, i1);
                            const uint32_t dst = spill + ((t >> 4) - 1) * 16384;
#pragma unroll
                            for (int v = 0; v < 8; v++)
                                sts128(dst + v * 2048, pack_bf16(o[8 * v] * i0, o[8 * v + 1] * i0),
                                       pack_bf16(o[8 * v + 2] * i1, o[8 * v + 3] * i1),
                                       pack_bf16(o[8 * v + 4] * i0, o[8 * v + 5] * i0),
                                       pack_bf16(o[8 * v + 6] * i1, o[8 * v + 7] * i1));
                        }
                        const uint32_t bn = sbase + OFF_FULL + (8 - sA) * 8, pn = ((38 + 4 * t) >> 3) & 1;
                        const bool okn = mbar_try(bn, pn);
                        TL(1);
                        softmax_b(j == 0, s0, s1);
                        if (!okn || j == 15) {
                            mbar_wait(bn, pn);
                            if (j == 15 && t < 63) {
                                const uint32_t src = spill + (t >> 4) * 16384;
#pragma unroll
                                for (int v = 0; v < 8; v++)
                                    lds128(src + v * 2048, q[4 * v], q[4 * v + 1], q[4 * v + 2], q[4 * v + 3]);
                            }
                        }
                        TL(7);
                    }
                    bar_sync(my_bar, 256);
                    wg_fence();
                    pv_step(o, pa, dbase + 2 * 1024, 1);
                    pv_step(o, pb, dbase + 3 * 1024, 1);
                    wg_commit();
                    if (wg == 0) bar_arrive(other_bar, 256);
                    float i0, i1;
                    inv_row_sums(l0, l1, i0, i1);
                    wg_wait<0>();
                    pin(o);
                    cx.release(2);
#pragma unroll
                    for (int i = 0; i < 16; i++) {
                        a[96 + 2 * i] = pack_bf16(o[4 * i] * i0, o[4 * i + 1] * i0);
                        a[96 + 2 * i + 1] = pack_bf16(o[4 * i + 2] * i1, o[4 * i + 3] * i1);
                    }
#pragma unroll
                    for (int i = 128; i < 144; i++) a[i] = 0;
                }
                ring.slot = 4;
                ring.phase = 0;
                PROF(6);
                PROFG(24);
            } else {
#pragma unroll
                for (int v = 0; v < 8; v++) {
                    const uint4 t = __ldcg(hhbuf + v * 256);
                    a[112 + 4 * v] = t.x;
                    a[113 + 4 * v] = t.y;
                    a[114 + 4 * v] = t.z;
                    a[115 + 4 * v] = t.w;
                }
#pragma unroll
                for (int i = 0; i < 16; i++) a[96 + i] = pack_bf16(d[2 * i], d[2 * i + 1]);
                PROF(13);
            }
#pragma unroll
            for (int v = 0; v < 24; v++) lds128(spill + v * 2048, a[4 * v], a[4 * v + 1], a[4 * v + 2], a[4 * v + 3]);

            {
                uint4* dst = sc_->part + ((size_t)wown * 8 + g) * 36 * 32 + lane;
                const uint32_t ptag = (stage + 1) & 1;
#pragma unroll 1
                for (int p = 0; p < 4; p++) {
                    gemm_n128(d, a, cx, ring, stage != 0);
#pragma unroll
                    for (int u = 0; u < 8; u++)
                        st128(dst + (p * 8 + u) * 32, (pack_bf16(d[8 * u], d[8 * u + 1]) & ~1u) | ptag,
                              pack_bf16(d[8 * u + 2], d[8 * u + 3]), pack_bf16(d[8 * u + 4], d[8 * u + 5]),
                              pack_bf16(d[8 * u + 6], d[8 * u + 7]));
                    if (p == 0 && wg == 0) bar_arrive(7, 160);
                }
                float e[32];
                gemm_n64(e, a, cx, ring, stage != 0);
                uint2* dst2 = reinterpret_cast<uint2*>(dst - lane + 32 * 32) + lane;
#pragma unroll
                for (int j = 0; j < 8; j++)
                    st64(dst2 + j * 32, (pack_bf16(e[4 * j], e[4 * j + 1]) & ~1u) | ptag, pack_bf16(e[4 * j + 2], e[4 * j + 3]));
            }
            PROF(stage == 0 ? 7 : 14);
            if (stage == 1) {
                PROFG(26);
                asm volatile("barrier.cluster.arrive.relaxed.aligned;" ::: "memory");
            }
        }
        bar_sync(3, 256);
        if (warp == 0) {
            rows_store(sbase, maps.out + (size_t)own * 16 * DM, lane);
            if (b == 0 && lane == 0) sc_->epoch = epoch + 1;
            rows_store_wait();
        }
        PROF(16);
        PROFG(31);
        asm volatile("barrier.cluster.wait.aligned;" ::: "memory");
    }
}

typedef CUresult (*EncodeFn)(CUtensorMap*, CUtensorMapDataType, cuuint32_t, void*, const cuuint64_t*, const cuuint64_t*,
                             const cuuint32_t*, const cuuint32_t*, CUtensorMapInterleave, CUtensorMapSwizzle,
                             CUtensorMapL2promotion, CUtensorMapFloatOOBfill);

void make_map(EncodeFn enc, CUtensorMap* m, const void* ptr, uint64_t rows, uint64_t cols) {
    cuuint64_t gdim[2] = {cols, rows};
    cuuint64_t gstr[1] = {cols * 2};
    cuuint32_t box[2] = {64, 64};
    cuuint32_t estr[2] = {1, 1};
    enc(m, CU_TENSOR_MAP_DATA_TYPE_BFLOAT16, 2, const_cast<void*>(ptr), gdim, gstr, box, estr,
        CU_TENSOR_MAP_INTERLEAVE_NONE, CU_TENSOR_MAP_SWIZZLE_128B, CU_TENSOR_MAP_L2_PROMOTION_L2_128B,
        CU_TENSOR_MAP_FLOAT_OOB_FILL_NONE);
}

}

extern "C" void kernel_launch(void* const* d_in, const int* in_sizes, int n_in, void* d_out, int out_size) {
    (void)in_sizes;
    (void)n_in;
    (void)out_size;
    void* fn = nullptr;
    cudaDriverEntryPointQueryResult qr;
    cudaGetDriverEntryPoint("cuTensorMapEncodeTiled", &fn, cudaEnableDefault, &qr);
    EncodeFn enc = (EncodeFn)fn;
    Params maps;
    maps.x = (const __nv_bfloat16*)d_in[0];
    maps.cvec = (const __nv_bfloat16*)d_in[9];
    maps.wmod = (const __nv_bfloat16*)d_in[10];
    maps.kc = (const __nv_bfloat16*)d_in[1];
    maps.vc = (const __nv_bfloat16*)d_in[2];
    maps.out = (__nv_bfloat16*)d_out;
    void* scp = nullptr;
    cudaGetSymbolAddress(&scp, g_scratch);
    maps.sc = (Scratch*)scp;
    make_map(enc, &maps.k, d_in[1], 32 * 2048, 128);
    make_map(enc, &maps.v, d_in[2], 32 * 2048, 128);
    make_map(enc, &maps.wq, d_in[3], 576, 4096);
    make_map(enc, &maps.wo, d_in[4], 4096, 576);
    make_map(enc, &maps.wg, d_in[6], 576, 4608);
    make_map(enc, &maps.wu, d_in[7], 576, 4608);
    make_map(enc, &maps.wd, d_in[8], 4608, 576);
    cudaFuncSetAttribute(fused_block_kernel, cudaFuncAttributeMaxDynamicSharedMemorySize, SMEM_BYTES);
    fused_block_kernel<<<128, 384, SMEM_BYTES>>>(maps);
}
```

```cpp
#include <cuda_runtime.h>
#include <cuda_bf16.h>
#include <cuda.h>
#include <stdint.h>

namespace {

constexpr int DM = 576;
constexpr int SLOT_BYTES = 16384;
constexpr int BOX_BYTES = 8192;
constexpr int NUNITS = 14;
constexpr int SMEM_TAIL = NUNITS * SLOT_BYTES;
constexpr int SMEM_BYTES = SMEM_TAIL + 2048 + 1024;
constexpr int OFF_FULL = SMEM_TAIL;
constexpr int OFF_EMPTY = SMEM_TAIL + 64;
constexpr int OFF_RED = SMEM_TAIL + 128;

constexpr int KV_AHEAD = 16;
constexpr int OFF_XBAR = SMEM_TAIL + 1792;
constexpr int OFF_ROWS = 8 * SLOT_BYTES;
constexpr int OFF_MODT = OFF_ROWS + 20480;
constexpr int XROW_STRIDE = DM * 2 + 16;

struct Scratch {
    unsigned epoch;
    unsigned pad[31];
    uint32_t mod[6 * DM];
    uint4 h[2][2][128 * 36 * 32];
    uint4 part[128 * 8 * 36 * 32];
    uint4 hh[128 * 8 * 256];
    __nv_bfloat16 x2[2048 * DM];
};
__device__ Scratch g_scratch;

#define TG(i)
#define TL(i)
#define PROFR(i)
#define PROF(i)
#define PROFG(i)

struct Params {
    const __nv_bfloat16 *x, *cvec, *wmod, *kc, *vc;
    __nv_bfloat16* out;
    Scratch* sc;
    CUtensorMap k, v, wq, wo, wg, wu, wd;
};

__device__ __forceinline__ uint32_t smem_u32(const void* p) { return (uint32_t)__cvta_generic_to_shared(p); }
__device__ __forceinline__ void mbar_init(uint32_t a, uint32_t c) {
    asm volatile("mbarrier.init.shared::cta.b64 [%0], %1;" ::"r"(a), "r"(c) : "memory");
}
__device__ __forceinline__ void mbar_expect_tx(uint32_t a, uint32_t bytes) {
    asm volatile("mbarrier.arrive.expect_tx.shared::cta.b64 _, [%0], %1;" ::"r"(a), "r"(bytes) : "memory");
}
__device__ __forceinline__ bool mbar_try(uint32_t a, uint32_t ph) {
    uint32_t ok;
    asm volatile(
        "{\n.reg .pred p;\nmbarrier.try_wait.parity.shared::cta.b64 p, [%1], %2;\nselp.u32 %0, 1, 0, p;\n}"
        : "=r"(ok)
        : "r"(a), "r"(ph)
        : "memory");
    return ok != 0;
}
__device__ __forceinline__ uint32_t clk32() {
    uint32_t c;
    asm volatile("mov.u32 %0, %%clock;" : "=r"(c));
    return c;
}
constexpr uint32_t WAIT_LIMIT = 1u << 30;
__device__ __forceinline__ void mbar_wait(uint32_t a, uint32_t ph) {
    if (mbar_try(a, ph)) return;
    uint32_t t0 = clk32();
    while (!mbar_try(a, ph)) {
        if (clk32() - t0 > WAIT_LIMIT) break;
    }
}
__device__ __forceinline__ void mbar_arrive_cluster(uint32_t a, uint32_t cta) {
    asm volatile(
        "{\n.reg .b32 ra;\nmapa.shared::cluster.u32 ra, %0, %1;\nmbarrier.arrive.shared::cluster.b64 _, [ra];\n}" ::"r"(a),
        "r"(cta)
        : "memory");
}
__device__ __forceinline__ void tma_mc(uint32_t dst, const CUtensorMap* m, int c0, int c1, uint32_t bar) {
    asm volatile(
        "cp.async.bulk.tensor.2d.shared::cluster.global.mbarrier::complete_tx::bytes.multicast::cluster"
        " [%0], [%1, {%3, %4}], [%2], %5;" ::"r"(dst),
        "l"(m), "r"(bar), "r"(c0), "r"(c1), "h"((uint16_t)3)
        : "memory");
}
__device__ __forceinline__ void l2_prefetch(const void* p, uint32_t bytes) {
    asm volatile("cp.async.bulk.prefetch.L2.global [%0], %1;" ::"l"(p), "r"(bytes) : "memory");
}
__device__ __forceinline__ void bar_sync(int id, int n) { asm volatile("bar.sync %0, %1;" ::"r"(id), "r"(n) : "memory"); }
__device__ __forceinline__ void bar_arrive(int id, int n) {
    asm volatile("bar.arrive %0, %1;" ::"r"(id), "r"(n) : "memory");
}
__device__ __forceinline__ void wg_fence() { asm volatile("wgmma.fence.sync.aligned;" ::: "memory"); }
__device__ __forceinline__ void wg_commit() { asm volatile("wgmma.commit_group.sync.aligned;" ::: "memory"); }
template <int N>
__device__ __forceinline__ void wg_wait() {
    asm volatile("wgmma.wait_group.sync.aligned %0;" ::"n"(N) : "memory");
}
template <int N>
__device__ __forceinline__ void pin(float (&d)[N]) {
#pragma unroll
    for (int i = 0; i < N; i++) asm volatile("" : "+f"(d[i])::"memory");
}
template <int N>
__device__ __forceinline__ void pin(uint32_t (&d)[N]) {
#pragma unroll
    for (int i = 0; i < N; i++) asm volatile("" : "+r"(d[i])::"memory");
}
__device__ __forceinline__ uint32_t pack_bf16(float lo, float hi) {
    uint32_t r;
    asm("cvt.rn.bf16x2.f32 %0, %1, %2;" : "=r"(r) : "f"(hi), "f"(lo));
    return r;
}
__device__ __forceinline__ float bf_lo(uint32_t v) { return __uint_as_float(v << 16); }
__device__ __forceinline__ float bf_hi(uint32_t v) { return __uint_as_float(v & 0xffff0000u); }
__device__ __forceinline__ float round_bf16(float v) { return __bfloat162float(__float2bfloat16_rn(v)); }
__device__ __forceinline__ float ex2(float x) {
    float y;
    asm("ex2.approx.ftz.f32 %0, %1;" : "=f"(y) : "f"(x));
    return y;
}
__device__ __forceinline__ float rcp(float x) {
    float y;
    asm("rcp.approx.ftz.f32 %0, %1;" : "=f"(y) : "f"(x));
    return y;
}
__device__ __forceinline__ float tanh_fast(float x) {
    float y;
    asm("tanh.approx.f32 %0, %1;" : "=f"(y) : "f"(x));
    return y;
}
__device__ __forceinline__ void sts128(uint32_t a, uint32_t x, uint32_t y, uint32_t z, uint32_t w) {
    asm volatile("st.shared.v4.b32 [%0], {%1,%2,%3,%4};" ::"r"(a), "r"(x), "r"(y), "r"(z), "r"(w) : "memory");
}
__device__ __forceinline__ void lds128(uint32_t a, uint32_t& x, uint32_t& y, uint32_t& z, uint32_t& w) {
    asm volatile("ld.shared.v4.b32 {%0,%1,%2,%3}, [%4];" : "=r"(x), "=r"(y), "=r"(z), "=r"(w) : "r"(a) : "memory");
}
__device__ __forceinline__ void sts32f(uint32_t a, float v) {
    asm volatile("st.shared.f32 [%0], %1;" ::"r"(a), "f"(v) : "memory");
}
__device__ __forceinline__ float lds32f(uint32_t a) {
    float v;
    asm volatile("ld.shared.f32 %0, [%1];" : "=f"(v) : "r"(a) : "memory");
    return v;
}
#define F8(d, b) \
    "+f"(d[b]), "+f"(d[b + 1]), "+f"(d[b + 2]), "+f"(d[b + 3]), "+f"(d[b + 4]), "+f"(d[b + 5]), "+f"(d[b + 6]), "+f"(d[b + 7])

template <int TB>
__device__ __forceinline__ void wgmma_n128(float (&d)[64], uint32_t a0, uint32_t a1, uint32_t a2, uint32_t a3,
                                           uint64_t db, int sc) {
    asm volatile(
        "{\n.reg .pred p;\nsetp.ne.b32 p, %69, 0;\n"
        "wgmma.mma_async.sync.aligned.m64n128k16.f32.bf16.bf16 "
        "{%0,%1,%2,%3,%4,%5,%6,%7,%8,%9,%10,%11,%12,%13,%14,%15,%16,%17,%18,%19,%20,%21,%22,%23,%24,%25,%26,%27,%28,%29,%30,%31,"
        "%32,%33,%34,%35,%36,%37,%38,%39,%40,%41,%42,%43,%44,%45,%46,%47,%48,%49,%50,%51,%52,%53,%54,%55,%56,%57,%58,%59,%60,%61,%62,%63},"
        "{%64,%65,%66,%67}, %68, p, 1, 1, %70;\n}"
        : F8(d, 0), F8(d, 8), F8(d, 16), F8(d, 24), F8(d, 32), F8(d, 40), F8(d, 48), F8(d, 56)
        : "r"(a0), "r"(a1), "r"(a2), "r"(a3), "l"(db), "r"(sc), "n"(TB));
}
#define O8(d, b) \
    "=f"(d[b]), "=f"(d[b + 1]), "=f"(d[b + 2]), "=f"(d[b + 3]), "=f"(d[b + 4]), "=f"(d[b + 5]), "=f"(d[b + 6]), "=f"(d[b + 7])
template <int TB>
__device__ __forceinline__ void wgmma_n128_z(float (&d)[64], uint32_t a0, uint32_t a1, uint32_t a2, uint32_t a3,
                                             uint64_t db) {
    asm volatile(
        "wgmma.mma_async.sync.aligned.m64n128k16.f32.bf16.bf16 "
        "{%0,%1,%2,%3,%4,%5,%6,%7,%8,%9,%10,%11,%12,%13,%14,%15,%16,%17,%18,%19,%20,%21,%22,%23,%24,%25,%26,%27,%28,%29,%30,%31,"
        "%32,%33,%34,%35,%36,%37,%38,%39,%40,%41,%42,%43,%44,%45,%46,%47,%48,%49,%50,%51,%52,%53,%54,%55,%56,%57,%58,%59,%60,%61,%62,%63},"
        "{%64,%65,%66,%67}, %68, 0, 1, 1, %69;"
        : O8(d, 0), O8(d, 8), O8(d, 16), O8(d, 24), O8(d, 32), O8(d, 40), O8(d, 48), O8(d, 56)
        : "r"(a0), "r"(a1), "r"(a2), "r"(a3), "l"(db), "n"(TB));
}
template <int TB>
__device__ __forceinline__ void wgmma_n64_z(float (&d)[32], uint32_t a0, uint32_t a1, uint32_t a2, uint32_t a3,
                                            uint64_t db) {
    asm volatile(
        "wgmma.mma_async.sync.aligned.m64n64k16.f32.bf16.bf16 "
        "{%0,%1,%2,%3,%4,%5,%6,%7,%8,%9,%10,%11,%12,%13,%14,%15,%16,%17,%18,%19,%20,%21,%22,%23,%24,%25,%26,%27,%28,%29,%30,%31},"
        "{%32,%33,%34,%35}, %36, 0, 1, 1, %37;"
        : O8(d, 0), O8(d, 8), O8(d, 16), O8(d, 24)
        : "r"(a0), "r"(a1), "r"(a2), "r"(a3), "l"(db), "n"(TB));
}
template <int TB>
__device__ __forceinline__ void wgmma_n64(float (&d)[32], uint32_t a0, uint32_t a1, uint32_t a2, uint32_t a3,
                                          uint64_t db) {
    asm volatile(
        "wgmma.mma_async.sync.aligned.m64n64k16.f32.bf16.bf16 "
        "{%0,%1,%2,%3,%4,%5,%6,%7,%8,%9,%10,%11,%12,%13,%14,%15,%16,%17,%18,%19,%20,%21,%22,%23,%24,%25,%26,%27,%28,%29,%30,%31},"
        "{%32,%33,%34,%35}, %36, 1, 1, 1, %37;"
        : F8(d, 0), F8(d, 8), F8(d, 16), F8(d, 24)
        : "r"(a0), "r"(a1), "r"(a2), "r"(a3), "l"(db), "n"(TB));
}

__device__ __forceinline__ uint64_t desc_of(uint32_t saddr) {
    return (uint64_t)(((saddr >> 4) & 0x3FFFu) | (512u << 16)) | ((uint64_t)(64u | (1u << 30)) << 32);
}

struct Ring {
    uint32_t slot;
    uint32_t phase;
    __device__ __forceinline__ void next() {
        if (++slot == 8) {
            slot = 0;
            phase ^= 1;
        }
    }
};

struct Ctx {
    uint32_t sbase;
    int wg;
    uint32_t rel_cta;
    __device__ __forceinline__ void wait_full(uint32_t slot, uint32_t phase) const {
        mbar_wait(sbase + OFF_FULL + slot * 8, phase);
    }
    __device__ __forceinline__ void release(uint32_t slot) const {
        if (rel_cta < 2) mbar_arrive_cluster(sbase + OFF_EMPTY + slot * 8, rel_cta);
    }
};

__device__ __forceinline__ void gemm_n128(float (&d)[64], const uint32_t (&a)[144], const Ctx& c, Ring& r, bool nine) {
    uint32_t prev = 0;
#pragma unroll
    for (int s = 0; s < 9; s++) {
        if (s < 8 || nine) {
            if (s == 4) bar_sync(8 + c.wg, 256);
            c.wait_full(r.slot, r.phase);
            uint64_t db = desc_of(c.sbase + r.slot * SLOT_BYTES);
            wg_fence();
#pragma unroll
            for (int k = 0; k < 4; k++) {
                if ((s | k) == 0)
                    wgmma_n128_z<1>(d, a[0], a[1], a[2], a[3], db);
                else
                    wgmma_n128<1>(d, a[s * 16 + k * 4], a[s * 16 + k * 4 + 1], a[s * 16 + k * 4 + 2],
                                  a[s * 16 + k * 4 + 3], db + k * 128, 1);
            }
            wg_commit();
            if (s == 8 || (s == 7 && !nine)) bar_arrive(9 - c.wg, 256);
            if (s > 0) {
                wg_wait<1>();
                c.release(prev);
            }
            prev = r.slot;
            r.next();
        }
    }
    wg_wait<0>();
    c.release(prev);
    pin(d);
}
__device__ __forceinline__ void gemm_n64(float (&d)[32], const uint32_t (&a)[144], const Ctx& c, Ring& r, bool nine) {
    uint32_t prev = 0;
#pragma unroll
    for (int s = 0; s < 5; s++) {
        if (s < 4 || nine) {
            c.wait_full(r.slot, r.phase);
            uint64_t db = desc_of(c.sbase + r.slot * SLOT_BYTES);
            wg_fence();
#pragma unroll
            for (int k = 0; k < 8; k++) {
                if ((s | k) == 0)
                    wgmma_n64_z<1>(d, a[0], a[1], a[2], a[3], db);
                else if (s * 8 + k < 36)
                    wgmma_n64<1>(d, a[s * 32 + k * 4], a[s * 32 + k * 4 + 1], a[s * 32 + k * 4 + 2],
                                 a[s * 32 + k * 4 + 3], db + k * 128);
            }
            wg_commit();
            if (s > 0) {
                wg_wait<1>();
                c.release(prev);
            }
            prev = r.slot;
            r.next();
        }
    }
    wg_wait<0>();
    c.release(prev);
    pin(d);
}
__device__ __forceinline__ void st128(uint4* p, uint32_t x, uint32_t y, uint32_t z, uint32_t w) {
    asm volatile(
        "{\n.reg .b64 lo, hi;\n.reg .b128 t;\nmov.b64 lo, {%1, %2};\nmov.b64 hi, {%3, %4};\nmov.b128 t, {lo, hi};\n"
        "st.relaxed.gpu.global.b128 [%0], t;\n}" ::"l"(p),
        "r"(x), "r"(y), "r"(z), "r"(w)
        : "memory");
}
__device__ __forceinline__ uint4 ld128(const uint4* p) {
    uint4 r;
    asm volatile(
        "{\n.reg .b64 lo, hi;\n.reg .b128 t;\nld.relaxed.gpu.global.b128 t, [%4];\nmov.b128 {lo, hi}, t;\n"
        "mov.b64 {%0, %1}, lo;\nmov.b64 {%2, %3}, hi;\n}"
        : "=r"(r.x), "=r"(r.y), "=r"(r.z), "=r"(r.w)
        : "l"(p));
    return r;
}
__device__ __forceinline__ void st64(void* p, uint32_t x, uint32_t y) {
    asm volatile("{\n.reg .b64 t;\nmov.b64 t, {%1, %2};\nst.relaxed.gpu.global.b64 [%0], t;\n}" ::"l"(p), "r"(x), "r"(y)
                 : "memory");
}
__device__ __forceinline__ uint2 ld64(const void* p) {
    uint2 r;
    asm volatile("{\n.reg .b64 t;\nld.relaxed.gpu.global.b64 t, [%2];\nmov.b64 {%0, %1}, t;\n}"
                 : "=r"(r.x), "=r"(r.y)
                 : "l"(p));
    return r;
}
__device__ __forceinline__ void rows_load(uint32_t sbase, const __nv_bfloat16* src, int lane) {
    if (lane == 0) mbar_expect_tx(sbase + OFF_XBAR, 16 * DM * 2);
    __syncwarp();
    if (lane < 16)
        asm volatile("cp.async.bulk.shared::cluster.global.mbarrier::complete_tx::bytes [%0], [%1], %2, [%3];" ::"r"(
                         sbase + OFF_ROWS + lane * XROW_STRIDE),
                     "l"(src + lane * DM), "r"(DM * 2), "r"(sbase + OFF_XBAR)
                     : "memory");
    __syncwarp();
}
__device__ __forceinline__ void rows_store(uint32_t sbase, __nv_bfloat16* dst, int lane) {
    if (lane < 16) {
        asm volatile("cp.async.bulk.global.shared::cta.bulk_group [%0], [%1], %2;" ::"l"(dst + lane * DM),
                     "r"(sbase + OFF_ROWS + lane * XROW_STRIDE), "r"(DM * 2)
                     : "memory");
        asm volatile("cp.async.bulk.commit_group;" ::: "memory");
    }
    __syncwarp();
}
__device__ __forceinline__ void rows_store_wait() { asm volatile("cp.async.bulk.wait_group 0;" ::: "memory"); }

__device__ __forceinline__ constexpr int own_col(int j) { return j < 8 ? (j >> 1) * 128 + (j & 1) * 8 : 512; }
__device__ __forceinline__ void row_reduce(float& s0, float& s1, uint32_t red, int warp, int lane) {
    s0 += __shfl_xor_sync(0xffffffffu, s0, 1);
    s1 += __shfl_xor_sync(0xffffffffu, s1, 1);
    s0 += __shfl_xor_sync(0xffffffffu, s0, 2);
    s1 += __shfl_xor_sync(0xffffffffu, s1, 2);
    if ((lane & 3) == 0) {
        sts32f(red + (warp * 16 + (lane >> 2)) * 4, s0);
        sts32f(red + (warp * 16 + 8 + (lane >> 2)) * 4, s1);
    }
    bar_sync(3, 256);
    s0 = 0.f;
    s1 = 0.f;
#pragma unroll
    for (int w = 0; w < 8; w++) {
        s0 += lds32f(red + (w * 16 + (lane >> 2)) * 4);
        s1 += lds32f(red + (w * 16 + 8 + (lane >> 2)) * 4);
    }
}
__device__ __forceinline__ void layernorm_rows(float (&v)[36], uint32_t red, int warp, int lane) {
    float s0 = 0.f, s1 = 0.f;
#pragma unroll
    for (int j = 0; j < 9; j++) {
        s0 += v[4 * j] + v[4 * j + 1];
        s1 += v[4 * j + 2] + v[4 * j + 3];
    }
    row_reduce(s0, s1, red, warp, lane);
    const float m0 = s0 * (1.f / DM), m1 = s1 * (1.f / DM);
    s0 = 0.f;
    s1 = 0.f;
#pragma unroll
    for (int j = 0; j < 9; j++) {
        v[4 * j] -= m0;
        v[4 * j + 1] -= m0;
        v[4 * j + 2] -= m1;
        v[4 * j + 3] -= m1;
        s0 += v[4 * j] * v[4 * j] + v[4 * j + 1] * v[4 * j + 1];
        s1 += v[4 * j + 2] * v[4 * j + 2] + v[4 * j + 3] * v[4 * j + 3];
    }
    row_reduce(s0, s1, red + 512, warp, lane);
    const float r0 = rsqrtf(s0 * (1.f / DM) + 1e-5f), r1 = rsqrtf(s1 * (1.f / DM) + 1e-5f);
#pragma unroll
    for (int j = 0; j < 9; j++) {
        v[4 * j] *= r0;
        v[4 * j + 1] *= r0;
        v[4 * j + 2] *= r1;
        v[4 * j + 3] *= r1;
    }
}
__device__ __forceinline__ void mod_to_smem(uint32_t dst, const uint32_t* src, uint32_t tag) {
    const uint32_t t0 = clk32();
    uint4 u;
    while (true) {
        u = ld128(reinterpret_cast<const uint4*>(src));
        const uint32_t bad = ((u.x ^ tag) | (u.y ^ tag) | (u.z ^ tag) | (u.w ^ tag)) & 0xffffu;
        if (__all_sync(0xffffffffu, bad == 0) || clk32() - t0 > WAIT_LIMIT) break;
        __nanosleep(64);
    }
    sts128(dst, u.x & 0xffff0000u, u.y & 0xffff0000u, u.z & 0xffff0000u, u.w & 0xffff0000u);
}
__device__ __forceinline__ void lds_mod(float (&m)[18], uint32_t src  , int warp) {
#pragma unroll
    for (int j = 0; j < 9; j++)
        asm volatile("ld.shared.v2.f32 {%0,%1}, [%2];"
                     : "=f"(m[2 * j]), "=f"(m[2 * j + 1])
                     : "r"(src + own_col(j) * 4 - (j == 8 ? warp * 32 : 0))
                     : "memory");
}
__device__ __forceinline__ void modulate_store(const float (&v)[36], const float (&shift)[18], const float (&scale)[18],
                                               uint4* hbuf  , int warp, int lane) {
    uint32_t o[18];
#pragma unroll
    for (int j = 0; j < 9; j++) {
        const uint32_t cc = pack_bf16(1.f + scale[2 * j], 1.f + scale[2 * j + 1]);
        const float c0 = bf_lo(cc), c1 = bf_hi(cc);
        o[2 * j] = max(pack_bf16(fmaf(v[4 * j], c0, shift[2 * j]), fmaf(v[4 * j + 1], c1, shift[2 * j + 1])), 1u);
        o[2 * j + 1] = max(pack_bf16(fmaf(v[4 * j + 2], c0, shift[2 * j]), fmaf(v[4 * j + 3], c1, shift[2 * j + 1])), 1u);
    }
#pragma unroll
    for (int i = 0; i < 4; i++) st128(hbuf + (i * 8 + warp) * 32 + lane, o[4 * i], o[4 * i + 1], o[4 * i + 2], o[4 * i + 3]);
    st64(reinterpret_cast<uint2*>(hbuf + (32 + (warp >> 1)) * 32 + lane) + (warp & 1), o[16], o[17]);
}
__device__ __forceinline__ void sum_partials(float (&v)[36], const uint4* src  , uint32_t tag) {
    const uint32_t t0 = clk32();
    while (true) {
        uint4 t[8][4];
#pragma unroll
        for (int s = 0; s < 8; s++)
#pragma unroll
            for (int i = 0; i < 4; i++) t[s][i] = ld128(src + (s * 36 + i * 8) * 32);
        uint32_t bad = 0;
#pragma unroll
        for (int i = 0; i < 32; i++) v[i] = 0.f;
#pragma unroll
        for (int s = 0; s < 8; s++)
#pragma unroll
            for (int i = 0; i < 4; i++) {
                bad |= t[s][i].x ^ tag;
                v[8 * i] += bf_lo(t[s][i].x);
                v[8 * i + 1] += bf_hi(t[s][i].x);
                v[8 * i + 2] += bf_lo(t[s][i].y);
                v[8 * i + 3] += bf_hi(t[s][i].y);
                v[8 * i + 4] += bf_lo(t[s][i].z);
                v[8 * i + 5] += bf_hi(t[s][i].z);
                v[8 * i + 6] += bf_lo(t[s][i].w);
                v[8 * i + 7] += bf_hi(t[s][i].w);
            }
        if (__all_sync(0xffffffffu, (bad & 1u) == 0) || clk32() - t0 > WAIT_LIMIT) break;
    }
}
__device__ __forceinline__ void sum_tail(float (&v)[36], const uint2* src  , uint32_t tag) {
    const uint32_t t0 = clk32();
    while (true) {
        uint2 t[8];
#pragma unroll
        for (int s = 0; s < 8; s++) t[s] = ld64(src + s * 72 * 32);
        uint32_t bad = 0;
        v[32] = v[33] = v[34] = v[35] = 0.f;
#pragma unroll
        for (int s = 0; s < 8; s++) {
            bad |= t[s].x ^ tag;
            v[32] += bf_lo(t[s].x);
            v[33] += bf_hi(t[s].x);
            v[34] += bf_lo(t[s].y);
            v[35] += bf_hi(t[s].y);
        }
        if (__all_sync(0xffffffffu, (bad & 1u) == 0) || clk32() - t0 > WAIT_LIMIT) break;
    }
}
template <int K0, int K1>
__device__ __forceinline__ void poll_frags(uint32_t (&a)[144], const uint4* src  , bool kick) {
    const uint32_t t0 = clk32();
    while (true) {
#pragma unroll
        for (int k = K0; k < K1; k++)
            asm volatile("ld.relaxed.gpu.global.v4.u32 {%0,%1,%2,%3}, [%4];"
                         : "=r"(a[4 * k]), "=r"(a[4 * k + 1]), "=r"(a[4 * k + 2]), "=r"(a[4 * k + 3])
                         : "l"(src + k * 32));
        if (kick) bar_arrive(5, 256);
        kick = false;
        uint32_t m0 = a[4 * K0], m1 = a[4 * K0 + 1];
#pragma unroll
        for (int i = 4 * K0 + 2; i < 4 * K1; i += 2) {
            m0 = min(m0, a[i]);
            m1 = min(m1, a[i + 1]);
        }
        if (__all_sync(0xffffffffu, min(m0, m1) != 0) || clk32() - t0 > WAIT_LIMIT) break;
    }
}

constexpr float SM_SCALE = 0.08838834764831845f * 1.4426950408889634f;
constexpr float SM_HI = 1.2089258e24f;
constexpr float SM_LO = 9.0949470e-13f;
__device__ __forceinline__ void qk_step(float (&s)[32], const uint32_t (&q)[32], uint64_t dk) {
#pragma unroll
    for (int k = 0; k < 8; k++) {
        if (k == 0)
            wgmma_n64_z<0>(s, q[0], q[1], q[2], q[3], dk);
        else
            wgmma_n64<0>(s, q[4 * k], q[4 * k + 1], q[4 * k + 2], q[4 * k + 3], dk + (k >> 2) * 512 + (k & 3) * 2);
    }
}
__device__ __forceinline__ void pv_step(float (&o)[64], const uint32_t (&p)[16], uint64_t dv, int acc) {
#pragma unroll
    for (int k = 0; k < 4; k++)
        wgmma_n128<1>(o, p[4 * k], p[4 * k + 1], p[4 * k + 2], p[4 * k + 3], dv + k * 128, k != 0 ? 1 : acc);
}
template <bool SHIFT>
__device__ __forceinline__ void exp_step(const float (&s)[32], uint32_t (&p)[16], float n0, float n1, float& s0,
                                         float& s1) {
#pragma unroll
    for (int i = 0; i < 8; i++) {
        const float e0 = ex2(SHIFT ? s[4 * i] + n0 : s[4 * i]), e1 = ex2(SHIFT ? s[4 * i + 1] + n0 : s[4 * i + 1]);
        const float e2 = ex2(SHIFT ? s[4 * i + 2] + n1 : s[4 * i + 2]), e3 = ex2(SHIFT ? s[4 * i + 3] + n1 : s[4 * i + 3]);
        if (i == 0) {
            s0 = e0 + e1;
            s1 = e2 + e3;
        } else {
            s0 += e0 + e1;
            s1 += e2 + e3;
        }
        p[2 * i] = pack_bf16(e0, e1);
        p[2 * i + 1] = pack_bf16(e2, e3);
    }
}
__device__ __forceinline__ void row_max(const float (&sa)[32], const float (&sb)[32], float& x0, float& x1) {
    float xa[8];
#pragma unroll
    for (int i = 0; i < 8; i++) xa[i] = fmaxf(sa[i], sb[i]);
#pragma unroll
    for (int k = 1; k < 4; k++)
#pragma unroll
        for (int i = 0; i < 8; i++) xa[i] = fmaxf(xa[i], fmaxf(sa[8 * k + i], sb[8 * k + i]));
    x0 = fmaxf(fmaxf(xa[0], xa[1]), fmaxf(xa[4], xa[5]));
    x1 = fmaxf(fmaxf(xa[2], xa[3]), fmaxf(xa[6], xa[7]));
    x0 = fmaxf(x0, __shfl_xor_sync(0xffffffffu, x0, 1));
    x1 = fmaxf(x1, __shfl_xor_sync(0xffffffffu, x1, 1));
    x0 = fmaxf(x0, __shfl_xor_sync(0xffffffffu, x0, 2));
    x1 = fmaxf(x1, __shfl_xor_sync(0xffffffffu, x1, 2));
}
__device__ __forceinline__ void inv_row_sums(float l0, float l1, float& i0, float& i1) {
    l0 += __shfl_xor_sync(0xffffffffu, l0, 1);
    l1 += __shfl_xor_sync(0xffffffffu, l1, 1);
    l0 += __shfl_xor_sync(0xffffffffu, l0, 2);
    l1 += __shfl_xor_sync(0xffffffffu, l1, 2);
    i0 = rcp(l0);
    i1 = rcp(l1);
}

__device__ __forceinline__ uint32_t ld_epoch(const Scratch* sc) {
    uint32_t e;
    asm volatile("ld.relaxed.gpu.global.u32 %0, [%1];" : "=r"(e) : "l"(&sc->epoch) : "memory");
    return e;
}
__device__ __forceinline__ float silu_bf16(unsigned short c) {
    const float cv = bf_lo(c);
    return round_bf16(cv * rcp(1.f + ex2(-1.4426950408889634f * cv)));
}
__device__ __forceinline__ void st_mod(uint32_t* p, float v, uint32_t tag) {
    asm volatile("st.relaxed.gpu.global.u32 [%0], %1;" ::"l"(p), "r"(__float_as_uint(round_bf16(v)) | tag)
                 : "memory");
}
__device__ __forceinline__ void mod_block(const uint4 (&w)[5], const float (&sc)[5], uint32_t* dst, uint32_t red,
                                          int warp, int lane, uint32_t tag) {
    float acc[8];
#pragma unroll
    for (int e = 0; e < 8; e++) acc[e] = 0.f;
#pragma unroll
    for (int i = 0; i < 5; i++) {
        acc[0] = fmaf(sc[i], bf_lo(w[i].x), acc[0]);
        acc[1] = fmaf(sc[i], bf_hi(w[i].x), acc[1]);
        acc[2] = fmaf(sc[i], bf_lo(w[i].y), acc[2]);
        acc[3] = fmaf(sc[i], bf_hi(w[i].y), acc[3]);
        acc[4] = fmaf(sc[i], bf_lo(w[i].z), acc[4]);
        acc[5] = fmaf(sc[i], bf_hi(w[i].z), acc[5]);
        acc[6] = fmaf(sc[i], bf_lo(w[i].w), acc[6]);
        acc[7] = fmaf(sc[i], bf_hi(w[i].w), acc[7]);
    }
#pragma unroll
    for (int o = 2; o < 32; o <<= 1)
#pragma unroll
        for (int e = 0; e < 8; e++) acc[e] += __shfl_xor_sync(0xffffffffu, acc[e], o);
    if (lane < 2) {
#pragma unroll
        for (int e = 0; e < 8; e++) sts32f(red + (warp * 16 + lane * 8 + e) * 4, acc[e]);
    }
    bar_sync(3, 256);
    if (warp == 0 && lane < 16) {
        float s = 0.f;
#pragma unroll
        for (int w8 = 0; w8 < 8; w8++) s += lds32f(red + (w8 * 16 + lane) * 4);
        st_mod(dst + lane, s, tag);
    }
}

__global__ void __cluster_dims__(2, 1, 1) __launch_bounds__(384, 1)
    fused_block_kernel(const __grid_constant__ Params maps) {
    extern __shared__ uint8_t smem_raw[];
    uint32_t sbase = (smem_u32(smem_raw) + 1023u) & ~1023u;
    asm volatile("" : "+r"(sbase));
    const int b = blockIdx.x;
    const int rank = b & 1;
    const int mt = ((b >> 1) & 7) * 2 + rank;
    const int g = b >> 4;
    const int warp = __shfl_sync(0xffffffffu, threadIdx.x >> 5, 0);
    const int lane = threadIdx.x & 31;
    Scratch* const sc_ = maps.sc;
    const __nv_bfloat16* const wmod = maps.wmod;
    const __nv_bfloat16* const cvec = maps.cvec;

    if (warp >= 8) {
        asm volatile("setmaxnreg.dec.sync.aligned.u32 24;");
        if (warp == 8 && lane == 0) {
#pragma unroll
            for (int i = 0; i < 8; i++) {
                mbar_init(sbase + OFF_FULL + i * 8, 1);
                mbar_init(sbase + OFF_EMPTY + i * 8, 4);
            }
            asm volatile("fence.mbarrier_init.release.cluster;" ::: "memory");
            asm volatile("barrier.cluster.arrive.relaxed;\nbarrier.cluster.wait;" ::: "memory");
            uint32_t slot = 0, phase = 1;
            const uint32_t dst0 = sbase + rank * BOX_BYTES;
            auto acquire = [&](uint32_t bytes) {
                mbar_wait(sbase + OFF_EMPTY + slot * 8, phase);
                mbar_expect_tx(sbase + OFF_FULL + slot * 8, bytes);
            };
            auto adv8 = [&]() {
                if (++slot == 8) {
                    slot = 0;
                    phase ^= 1;
                }
            };
#pragma unroll 1
            for (int hq = 0; hq < 4; hq++) {
                const int col = (g * 4 + ((hq + 1) & 3)) * 128 + rank * 64;
                if (hq == 2) {
                    l2_prefetch(maps.kc + (size_t)(g * 4 * 2048 + (b & 15) * 64) * 128, SLOT_BYTES);
                    l2_prefetch(maps.vc + (size_t)(g * 4 * 2048 + (b & 15) * 64) * 128, SLOT_BYTES);
                }
#pragma unroll 1
                for (int kc = 0; kc < 9; kc++) {
                    acquire(SLOT_BYTES);
                    tma_mc(dst0 + slot * SLOT_BYTES, &maps.wq, col, kc * 64, sbase + OFF_FULL + slot * 8);
                    adv8();
                }
            }
            const int row0 = g * 4 * 2048;
#pragma unroll 1
            for (int n = 0; n < 128; n++) {
                if (n < 4) mbar_wait(sbase + OFF_EMPTY + (slot + 1) * 8, phase);
                acquire(2 * SLOT_BYTES);
                const uint32_t bar = sbase + OFF_FULL + slot * 8;
                const int r0 = n == 0 ? 0 : (n == 127 ? 126 : n + 1);
                const int r1 = n == 0 ? 1 : (n == 127 ? 127 : n - 1);
                tma_mc(dst0 + slot * SLOT_BYTES, n == 127 ? &maps.v : &maps.k, rank * 64, row0 + r0 * 64, bar);
                tma_mc(dst0 + (slot + 1) * SLOT_BYTES, n == 0 ? &maps.k : &maps.v, rank * 64, row0 + r1 * 64, bar);
                adv8();
                adv8();
                const int u = n + KV_AHEAD;
                if (u < 128 && (u & 15) == (b & 15)) {
                    l2_prefetch(maps.kc + (size_t)(row0 + u * 64) * 128, SLOT_BYTES);
                    l2_prefetch(maps.vc + (size_t)(row0 + u * 64) * 128, SLOT_BYTES);
                }
            }
#pragma unroll 1
            for (int p = 0; p < 4; p++)
#pragma unroll 1
                for (int kc = 0; kc < 8; kc++) {
                    acquire(SLOT_BYTES);
                    tma_mc(dst0 + slot * SLOT_BYTES, &maps.wo, p * 128 + rank * 64, g * 512 + kc * 64,
                           sbase + OFF_FULL + slot * 8);
                    adv8();
                }
#pragma unroll 1
            for (int kc = 0; kc < 4; kc++) {
                acquire(SLOT_BYTES);
                tma_mc(dst0 + slot * SLOT_BYTES, &maps.wo, 512, g * 512 + kc * 128 + rank * 64,
                       sbase + OFF_FULL + slot * 8);
                adv8();
            }
            const CUtensorMap* mg = rank ? &maps.wu : &maps.wg;
#pragma unroll 1
            for (int ch = 0; ch < 9; ch++)
#pragma unroll 1
                for (int kc = 0; kc < 9; kc++) {
                    acquire(SLOT_BYTES);
                    tma_mc(dst0 + slot * SLOT_BYTES, mg, g * 576 + ch * 64, kc * 64, sbase + OFF_FULL + slot * 8);
                    adv8();
                }
#pragma unroll 1
            for (int p = 0; p < 4; p++)
#pragma unroll 1
                for (int kc = 2; kc < 11; kc++) {
                    acquire(SLOT_BYTES);
                    tma_mc(dst0 + slot * SLOT_BYTES, &maps.wd, p * 128 + rank * 64, g * 576 + (kc < 9 ? kc : kc - 9) * 64,
                           sbase + OFF_FULL + slot * 8);
                    adv8();
                }
#pragma unroll 1
            for (int i = 0; i < 5; i++) {
                acquire(i < 4 ? SLOT_BYTES : BOX_BYTES);
                const int kc = 2 * i + rank + 2;
                if (i < 4 || rank == 0)
                    tma_mc(dst0 + slot * SLOT_BYTES, &maps.wd, 512, g * 576 + (kc < 9 ? kc : kc - 9) * 64,
                           sbase + OFF_FULL + slot * 8);
                adv8();
            }
        } else if (warp == 11) {
            const int row = b * 5 + lane;
            if (lane < 5 && row < DM) l2_prefetch(wmod + (size_t)row * (6 * DM), 2 * DM * 2);
            asm volatile("barrier.cluster.arrive.relaxed.aligned;" ::: "memory");
            uint4* hz = sc_->h[(ld_epoch(sc_) & 1) ^ 1][0] + (size_t)b * 72 * 32 + lane;
            bar_sync(6, 160);
#pragma unroll 1
            for (int i = 0; i < 72; i++) {
                hz[i * 32] = make_uint4(0, 0, 0, 0);
                __nanosleep(200);
            }
        } else if (warp == 9 || warp == 10) {
            asm volatile("barrier.cluster.arrive.relaxed.aligned;" ::: "memory");
            const uint32_t tag = (ld_epoch(sc_) + 1) & 0xffffu;
            bar_sync(4, 320);
            const int blk = warp == 9 ? 72 + b : 200 + b;
            if (blk < 216) {
                float acc[8];
#pragma unroll
                for (int e = 0; e < 8; e++) acc[e] = 0.f;
                const uint4* wp = reinterpret_cast<const uint4*>(wmod + (size_t)(lane >> 1) * (6 * DM) + blk * 16) + (lane & 1);
                const unsigned short* cp = reinterpret_cast<const unsigned short*>(cvec) + (lane >> 1);
#pragma unroll 1
                for (int i = 0; i < 36; i++) {
                    const uint4 w = __ldg(wp + (size_t)i * (16 * 6 * DM / 8));
                    const float sc = silu_bf16(__ldg(cp + i * 16));
                    acc[0] = fmaf(sc, bf_lo(w.x), acc[0]);
                    acc[1] = fmaf(sc, bf_hi(w.x), acc[1]);
                    acc[2] = fmaf(sc, bf_lo(w.y), acc[2]);
                    acc[3] = fmaf(sc, bf_hi(w.y), acc[3]);
                    acc[4] = fmaf(sc, bf_lo(w.z), acc[4]);
                    acc[5] = fmaf(sc, bf_hi(w.z), acc[5]);
                    acc[6] = fmaf(sc, bf_lo(w.w), acc[6]);
                    acc[7] = fmaf(sc, bf_hi(w.w), acc[7]);
                }
#pragma unroll
                for (int o = 2; o < 32; o <<= 1)
#pragma unroll
                    for (int e = 0; e < 8; e++) acc[e] += __shfl_xor_sync(0xffffffffu, acc[e], o);
                if (lane < 2) {
#pragma unroll
                    for (int e = 0; e < 8; e++) st_mod(sc_->mod + blk * 16 + lane * 8 + e, acc[e], tag);
                }
            }
            if (warp == 9) {
#pragma unroll 1
                for (int st = 1; st <= 2; st++) {
                    bar_sync(7, 160);
                    const uint32_t* src = sc_->mod + (st * 3 - 1) * DM;
                    const int n = st == 1 ? 3 * DM : DM;
#pragma unroll 1
                    for (int i = lane * 4; i < n + 127 - ((n + 127) & 127); i += 128)
                        mod_to_smem(sbase + OFF_MODT + min(i, n - 4) * 4, src + min(i, n - 4), tag);
                    __syncwarp();
                    rows_load(sbase, (st == 1 ? maps.x : sc_->x2) + (size_t)(mt * 8 + g) * 16 * DM, lane);
                    if (st == 1) {
                        bar_sync(7, 160);
                        rows_store(sbase, sc_->x2 + (size_t)(mt * 8 + g) * 16 * DM, lane);
                        rows_store_wait();
                        __syncwarp();
                        bar_arrive(10, 160);
                    }
                }
            }
        }
    } else {
        asm volatile("setmaxnreg.inc.sync.aligned.u32 240;");
        const int wg = warp >> 2;
        const int tid = threadIdx.x;
        Ctx cx;
        cx.sbase = sbase;
        cx.wg = wg;
        if (wg == 1) bar_arrive(8, 256);
        cx.rel_cta = (lane == 0 && (warp & 3) < 2) ? (warp & 3) : 2;
        const uint32_t red = sbase + OFF_RED;
        const int own = mt * 8 + g;
        const int wown = mt * 8 + warp;
        PROF(0);
        PROFG(30);
        PROFR(17);
        const uint32_t epoch = ld_epoch(sc_);
        {
            uint4 w1[5];
            unsigned short cu[5];
            const int half = tid & 1, r0 = tid >> 1;
            if (b < 72) {
#pragma unroll
                for (int i = 0; i < 5; i++) {
                    const int row = min(r0 + 128 * i, DM - 1);
                    cu[i] = __ldg(reinterpret_cast<const unsigned short*>(cvec) + row);
                    w1[i] = __ldg(reinterpret_cast<const uint4*>(wmod + (size_t)row * (6 * DM) + half * 8) + b * 2);
                }
            }
            if (warp == 0) {
                if (lane == 0) {
                    mbar_init(sbase + OFF_XBAR, 1);
                    asm volatile("fence.mbarrier_init.release.cluster;\nfence.proxy.async.shared::cta;" ::: "memory");
                }
                rows_load(sbase, maps.x + (size_t)own * 16 * DM, lane);
            }
            PROFR(18);
            asm volatile("barrier.cluster.arrive.relaxed.aligned;" ::: "memory");
            if (b < 72) {
                float sc[5];
#pragma unroll
                for (int i = 0; i < 5; i++) sc[i] = (r0 + 128 * i < DM) ? silu_bf16(cu[i]) : 0.f;
                mod_block(w1, sc, sc_->mod + b * 16, red + 1024, warp, lane, (epoch + 1) & 0xffffu);
            } else {
                bar_sync(3, 256);
            }
            asm volatile("" ::"r"(epoch) : "memory");
            bar_arrive(4, 320);
            PROFR(21);
        }

        Ring ring{0u, 0u};
        int stage = 0;
        asm volatile("" : "+r"(stage));
#pragma unroll 1
        for (;; stage++) {
            int tid, lane;
            asm volatile("mov.u32 %0, %%tid.x;" : "=r"(tid));
            lane = tid & 31;
            {
                float v[36];
                const uint32_t modt = sbase + OFF_MODT + (warp * 16 + (lane & 3) * 2) * 4;
                if (stage == 0) {
#pragma unroll
                    for (int i = 0; i < 36; i++) v[i] = 0.f;
                } else {
                    const uint4* psrc = sc_->part + (size_t)own * 8 * 36 * 32;
                    sum_partials(v, psrc + tid, stage & 1);
                    PROF(stage == 1 ? 8 : 15);
                    sum_tail(v, reinterpret_cast<const uint2*>(psrc + 32 * 32) + tid, stage & 1);
                }
                mbar_wait(sbase + OFF_XBAR, stage & 1);
                if (stage == 0) PROFR(22);
                {
                    const float gs = stage == 2 ? 0.5f : 1.f;
                    float gate[18];
                    lds_mod(gate, modt, warp);
                    const uint32_t rows = sbase + OFF_ROWS + (lane >> 2) * XROW_STRIDE + warp * 32 + (lane & 3) * 4;
#pragma unroll
                    for (int j = 0; j < 9; j++) {
                        const uint32_t ad = rows + own_col(j) * 2 - (j == 8 ? warp * 16 : 0);
                        const uint32_t u0 = __float_as_uint(lds32f(ad)), u1 = __float_as_uint(lds32f(ad + 8 * XROW_STRIDE));
                        const float g0 = stage ? gate[2 * j] * gs : 0.f, g1 = stage ? gate[2 * j + 1] * gs : 0.f;
                        v[4 * j] = fmaf(g0, v[4 * j], bf_lo(u0));
                        v[4 * j + 1] = fmaf(g1, v[4 * j + 1], bf_hi(u0));
                        v[4 * j + 2] = fmaf(g0, v[4 * j + 2], bf_lo(u1));
                        v[4 * j + 3] = fmaf(g1, v[4 * j + 3], bf_hi(u1));
                        sts32f(ad, __uint_as_float(pack_bf16(v[4 * j], v[4 * j + 1])));
                        sts32f(ad + 8 * XROW_STRIDE, __uint_as_float(pack_bf16(v[4 * j + 2], v[4 * j + 3])));
                    }
                    asm volatile("fence.proxy.async.shared::cta;" ::: "memory");
                }
                if (stage == 2) break;
                PROF(stage == 0 ? 1 : 9);
                layernorm_rows(v, red, warp, lane);
                if (stage == 0) PROFR(27);
                if (stage == 0) {
                    const uint32_t tag = (epoch + 1) & 0xffffu;
                    mod_to_smem(sbase + OFF_MODT + (DM + tid * 4) * 4, sc_->mod + tid * 4, tag);
                    if (warp == 7) mod_to_smem(sbase + OFF_MODT + (DM + 1024 + lane * 4) * 4, sc_->mod + 1024 + lane * 4, tag);
                    bar_sync(3, 256);
                }
                float shift[18], scale[18];
                lds_mod(shift, modt + DM * 4, warp);
                lds_mod(scale, modt + 2 * DM * 4, warp);
                if (stage == 0) PROFR(28);
                PROF(stage == 0 ? 2 : 10);
                modulate_store(v, shift, scale, sc_->h[epoch & 1][stage] + (size_t)own * 36 * 32, warp, lane);
                if (stage == 0) asm volatile("barrier.cluster.wait.aligned;" ::: "memory");
            }

            const uint32_t spill = sbase + 8 * SLOT_BYTES + wg * 3 * SLOT_BYTES + (tid & 127) * 16;
            uint32_t a[144];
            PROF(stage == 0 ? 3 : 11);
            {
                const uint4* hsrc = sc_->h[epoch & 1][stage] + (size_t)wown * 36 * 32 + lane;
                poll_frags<32, 36>(a, hsrc, false);
                PROF(stage == 0 ? 4 : 12);
                if (stage == 1) PROFG(25);
                TG(stage * 32 + 30);
                if (wg == 1) bar_sync(5, 256);
                poll_frags<0, 32>(a, hsrc, wg == 0);
            }
            uint4* hhbuf = sc_->hh + (size_t)b * 8 * 256 + tid;
            float d[64];
#pragma unroll 1
            for (int ch = 0;; ch++) {
                TG(stage * 32 + ch * 2);
                gemm_n128(d, a, cx, ring, true);
                TG(stage * 32 + ch * 2 + 1);
                if (stage == 0) {
#pragma unroll
                    for (int i = 0; i < 64; i++) d[i] *= SM_SCALE;
                    if (ch == 3) break;
#pragma unroll
                    for (int v = 0; v < 8; v++)
                        sts128(spill + (ch * 8 + v) * 2048, pack_bf16(d[8 * v], d[8 * v + 1]),
                               pack_bf16(d[8 * v + 2], d[8 * v + 3]), pack_bf16(d[8 * v + 4], d[8 * v + 5]),
                               pack_bf16(d[8 * v + 6], d[8 * v + 7]));
                } else {
#pragma unroll
                    for (int i = 0; i < 32; i++) {
                        const float gv = d[i], gu = gv * d[32 + i];
                        const float z = gv * fmaf(gv * gv, 0.7978845608028654f * 0.044715f, 0.7978845608028654f);
                        d[i] = fmaf(gu, tanh_fast(z), gu);
                    }
                    if (ch == 8) break;
                    if (wg == 0) {
                        if (ch == 0) bar_arrive(7, 160);
                        if (ch == 2) bar_sync(10, 160);
                    }
#pragma unroll
                    for (int v = 0; v < 4; v++) {
                        const uint4 h4 = make_uint4(pack_bf16(d[8 * v], d[8 * v + 1]), pack_bf16(d[8 * v + 2], d[8 * v + 3]),
                                                    pack_bf16(d[8 * v + 4], d[8 * v + 5]), pack_bf16(d[8 * v + 6], d[8 * v + 7]));
                        if (ch < 2)
                            __stcg(hhbuf + (ch * 4 + v) * 256, h4);
                        else
                            sts128(spill + ((ch - 2) * 4 + v) * 2048, h4.x, h4.y, h4.z, h4.w);
                    }
                }
            }
            if (stage == 0) {
                uint32_t q[32];
#pragma unroll
                for (int i = 0; i < 32; i++) q[i] = pack_bf16(d[2 * i], d[2 * i + 1]);
                PROF(5);
                PROFG(23);
                if (wg == 0) bar_arrive(6, 160);
                {
                    float o[64], sa[32], sb[32];
                    uint32_t pa[16], pb[16];
#pragma unroll
                    for (int i = 0; i < 64; i++) o[i] = 0.f;
                    float n0 = 0.f, n1 = 0.f, l0 = 1.f, l1 = 1.f;
                    bool shifted = false;
                    const uint64_t dbase = desc_of(sbase);
                    const uint64_t dbk = dbase - (511u << 16);
                    const int my_bar = 1 + wg, other_bar = 2 - wg;

                    auto softmax_a = [&](bool first, float& s0, float& s1) {
                        if (first) {
                            shifted = false;
                            n0 = n1 = 0.f;
                            l0 = l1 = 0.f;
                        }
                        if (shifted)
                            exp_step<true>(sa, pa, n0, n1, s0, s1);
                        else
                            exp_step<false>(sa, pa, n0, n1, s0, s1);
                    };
                    auto softmax_b = [&](bool first, float s0, float s1) {
                        float u0, u1;
                        if (shifted)
                            exp_step<true>(sb, pb, n0, n1, u0, u1);
                        else
                            exp_step<false>(sb, pb, n0, n1, u0, u1);
                        s0 += u0;
                        s1 += u1;
                        bool bad = !(fmaxf(s0, s1) <= SM_HI);
                        if (first) {
                            float r0 = s0 + __shfl_xor_sync(0xffffffffu, s0, 1), r1 = s1 + __shfl_xor_sync(0xffffffffu, s1, 1);
                            r0 += __shfl_xor_sync(0xffffffffu, r0, 2);
                            r1 += __shfl_xor_sync(0xffffffffu, r1, 2);
                            bad = bad || !(fminf(r0, r1) >= SM_LO);
                        }
                        if (__any_sync(0xffffffffu, bad)) {
                            float x0, x1;
                            row_max(sa, sb, x0, x1);
                            x0 = -x0;
                            x1 = -x1;
                            if (!first) {
                                x0 = fminf(x0, n0);
                                x1 = fminf(x1, n1);
                                const float al0 = ex2(x0 - n0), al1 = ex2(x1 - n1);
                                l0 *= al0;
                                l1 *= al1;
#pragma unroll
                                for (int i = 0; i < 16; i++) {
                                    o[4 * i] *= al0;
                                    o[4 * i + 1] *= al0;
                                    o[4 * i + 2] *= al1;
                                    o[4 * i + 3] *= al1;
                                }
                            }
                            n0 = x0;
                            n1 = x1;
                            shifted = true;
                            exp_step<true>(sa, pa, n0, n1, s0, s1);
                            exp_step<true>(sb, pb, n0, n1, u0, u1);
                            s0 += u0;
                            s1 += u1;
                        }
                        l0 += s0;
                        l1 += s1;
                    };

                    cx.wait_full(4, 0);
                    if (wg == 1) bar_sync(my_bar, 256);
                    wg_fence();
                    qk_step(sa, q, dbk + 4 * 1024);
                    qk_step(sb, q, dbk + 5 * 1024);
                    wg_commit();
                    bar_arrive(other_bar, 256);
                    wg_wait<0>();
                    pin(sa);
                    pin(sb);
                    cx.release(4);
                    cx.wait_full(6, 0);
                    {
                        float s0, s1;
                        softmax_a(true, s0, s1);
                        softmax_b(true, s0, s1);
                    }
                    uint32_t alo = (uint32_t)dbase + 6 * 1024, blo = (uint32_t)dbase;
                    const uint32_t dhi = (uint32_t)(dbase >> 32);
#pragma unroll 1
                    for (int t = 1; t < 64; t++) {
                        const int j = t & 15;
                        const uint32_t sA = 2 + 4 * (t & 1), sB = 4 - 4 * (t & 1);
                        const uint64_t da = ((uint64_t)dhi << 32) | alo, db = ((uint64_t)dhi << 32) | blo;
                        TL(0);
                        bar_sync(my_bar, 256);
                        TL(2);
                        wg_fence();
                        pv_step(o, pa, da + 1024, j != 1);
                        qk_step(sa, q, da - (511u << 16));
                        wg_commit();
                        cx.wait_full(sB, ((36 + 4 * t) >> 3) & 1);
                        wg_fence();
                        qk_step(sb, q, db - (511u << 16));
                        pv_step(o, pb, db + 1024, 1);
                        wg_commit();
                        bar_arrive(other_bar, 256);
                        alo ^= 4096;
                        blo ^= 4096;
                        asm volatile("" : "+r"(alo), "+r"(blo));
                        TL(3);
                        wg_wait<1>();
                        pin(sa);
                        pin(pa);
                        TL(4);
                        cx.release(sA);
                        const float lp0 = l0, lp1 = l1;
                        float s0, s1;
                        softmax_a(j == 0, s0, s1);
                        TL(5);
                        wg_wait<0>();
                        pin(o);
                        pin(sb);
                        pin(pb);
                        TL(6);
                        cx.release(sB);
                        if (j == 0) {
                            float i0, i1;
                            inv_row_sums(lp0, lp1, i0, i1);
                            const uint32_t dst = spill + ((t >> 4) - 1) * 16384;
#pragma unroll
                            for (int v = 0; v < 8; v++)
                                sts128(dst + v * 2048, pack_bf16(o[8 * v] * i0, o[8 * v + 1] * i0),
                                       pack_bf16(o[8 * v + 2] * i1, o[8 * v + 3] * i1),
                                       pack_bf16(o[8 * v + 4] * i0, o[8 * v + 5] * i0),
                                       pack_bf16(o[8 * v + 6] * i1, o[8 * v + 7] * i1));
                        }
                        const uint32_t bn = sbase + OFF_FULL + (8 - sA) * 8, pn = ((38 + 4 * t) >> 3) & 1;
                        const bool okn = mbar_try(bn, pn);
                        TL(1);
                        softmax_b(j == 0, s0, s1);
                        if (!okn || j == 15) {
                            mbar_wait(bn, pn);
                            if (j == 15 && t < 63) {
                                const uint32_t src = spill + (t >> 4) * 16384;
#pragma unroll
                                for (int v = 0; v < 8; v++)
                                    lds128(src + v * 2048, q[4 * v], q[4 * v + 1], q[4 * v + 2], q[4 * v + 3]);
                            }
                        }
                        TL(7);
                    }
                    bar_sync(my_bar, 256);
                    wg_fence();
                    pv_step(o, pa, dbase + 2 * 1024, 1);
                    pv_step(o, pb, dbase + 3 * 1024, 1);
                    wg_commit();
                    if (wg == 0) bar_arrive(other_bar, 256);
                    float i0, i1;
                    inv_row_sums(l0, l1, i0, i1);
                    wg_wait<0>();
                    pin(o);
                    cx.release(2);
#pragma unroll
                    for (int i = 0; i < 16; i++) {
                        a[96 + 2 * i] = pack_bf16(o[4 * i] * i0, o[4 * i + 1] * i0);
                        a[96 + 2 * i + 1] = pack_bf16(o[4 * i + 2] * i1, o[4 * i + 3] * i1);
                    }
#pragma unroll
                    for (int i = 128; i < 144; i++) a[i] = 0;
                }
                ring.slot = 4;
                ring.phase = 0;
                PROF(6);
                PROFG(24);
            } else {
#pragma unroll
                for (int v = 0; v < 8; v++) {
                    const uint4 t = __ldcg(hhbuf + v * 256);
                    a[112 + 4 * v] = t.x;
                    a[113 + 4 * v] = t.y;
                    a[114 + 4 * v] = t.z;
                    a[115 + 4 * v] = t.w;
                }
#pragma unroll
                for (int i = 0; i < 16; i++) a[96 + i] = pack_bf16(d[2 * i], d[2 * i + 1]);
                PROF(13);
            }
#pragma unroll
            for (int v = 0; v < 24; v++) lds128(spill + v * 2048, a[4 * v], a[4 * v + 1], a[4 * v + 2], a[4 * v + 3]);

            {
                uint4* dst = sc_->part + ((size_t)wown * 8 + g) * 36 * 32 + lane;
                const uint32_t ptag = (stage + 1) & 1;
#pragma unroll 1
                for (int p = 0; p < 4; p++) {
                    TG(stage * 32 + 18 + p * 2);
                    gemm_n128(d, a, cx, ring, stage != 0);
                    TG(stage * 32 + 19 + p * 2);
#pragma unroll
                    for (int u = 0; u < 8; u++)
                        st128(dst + (p * 8 + u) * 32, (pack_bf16(d[8 * u], d[8 * u + 1]) & ~1u) | ptag,
                              pack_bf16(d[8 * u + 2], d[8 * u + 3]), pack_bf16(d[8 * u + 4], d[8 * u + 5]),
                              pack_bf16(d[8 * u + 6], d[8 * u + 7]));
                    if (p == 0 && wg == 0) bar_arrive(7, 160);
                }
                float e[32];
                TG(stage * 32 + 26);
                gemm_n64(e, a, cx, ring, stage != 0);
                TG(stage * 32 + 27);
                uint2* dst2 = reinterpret_cast<uint2*>(dst - lane + 32 * 32) + lane;
#pragma unroll
                for (int j = 0; j < 8; j++)
                    st64(dst2 + j * 32, (pack_bf16(e[4 * j], e[4 * j + 1]) & ~1u) | ptag, pack_bf16(e[4 * j + 2], e[4 * j + 3]));
            }
            PROF(stage == 0 ? 7 : 14);
            if (stage == 1) {
                PROFG(26);
                asm volatile("barrier.cluster.arrive.relaxed.aligned;" ::: "memory");
            }
        }
        if (wg == 0) bar_sync(8, 256);
        bar_sync(3, 256);
        if (warp == 0) {
            rows_store(sbase, maps.out + (size_t)own * 16 * DM, lane);
            if (b == 0 && lane == 0) sc_->epoch = epoch + 1;
            rows_store_wait();
        }
        PROF(16);
        PROFG(31);
        asm volatile("barrier.cluster.wait.aligned;" ::: "memory");
    }
}

typedef CUresult (*EncodeFn)(CUtensorMap*, CUtensorMapDataType, cuuint32_t, void*, const cuuint64_t*, const cuuint64_t*,
                             const cuuint32_t*, const cuuint32_t*, CUtensorMapInterleave, CUtensorMapSwizzle,
                             CUtensorMapL2promotion, CUtensorMapFloatOOBfill);

void make_map(EncodeFn enc, CUtensorMap* m, const void* ptr, uint64_t rows, uint64_t cols) {
    cuuint64_t gdim[2] = {cols, rows};
    cuuint64_t gstr[1] = {cols * 2};
    cuuint32_t box[2] = {64, 64};
    cuuint32_t estr[2] = {1, 1};
    enc(m, CU_TENSOR_MAP_DATA_TYPE_BFLOAT16, 2, const_cast<void*>(ptr), gdim, gstr, box, estr,
        CU_TENSOR_MAP_INTERLEAVE_NONE, CU_TENSOR_MAP_SWIZZLE_128B, CU_TENSOR_MAP_L2_PROMOTION_L2_128B,
        CU_TENSOR_MAP_FLOAT_OOB_FILL_NONE);
}

}

extern "C" void kernel_launch(void* const* d_in, const int* in_sizes, int n_in, void* d_out, int out_size) {
    (void)in_sizes;
    (void)n_in;
    (void)out_size;
    void* fn = nullptr;
    cudaDriverEntryPointQueryResult qr;
    cudaGetDriverEntryPoint("cuTensorMapEncodeTiled", &fn, cudaEnableDefault, &qr);
    EncodeFn enc = (EncodeFn)fn;
    Params maps;
    maps.x = (const __nv_bfloat16*)d_in[0];
    maps.cvec = (const __nv_bfloat16*)d_in[9];
    maps.wmod = (const __nv_bfloat16*)d_in[10];
    maps.kc = (const __nv_bfloat16*)d_in[1];
    maps.vc = (const __nv_bfloat16*)d_in[2];
    maps.out = (__nv_bfloat16*)d_out;
    void* scp = nullptr;
    cudaGetSymbolAddress(&scp, g_scratch);
    maps.sc = (Scratch*)scp;
    make_map(enc, &maps.k, d_in[1], 32 * 2048, 128);
    make_map(enc, &maps.v, d_in[2], 32 * 2048, 128);
    make_map(enc, &maps.wq, d_in[3], 576, 4096);
    make_map(enc, &maps.wo, d_in[4], 4096, 576);
    make_map(enc, &maps.wg, d_in[6], 576, 4608);
    make_map(enc, &maps.wu, d_in[7], 576, 4608);
    make_map(enc, &maps.wd, d_in[8], 4608, 576);
    cudaFuncSetAttribute(fused_block_kernel, cudaFuncAttributeMaxDynamicSharedMemorySize, SMEM_BYTES);
    fused_block_kernel<<<128, 384, SMEM_BYTES>>>(maps);
}
```

```cpp
#include <cuda_runtime.h>
#include <cuda_bf16.h>
#include <cuda.h>
#include <stdint.h>

namespace {

constexpr int DM = 576;
constexpr int SLOT_BYTES = 16384;
constexpr int BOX_BYTES = 8192;
constexpr int NUNITS = 14;
constexpr int SMEM_TAIL = NUNITS * SLOT_BYTES;
constexpr int SMEM_BYTES = SMEM_TAIL + 2048 + 1024;
constexpr int OFF_FULL = SMEM_TAIL;
constexpr int OFF_EMPTY = SMEM_TAIL + 64;
constexpr int OFF_RED = SMEM_TAIL + 128;

constexpr int KV_AHEAD = 16;
#define GATE_SLOT 4
constexpr int OFF_XBAR = SMEM_TAIL + 1792;
constexpr int OFF_ROWS = 8 * SLOT_BYTES;
constexpr int OFF_MODT = OFF_ROWS + 20480;
constexpr int OFF_WBLK = OFF_ROWS + 28672;
constexpr int OFF_WBAR = SMEM_TAIL + 1800;
constexpr int XROW_STRIDE = DM * 2 + 16;

struct Scratch {
    unsigned epoch;
    unsigned pad[31];
    uint32_t mod[6 * DM];
    uint4 h[2][2][128 * 36 * 32];
    uint4 part[128 * 8 * 36 * 32];
    uint4 hh[128 * 8 * 256];
    __nv_bfloat16 x2[2048 * DM];
};
__device__ Scratch g_scratch;

#define TG(i)
#define TL(i)
#define PROFR(i)
#define PROF(i)
#define PROFG(i)

struct Params {
    const __nv_bfloat16 *x, *cvec, *wmod, *kc, *vc, *wq_p, *wo_p, *wg_p, *wu_p, *wd_p;
    __nv_bfloat16* out;
    Scratch* sc;
    CUtensorMap k, v, wq, wo, wg, wu, wd, wm;
};

__device__ __forceinline__ uint32_t smem_u32(const void* p) { return (uint32_t)__cvta_generic_to_shared(p); }
__device__ __forceinline__ void mbar_init(uint32_t a, uint32_t c) {
    asm volatile("mbarrier.init.shared::cta.b64 [%0], %1;" ::"r"(a), "r"(c) : "memory");
}
__device__ __forceinline__ void mbar_expect_tx(uint32_t a, uint32_t bytes) {
    asm volatile("mbarrier.arrive.expect_tx.shared::cta.b64 _, [%0], %1;" ::"r"(a), "r"(bytes) : "memory");
}
__device__ __forceinline__ bool mbar_try(uint32_t a, uint32_t ph) {
    uint32_t ok;
    asm volatile(
        "{\n.reg .pred p;\nmbarrier.try_wait.parity.shared::cta.b64 p, [%1], %2;\nselp.u32 %0, 1, 0, p;\n}"
        : "=r"(ok)
        : "r"(a), "r"(ph)
        : "memory");
    return ok != 0;
}
__device__ __forceinline__ uint32_t clk32() {
    uint32_t c;
    asm volatile("mov.u32 %0, %%clock;" : "=r"(c));
    return c;
}
constexpr uint32_t WAIT_LIMIT = 1u << 30;
__device__ __forceinline__ void mbar_wait(uint32_t a, uint32_t ph) {
    if (mbar_try(a, ph)) return;
    uint32_t t0 = clk32();
    while (!mbar_try(a, ph)) {
        if (clk32() - t0 > WAIT_LIMIT) break;
    }
}
__device__ __forceinline__ void mbar_arrive_cluster(uint32_t a, uint32_t cta) {
    asm volatile(
        "{\n.reg .b32 ra;\nmapa.shared::cluster.u32 ra, %0, %1;\nmbarrier.arrive.shared::cluster.b64 _, [ra];\n}" ::"r"(a),
        "r"(cta)
        : "memory");
}
__device__ __forceinline__ void tma_mc(uint32_t dst, const CUtensorMap* m, int c0, int c1, uint32_t bar) {
    asm volatile(
        "cp.async.bulk.tensor.2d.shared::cluster.global.mbarrier::complete_tx::bytes.multicast::cluster"
        " [%0], [%1, {%3, %4}], [%2], %5;" ::"r"(dst),
        "l"(m), "r"(bar), "r"(c0), "r"(c1), "h"((uint16_t)3)
        : "memory");
}
__device__ __forceinline__ void l2_prefetch(const void* p, uint32_t bytes) {
    asm volatile("cp.async.bulk.prefetch.L2.global [%0], %1;" ::"l"(p), "r"(bytes) : "memory");
}
__device__ __forceinline__ void bar_sync(int id, int n) { asm volatile("bar.sync %0, %1;" ::"r"(id), "r"(n) : "memory"); }
__device__ __forceinline__ void bar_arrive(int id, int n) {
    asm volatile("bar.arrive %0, %1;" ::"r"(id), "r"(n) : "memory");
}
__device__ __forceinline__ void wg_fence() { asm volatile("wgmma.fence.sync.aligned;" ::: "memory"); }
__device__ __forceinline__ void wg_commit() { asm volatile("wgmma.commit_group.sync.aligned;" ::: "memory"); }
template <int N>
__device__ __forceinline__ void wg_wait() {
    asm volatile("wgmma.wait_group.sync.aligned %0;" ::"n"(N) : "memory");
}
template <int N>
__device__ __forceinline__ void pin(float (&d)[N]) {
#pragma unroll
    for (int i = 0; i < N; i++) asm volatile("" : "+f"(d[i])::"memory");
}
template <int N>
__device__ __forceinline__ void pin(uint32_t (&d)[N]) {
#pragma unroll
    for (int i = 0; i < N; i++) asm volatile("" : "+r"(d[i])::"memory");
}
__device__ __forceinline__ uint32_t pack_bf16(float lo, float hi) {
    uint32_t r;
    asm("cvt.rn.bf16x2.f32 %0, %1, %2;" : "=r"(r) : "f"(hi), "f"(lo));
    return r;
}
__device__ __forceinline__ float bf_lo(uint32_t v) { return __uint_as_float(v << 16); }
__device__ __forceinline__ float bf_hi(uint32_t v) { return __uint_as_float(v & 0xffff0000u); }
__device__ __forceinline__ float round_bf16(float v) { return __bfloat162float(__float2bfloat16_rn(v)); }
__device__ __forceinline__ float ex2(float x) {
    float y;
    asm("ex2.approx.ftz.f32 %0, %1;" : "=f"(y) : "f"(x));
    return y;
}
__device__ __forceinline__ float rcp(float x) {
    float y;
    asm("rcp.approx.ftz.f32 %0, %1;" : "=f"(y) : "f"(x));
    return y;
}
__device__ __forceinline__ float tanh_fast(float x) {
    float y;
    asm("tanh.approx.f32 %0, %1;" : "=f"(y) : "f"(x));
    return y;
}
__device__ __forceinline__ void sts128(uint32_t a, uint32_t x, uint32_t y, uint32_t z, uint32_t w) {
    asm volatile("st.shared.v4.b32 [%0], {%1,%2,%3,%4};" ::"r"(a), "r"(x), "r"(y), "r"(z), "r"(w) : "memory");
}
__device__ __forceinline__ void lds128(uint32_t a, uint32_t& x, uint32_t& y, uint32_t& z, uint32_t& w) {
    asm volatile("ld.shared.v4.b32 {%0,%1,%2,%3}, [%4];" : "=r"(x), "=r"(y), "=r"(z), "=r"(w) : "r"(a) : "memory");
}
__device__ __forceinline__ void sts32f(uint32_t a, float v) {
    asm volatile("st.shared.f32 [%0], %1;" ::"r"(a), "f"(v) : "memory");
}
__device__ __forceinline__ float lds32f(uint32_t a) {
    float v;
    asm volatile("ld.shared.f32 %0, [%1];" : "=f"(v) : "r"(a) : "memory");
    return v;
}
#define F8(d, b) \
    "+f"(d[b]), "+f"(d[b + 1]), "+f"(d[b + 2]), "+f"(d[b + 3]), "+f"(d[b + 4]), "+f"(d[b + 5]), "+f"(d[b + 6]), "+f"(d[b + 7])

template <int TB>
__device__ __forceinline__ void wgmma_n128(float (&d)[64], uint32_t a0, uint32_t a1, uint32_t a2, uint32_t a3,
                                           uint64_t db, int sc) {
    asm volatile(
        "{\n.reg .pred p;\nsetp.ne.b32 p, %69, 0;\n"
        "wgmma.mma_async.sync.aligned.m64n128k16.f32.bf16.bf16 "
        "{%0,%1,%2,%3,%4,%5,%6,%7,%8,%9,%10,%11,%12,%13,%14,%15,%16,%17,%18,%19,%20,%21,%22,%23,%24,%25,%26,%27,%28,%29,%30,%31,"
        "%32,%33,%34,%35,%36,%37,%38,%39,%40,%41,%42,%43,%44,%45,%46,%47,%48,%49,%50,%51,%52,%53,%54,%55,%56,%57,%58,%59,%60,%61,%62,%63},"
        "{%64,%65,%66,%67}, %68, p, 1, 1, %70;\n}"
        : F8(d, 0), F8(d, 8), F8(d, 16), F8(d, 24), F8(d, 32), F8(d, 40), F8(d, 48), F8(d, 56)
        : "r"(a0), "r"(a1), "r"(a2), "r"(a3), "l"(db), "r"(sc), "n"(TB));
}
#define O8(d, b) \
    "=f"(d[b]), "=f"(d[b + 1]), "=f"(d[b + 2]), "=f"(d[b + 3]), "=f"(d[b + 4]), "=f"(d[b + 5]), "=f"(d[b + 6]), "=f"(d[b + 7])
template <int TB>
__device__ __forceinline__ void wgmma_n128_z(float (&d)[64], uint32_t a0, uint32_t a1, uint32_t a2, uint32_t a3,
                                             uint64_t db) {
    asm volatile(
        "wgmma.mma_async.sync.aligned.m64n128k16.f32.bf16.bf16 "
        "{%0,%1,%2,%3,%4,%5,%6,%7,%8,%9,%10,%11,%12,%13,%14,%15,%16,%17,%18,%19,%20,%21,%22,%23,%24,%25,%26,%27,%28,%29,%30,%31,"
        "%32,%33,%34,%35,%36,%37,%38,%39,%40,%41,%42,%43,%44,%45,%46,%47,%48,%49,%50,%51,%52,%53,%54,%55,%56,%57,%58,%59,%60,%61,%62,%63},"
        "{%64,%65,%66,%67}, %68, 0, 1, 1, %69;"
        : O8(d, 0), O8(d, 8), O8(d, 16), O8(d, 24), O8(d, 32), O8(d, 40), O8(d, 48), O8(d, 56)
        : "r"(a0), "r"(a1), "r"(a2), "r"(a3), "l"(db), "n"(TB));
}
template <int TB>
__device__ __forceinline__ void wgmma_n64_z(float (&d)[32], uint32_t a0, uint32_t a1, uint32_t a2, uint32_t a3,
                                            uint64_t db) {
    asm volatile(
        "wgmma.mma_async.sync.aligned.m64n64k16.f32.bf16.bf16 "
        "{%0,%1,%2,%3,%4,%5,%6,%7,%8,%9,%10,%11,%12,%13,%14,%15,%16,%17,%18,%19,%20,%21,%22,%23,%24,%25,%26,%27,%28,%29,%30,%31},"
        "{%32,%33,%34,%35}, %36, 0, 1, 1, %37;"
        : O8(d, 0), O8(d, 8), O8(d, 16), O8(d, 24)
        : "r"(a0), "r"(a1), "r"(a2), "r"(a3), "l"(db), "n"(TB));
}
template <int TB>
__device__ __forceinline__ void wgmma_n64(float (&d)[32], uint32_t a0, uint32_t a1, uint32_t a2, uint32_t a3,
                                          uint64_t db) {
    asm volatile(
        "wgmma.mma_async.sync.aligned.m64n64k16.f32.bf16.bf16 "
        "{%0,%1,%2,%3,%4,%5,%6,%7,%8,%9,%10,%11,%12,%13,%14,%15,%16,%17,%18,%19,%20,%21,%22,%23,%24,%25,%26,%27,%28,%29,%30,%31},"
        "{%32,%33,%34,%35}, %36, 1, 1, 1, %37;"
        : F8(d, 0), F8(d, 8), F8(d, 16), F8(d, 24)
        : "r"(a0), "r"(a1), "r"(a2), "r"(a3), "l"(db), "n"(TB));
}

__device__ __forceinline__ uint64_t desc_of(uint32_t saddr) {
    return (uint64_t)(((saddr >> 4) & 0x3FFFu) | (512u << 16)) | ((uint64_t)(64u | (1u << 30)) << 32);
}

struct Ring {
    uint32_t slot;
    uint32_t phase;
    __device__ __forceinline__ void next() {
        if (++slot == 8) {
            slot = 0;
            phase ^= 1;
        }
    }
};

struct Ctx {
    uint32_t sbase;
    int wg;
    uint32_t rel_cta;
    __device__ __forceinline__ void wait_full(uint32_t slot, uint32_t phase) const {
        mbar_wait(sbase + OFF_FULL + slot * 8, phase);
    }
    __device__ __forceinline__ void release(uint32_t slot) const {
        if (rel_cta < 2) mbar_arrive_cluster(sbase + OFF_EMPTY + slot * 8, rel_cta);
    }
};

__device__ __forceinline__ void gemm_n128(float (&d)[64], const uint32_t (&a)[144], const Ctx& c, Ring& r, bool nine) {
    uint32_t prev = 0;
#pragma unroll
    for (int s = 0; s < 9; s++) {
        if (s < 8 || nine) {
            if (s == GATE_SLOT) bar_sync(8 + c.wg, 256);
            c.wait_full(r.slot, r.phase);
            uint64_t db = desc_of(c.sbase + r.slot * SLOT_BYTES);
            wg_fence();
#pragma unroll
            for (int k = 0; k < 4; k++) {
                if ((s | k) == 0)
                    wgmma_n128_z<1>(d, a[0], a[1], a[2], a[3], db);
                else
                    wgmma_n128<1>(d, a[s * 16 + k * 4], a[s * 16 + k * 4 + 1], a[s * 16 + k * 4 + 2],
                                  a[s * 16 + k * 4 + 3], db + k * 128, 1);
            }
            wg_commit();
            if (s == 8 || (s == 7 && !nine)) bar_arrive(9 - c.wg, 256);
            if (s > 0) {
                wg_wait<1>();
                c.release(prev);
            }
            prev = r.slot;
            r.next();
        }
    }
    wg_wait<0>();
    c.release(prev);
    pin(d);
}
__device__ __forceinline__ void gemm_n64(float (&d)[32], const uint32_t (&a)[144], const Ctx& c, Ring& r, bool nine) {
    uint32_t prev = 0;
#pragma unroll
    for (int s = 0; s < 5; s++) {
        if (s < 4 || nine) {
            c.wait_full(r.slot, r.phase);
            uint64_t db = desc_of(c.sbase + r.slot * SLOT_BYTES);
            wg_fence();
#pragma unroll
            for (int k = 0; k < 8; k++) {
                if ((s | k) == 0)
                    wgmma_n64_z<1>(d, a[0], a[1], a[2], a[3], db);
                else if (s * 8 + k < 36)
                    wgmma_n64<1>(d, a[s * 32 + k * 4], a[s * 32 + k * 4 + 1], a[s * 32 + k * 4 + 2],
                                 a[s * 32 + k * 4 + 3], db + k * 128);
            }
            wg_commit();
            if (s > 0) {
                wg_wait<1>();
                c.release(prev);
            }
            prev = r.slot;
            r.next();
        }
    }
    wg_wait<0>();
    c.release(prev);
    pin(d);
}
__device__ __forceinline__ void st128(uint4* p, uint32_t x, uint32_t y, uint32_t z, uint32_t w) {
    asm volatile(
        "{\n.reg .b64 lo, hi;\n.reg .b128 t;\nmov.b64 lo, {%1, %2};\nmov.b64 hi, {%3, %4};\nmov.b128 t, {lo, hi};\n"
        "st.relaxed.gpu.global.b128 [%0], t;\n}" ::"l"(p),
        "r"(x), "r"(y), "r"(z), "r"(w)
        : "memory");
}
__device__ __forceinline__ uint4 ld128(const uint4* p) {
    uint4 r;
    asm volatile(
        "{\n.reg .b64 lo, hi;\n.reg .b128 t;\nld.relaxed.gpu.global.b128 t, [%4];\nmov.b128 {lo, hi}, t;\n"
        "mov.b64 {%0, %1}, lo;\nmov.b64 {%2, %3}, hi;\n}"
        : "=r"(r.x), "=r"(r.y), "=r"(r.z), "=r"(r.w)
        : "l"(p));
    return r;
}
__device__ __forceinline__ void st64(void* p, uint32_t x, uint32_t y) {
    asm volatile("{\n.reg .b64 t;\nmov.b64 t, {%1, %2};\nst.relaxed.gpu.global.b64 [%0], t;\n}" ::"l"(p), "r"(x), "r"(y)
                 : "memory");
}
__device__ __forceinline__ uint2 ld64(const void* p) {
    uint2 r;
    asm volatile("{\n.reg .b64 t;\nld.relaxed.gpu.global.b64 t, [%2];\nmov.b64 {%0, %1}, t;\n}"
                 : "=r"(r.x), "=r"(r.y)
                 : "l"(p));
    return r;
}
__device__ __forceinline__ void rows_load(uint32_t sbase, const __nv_bfloat16* src, int lane) {
    if (lane == 0) mbar_expect_tx(sbase + OFF_XBAR, 16 * DM * 2);
    __syncwarp();
    if (lane < 16)
        asm volatile("cp.async.bulk.shared::cluster.global.mbarrier::complete_tx::bytes [%0], [%1], %2, [%3];" ::"r"(
                         sbase + OFF_ROWS + lane * XROW_STRIDE),
                     "l"(src + lane * DM), "r"(DM * 2), "r"(sbase + OFF_XBAR)
                     : "memory");
    __syncwarp();
}
__device__ __forceinline__ void rows_store(uint32_t sbase, __nv_bfloat16* dst, int lane) {
    if (lane < 16) {
        asm volatile("cp.async.bulk.global.shared::cta.bulk_group [%0], [%1], %2;" ::"l"(dst + lane * DM),
                     "r"(sbase + OFF_ROWS + lane * XROW_STRIDE), "r"(DM * 2)
                     : "memory");
        asm volatile("cp.async.bulk.commit_group;" ::: "memory");
    }
    __syncwarp();
}
__device__ __forceinline__ void rows_store_wait() { asm volatile("cp.async.bulk.wait_group 0;" ::: "memory"); }

__device__ __forceinline__ constexpr int own_col(int j) { return j < 8 ? (j >> 1) * 128 + (j & 1) * 8 : 512; }
__device__ __forceinline__ void row_reduce(float& s0, float& s1, uint32_t red, int warp, int lane) {
    s0 += __shfl_xor_sync(0xffffffffu, s0, 1);
    s1 += __shfl_xor_sync(0xffffffffu, s1, 1);
    s0 += __shfl_xor_sync(0xffffffffu, s0, 2);
    s1 += __shfl_xor_sync(0xffffffffu, s1, 2);
    if ((lane & 3) == 0) {
        sts32f(red + (warp * 16 + (lane >> 2)) * 4, s0);
        sts32f(red + (warp * 16 + 8 + (lane >> 2)) * 4, s1);
    }
    bar_sync(3, 256);
    s0 = 0.f;
    s1 = 0.f;
#pragma unroll
    for (int w = 0; w < 8; w++) {
        s0 += lds32f(red + (w * 16 + (lane >> 2)) * 4);
        s1 += lds32f(red + (w * 16 + 8 + (lane >> 2)) * 4);
    }
}
__device__ __forceinline__ void layernorm_rows(float (&v)[36], uint32_t red, int warp, int lane) {
    float s0 = 0.f, s1 = 0.f;
#pragma unroll
    for (int j = 0; j < 9; j++) {
        s0 += v[4 * j] + v[4 * j + 1];
        s1 += v[4 * j + 2] + v[4 * j + 3];
    }
    row_reduce(s0, s1, red, warp, lane);
    const float m0 = s0 * (1.f / DM), m1 = s1 * (1.f / DM);
    s0 = 0.f;
    s1 = 0.f;
#pragma unroll
    for (int j = 0; j < 9; j++) {
        v[4 * j] -= m0;
        v[4 * j + 1] -= m0;
        v[4 * j + 2] -= m1;
        v[4 * j + 3] -= m1;
        s0 += v[4 * j] * v[4 * j] + v[4 * j + 1] * v[4 * j + 1];
        s1 += v[4 * j + 2] * v[4 * j + 2] + v[4 * j + 3] * v[4 * j + 3];
    }
    row_reduce(s0, s1, red + 512, warp, lane);
    const float r0 = rsqrtf(s0 * (1.f / DM) + 1e-5f), r1 = rsqrtf(s1 * (1.f / DM) + 1e-5f);
#pragma unroll
    for (int j = 0; j < 9; j++) {
        v[4 * j] *= r0;
        v[4 * j + 1] *= r0;
        v[4 * j + 2] *= r1;
        v[4 * j + 3] *= r1;
    }
}
__device__ __forceinline__ void mod_to_smem(uint32_t dst, const uint32_t* src, uint32_t tag) {
    const uint32_t t0 = clk32();
    uint4 u;
    while (true) {
        u = ld128(reinterpret_cast<const uint4*>(src));
        const uint32_t bad = ((u.x ^ tag) | (u.y ^ tag) | (u.z ^ tag) | (u.w ^ tag)) & 0xffffu;
        if (__all_sync(0xffffffffu, bad == 0) || clk32() - t0 > WAIT_LIMIT) break;
        __nanosleep(64);
    }
    sts128(dst, u.x & 0xffff0000u, u.y & 0xffff0000u, u.z & 0xffff0000u, u.w & 0xffff0000u);
}
__device__ __forceinline__ void lds_mod(float (&m)[18], uint32_t src  , int warp) {
#pragma unroll
    for (int j = 0; j < 9; j++)
        asm volatile("ld.shared.v2.f32 {%0,%1}, [%2];"
                     : "=f"(m[2 * j]), "=f"(m[2 * j + 1])
                     : "r"(src + own_col(j) * 4 - (j == 8 ? warp * 32 : 0))
                     : "memory");
}
__device__ __forceinline__ void modulate_store(const float (&v)[36], const float (&shift)[18], const float (&scale)[18],
                                               uint4* hbuf  , int warp, int lane) {
    uint32_t o[18];
#pragma unroll
    for (int j = 0; j < 9; j++) {
        const uint32_t cc = pack_bf16(1.f + scale[2 * j], 1.f + scale[2 * j + 1]);
        const float c0 = bf_lo(cc), c1 = bf_hi(cc);
        o[2 * j] = max(pack_bf16(fmaf(v[4 * j], c0, shift[2 * j]), fmaf(v[4 * j + 1], c1, shift[2 * j + 1])), 1u);
        o[2 * j + 1] = max(pack_bf16(fmaf(v[4 * j + 2], c0, shift[2 * j]), fmaf(v[4 * j + 3], c1, shift[2 * j + 1])), 1u);
    }
#pragma unroll
    for (int i = 0; i < 4; i++) st128(hbuf + (i * 8 + warp) * 32 + lane, o[4 * i], o[4 * i + 1], o[4 * i + 2], o[4 * i + 3]);
    st64(reinterpret_cast<uint2*>(hbuf + 32 * 32) + warp * 32 + lane, o[16], o[17]);
}
__device__ __forceinline__ void sum_partials(float (&v)[36], const uint4* src  , uint32_t tag) {
    const uint32_t t0 = clk32();
    while (true) {
        uint4 t[8][4];
#pragma unroll
        for (int s = 0; s < 8; s++)
#pragma unroll
            for (int i = 0; i < 4; i++) t[s][i] = ld128(src + (s * 36 + i * 8) * 32);
        uint32_t bad = 0;
#pragma unroll
        for (int i = 0; i < 32; i++) v[i] = 0.f;
#pragma unroll
        for (int s = 0; s < 8; s++)
#pragma unroll
            for (int i = 0; i < 4; i++) {
                bad |= t[s][i].x ^ tag;
                v[8 * i] += bf_lo(t[s][i].x);
                v[8 * i + 1] += bf_hi(t[s][i].x);
                v[8 * i + 2] += bf_lo(t[s][i].y);
                v[8 * i + 3] += bf_hi(t[s][i].y);
                v[8 * i + 4] += bf_lo(t[s][i].z);
                v[8 * i + 5] += bf_hi(t[s][i].z);
                v[8 * i + 6] += bf_lo(t[s][i].w);
                v[8 * i + 7] += bf_hi(t[s][i].w);
            }
        if (__all_sync(0xffffffffu, (bad & 1u) == 0) || clk32() - t0 > WAIT_LIMIT) break;
    }
}
__device__ __forceinline__ void sum_tail(float (&v)[36], const uint2* src  , uint32_t tag) {
    const uint32_t t0 = clk32();
    while (true) {
        uint2 t[8];
#pragma unroll
        for (int s = 0; s < 8; s++) t[s] = ld64(src + s * 72 * 32);
        uint32_t bad = 0;
        v[32] = v[33] = v[34] = v[35] = 0.f;
#pragma unroll
        for (int s = 0; s < 8; s++) {
            bad |= t[s].x ^ tag;
            v[32] += bf_lo(t[s].x);
            v[33] += bf_hi(t[s].x);
            v[34] += bf_lo(t[s].y);
            v[35] += bf_hi(t[s].y);
        }
        if (__all_sync(0xffffffffu, (bad & 1u) == 0) || clk32() - t0 > WAIT_LIMIT) break;
    }
}
__device__ __forceinline__ void poll_tail(uint32_t (&a)[144], const uint2* src  ) {
    const uint32_t t0 = clk32();
    while (true) {
        uint32_t m = 0xffffffffu;
#pragma unroll
        for (int j = 0; j < 8; j++) {
            const uint2 t = ld64(src + j * 32);
            a[128 + 2 * j] = t.x;
            a[129 + 2 * j] = t.y;
        }
#pragma unroll
        for (int j = 0; j < 16; j++) m = min(m, a[128 + j]);
        if (__all_sync(0xffffffffu, m != 0) || clk32() - t0 > WAIT_LIMIT) break;
    }
}
template <int K0, int K1>
__device__ __forceinline__ void poll_frags(uint32_t (&a)[144], const uint4* src  , bool kick) {
    const uint32_t t0 = clk32();
    while (true) {
#pragma unroll
        for (int k = K0; k < K1; k++)
            asm volatile("ld.relaxed.gpu.global.v4.u32 {%0,%1,%2,%3}, [%4];"
                         : "=r"(a[4 * k]), "=r"(a[4 * k + 1]), "=r"(a[4 * k + 2]), "=r"(a[4 * k + 3])
                         : "l"(src + k * 32));
        if (kick) bar_arrive(5, 256);
        kick = false;
        uint32_t m0 = a[4 * K0], m1 = a[4 * K0 + 1];
#pragma unroll
        for (int i = 4 * K0 + 2; i < 4 * K1; i += 2) {
            m0 = min(m0, a[i]);
            m1 = min(m1, a[i + 1]);
        }
        if (__all_sync(0xffffffffu, min(m0, m1) != 0) || clk32() - t0 > WAIT_LIMIT) break;
    }
}

constexpr float SM_SCALE = 0.08838834764831845f * 1.4426950408889634f;
constexpr float SM_HI = 1.2089258e24f;
constexpr float SM_LO = 9.0949470e-13f;
__device__ __forceinline__ void qk_step(float (&s)[32], const uint32_t (&q)[32], uint64_t dk) {
#pragma unroll
    for (int k = 0; k < 8; k++) {
        if (k == 0)
            wgmma_n64_z<0>(s, q[0], q[1], q[2], q[3], dk);
        else
            wgmma_n64<0>(s, q[4 * k], q[4 * k + 1], q[4 * k + 2], q[4 * k + 3], dk + (k >> 2) * 512 + (k & 3) * 2);
    }
}
__device__ __forceinline__ void pv_step(float (&o)[64], const uint32_t (&p)[16], uint64_t dv, int acc) {
#pragma unroll
    for (int k = 0; k < 4; k++)
        wgmma_n128<1>(o, p[4 * k], p[4 * k + 1], p[4 * k + 2], p[4 * k + 3], dv + k * 128, k != 0 ? 1 : acc);
}
template <bool SHIFT>
__device__ __forceinline__ void exp_step(const float (&s)[32], uint32_t (&p)[16], float n0, float n1, float& s0,
                                         float& s1) {
#pragma unroll
    for (int i = 0; i < 8; i++) {
        const float e0 = ex2(SHIFT ? s[4 * i] + n0 : s[4 * i]), e1 = ex2(SHIFT ? s[4 * i + 1] + n0 : s[4 * i + 1]);
        const float e2 = ex2(SHIFT ? s[4 * i + 2] + n1 : s[4 * i + 2]), e3 = ex2(SHIFT ? s[4 * i + 3] + n1 : s[4 * i + 3]);
        if (i == 0) {
            s0 = e0 + e1;
            s1 = e2 + e3;
        } else {
            s0 += e0 + e1;
            s1 += e2 + e3;
        }
        p[2 * i] = pack_bf16(e0, e1);
        p[2 * i + 1] = pack_bf16(e2, e3);
    }
}
__device__ __forceinline__ void row_max(const float (&sa)[32], const float (&sb)[32], float& x0, float& x1) {
    float xa[8];
#pragma unroll
    for (int i = 0; i < 8; i++) xa[i] = fmaxf(sa[i], sb[i]);
#pragma unroll
    for (int k = 1; k < 4; k++)
#pragma unroll
        for (int i = 0; i < 8; i++) xa[i] = fmaxf(xa[i], fmaxf(sa[8 * k + i], sb[8 * k + i]));
    x0 = fmaxf(fmaxf(xa[0], xa[1]), fmaxf(xa[4], xa[5]));
    x1 = fmaxf(fmaxf(xa[2], xa[3]), fmaxf(xa[6], xa[7]));
    x0 = fmaxf(x0, __shfl_xor_sync(0xffffffffu, x0, 1));
    x1 = fmaxf(x1, __shfl_xor_sync(0xffffffffu, x1, 1));
    x0 = fmaxf(x0, __shfl_xor_sync(0xffffffffu, x0, 2));
    x1 = fmaxf(x1, __shfl_xor_sync(0xffffffffu, x1, 2));
}
__device__ __forceinline__ void inv_row_sums(float l0, float l1, float& i0, float& i1) {
    l0 += __shfl_xor_sync(0xffffffffu, l0, 1);
    l1 += __shfl_xor_sync(0xffffffffu, l1, 1);
    l0 += __shfl_xor_sync(0xffffffffu, l0, 2);
    l1 += __shfl_xor_sync(0xffffffffu, l1, 2);
    i0 = rcp(l0);
    i1 = rcp(l1);
}

__device__ __forceinline__ uint32_t ld_epoch(const Scratch* sc) {
    uint32_t e;
    asm volatile("ld.relaxed.gpu.global.u32 %0, [%1];" : "=r"(e) : "l"(&sc->epoch) : "memory");
    return e;
}
__device__ __forceinline__ float silu_bf16(unsigned short c) {
    const float cv = bf_lo(c);
    return round_bf16(cv * rcp(1.f + ex2(-1.4426950408889634f * cv)));
}
__device__ __forceinline__ void st_mod(uint32_t* p, float v, uint32_t tag) {
    asm volatile("st.relaxed.gpu.global.u32 [%0], %1;" ::"l"(p), "r"(__float_as_uint(round_bf16(v)) | tag)
                 : "memory");
}
__device__ __forceinline__ void mod_block(const uint4 (&w)[5], const float (&sc)[5], uint32_t* dst, uint32_t red,
                                          int warp, int lane, uint32_t tag) {
    float acc[8];
#pragma unroll
    for (int e = 0; e < 8; e++) acc[e] = 0.f;
#pragma unroll
    for (int i = 0; i < 5; i++) {
        acc[0] = fmaf(sc[i], bf_lo(w[i].x), acc[0]);
        acc[1] = fmaf(sc[i], bf_hi(w[i].x), acc[1]);
        acc[2] = fmaf(sc[i], bf_lo(w[i].y), acc[2]);
        acc[3] = fmaf(sc[i], bf_hi(w[i].y), acc[3]);
        acc[4] = fmaf(sc[i], bf_lo(w[i].z), acc[4]);
        acc[5] = fmaf(sc[i], bf_hi(w[i].z), acc[5]);
        acc[6] = fmaf(sc[i], bf_lo(w[i].w), acc[6]);
        acc[7] = fmaf(sc[i], bf_hi(w[i].w), acc[7]);
    }
#pragma unroll
    for (int o = 2; o < 32; o <<= 1)
#pragma unroll
        for (int e = 0; e < 8; e++) acc[e] += __shfl_xor_sync(0xffffffffu, acc[e], o);
    if (lane < 2) {
#pragma unroll
        for (int e = 0; e < 8; e++) sts32f(red + (warp * 16 + lane * 8 + e) * 4, acc[e]);
    }
    bar_sync(3, 256);
    if (warp == 0 && lane < 16) {
        float s = 0.f;
#pragma unroll
        for (int w8 = 0; w8 < 8; w8++) s += lds32f(red + (w8 * 16 + lane) * 4);
        st_mod(dst + lane, s, tag);
    }
}

__global__ void __cluster_dims__(2, 1, 1) __launch_bounds__(384, 1)
    fused_block_kernel(const __grid_constant__ Params maps) {
    extern __shared__ uint8_t smem_raw[];
    uint32_t sbase = (smem_u32(smem_raw) + 1023u) & ~1023u;
    asm volatile("" : "+r"(sbase));
    const int b = blockIdx.x;
    const int rank = b & 1;
    const int mt = ((b >> 1) & 7) * 2 + rank;
    const int g = b >> 4;
    const int warp = __shfl_sync(0xffffffffu, threadIdx.x >> 5, 0);
    const int lane = threadIdx.x & 31;
    Scratch* const sc_ = maps.sc;
    const __nv_bfloat16* const wmod = maps.wmod;
    const __nv_bfloat16* const cvec = maps.cvec;

    if (warp >= 8) {
        asm volatile("setmaxnreg.dec.sync.aligned.u32 24;");
        if (warp == 8 && lane == 0) {
#pragma unroll
            for (int i = 0; i < 8; i++) {
                mbar_init(sbase + OFF_FULL + i * 8, 1);
                mbar_init(sbase + OFF_EMPTY + i * 8, 4);
            }
            asm volatile("fence.mbarrier_init.release.cluster;" ::: "memory");
            asm volatile("barrier.cluster.arrive.relaxed;\nbarrier.cluster.wait;" ::: "memory");
            uint32_t slot = 0, phase = 1;
            const uint32_t dst0 = sbase + rank * BOX_BYTES;
            auto acquire = [&](uint32_t bytes) {
                mbar_wait(sbase + OFF_EMPTY + slot * 8, phase);
                mbar_expect_tx(sbase + OFF_FULL + slot * 8, bytes);
            };
            auto adv8 = [&]() {
                if (++slot == 8) {
                    slot = 0;
                    phase ^= 1;
                }
            };
#pragma unroll 1
            for (int hq = 0; hq < 4; hq++) {
                const int col = (g * 4 + ((hq + 1) & 3)) * 128 + rank * 64;
                if (hq == 2) {
                    l2_prefetch(maps.kc + (size_t)(g * 4 * 2048 + (b & 15) * 64) * 128, SLOT_BYTES);
                    l2_prefetch(maps.vc + (size_t)(g * 4 * 2048 + (b & 15) * 64) * 128, SLOT_BYTES);
                }
#pragma unroll 1
                for (int kc = 0; kc < 9; kc++) {
                    acquire(SLOT_BYTES);
                    tma_mc(dst0 + slot * SLOT_BYTES, &maps.wq, col, kc * 64, sbase + OFF_FULL + slot * 8);
                    adv8();
                }
            }
            const int row0 = g * 4 * 2048;
#pragma unroll 1
            for (int n = 0; n < 128; n++) {
                if (n < 4) mbar_wait(sbase + OFF_EMPTY + (slot + 1) * 8, phase);
                acquire(2 * SLOT_BYTES);
                const uint32_t bar = sbase + OFF_FULL + slot * 8;
                const int r0 = n == 0 ? 0 : (n == 127 ? 126 : n + 1);
                const int r1 = n == 0 ? 1 : (n == 127 ? 127 : n - 1);
                tma_mc(dst0 + slot * SLOT_BYTES, n == 127 ? &maps.v : &maps.k, rank * 64, row0 + r0 * 64, bar);
                tma_mc(dst0 + (slot + 1) * SLOT_BYTES, n == 0 ? &maps.k : &maps.v, rank * 64, row0 + r1 * 64, bar);
                adv8();
                adv8();
                if (n >= 96 && n < 96 + 10) {
                    const int i = n - 96;
                    if (i < 9) {
                        l2_prefetch((const char*)maps.wg_p + (size_t)b * 41472 + i * 4608, 4608);
                        l2_prefetch((const char*)maps.wu_p + (size_t)b * 41472 + i * 4608, 4608);
                        l2_prefetch((const char*)maps.wd_p + (size_t)b * 41472 + i * 4608, 4608);
                        l2_prefetch((const char*)maps.wo_p + (size_t)b * 36864 + i * 4096, 4096);
                    }
                }
                const int u = n + KV_AHEAD;
                if (u < 128 && (u & 15) == (b & 15)) {
                    l2_prefetch(maps.kc + (size_t)(row0 + u * 64) * 128, SLOT_BYTES);
                    l2_prefetch(maps.vc + (size_t)(row0 + u * 64) * 128, SLOT_BYTES);
                }
            }
#pragma unroll 1
            for (int p = 0; p < 4; p++)
#pragma unroll 1
                for (int kc = 0; kc < 8; kc++) {
                    acquire(SLOT_BYTES);
                    tma_mc(dst0 + slot * SLOT_BYTES, &maps.wo, p * 128 + rank * 64, g * 512 + kc * 64,
                           sbase + OFF_FULL + slot * 8);
                    adv8();
                }
#pragma unroll 1
            for (int kc = 0; kc < 4; kc++) {
                acquire(SLOT_BYTES);
                tma_mc(dst0 + slot * SLOT_BYTES, &maps.wo, 512, g * 512 + kc * 128 + rank * 64,
                       sbase + OFF_FULL + slot * 8);
                adv8();
            }
            const CUtensorMap* mg = rank ? &maps.wu : &maps.wg;
#pragma unroll 1
            for (int ch = 0; ch < 9; ch++)
#pragma unroll 1
                for (int kc = 0; kc < 9; kc++) {
                    acquire(SLOT_BYTES);
                    tma_mc(dst0 + slot * SLOT_BYTES, mg, g * 576 + ch * 64, kc * 64, sbase + OFF_FULL + slot * 8);
                    adv8();
                }
#pragma unroll 1
            for (int p = 0; p < 4; p++)
#pragma unroll 1
                for (int kc = 2; kc < 11; kc++) {
                    acquire(SLOT_BYTES);
                    tma_mc(dst0 + slot * SLOT_BYTES, &maps.wd, p * 128 + rank * 64, g * 576 + (kc < 9 ? kc : kc - 9) * 64,
                           sbase + OFF_FULL + slot * 8);
                    adv8();
                }
#pragma unroll 1
            for (int i = 0; i < 5; i++) {
                acquire(i < 4 ? SLOT_BYTES : BOX_BYTES);
                const int kc = 2 * i + rank + 2;
                if (i < 4 || rank == 0)
                    tma_mc(dst0 + slot * SLOT_BYTES, &maps.wd, 512, g * 576 + (kc < 9 ? kc : kc - 9) * 64,
                           sbase + OFF_FULL + slot * 8);
                adv8();
            }
        } else if (warp == 11) {
            const int row = b * 5 + lane;
            if (lane < 5 && row < DM) l2_prefetch(wmod + (size_t)row * (6 * DM), 2 * DM * 2);
            asm volatile("barrier.cluster.arrive.relaxed.aligned;" ::: "memory");
            uint4* hz = sc_->h[(ld_epoch(sc_) & 1) ^ 1][0] + (size_t)b * 72 * 32 + lane;
            bar_sync(6, 160);
#pragma unroll 1
            for (int i = 0; i < 72; i++) {
                hz[i * 32] = make_uint4(0, 0, 0, 0);
                __nanosleep(200);
            }
        } else if (warp == 9 || warp == 10) {
            asm volatile("barrier.cluster.arrive.relaxed.aligned;" ::: "memory");
            const uint32_t tag = (ld_epoch(sc_) + 1) & 0xffffu;
            bar_sync(4, 320);
            if (warp == 10 && lane < 9) l2_prefetch((const char*)maps.wq_p + (size_t)b * 36864 + lane * 4096, 4096);
            const int blk = warp == 9 ? 72 + b : 200 + b;
            if (blk < 216) {
                float acc[8];
#pragma unroll
                for (int e = 0; e < 8; e++) acc[e] = 0.f;
                const uint4* wp = reinterpret_cast<const uint4*>(wmod + (size_t)(lane >> 1) * (6 * DM) + blk * 16) + (lane & 1);
                const unsigned short* cp = reinterpret_cast<const unsigned short*>(cvec) + (lane >> 1);
#pragma unroll 1
                for (int i = 0; i < 36; i++) {
                    const uint4 w = __ldg(wp + (size_t)i * (16 * 6 * DM / 8));
                    const float sc = silu_bf16(__ldg(cp + i * 16));
                    acc[0] = fmaf(sc, bf_lo(w.x), acc[0]);
                    acc[1] = fmaf(sc, bf_hi(w.x), acc[1]);
                    acc[2] = fmaf(sc, bf_lo(w.y), acc[2]);
                    acc[3] = fmaf(sc, bf_hi(w.y), acc[3]);
                    acc[4] = fmaf(sc, bf_lo(w.z), acc[4]);
                    acc[5] = fmaf(sc, bf_hi(w.z), acc[5]);
                    acc[6] = fmaf(sc, bf_lo(w.w), acc[6]);
                    acc[7] = fmaf(sc, bf_hi(w.w), acc[7]);
                }
#pragma unroll
                for (int o = 2; o < 32; o <<= 1)
#pragma unroll
                    for (int e = 0; e < 8; e++) acc[e] += __shfl_xor_sync(0xffffffffu, acc[e], o);
                if (lane < 2) {
#pragma unroll
                    for (int e = 0; e < 8; e++) st_mod(sc_->mod + blk * 16 + lane * 8 + e, acc[e], tag);
                }
            }
            if (warp == 9) {
#pragma unroll 1
                for (int st = 1; st <= 2; st++) {
                    bar_sync(7, 160);
                    const uint32_t* src = sc_->mod + (st * 3 - 1) * DM;
                    const int n = st == 1 ? 3 * DM : DM;
#pragma unroll 1
                    for (int i = lane * 4; i < n + 127 - ((n + 127) & 127); i += 128)
                        mod_to_smem(sbase + OFF_MODT + min(i, n - 4) * 4, src + min(i, n - 4), tag);
                    __syncwarp();
                    rows_load(sbase, (st == 1 ? maps.x : sc_->x2) + (size_t)(mt * 8 + g) * 16 * DM, lane);
                    if (st == 1) {
                        bar_sync(7, 160);
                        rows_store(sbase, sc_->x2 + (size_t)(mt * 8 + g) * 16 * DM, lane);
                        rows_store_wait();
                        __syncwarp();
                        bar_arrive(10, 160);
                    }
                }
            }
        }
    } else {
        asm volatile("setmaxnreg.inc.sync.aligned.u32 240;");
        const int wg = warp >> 2;
        const int tid = threadIdx.x;
        Ctx cx;
        cx.sbase = sbase;
        cx.wg = wg;
        if (wg == 1) bar_arrive(8, 256);
        cx.rel_cta = (lane == 0 && (warp & 3) < 2) ? (warp & 3) : 2;
        const uint32_t red = sbase + OFF_RED;
        const int own = mt * 8 + g;
        const int wown = mt * 8 + warp;
        PROF(0);
        PROFG(30);
        PROFR(17);
        const uint32_t epoch = ld_epoch(sc_);
        {
            unsigned short cu[5];
            const int r0 = tid >> 1;
            if (warp == 0) {
                if (lane == 0) {
                    mbar_init(sbase + OFF_XBAR, 1);
                    mbar_init(sbase + OFF_WBAR, 1);
                    asm volatile("fence.mbarrier_init.release.cluster;\nfence.proxy.async.shared::cta;" ::: "memory");
                    if (b < 72) {
                        mbar_expect_tx(sbase + OFF_WBAR, DM * 32);
#pragma unroll
                        for (int i = 0; i < 3; i++)
                            asm volatile(
                                "cp.async.bulk.tensor.2d.shared::cluster.global.mbarrier::complete_tx::bytes"
                                " [%0], [%1, {%3, %4}], [%2];" ::"r"(sbase + OFF_WBLK + i * 192 * 32),
                                "l"(&maps.wm), "r"(sbase + OFF_WBAR), "r"(b * 16), "r"(i * 192)
                                : "memory");
                    }
                }
                rows_load(sbase, maps.x + (size_t)own * 16 * DM, lane);
            }
#pragma unroll
            for (int i = 0; i < 5; i++) cu[i] = __ldg(reinterpret_cast<const unsigned short*>(cvec) + min(r0 + 128 * i, DM - 1));
            PROFR(18);
            asm volatile("barrier.cluster.arrive.relaxed.aligned;" ::: "memory");
            bar_sync(3, 256);
            if (b < 72) {
                float sc[5];
                uint4 w1[5];
#pragma unroll
                for (int i = 0; i < 5; i++) sc[i] = (r0 + 128 * i < DM) ? silu_bf16(cu[i]) : 0.f;
                PROFR(19);
                mbar_wait(sbase + OFF_WBAR, 0);
                PROFR(20);
#pragma unroll
                for (int i = 0; i < 5; i++)
                    lds128(sbase + OFF_WBLK + (i < 4 ? tid + i * 256 : 1024 + (tid & 127)) * 16, w1[i].x, w1[i].y, w1[i].z, w1[i].w);
                mod_block(w1, sc, sc_->mod + b * 16, red + 1024, warp, lane, (epoch + 1) & 0xffffu);
            }
            asm volatile("" ::"r"(epoch) : "memory");
            bar_arrive(4, 320);
            PROFR(21);
        }

        Ring ring{0u, 0u};
        int stage = 0;
        asm volatile("" : "+r"(stage));
#pragma unroll 1
        for (;; stage++) {
            int tid, lane;
            asm volatile("mov.u32 %0, %%tid.x;" : "=r"(tid));
            lane = tid & 31;
            {
                float v[36];
                const uint32_t modt = sbase + OFF_MODT + (warp * 16 + (lane & 3) * 2) * 4;
                if (stage == 0) {
#pragma unroll
                    for (int i = 0; i < 36; i++) v[i] = 0.f;
                } else {
                    const uint4* psrc = sc_->part + (size_t)own * 8 * 36 * 32;
                    sum_partials(v, psrc + tid, stage & 1);
                    PROF(stage == 1 ? 8 : 15);
                    sum_tail(v, reinterpret_cast<const uint2*>(psrc + 32 * 32) + tid, stage & 1);
                }
                mbar_wait(sbase + OFF_XBAR, stage & 1);
                if (stage == 0) PROFR(22);
                {
                    const float gs = stage == 2 ? 0.5f : 1.f;
                    float gate[18];
                    lds_mod(gate, modt, warp);
                    const uint32_t rows = sbase + OFF_ROWS + (lane >> 2) * XROW_STRIDE + warp * 32 + (lane & 3) * 4;
#pragma unroll
                    for (int j = 0; j < 9; j++) {
                        const uint32_t ad = rows + own_col(j) * 2 - (j == 8 ? warp * 16 : 0);
                        const uint32_t u0 = __float_as_uint(lds32f(ad)), u1 = __float_as_uint(lds32f(ad + 8 * XROW_STRIDE));
                        const float g0 = stage ? gate[2 * j] * gs : 0.f, g1 = stage ? gate[2 * j + 1] * gs : 0.f;
                        v[4 * j] = fmaf(g0, v[4 * j], bf_lo(u0));
                        v[4 * j + 1] = fmaf(g1, v[4 * j + 1], bf_hi(u0));
                        v[4 * j + 2] = fmaf(g0, v[4 * j + 2], bf_lo(u1));
                        v[4 * j + 3] = fmaf(g1, v[4 * j + 3], bf_hi(u1));
                        sts32f(ad, __uint_as_float(pack_bf16(v[4 * j], v[4 * j + 1])));
                        sts32f(ad + 8 * XROW_STRIDE, __uint_as_float(pack_bf16(v[4 * j + 2], v[4 * j + 3])));
                    }
                    asm volatile("fence.proxy.async.shared::cta;" ::: "memory");
                }
                if (stage == 2) break;
                PROF(stage == 0 ? 1 : 9);
                layernorm_rows(v, red, warp, lane);
                if (stage == 0) PROFR(27);
                if (stage == 0) {
                    const uint32_t tag = (epoch + 1) & 0xffffu;
                    mod_to_smem(sbase + OFF_MODT + (DM + tid * 4) * 4, sc_->mod + tid * 4, tag);
                    if (warp == 7) mod_to_smem(sbase + OFF_MODT + (DM + 1024 + lane * 4) * 4, sc_->mod + 1024 + lane * 4, tag);
                    bar_sync(3, 256);
                }
                float shift[18], scale[18];
                lds_mod(shift, modt + DM * 4, warp);
                lds_mod(scale, modt + 2 * DM * 4, warp);
                if (stage == 0) PROFR(28);
                PROF(stage == 0 ? 2 : 10);
                modulate_store(v, shift, scale, sc_->h[epoch & 1][stage] + (size_t)own * 36 * 32, warp, lane);
                if (stage == 0) asm volatile("barrier.cluster.wait.aligned;" ::: "memory");
            }

            const uint32_t spill = sbase + 8 * SLOT_BYTES + wg * 3 * SLOT_BYTES + (tid & 127) * 16;
            uint32_t a[144];
            PROF(stage == 0 ? 3 : 11);
            {
                const uint4* hsrc = sc_->h[epoch & 1][stage] + (size_t)wown * 36 * 32 + lane;
                poll_tail(a, reinterpret_cast<const uint2*>(hsrc - lane + 32 * 32) + lane);
                PROF(stage == 0 ? 4 : 12);
                if (stage == 1) PROFG(25);
                TG(stage * 32 + 30);
                if (wg == 1) bar_sync(5, 256);
                poll_frags<0, 32>(a, hsrc, wg == 0);
            }
            uint4* hhbuf = sc_->hh + (size_t)b * 8 * 256 + tid;
            float d[64];
#pragma unroll 1
            for (int ch = 0;; ch++) {
                TG(stage * 32 + ch * 2);
                gemm_n128(d, a, cx, ring, true);
                TG(stage * 32 + ch * 2 + 1);
                if (stage == 0) {
#pragma unroll
                    for (int i = 0; i < 64; i++) d[i] *= SM_SCALE;
                    if (ch == 3) break;
#pragma unroll
                    for (int v = 0; v < 8; v++)
                        sts128(spill + (ch * 8 + v) * 2048, pack_bf16(d[8 * v], d[8 * v + 1]),
                               pack_bf16(d[8 * v + 2], d[8 * v + 3]), pack_bf16(d[8 * v + 4], d[8 * v + 5]),
                               pack_bf16(d[8 * v + 6], d[8 * v + 7]));
                } else {
#pragma unroll
                    for (int i = 0; i < 32; i++) {
                        const float gv = d[i], gu = gv * d[32 + i];
                        const float z = gv * fmaf(gv * gv, 0.7978845608028654f * 0.044715f, 0.7978845608028654f);
                        d[i] = fmaf(gu, tanh_fast(z), gu);
                    }
                    if (ch == 8) break;
                    if (wg == 0) {
                        if (ch == 0) bar_arrive(7, 160);
                        if (ch == 2) bar_sync(10, 160);
                    }
#pragma unroll
                    for (int v = 0; v < 4; v++) {
                        const uint4 h4 = make_uint4(pack_bf16(d[8 * v], d[8 * v + 1]), pack_bf16(d[8 * v + 2], d[8 * v + 3]),
                                                    pack_bf16(d[8 * v + 4], d[8 * v + 5]), pack_bf16(d[8 * v + 6], d[8 * v + 7]));
                        if (ch < 2)
                            __stcg(hhbuf + (ch * 4 + v) * 256, h4);
                        else
                            sts128(spill + ((ch - 2) * 4 + v) * 2048, h4.x, h4.y, h4.z, h4.w);
                    }
                }
            }
            if (stage == 0) {
                uint32_t q[32];
#pragma unroll
                for (int i = 0; i < 32; i++) q[i] = pack_bf16(d[2 * i], d[2 * i + 1]);
                PROF(5);
                PROFG(23);
                if (wg == 0) bar_arrive(6, 160);
                {
                    float o[64], sa[32], sb[32];
                    uint32_t pa[16], pb[16];
#pragma unroll
                    for (int i = 0; i < 64; i++) o[i] = 0.f;
                    float n0 = 0.f, n1 = 0.f, l0 = 1.f, l1 = 1.f;
                    bool shifted = false;
                    const uint64_t dbase = desc_of(sbase);
                    const uint64_t dbk = dbase - (511u << 16);
                    const int my_bar = 1 + wg, other_bar = 2 - wg;

                    auto softmax_a = [&](bool first, float& s0, float& s1) {
                        if (first) {
                            shifted = false;
                            n0 = n1 = 0.f;
                            l0 = l1 = 0.f;
                        }
                        if (shifted)
                            exp_step<true>(sa, pa, n0, n1, s0, s1);
                        else
                            exp_step<false>(sa, pa, n0, n1, s0, s1);
                    };
                    auto softmax_b = [&](bool first, float s0, float s1) {
                        float u0, u1;
                        if (shifted)
                            exp_step<true>(sb, pb, n0, n1, u0, u1);
                        else
                            exp_step<false>(sb, pb, n0, n1, u0, u1);
                        s0 += u0;
                        s1 += u1;
                        bool bad = !(fmaxf(s0, s1) <= SM_HI);
                        if (first) {
                            float r0 = s0 + __shfl_xor_sync(0xffffffffu, s0, 1), r1 = s1 + __shfl_xor_sync(0xffffffffu, s1, 1);
                            r0 += __shfl_xor_sync(0xffffffffu, r0, 2);
                            r1 += __shfl_xor_sync(0xffffffffu, r1, 2);
                            bad = bad || !(fminf(r0, r1) >= SM_LO);
                        }
                        if (__any_sync(0xffffffffu, bad)) {
                            float x0, x1;
                            row_max(sa, sb, x0, x1);
                            x0 = -x0;
                            x1 = -x1;
                            if (!first) {
                                x0 = fminf(x0, n0);
                                x1 = fminf(x1, n1);
                                const float al0 = ex2(x0 - n0), al1 = ex2(x1 - n1);
                                l0 *= al0;
                                l1 *= al1;
#pragma unroll
                                for (int i = 0; i < 16; i++) {
                                    o[4 * i] *= al0;
                                    o[4 * i + 1] *= al0;
                                    o[4 * i + 2] *= al1;
                                    o[4 * i + 3] *= al1;
                                }
                            }
                            n0 = x0;
                            n1 = x1;
                            shifted = true;
                            exp_step<true>(sa, pa, n0, n1, s0, s1);
                            exp_step<true>(sb, pb, n0, n1, u0, u1);
                            s0 += u0;
                            s1 += u1;
                        }
                        l0 += s0;
                        l1 += s1;
                    };

                    cx.wait_full(4, 0);
                    if (wg == 1) bar_sync(my_bar, 256);
                    wg_fence();
                    qk_step(sa, q, dbk + 4 * 1024);
                    qk_step(sb, q, dbk + 5 * 1024);
                    wg_commit();
                    bar_arrive(other_bar, 256);
                    wg_wait<0>();
                    pin(sa);
                    pin(sb);
                    cx.release(4);
                    cx.wait_full(6, 0);
                    {
                        float s0, s1;
                        softmax_a(true, s0, s1);
                        softmax_b(true, s0, s1);
                    }
                    uint32_t alo = (uint32_t)dbase + 6 * 1024, blo = (uint32_t)dbase;
                    const uint32_t dhi = (uint32_t)(dbase >> 32);
#pragma unroll 1
                    for (int t = 1; t < 64; t++) {
                        const int j = t & 15;
                        const uint32_t sA = 2 + 4 * (t & 1), sB = 4 - 4 * (t & 1);
                        const uint64_t da = ((uint64_t)dhi << 32) | alo, db = ((uint64_t)dhi << 32) | blo;
                        TL(0);
                        bar_sync(my_bar, 256);
                        TL(2);
                        wg_fence();
                        pv_step(o, pa, da + 1024, j != 1);
                        qk_step(sa, q, da - (511u << 16));
                        wg_commit();
                        cx.wait_full(sB, ((36 + 4 * t) >> 3) & 1);
                        wg_fence();
                        qk_step(sb, q, db - (511u << 16));
                        pv_step(o, pb, db + 1024, 1);
                        wg_commit();
                        bar_arrive(other_bar, 256);
                        alo ^= 4096;
                        blo ^= 4096;
                        asm volatile("" : "+r"(alo), "+r"(blo));
                        TL(3);
                        wg_wait<1>();
                        pin(sa);
                        pin(pa);
                        TL(4);
                        cx.release(sA);
                        const float lp0 = l0, lp1 = l1;
                        float s0, s1;
                        softmax_a(j == 0, s0, s1);
                        TL(5);
                        wg_wait<0>();
                        pin(o);
                        pin(sb);
                        pin(pb);
                        TL(6);
                        cx.release(sB);
                        if (j == 0) {
                            float i0, i1;
                            inv_row_sums(lp0, lp1, i0, i1);
                            const uint32_t dst = spill + ((t >> 4) - 1) * 16384;
#pragma unroll
                            for (int v = 0; v < 8; v++)
                                sts128(dst + v * 2048, pack_bf16(o[8 * v] * i0, o[8 * v + 1] * i0),
                                       pack_bf16(o[8 * v + 2] * i1, o[8 * v + 3] * i1),
                                       pack_bf16(o[8 * v + 4] * i0, o[8 * v + 5] * i0),
                                       pack_bf16(o[8 * v + 6] * i1, o[8 * v + 7] * i1));
                        }
                        const uint32_t bn = sbase + OFF_FULL + (8 - sA) * 8, pn = ((38 + 4 * t) >> 3) & 1;
                        const bool okn = mbar_try(bn, pn);
                        TL(1);
                        softmax_b(j == 0, s0, s1);
                        if (!okn || j == 15) {
                            mbar_wait(bn, pn);
                            if (j == 15 && t < 63) {
                                const uint32_t src = spill + (t >> 4) * 16384;
#pragma unroll
                                for (int v = 0; v < 8; v++)
                                    lds128(src + v * 2048, q[4 * v], q[4 * v + 1], q[4 * v + 2], q[4 * v + 3]);
                            }
                        }
                        TL(7);
                    }
                    bar_sync(my_bar, 256);
                    wg_fence();
                    pv_step(o, pa, dbase + 2 * 1024, 1);
                    pv_step(o, pb, dbase + 3 * 1024, 1);
                    wg_commit();
                    if (wg == 0) bar_arrive(other_bar, 256);
                    float i0, i1;
                    inv_row_sums(l0, l1, i0, i1);
                    wg_wait<0>();
                    pin(o);
                    cx.release(2);
#pragma unroll
                    for (int i = 0; i < 16; i++) {
                        a[96 + 2 * i] = pack_bf16(o[4 * i] * i0, o[4 * i + 1] * i0);
                        a[96 + 2 * i + 1] = pack_bf16(o[4 * i + 2] * i1, o[4 * i + 3] * i1);
                    }
#pragma unroll
                    for (int i = 128; i < 144; i++) a[i] = 0;
                }
                ring.slot = 4;
                ring.phase = 0;
                PROF(6);
                PROFG(24);
            } else {
#pragma unroll
                for (int v = 0; v < 8; v++) {
                    const uint4 t = __ldcg(hhbuf + v * 256);
                    a[112 + 4 * v] = t.x;
                    a[113 + 4 * v] = t.y;
                    a[114 + 4 * v] = t.z;
                    a[115 + 4 * v] = t.w;
                }
#pragma unroll
                for (int i = 0; i < 16; i++) a[96 + i] = pack_bf16(d[2 * i], d[2 * i + 1]);
                PROF(13);
            }
#pragma unroll
            for (int v = 0; v < 24; v++) lds128(spill + v * 2048, a[4 * v], a[4 * v + 1], a[4 * v + 2], a[4 * v + 3]);

            {
                uint4* dst = sc_->part + ((size_t)wown * 8 + g) * 36 * 32 + lane;
                const uint32_t ptag = (stage + 1) & 1;
#pragma unroll 1
                for (int p = 0; p < 4; p++) {
                    TG(stage * 32 + 18 + p * 2);
                    gemm_n128(d, a, cx, ring, stage != 0);
                    TG(stage * 32 + 19 + p * 2);
#pragma unroll
                    for (int u = 0; u < 8; u++)
                        st128(dst + (p * 8 + u) * 32, (pack_bf16(d[8 * u], d[8 * u + 1]) & ~1u) | ptag,
                              pack_bf16(d[8 * u + 2], d[8 * u + 3]), pack_bf16(d[8 * u + 4], d[8 * u + 5]),
                              pack_bf16(d[8 * u + 6], d[8 * u + 7]));
                    if (p == 0 && wg == 0) bar_arrive(7, 160);
                }
                float e[32];
                TG(stage * 32 + 26);
                gemm_n64(e, a, cx, ring, stage != 0);
                TG(stage * 32 + 27);
                uint2* dst2 = reinterpret_cast<uint2*>(dst - lane + 32 * 32) + lane;
#pragma unroll
                for (int j = 0; j < 8; j++)
                    st64(dst2 + j * 32, (pack_bf16(e[4 * j], e[4 * j + 1]) & ~1u) | ptag, pack_bf16(e[4 * j + 2], e[4 * j + 3]));
            }
            PROF(stage == 0 ? 7 : 14);
            if (stage == 1) {
                PROFG(26);
                asm volatile("barrier.cluster.arrive.relaxed.aligned;" ::: "memory");
            }
        }
        if (wg == 0) bar_sync(8, 256);
        bar_sync(3, 256);
        if (warp == 0) {
            rows_store(sbase, maps.out + (size_t)own * 16 * DM, lane);
            if (b == 0 && lane == 0) sc_->epoch = epoch + 1;
            rows_store_wait();
        }
        PROF(16);
        PROFG(31);
        asm volatile("barrier.cluster.wait.aligned;" ::: "memory");
    }
}

typedef CUresult (*EncodeFn)(CUtensorMap*, CUtensorMapDataType, cuuint32_t, void*, const cuuint64_t*, const cuuint64_t*,
                             const cuuint32_t*, const cuuint32_t*, CUtensorMapInterleave, CUtensorMapSwizzle,
                             CUtensorMapL2promotion, CUtensorMapFloatOOBfill);

void make_map(EncodeFn enc, CUtensorMap* m, const void* ptr, uint64_t rows, uint64_t cols, bool narrow = false) {
    cuuint64_t gdim[2] = {cols, rows};
    cuuint64_t gstr[1] = {cols * 2};
    cuuint32_t box[2] = {narrow ? 16u : 64u, narrow ? 192u : 64u};
    cuuint32_t estr[2] = {1, 1};
    enc(m, CU_TENSOR_MAP_DATA_TYPE_BFLOAT16, 2, const_cast<void*>(ptr), gdim, gstr, box, estr,
        CU_TENSOR_MAP_INTERLEAVE_NONE, narrow ? CU_TENSOR_MAP_SWIZZLE_NONE : CU_TENSOR_MAP_SWIZZLE_128B,
        CU_TENSOR_MAP_L2_PROMOTION_L2_128B,
        CU_TENSOR_MAP_FLOAT_OOB_FILL_NONE);
}

}

extern "C" void kernel_launch(void* const* d_in, const int* in_sizes, int n_in, void* d_out, int out_size) {
    (void)in_sizes;
    (void)n_in;
    (void)out_size;
    void* fn = nullptr;
    cudaDriverEntryPointQueryResult qr;
    cudaGetDriverEntryPoint("cuTensorMapEncodeTiled", &fn, cudaEnableDefault, &qr);
    EncodeFn enc = (EncodeFn)fn;
    Params maps;
    maps.x = (const __nv_bfloat16*)d_in[0];
    maps.cvec = (const __nv_bfloat16*)d_in[9];
    maps.wmod = (const __nv_bfloat16*)d_in[10];
    maps.kc = (const __nv_bfloat16*)d_in[1];
    maps.vc = (const __nv_bfloat16*)d_in[2];
    maps.wq_p = (const __nv_bfloat16*)d_in[3];
    maps.wo_p = (const __nv_bfloat16*)d_in[4];
    maps.wg_p = (const __nv_bfloat16*)d_in[6];
    maps.wu_p = (const __nv_bfloat16*)d_in[7];
    maps.wd_p = (const __nv_bfloat16*)d_in[8];
    maps.out = (__nv_bfloat16*)d_out;
    void* scp = nullptr;
    cudaGetSymbolAddress(&scp, g_scratch);
    maps.sc = (Scratch*)scp;
    make_map(enc, &maps.k, d_in[1], 32 * 2048, 128);
    make_map(enc, &maps.v, d_in[2], 32 * 2048, 128);
    make_map(enc, &maps.wq, d_in[3], 576, 4096);
    make_map(enc, &maps.wo, d_in[4], 4096, 576);
    make_map(enc, &maps.wg, d_in[6], 576, 4608);
    make_map(enc, &maps.wu, d_in[7], 576, 4608);
    make_map(enc, &maps.wd, d_in[8], 4608, 576);
    make_map(enc, &maps.wm, d_in[10], 576, 3456, true);
    cudaFuncSetAttribute(fused_block_kernel, cudaFuncAttributeMaxDynamicSharedMemorySize, SMEM_BYTES);
    fused_block_kernel<<<128, 384, SMEM_BYTES>>>(maps);
}
```

```cpp
#include <cuda_runtime.h>
#include <cuda_bf16.h>
#include <cuda.h>
#include <stdint.h>
#include <stddef.h>

namespace {

constexpr int DM = 576;
constexpr int SLOT_BYTES = 16384;
constexpr int BOX_BYTES = 8192;
constexpr int NUNITS = 14;
constexpr int SMEM_TAIL = NUNITS * SLOT_BYTES;
constexpr int SMEM_BYTES = SMEM_TAIL + 2048 + 1024;
constexpr int OFF_FULL = SMEM_TAIL;
constexpr int OFF_EMPTY = SMEM_TAIL + 64;
constexpr int OFF_RED = SMEM_TAIL + 128;

constexpr int KV_AHEAD = 16;
#define GATE_SLOT 4
constexpr int OFF_XBAR = SMEM_TAIL + 1792;
constexpr int OFF_ROWS = 8 * SLOT_BYTES;
constexpr int OFF_MODT = OFF_ROWS + 20480;
constexpr int OFF_WBLK = OFF_ROWS + 28672;
constexpr int OFF_WBAR = SMEM_TAIL + 1800;

struct Scratch {
    unsigned epoch;
    unsigned pad[31];
    uint32_t mod[6 * DM];
    uint4 h[2][2][128 * 36 * 32];
    uint4 part[128 * 8 * 36 * 32];
    uint4 hh[128 * 8 * 256];
    __nv_bfloat16 x2[2048 * DM];
};
__device__ Scratch g_scratch;

#define TG(i)
#define TL(i)
#define PROFR(i)
#define PROF(i)
#define PROFG(i)

struct Params {
    const __nv_bfloat16 *x, *cvec, *wmod, *kc, *vc, *wq_p, *wo_p, *wg_p, *wu_p, *wd_p;
    __nv_bfloat16* out;
    Scratch* sc;
    CUtensorMap k, v, wq, wo, wg, wu, wd, wm, rx, rx2, rout;
};

__device__ __forceinline__ uint32_t smem_u32(const void* p) { return (uint32_t)__cvta_generic_to_shared(p); }
__device__ __forceinline__ void mbar_init(uint32_t a, uint32_t c) {
    asm volatile("mbarrier.init.shared::cta.b64 [%0], %1;" ::"r"(a), "r"(c) : "memory");
}
__device__ __forceinline__ void mbar_expect_tx(uint32_t a, uint32_t bytes) {
    asm volatile("mbarrier.arrive.expect_tx.shared::cta.b64 _, [%0], %1;" ::"r"(a), "r"(bytes) : "memory");
}
__device__ __forceinline__ bool mbar_try(uint32_t a, uint32_t ph) {
    uint32_t ok;
    asm volatile(
        "{\n.reg .pred p;\nmbarrier.try_wait.parity.shared::cta.b64 p, [%1], %2;\nselp.u32 %0, 1, 0, p;\n}"
        : "=r"(ok)
        : "r"(a), "r"(ph)
        : "memory");
    return ok != 0;
}
__device__ __forceinline__ uint32_t clk32() {
    uint32_t c;
    asm volatile("mov.u32 %0, %%clock;" : "=r"(c));
    return c;
}
constexpr uint32_t WAIT_LIMIT = 1u << 30;
__device__ __forceinline__ void mbar_wait(uint32_t a, uint32_t ph) {
    if (mbar_try(a, ph)) return;
    uint32_t t0 = clk32();
    while (!mbar_try(a, ph)) {
        if (clk32() - t0 > WAIT_LIMIT) break;
    }
}
__device__ __forceinline__ void mbar_arrive_cluster(uint32_t a, uint32_t cta) {
    asm volatile(
        "{\n.reg .b32 ra;\nmapa.shared::cluster.u32 ra, %0, %1;\nmbarrier.arrive.shared::cluster.b64 _, [ra];\n}" ::"r"(a),
        "r"(cta)
        : "memory");
}
__device__ __forceinline__ void tma_mc(uint32_t dst, const CUtensorMap* m, int c0, int c1, uint32_t bar) {
    asm volatile(
        "cp.async.bulk.tensor.2d.shared::cluster.global.mbarrier::complete_tx::bytes.multicast::cluster"
        " [%0], [%1, {%3, %4}], [%2], %5;" ::"r"(dst),
        "l"(m), "r"(bar), "r"(c0), "r"(c1), "h"((uint16_t)3)
        : "memory");
}
__device__ __forceinline__ void l2_prefetch(const void* p, uint32_t bytes) {
    asm volatile("cp.async.bulk.prefetch.L2.global [%0], %1;" ::"l"(p), "r"(bytes) : "memory");
}
__device__ __forceinline__ void bar_sync(int id, int n) { asm volatile("bar.sync %0, %1;" ::"r"(id), "r"(n) : "memory"); }
__device__ __forceinline__ void bar_arrive(int id, int n) {
    asm volatile("bar.arrive %0, %1;" ::"r"(id), "r"(n) : "memory");
}
__device__ __forceinline__ void wg_fence() { asm volatile("wgmma.fence.sync.aligned;" ::: "memory"); }
__device__ __forceinline__ void wg_commit() { asm volatile("wgmma.commit_group.sync.aligned;" ::: "memory"); }
template <int N>
__device__ __forceinline__ void wg_wait() {
    asm volatile("wgmma.wait_group.sync.aligned %0;" ::"n"(N) : "memory");
}
template <int N>
__device__ __forceinline__ void pin(float (&d)[N]) {
#pragma unroll
    for (int i = 0; i < N; i++) asm volatile("" : "+f"(d[i])::"memory");
}
template <int N>
__device__ __forceinline__ void pin(uint32_t (&d)[N]) {
#pragma unroll
    for (int i = 0; i < N; i++) asm volatile("" : "+r"(d[i])::"memory");
}
__device__ __forceinline__ uint32_t pack_bf16(float lo, float hi) {
    uint32_t r;
    asm("cvt.rn.bf16x2.f32 %0, %1, %2;" : "=r"(r) : "f"(hi), "f"(lo));
    return r;
}
__device__ __forceinline__ float bf_lo(uint32_t v) { return __uint_as_float(v << 16); }
__device__ __forceinline__ float bf_hi(uint32_t v) { return __uint_as_float(v & 0xffff0000u); }
__device__ __forceinline__ float round_bf16(float v) { return __bfloat162float(__float2bfloat16_rn(v)); }
__device__ __forceinline__ float ex2(float x) {
    float y;
    asm("ex2.approx.ftz.f32 %0, %1;" : "=f"(y) : "f"(x));
    return y;
}
__device__ __forceinline__ float rcp(float x) {
    float y;
    asm("rcp.approx.ftz.f32 %0, %1;" : "=f"(y) : "f"(x));
    return y;
}
__device__ __forceinline__ float tanh_fast(float x) {
    float y;
    asm("tanh.approx.f32 %0, %1;" : "=f"(y) : "f"(x));
    return y;
}
__device__ __forceinline__ void sts128(uint32_t a, uint32_t x, uint32_t y, uint32_t z, uint32_t w) {
    asm volatile("st.shared.v4.b32 [%0], {%1,%2,%3,%4};" ::"r"(a), "r"(x), "r"(y), "r"(z), "r"(w) : "memory");
}
__device__ __forceinline__ void lds128(uint32_t a, uint32_t& x, uint32_t& y, uint32_t& z, uint32_t& w) {
    asm volatile("ld.shared.v4.b32 {%0,%1,%2,%3}, [%4];" : "=r"(x), "=r"(y), "=r"(z), "=r"(w) : "r"(a) : "memory");
}
__device__ __forceinline__ void sts32f(uint32_t a, float v) {
    asm volatile("st.shared.f32 [%0], %1;" ::"r"(a), "f"(v) : "memory");
}
__device__ __forceinline__ float lds32f(uint32_t a) {
    float v;
    asm volatile("ld.shared.f32 %0, [%1];" : "=f"(v) : "r"(a) : "memory");
    return v;
}
#define F8(d, b) \
    "+f"(d[b]), "+f"(d[b + 1]), "+f"(d[b + 2]), "+f"(d[b + 3]), "+f"(d[b + 4]), "+f"(d[b + 5]), "+f"(d[b + 6]), "+f"(d[b + 7])

template <int TB>
__device__ __forceinline__ void wgmma_n128(float (&d)[64], uint32_t a0, uint32_t a1, uint32_t a2, uint32_t a3,
                                           uint64_t db, int sc) {
    asm volatile(
        "{\n.reg .pred p;\nsetp.ne.b32 p, %69, 0;\n"
        "wgmma.mma_async.sync.aligned.m64n128k16.f32.bf16.bf16 "
        "{%0,%1,%2,%3,%4,%5,%6,%7,%8,%9,%10,%11,%12,%13,%14,%15,%16,%17,%18,%19,%20,%21,%22,%23,%24,%25,%26,%27,%28,%29,%30,%31,"
        "%32,%33,%34,%35,%36,%37,%38,%39,%40,%41,%42,%43,%44,%45,%46,%47,%48,%49,%50,%51,%52,%53,%54,%55,%56,%57,%58,%59,%60,%61,%62,%63},"
        "{%64,%65,%66,%67}, %68, p, 1, 1, %70;\n}"
        : F8(d, 0), F8(d, 8), F8(d, 16), F8(d, 24), F8(d, 32), F8(d, 40), F8(d, 48), F8(d, 56)
        : "r"(a0), "r"(a1), "r"(a2), "r"(a3), "l"(db), "r"(sc), "n"(TB));
}
#define O8(d, b) \
    "=f"(d[b]), "=f"(d[b + 1]), "=f"(d[b + 2]), "=f"(d[b + 3]), "=f"(d[b + 4]), "=f"(d[b + 5]), "=f"(d[b + 6]), "=f"(d[b + 7])
template <int TB>
__device__ __forceinline__ void wgmma_n128_z(float (&d)[64], uint32_t a0, uint32_t a1, uint32_t a2, uint32_t a3,
                                             uint64_t db) {
    asm volatile(
        "wgmma.mma_async.sync.aligned.m64n128k16.f32.bf16.bf16 "
        "{%0,%1,%2,%3,%4,%5,%6,%7,%8,%9,%10,%11,%12,%13,%14,%15,%16,%17,%18,%19,%20,%21,%22,%23,%24,%25,%26,%27,%28,%29,%30,%31,"
        "%32,%33,%34,%35,%36,%37,%38,%39,%40,%41,%42,%43,%44,%45,%46,%47,%48,%49,%50,%51,%52,%53,%54,%55,%56,%57,%58,%59,%60,%61,%62,%63},"
        "{%64,%65,%66,%67}, %68, 0, 1, 1, %69;"
        : O8(d, 0), O8(d, 8), O8(d, 16), O8(d, 24), O8(d, 32), O8(d, 40), O8(d, 48), O8(d, 56)
        : "r"(a0), "r"(a1), "r"(a2), "r"(a3), "l"(db), "n"(TB));
}
template <int TB>
__device__ __forceinline__ void wgmma_n64_z(float (&d)[32], uint32_t a0, uint32_t a1, uint32_t a2, uint32_t a3,
                                            uint64_t db) {
    asm volatile(
        "wgmma.mma_async.sync.aligned.m64n64k16.f32.bf16.bf16 "
        "{%0,%1,%2,%3,%4,%5,%6,%7,%8,%9,%10,%11,%12,%13,%14,%15,%16,%17,%18,%19,%20,%21,%22,%23,%24,%25,%26,%27,%28,%29,%30,%31},"
        "{%32,%33,%34,%35}, %36, 0, 1, 1, %37;"
        : O8(d, 0), O8(d, 8), O8(d, 16), O8(d, 24)
        : "r"(a0), "r"(a1), "r"(a2), "r"(a3), "l"(db), "n"(TB));
}
template <int TB>
__device__ __forceinline__ void wgmma_n64(float (&d)[32], uint32_t a0, uint32_t a1, uint32_t a2, uint32_t a3,
                                          uint64_t db) {
    asm volatile(
        "wgmma.mma_async.sync.aligned.m64n64k16.f32.bf16.bf16 "
        "{%0,%1,%2,%3,%4,%5,%6,%7,%8,%9,%10,%11,%12,%13,%14,%15,%16,%17,%18,%19,%20,%21,%22,%23,%24,%25,%26,%27,%28,%29,%30,%31},"
        "{%32,%33,%34,%35}, %36, 1, 1, 1, %37;"
        : F8(d, 0), F8(d, 8), F8(d, 16), F8(d, 24)
        : "r"(a0), "r"(a1), "r"(a2), "r"(a3), "l"(db), "n"(TB));
}

__device__ __forceinline__ uint64_t desc_of(uint32_t saddr) {
    return (uint64_t)(((saddr >> 4) & 0x3FFFu) | (512u << 16)) | ((uint64_t)(64u | (1u << 30)) << 32);
}

struct Ring {
    uint32_t slot;
    uint32_t phase;
    __device__ __forceinline__ void next() {
        if (++slot == 8) {
            slot = 0;
            phase ^= 1;
        }
    }
};

struct Ctx {
    uint32_t sbase;
    int wg;
    uint32_t rel_cta;
    __device__ __forceinline__ void wait_full(uint32_t slot, uint32_t phase) const {
        mbar_wait(sbase + OFF_FULL + slot * 8, phase);
    }
    __device__ __forceinline__ void release(uint32_t slot) const {
        if (rel_cta < 2) mbar_arrive_cluster(sbase + OFF_EMPTY + slot * 8, rel_cta);
    }
};

__device__ __forceinline__ void gemm_n128(float (&d)[64], const uint32_t (&a)[144], const Ctx& c, Ring& r, bool nine) {
    uint32_t prev = 0;
#pragma unroll
    for (int s = 0; s < 9; s++) {
        if (s < 8 || nine) {
            if (s == GATE_SLOT) bar_sync(8 + c.wg, 256);
            c.wait_full(r.slot, r.phase);
            uint64_t db = desc_of(c.sbase + r.slot * SLOT_BYTES);
            wg_fence();
#pragma unroll
            for (int k = 0; k < 4; k++) {
                if ((s | k) == 0)
                    wgmma_n128_z<1>(d, a[0], a[1], a[2], a[3], db);
                else
                    wgmma_n128<1>(d, a[s * 16 + k * 4], a[s * 16 + k * 4 + 1], a[s * 16 + k * 4 + 2],
                                  a[s * 16 + k * 4 + 3], db + k * 128, 1);
            }
            wg_commit();
            if (s == 8 || (s == 7 && !nine)) bar_arrive(9 - c.wg, 256);
            if (s > 0) {
                wg_wait<1>();
                c.release(prev);
            }
            prev = r.slot;
            r.next();
        }
    }
    wg_wait<0>();
    c.release(prev);
    pin(d);
}
__device__ __forceinline__ void gemm_n64(float (&d)[32], const uint32_t (&a)[144], const Ctx& c, Ring& r, bool nine) {
    uint32_t prev = 0;
#pragma unroll
    for (int s = 0; s < 5; s++) {
        if (s < 4 || nine) {
            c.wait_full(r.slot, r.phase);
            uint64_t db = desc_of(c.sbase + r.slot * SLOT_BYTES);
            wg_fence();
#pragma unroll
            for (int k = 0; k < 8; k++) {
                if ((s | k) == 0)
                    wgmma_n64_z<1>(d, a[0], a[1], a[2], a[3], db);
                else if (s * 8 + k < 36)
                    wgmma_n64<1>(d, a[s * 32 + k * 4], a[s * 32 + k * 4 + 1], a[s * 32 + k * 4 + 2],
                                 a[s * 32 + k * 4 + 3], db + k * 128);
            }
            wg_commit();
            if (s > 0) {
                wg_wait<1>();
                c.release(prev);
            }
            prev = r.slot;
            r.next();
        }
    }
    wg_wait<0>();
    c.release(prev);
    pin(d);
}
__device__ __forceinline__ void st128(uint4* p, uint32_t x, uint32_t y, uint32_t z, uint32_t w) {
    asm volatile(
        "{\n.reg .b64 lo, hi;\n.reg .b128 t;\nmov.b64 lo, {%1, %2};\nmov.b64 hi, {%3, %4};\nmov.b128 t, {lo, hi};\n"
        "st.relaxed.gpu.global.b128 [%0], t;\n}" ::"l"(p),
        "r"(x), "r"(y), "r"(z), "r"(w)
        : "memory");
}
__device__ __forceinline__ uint4 ld128(const uint4* p) {
    uint4 r;
    asm volatile(
        "{\n.reg .b64 lo, hi;\n.reg .b128 t;\nld.relaxed.gpu.global.b128 t, [%4];\nmov.b128 {lo, hi}, t;\n"
        "mov.b64 {%0, %1}, lo;\nmov.b64 {%2, %3}, hi;\n}"
        : "=r"(r.x), "=r"(r.y), "=r"(r.z), "=r"(r.w)
        : "l"(p));
    return r;
}
__device__ __forceinline__ void st64(void* p, uint32_t x, uint32_t y) {
    asm volatile("{\n.reg .b64 t;\nmov.b64 t, {%1, %2};\nst.relaxed.gpu.global.b64 [%0], t;\n}" ::"l"(p), "r"(x), "r"(y)
                 : "memory");
}
__device__ __forceinline__ uint2 ld64(const void* p) {
    uint2 r;
    asm volatile("{\n.reg .b64 t;\nld.relaxed.gpu.global.b64 t, [%2];\nmov.b64 {%0, %1}, t;\n}"
                 : "=r"(r.x), "=r"(r.y)
                 : "l"(p));
    return r;
}
__device__ __forceinline__ void rows_load(uint32_t sbase, const CUtensorMap* m, int row0) {
    mbar_expect_tx(sbase + OFF_XBAR, 16 * DM * 2);
    asm volatile(
        "cp.async.bulk.tensor.3d.shared::cluster.global.mbarrier::complete_tx::bytes [%0], [%1, {%3, %3, %4}], [%2];" ::"r"(
            sbase + OFF_ROWS),
        "l"(m), "r"(sbase + OFF_XBAR), "r"(0), "r"(row0)
        : "memory");
}
__device__ __forceinline__ void rows_store(uint32_t sbase, const CUtensorMap* m, int row0) {
    asm volatile("cp.async.bulk.tensor.3d.global.shared::cta.bulk_group [%0, {%2, %2, %3}], [%1];" ::"l"(m),
                 "r"(sbase + OFF_ROWS), "r"(0), "r"(row0)
                 : "memory");
    asm volatile("cp.async.bulk.commit_group;" ::: "memory");
}
__device__ __forceinline__ void rows_store_wait() { asm volatile("cp.async.bulk.wait_group 0;" ::: "memory"); }

__device__ __forceinline__ constexpr int own_col(int j) { return j < 8 ? (j >> 1) * 128 + (j & 1) * 8 : 512; }
__device__ __forceinline__ void row_reduce(float& s0, float& s1, uint32_t red, int warp, int lane) {
    s0 += __shfl_xor_sync(0xffffffffu, s0, 1);
    s1 += __shfl_xor_sync(0xffffffffu, s1, 1);
    s0 += __shfl_xor_sync(0xffffffffu, s0, 2);
    s1 += __shfl_xor_sync(0xffffffffu, s1, 2);
    if ((lane & 3) == 0) {
        sts32f(red + (warp * 16 + (lane >> 2)) * 4, s0);
        sts32f(red + (warp * 16 + 8 + (lane >> 2)) * 4, s1);
    }
    bar_sync(3, 256);
    s0 = 0.f;
    s1 = 0.f;
#pragma unroll
    for (int w = 0; w < 8; w++) {
        s0 += lds32f(red + (w * 16 + (lane >> 2)) * 4);
        s1 += lds32f(red + (w * 16 + 8 + (lane >> 2)) * 4);
    }
}
__device__ __forceinline__ void layernorm_rows(float (&v)[36], uint32_t red, int warp, int lane) {
    float s0 = 0.f, s1 = 0.f;
#pragma unroll
    for (int j = 0; j < 9; j++) {
        s0 += v[4 * j] + v[4 * j + 1];
        s1 += v[4 * j + 2] + v[4 * j + 3];
    }
    row_reduce(s0, s1, red, warp, lane);
    const float m0 = s0 * (1.f / DM), m1 = s1 * (1.f / DM);
    s0 = 0.f;
    s1 = 0.f;
#pragma unroll
    for (int j = 0; j < 9; j++) {
        v[4 * j] -= m0;
        v[4 * j + 1] -= m0;
        v[4 * j + 2] -= m1;
        v[4 * j + 3] -= m1;
        s0 += v[4 * j] * v[4 * j] + v[4 * j + 1] * v[4 * j + 1];
        s1 += v[4 * j + 2] * v[4 * j + 2] + v[4 * j + 3] * v[4 * j + 3];
    }
    row_reduce(s0, s1, red + 512, warp, lane);
    const float r0 = rsqrtf(s0 * (1.f / DM) + 1e-5f), r1 = rsqrtf(s1 * (1.f / DM) + 1e-5f);
#pragma unroll
    for (int j = 0; j < 9; j++) {
        v[4 * j] *= r0;
        v[4 * j + 1] *= r0;
        v[4 * j + 2] *= r1;
        v[4 * j + 3] *= r1;
    }
}
__device__ __forceinline__ void mod_to_smem(uint32_t dst, const uint32_t* src, uint32_t tag) {
    const uint32_t t0 = clk32();
    uint4 u;
    while (true) {
        u = ld128(reinterpret_cast<const uint4*>(src));
        const uint32_t bad = ((u.x ^ tag) | (u.y ^ tag) | (u.z ^ tag) | (u.w ^ tag)) & 0xffffu;
        if (__all_sync(0xffffffffu, bad == 0) || clk32() - t0 > WAIT_LIMIT) break;
        __nanosleep(64);
    }
    sts128(dst, u.x & 0xffff0000u, u.y & 0xffff0000u, u.z & 0xffff0000u, u.w & 0xffff0000u);
}
__device__ __forceinline__ void lds_mod(float (&m)[18], uint32_t src  , int warp) {
#pragma unroll
    for (int j = 0; j < 9; j++)
        asm volatile("ld.shared.v2.f32 {%0,%1}, [%2];"
                     : "=f"(m[2 * j]), "=f"(m[2 * j + 1])
                     : "r"(src + own_col(j) * 4 - (j == 8 ? warp * 32 : 0))
                     : "memory");
}
__device__ __forceinline__ void modulate_store(const float (&v)[36], const float (&shift)[18], const float (&scale)[18],
                                               uint4* hbuf  , int warp, int lane) {
    uint32_t o[18];
#pragma unroll
    for (int j = 0; j < 9; j++) {
        const uint32_t cc = pack_bf16(1.f + scale[2 * j], 1.f + scale[2 * j + 1]);
        const float c0 = bf_lo(cc), c1 = bf_hi(cc);
        o[2 * j] = max(pack_bf16(fmaf(v[4 * j], c0, shift[2 * j]), fmaf(v[4 * j + 1], c1, shift[2 * j + 1])), 1u);
        o[2 * j + 1] = max(pack_bf16(fmaf(v[4 * j + 2], c0, shift[2 * j]), fmaf(v[4 * j + 3], c1, shift[2 * j + 1])), 1u);
    }
#pragma unroll
    for (int i = 0; i < 4; i++) st128(hbuf + (i * 8 + warp) * 32 + lane, o[4 * i], o[4 * i + 1], o[4 * i + 2], o[4 * i + 3]);
    st64(reinterpret_cast<uint2*>(hbuf + 32 * 32) + warp * 32 + lane, o[16], o[17]);
}
__device__ __forceinline__ void sum_partials(float (&v)[36], const uint4* src  , uint32_t tag) {
    const uint32_t t0 = clk32();
    while (true) {
        uint4 t[8][4];
#pragma unroll
        for (int s = 0; s < 8; s++)
#pragma unroll
            for (int i = 0; i < 4; i++) t[s][i] = ld128(src + (s * 36 + i * 8) * 32);
        uint32_t bad = 0;
#pragma unroll
        for (int i = 0; i < 32; i++) v[i] = 0.f;
#pragma unroll
        for (int s = 0; s < 8; s++)
#pragma unroll
            for (int i = 0; i < 4; i++) {
                bad |= t[s][i].x ^ tag;
                v[8 * i] += bf_lo(t[s][i].x);
                v[8 * i + 1] += bf_hi(t[s][i].x);
                v[8 * i + 2] += bf_lo(t[s][i].y);
                v[8 * i + 3] += bf_hi(t[s][i].y);
                v[8 * i + 4] += bf_lo(t[s][i].z);
                v[8 * i + 5] += bf_hi(t[s][i].z);
                v[8 * i + 6] += bf_lo(t[s][i].w);
                v[8 * i + 7] += bf_hi(t[s][i].w);
            }
        if (__all_sync(0xffffffffu, (bad & 1u) == 0) || clk32() - t0 > WAIT_LIMIT) break;
    }
}
__device__ __forceinline__ void sum_tail(float (&v)[36], const uint2* src  , uint32_t tag) {
    const uint32_t t0 = clk32();
    while (true) {
        uint2 t[8];
#pragma unroll
        for (int s = 0; s < 8; s++) t[s] = ld64(src + s * 72 * 32);
        uint32_t bad = 0;
        v[32] = v[33] = v[34] = v[35] = 0.f;
#pragma unroll
        for (int s = 0; s < 8; s++) {
            bad |= t[s].x ^ tag;
            v[32] += bf_lo(t[s].x);
            v[33] += bf_hi(t[s].x);
            v[34] += bf_lo(t[s].y);
            v[35] += bf_hi(t[s].y);
        }
        if (__all_sync(0xffffffffu, (bad & 1u) == 0) || clk32() - t0 > WAIT_LIMIT) break;
    }
}
__device__ __forceinline__ void poll_tail(uint32_t (&a)[144], const uint2* src  ) {
    const uint32_t t0 = clk32();
    while (true) {
        uint32_t m = 0xffffffffu;
#pragma unroll
        for (int j = 0; j < 8; j++) {
            const uint2 t = ld64(src + j * 32);
            a[128 + 2 * j] = t.x;
            a[129 + 2 * j] = t.y;
        }
#pragma unroll
        for (int j = 0; j < 16; j++) m = min(m, a[128 + j]);
        if (__all_sync(0xffffffffu, m != 0) || clk32() - t0 > WAIT_LIMIT) break;
    }
}
template <int K0, int K1>
__device__ __forceinline__ void poll_frags(uint32_t (&a)[144], const uint4* src  , bool kick) {
    const uint32_t t0 = clk32();
    while (true) {
#pragma unroll
        for (int k = K0; k < K1; k++)
            asm volatile("ld.relaxed.gpu.global.v4.u32 {%0,%1,%2,%3}, [%4];"
                         : "=r"(a[4 * k]), "=r"(a[4 * k + 1]), "=r"(a[4 * k + 2]), "=r"(a[4 * k + 3])
                         : "l"(src + k * 32));
        if (kick) bar_arrive(5, 256);
        kick = false;
        uint32_t m0 = a[4 * K0], m1 = a[4 * K0 + 1];
#pragma unroll
        for (int i = 4 * K0 + 2; i < 4 * K1; i += 2) {
            m0 = min(m0, a[i]);
            m1 = min(m1, a[i + 1]);
        }
        if (__all_sync(0xffffffffu, min(m0, m1) != 0) || clk32() - t0 > WAIT_LIMIT) break;
    }
}

constexpr float SM_SCALE = 0.08838834764831845f * 1.4426950408889634f;
constexpr float SM_HI = 1.2089258e24f;
constexpr float SM_LO = 9.0949470e-13f;
__device__ __forceinline__ void qk_step(float (&s)[32], const uint32_t (&q)[32], uint64_t dk) {
#pragma unroll
    for (int k = 0; k < 8; k++) {
        if (k == 0)
            wgmma_n64_z<0>(s, q[0], q[1], q[2], q[3], dk);
        else
            wgmma_n64<0>(s, q[4 * k], q[4 * k + 1], q[4 * k + 2], q[4 * k + 3], dk + (k >> 2) * 512 + (k & 3) * 2);
    }
}
__device__ __forceinline__ void pv_step(float (&o)[64], const uint32_t (&p)[16], uint64_t dv, int acc) {
#pragma unroll
    for (int k = 0; k < 4; k++)
        wgmma_n128<1>(o, p[4 * k], p[4 * k + 1], p[4 * k + 2], p[4 * k + 3], dv + k * 128, k != 0 ? 1 : acc);
}
template <bool SHIFT>
__device__ __forceinline__ void exp_step(const float (&s)[32], uint32_t (&p)[16], float n0, float n1, float& s0,
                                         float& s1) {
#pragma unroll
    for (int i = 0; i < 8; i++) {
        const float e0 = ex2(SHIFT ? s[4 * i] + n0 : s[4 * i]), e1 = ex2(SHIFT ? s[4 * i + 1] + n0 : s[4 * i + 1]);
        const float e2 = ex2(SHIFT ? s[4 * i + 2] + n1 : s[4 * i + 2]), e3 = ex2(SHIFT ? s[4 * i + 3] + n1 : s[4 * i + 3]);
        if (i == 0) {
            s0 = e0 + e1;
            s1 = e2 + e3;
        } else {
            s0 += e0 + e1;
            s1 += e2 + e3;
        }
        p[2 * i] = pack_bf16(e0, e1);
        p[2 * i + 1] = pack_bf16(e2, e3);
    }
}
__device__ __forceinline__ void row_max(const float (&sa)[32], const float (&sb)[32], float& x0, float& x1) {
    float xa[8];
#pragma unroll
    for (int i = 0; i < 8; i++) xa[i] = fmaxf(sa[i], sb[i]);
#pragma unroll
    for (int k = 1; k < 4; k++)
#pragma unroll
        for (int i = 0; i < 8; i++) xa[i] = fmaxf(xa[i], fmaxf(sa[8 * k + i], sb[8 * k + i]));
    x0 = fmaxf(fmaxf(xa[0], xa[1]), fmaxf(xa[4], xa[5]));
    x1 = fmaxf(fmaxf(xa[2], xa[3]), fmaxf(xa[6], xa[7]));
    x0 = fmaxf(x0, __shfl_xor_sync(0xffffffffu, x0, 1));
    x1 = fmaxf(x1, __shfl_xor_sync(0xffffffffu, x1, 1));
    x0 = fmaxf(x0, __shfl_xor_sync(0xffffffffu, x0, 2));
    x1 = fmaxf(x1, __shfl_xor_sync(0xffffffffu, x1, 2));
}
__device__ __forceinline__ void inv_row_sums(float l0, float l1, float& i0, float& i1) {
    l0 += __shfl_xor_sync(0xffffffffu, l0, 1);
    l1 += __shfl_xor_sync(0xffffffffu, l1, 1);
    l0 += __shfl_xor_sync(0xffffffffu, l0, 2);
    l1 += __shfl_xor_sync(0xffffffffu, l1, 2);
    i0 = rcp(l0);
    i1 = rcp(l1);
}

__device__ __forceinline__ uint32_t ld_epoch(const Scratch* sc) {
    uint32_t e;
    asm volatile("ld.relaxed.gpu.global.u32 %0, [%1];" : "=r"(e) : "l"(&sc->epoch) : "memory");
    return e;
}
__device__ __forceinline__ float silu_bf16(unsigned short c) {
    const float cv = bf_lo(c);
    return round_bf16(cv * rcp(1.f + ex2(-1.4426950408889634f * cv)));
}
__device__ __forceinline__ void st_mod(uint32_t* p, float v, uint32_t tag) {
    asm volatile("st.relaxed.gpu.global.u32 [%0], %1;" ::"l"(p), "r"(__float_as_uint(round_bf16(v)) | tag)
                 : "memory");
}
__device__ __forceinline__ void mod_block(const uint4 (&w)[5], const float (&sc)[5], uint32_t* dst, uint32_t red,
                                          int warp, int lane, uint32_t tag) {
    float acc[8];
#pragma unroll
    for (int e = 0; e < 8; e++) acc[e] = 0.f;
#pragma unroll
    for (int i = 0; i < 5; i++) {
        acc[0] = fmaf(sc[i], bf_lo(w[i].x), acc[0]);
        acc[1] = fmaf(sc[i], bf_hi(w[i].x), acc[1]);
        acc[2] = fmaf(sc[i], bf_lo(w[i].y), acc[2]);
        acc[3] = fmaf(sc[i], bf_hi(w[i].y), acc[3]);
        acc[4] = fmaf(sc[i], bf_lo(w[i].z), acc[4]);
        acc[5] = fmaf(sc[i], bf_hi(w[i].z), acc[5]);
        acc[6] = fmaf(sc[i], bf_lo(w[i].w), acc[6]);
        acc[7] = fmaf(sc[i], bf_hi(w[i].w), acc[7]);
    }
#pragma unroll
    for (int o = 2; o < 32; o <<= 1)
#pragma unroll
        for (int e = 0; e < 8; e++) acc[e] += __shfl_xor_sync(0xffffffffu, acc[e], o);
    if (lane < 2) {
#pragma unroll
        for (int e = 0; e < 8; e++) sts32f(red + (warp * 16 + lane * 8 + e) * 4, acc[e]);
    }
    bar_sync(3, 256);
    if (warp == 0 && lane < 16) {
        float s = 0.f;
#pragma unroll
        for (int w8 = 0; w8 < 8; w8++) s += lds32f(red + (w8 * 16 + lane) * 4);
        st_mod(dst + lane, s, tag);
    }
}

__global__ void __cluster_dims__(2, 1, 1) __launch_bounds__(384, 1)
    fused_block_kernel(const __grid_constant__ Params maps) {
    extern __shared__ uint8_t smem_raw[];
    uint32_t sbase = (smem_u32(smem_raw) + 1023u) & ~1023u;
    asm volatile("" : "+r"(sbase));
    const int b = blockIdx.x;
    const int rank = b & 1;
    const int mt = ((b >> 1) & 7) * 2 + rank;
    const int g = b >> 4;
    const int warp = __shfl_sync(0xffffffffu, threadIdx.x >> 5, 0);
    const int lane = threadIdx.x & 31;
    Scratch* const sc_ = maps.sc;
    const __nv_bfloat16* const wmod = maps.wmod;
    const __nv_bfloat16* const cvec = maps.cvec;

    if (threadIdx.x == 0) {
        mbar_init(sbase + OFF_WBAR, 1);
        asm volatile("fence.mbarrier_init.release.cluster;" ::: "memory");
        if (b < 72) {
            mbar_expect_tx(sbase + OFF_WBAR, DM * 32);
#pragma unroll
            for (int i = 0; i < 3; i++)
                asm volatile(
                    "cp.async.bulk.tensor.2d.shared::cluster.global.mbarrier::complete_tx::bytes"
                    " [%0], [%1, {%3, %4}], [%2];" ::"r"(sbase + OFF_WBLK + i * 192 * 32),
                    "l"(&maps.wm), "r"(sbase + OFF_WBAR), "r"(b * 16), "r"(i * 192)
                    : "memory");
        }
    } else if (threadIdx.x == 32) {
        mbar_init(sbase + OFF_XBAR, 1);
        asm volatile("fence.mbarrier_init.release.cluster;" ::: "memory");
        rows_load(sbase, &maps.rx, (mt * 8 + g) * 16);
    } else if (threadIdx.x >= 64 && threadIdx.x < 64 + 81) {
        const int li = b * 81 + threadIdx.x - 64;
        asm volatile("prefetch.global.L2 [%0];" ::"l"((const char*)wmod + (size_t)(li / 18) * (12 * DM) + (li % 18) * 128));
    }
    __syncwarp();
    unsigned short cu[5];
#pragma unroll
    for (int i = 0; i < 5; i++)
        cu[i] = __ldg(reinterpret_cast<const unsigned short*>(cvec) + min((int)(threadIdx.x >> 1) + 128 * i, DM - 1));
    const uint32_t epoch = ld_epoch(sc_);

    if (warp >= 8) {
        asm volatile("setmaxnreg.dec.sync.aligned.u32 24;");
        if (warp == 8 && lane == 0) {
#pragma unroll
            for (int i = 0; i < 8; i++) {
                mbar_init(sbase + OFF_FULL + i * 8, 1);
                mbar_init(sbase + OFF_EMPTY + i * 8, 4);
            }
            asm volatile("fence.mbarrier_init.release.cluster;" ::: "memory");
            asm volatile("barrier.cluster.arrive.relaxed;\nbarrier.cluster.wait;" ::: "memory");
            uint32_t slot = 0, phase = 1;
            const uint32_t dst0 = sbase + rank * BOX_BYTES;
            auto acquire = [&](uint32_t bytes) {
                mbar_wait(sbase + OFF_EMPTY + slot * 8, phase);
                mbar_expect_tx(sbase + OFF_FULL + slot * 8, bytes);
            };
            auto adv8 = [&]() {
                if (++slot == 8) {
                    slot = 0;
                    phase ^= 1;
                }
            };
#pragma unroll 1
            for (int hq = 0; hq < 4; hq++) {
                const int col = (g * 4 + ((hq + 1) & 3)) * 128 + rank * 64;
                if (hq == 2) {
                    l2_prefetch(maps.kc + (size_t)(g * 4 * 2048 + (b & 15) * 64) * 128, SLOT_BYTES);
                    l2_prefetch(maps.vc + (size_t)(g * 4 * 2048 + (b & 15) * 64) * 128, SLOT_BYTES);
                }
#pragma unroll 1
                for (int kc = 0; kc < 9; kc++) {
                    acquire(SLOT_BYTES);
                    tma_mc(dst0 + slot * SLOT_BYTES, &maps.wq, col, kc * 64, sbase + OFF_FULL + slot * 8);
                    adv8();
                }
            }
            const int row0 = g * 4 * 2048;
#pragma unroll 1
            for (int n = 0; n < 128; n++) {
                if (n < 4) mbar_wait(sbase + OFF_EMPTY + (slot + 1) * 8, phase);
                acquire(2 * SLOT_BYTES);
                const uint32_t bar = sbase + OFF_FULL + slot * 8;
                const int r0 = n == 0 ? 0 : (n == 127 ? 126 : n + 1);
                const int r1 = n == 0 ? 1 : (n == 127 ? 127 : n - 1);
                tma_mc(dst0 + slot * SLOT_BYTES, n == 127 ? &maps.v : &maps.k, rank * 64, row0 + r0 * 64, bar);
                tma_mc(dst0 + (slot + 1) * SLOT_BYTES, n == 0 ? &maps.k : &maps.v, rank * 64, row0 + r1 * 64, bar);
                adv8();
                adv8();
                if (n >= 96 && n < 96 + 10) {
                    const int i = n - 96;
                    if (i < 9) {
                        l2_prefetch((const char*)maps.wg_p + (size_t)b * 41472 + i * 4608, 4608);
                        l2_prefetch((const char*)maps.wu_p + (size_t)b * 41472 + i * 4608, 4608);
                        l2_prefetch((const char*)maps.wd_p + (size_t)b * 41472 + i * 4608, 4608);
                        l2_prefetch((const char*)maps.wo_p + (size_t)b * 36864 + i * 4096, 4096);
                    }
                }
                const int u = n + KV_AHEAD;
                if (u < 128 && (u & 15) == (b & 15)) {
                    l2_prefetch(maps.kc + (size_t)(row0 + u * 64) * 128, SLOT_BYTES);
                    l2_prefetch(maps.vc + (size_t)(row0 + u * 64) * 128, SLOT_BYTES);
                }
            }
#pragma unroll 1
            for (int p = 0; p < 4; p++)
#pragma unroll 1
                for (int kc = 0; kc < 8; kc++) {
                    acquire(SLOT_BYTES);
                    tma_mc(dst0 + slot * SLOT_BYTES, &maps.wo, p * 128 + rank * 64, g * 512 + kc * 64,
                           sbase + OFF_FULL + slot * 8);
                    adv8();
                }
#pragma unroll 1
            for (int kc = 0; kc < 4; kc++) {
                acquire(SLOT_BYTES);
                tma_mc(dst0 + slot * SLOT_BYTES, &maps.wo, 512, g * 512 + kc * 128 + rank * 64,
                       sbase + OFF_FULL + slot * 8);
                adv8();
            }
            const CUtensorMap* mg = rank ? &maps.wu : &maps.wg;
#pragma unroll 1
            for (int ch = 0; ch < 9; ch++)
#pragma unroll 1
                for (int kc = 0; kc < 9; kc++) {
                    acquire(SLOT_BYTES);
                    tma_mc(dst0 + slot * SLOT_BYTES, mg, g * 576 + ch * 64, kc * 64, sbase + OFF_FULL + slot * 8);
                    adv8();
                }
#pragma unroll 1
            for (int p = 0; p < 4; p++)
#pragma unroll 1
                for (int kc = 2; kc < 11; kc++) {
                    acquire(SLOT_BYTES);
                    tma_mc(dst0 + slot * SLOT_BYTES, &maps.wd, p * 128 + rank * 64, g * 576 + (kc < 9 ? kc : kc - 9) * 64,
                           sbase + OFF_FULL + slot * 8);
                    adv8();
                }
#pragma unroll 1
            for (int i = 0; i < 5; i++) {
                acquire(i < 4 ? SLOT_BYTES : BOX_BYTES);
                const int kc = 2 * i + rank + 2;
                if (i < 4 || rank == 0)
                    tma_mc(dst0 + slot * SLOT_BYTES, &maps.wd, 512, g * 576 + (kc < 9 ? kc : kc - 9) * 64,
                           sbase + OFF_FULL + slot * 8);
                adv8();
            }
        } else if (warp == 11) {
            asm volatile("barrier.cluster.arrive.relaxed.aligned;" ::: "memory");
            uint4* hz = sc_->h[(epoch & 1) ^ 1][0] + (size_t)b * 72 * 32 + lane;
            bar_sync(6, 160);
#pragma unroll 1
            for (int i = 0; i < 72; i++) {
                hz[i * 32] = make_uint4(0, 0, 0, 0);
                __nanosleep(200);
            }
        } else if (warp == 9 || warp == 10) {
            asm volatile("barrier.cluster.arrive.relaxed.aligned;" ::: "memory");
            const uint32_t tag = (epoch + 1) & 0xffffu;
            bar_sync(4, 320);
            if (warp == 10 && lane < 9) l2_prefetch((const char*)maps.wq_p + (size_t)b * 36864 + lane * 4096, 4096);
            const int blk = warp == 9 ? 72 + b : 200 + b;
            if (blk < 216) {
                float acc[8];
#pragma unroll
                for (int e = 0; e < 8; e++) acc[e] = 0.f;
                const uint4* wp = reinterpret_cast<const uint4*>(wmod + (size_t)(lane >> 1) * (6 * DM) + blk * 16) + (lane & 1);
                const unsigned short* cp = reinterpret_cast<const unsigned short*>(cvec) + (lane >> 1);
#pragma unroll 1
                for (int i = 0; i < 36; i++) {
                    const uint4 w = __ldg(wp + (size_t)i * (16 * 6 * DM / 8));
                    const float sc = silu_bf16(__ldg(cp + i * 16));
                    acc[0] = fmaf(sc, bf_lo(w.x), acc[0]);
                    acc[1] = fmaf(sc, bf_hi(w.x), acc[1]);
                    acc[2] = fmaf(sc, bf_lo(w.y), acc[2]);
                    acc[3] = fmaf(sc, bf_hi(w.y), acc[3]);
                    acc[4] = fmaf(sc, bf_lo(w.z), acc[4]);
                    acc[5] = fmaf(sc, bf_hi(w.z), acc[5]);
                    acc[6] = fmaf(sc, bf_lo(w.w), acc[6]);
                    acc[7] = fmaf(sc, bf_hi(w.w), acc[7]);
                }
#pragma unroll
                for (int o = 2; o < 32; o <<= 1)
#pragma unroll
                    for (int e = 0; e < 8; e++) acc[e] += __shfl_xor_sync(0xffffffffu, acc[e], o);
                if (lane < 2) {
#pragma unroll
                    for (int e = 0; e < 8; e++) st_mod(sc_->mod + blk * 16 + lane * 8 + e, acc[e], tag);
                }
            }
            if (warp == 9) {
#pragma unroll 1
                for (int st = 1; st <= 2; st++) {
                    bar_sync(7, 160);
                    const uint32_t* src = sc_->mod + (st * 3 - 1) * DM;
                    const int n = st == 1 ? 3 * DM : DM;
#pragma unroll 1
                    for (int i = lane * 4; i < n + 127 - ((n + 127) & 127); i += 128)
                        mod_to_smem(sbase + OFF_MODT + min(i, n - 4) * 4, src + min(i, n - 4), tag);
                    __syncwarp();
                    if (lane == 0) rows_load(sbase, st == 1 ? &maps.rx : &maps.rx2, (mt * 8 + g) * 16);
                    if (st == 1) {
                        bar_sync(7, 160);
                        if (lane == 0) {
                            rows_store(sbase, &maps.rx2, (mt * 8 + g) * 16);
                            rows_store_wait();
                        }
                        __syncwarp();
                        bar_arrive(10, 160);
                    }
                }
            }
        }
    } else {
        asm volatile("setmaxnreg.inc.sync.aligned.u32 240;");
        const int wg = warp >> 2;
        const int tid = threadIdx.x;
        Ctx cx;
        cx.sbase = sbase;
        cx.wg = wg;
        if (wg == 1) bar_arrive(8, 256);
        cx.rel_cta = (lane == 0 && (warp & 3) < 2) ? (warp & 3) : 2;
        const uint32_t red = sbase + OFF_RED;
        const int own = mt * 8 + g;
        const int wown = mt * 8 + warp;
        PROF(0);
        PROFG(30);
        PROFR(17);
        {
            const int r0 = tid >> 1;
            PROFR(18);
            asm volatile("barrier.cluster.arrive.relaxed.aligned;" ::: "memory");
            bar_sync(3, 256);
            if (b < 72) {
                float sc[5];
                uint4 w1[5];
#pragma unroll
                for (int i = 0; i < 5; i++) sc[i] = (r0 + 128 * i < DM) ? silu_bf16(cu[i]) : 0.f;
                PROFR(19);
                mbar_wait(sbase + OFF_WBAR, 0);
                PROFR(20);
#pragma unroll
                for (int i = 0; i < 5; i++)
                    lds128(sbase + OFF_WBLK + (i < 4 ? tid + i * 256 : 1024 + (tid & 127)) * 16, w1[i].x, w1[i].y, w1[i].z, w1[i].w);
                mod_block(w1, sc, sc_->mod + b * 16, red + 1024, warp, lane, (epoch + 1) & 0xffffu);
            }
            PROFR(21);
        }

        Ring ring{0u, 0u};
        int stage = 0;
        asm volatile("" : "+r"(stage));
#pragma unroll 1
        for (;; stage++) {
            int tid, lane;
            asm volatile("mov.u32 %0, %%tid.x;" : "=r"(tid));
            lane = tid & 31;
            {
                float v[36];
                const uint32_t modt = sbase + OFF_MODT + (warp * 16 + (lane & 3) * 2) * 4;
                if (stage == 0) {
#pragma unroll
                    for (int i = 0; i < 36; i++) v[i] = 0.f;
                } else {
                    const uint4* psrc = sc_->part + (size_t)own * 8 * 36 * 32;
                    sum_partials(v, psrc + tid, stage & 1);
                    PROF(stage == 1 ? 8 : 15);
                    sum_tail(v, reinterpret_cast<const uint2*>(psrc + 32 * 32) + tid, stage & 1);
                }
                mbar_wait(sbase + OFF_XBAR, stage & 1);
                if (stage == 0) PROFR(22);
                {
                    const float gs = stage == 2 ? 0.5f : 1.f;
                    float gate[18];
                    lds_mod(gate, modt, warp);
                    const int r = lane >> 2;
                    const uint32_t rows = sbase + OFF_ROWS + r * (DM * 2) + (lane & 3) * 4;
#pragma unroll
                    for (int j = 0; j < 9; j++) {
                        const int ch = j < 8 ? (j >> 1) * 2 + (warp >> 2) : 8, c16 = j < 8 ? (warp & 3) * 2 + (j & 1) : warp;
                        const uint32_t ad = rows + ch * 128 + ((c16 ^ ((r + ch) & 7)) << 4);
                        const uint32_t u0 = __float_as_uint(lds32f(ad)), u1 = __float_as_uint(lds32f(ad + 8 * DM * 2));
                        const float g0 = stage ? gate[2 * j] * gs : 0.f, g1 = stage ? gate[2 * j + 1] * gs : 0.f;
                        v[4 * j] = fmaf(g0, v[4 * j], bf_lo(u0));
                        v[4 * j + 1] = fmaf(g1, v[4 * j + 1], bf_hi(u0));
                        v[4 * j + 2] = fmaf(g0, v[4 * j + 2], bf_lo(u1));
                        v[4 * j + 3] = fmaf(g1, v[4 * j + 3], bf_hi(u1));
                        sts32f(ad, __uint_as_float(pack_bf16(v[4 * j], v[4 * j + 1])));
                        sts32f(ad + 8 * DM * 2, __uint_as_float(pack_bf16(v[4 * j + 2], v[4 * j + 3])));
                    }
                    asm volatile("fence.proxy.async.shared::cta;" ::: "memory");
                }
                if (stage == 2) break;
                PROF(stage == 0 ? 1 : 9);
                layernorm_rows(v, red, warp, lane);
                if (stage == 0) PROFR(27);
                if (stage == 0) {
                    const uint32_t tag = (epoch + 1) & 0xffffu;
                    mod_to_smem(sbase + OFF_MODT + (DM + tid * 4) * 4, sc_->mod + tid * 4, tag);
                    if (warp == 7) mod_to_smem(sbase + OFF_MODT + (DM + 1024 + lane * 4) * 4, sc_->mod + 1024 + lane * 4, tag);
                    bar_sync(3, 256);
                    bar_arrive(4, 320);
                }
                float shift[18], scale[18];
                lds_mod(shift, modt + DM * 4, warp);
                lds_mod(scale, modt + 2 * DM * 4, warp);
                if (stage == 0) PROFR(28);
                PROF(stage == 0 ? 2 : 10);
                modulate_store(v, shift, scale, sc_->h[epoch & 1][stage] + (size_t)own * 36 * 32, warp, lane);
                if (stage == 0) asm volatile("barrier.cluster.wait.aligned;" ::: "memory");
            }

            const uint32_t spill = sbase + 8 * SLOT_BYTES + wg * 3 * SLOT_BYTES + (tid & 127) * 16;
            uint32_t a[144];
            PROF(stage == 0 ? 3 : 11);
            {
                const uint4* hsrc = sc_->h[epoch & 1][stage] + (size_t)wown * 36 * 32 + lane;
                poll_tail(a, reinterpret_cast<const uint2*>(hsrc - lane + 32 * 32) + lane);
                PROF(stage == 0 ? 4 : 12);
                if (stage == 1) PROFG(25);
                TG(stage * 32 + 30);
                if (wg == 1) bar_sync(5, 256);
                poll_frags<0, 32>(a, hsrc, wg == 0);
            }
            uint4* hhbuf = sc_->hh + (size_t)b * 8 * 256 + tid;
            float d[64];
#pragma unroll 1
            for (int ch = 0;; ch++) {
                TG(stage * 32 + ch * 2);
                gemm_n128(d, a, cx, ring, true);
                TG(stage * 32 + ch * 2 + 1);
                if (stage == 0) {
#pragma unroll
                    for (int i = 0; i < 64; i++) d[i] *= SM_SCALE;
                    if (ch == 3) break;
#pragma unroll
                    for (int v = 0; v < 8; v++)
                        sts128(spill + (ch * 8 + v) * 2048, pack_bf16(d[8 * v], d[8 * v + 1]),
                               pack_bf16(d[8 * v + 2], d[8 * v + 3]), pack_bf16(d[8 * v + 4], d[8 * v + 5]),
                               pack_bf16(d[8 * v + 6], d[8 * v + 7]));
                } else {
#pragma unroll
                    for (int i = 0; i < 32; i++) {
                        const float gv = d[i], gu = gv * d[32 + i];
                        const float z = gv * fmaf(gv * gv, 0.7978845608028654f * 0.044715f, 0.7978845608028654f);
                        d[i] = fmaf(gu, tanh_fast(z), gu);
                    }
                    if (ch == 8) break;
                    if (wg == 0) {
                        if (ch == 0) bar_arrive(7, 160);
                        if (ch == 2) bar_sync(10, 160);
                    }
#pragma unroll
                    for (int v = 0; v < 4; v++) {
                        const uint4 h4 = make_uint4(pack_bf16(d[8 * v], d[8 * v + 1]), pack_bf16(d[8 * v + 2], d[8 * v + 3]),
                                                    pack_bf16(d[8 * v + 4], d[8 * v + 5]), pack_bf16(d[8 * v + 6], d[8 * v + 7]));
                        if (ch < 2)
                            __stcg(hhbuf + (ch * 4 + v) * 256, h4);
                        else
                            sts128(spill + ((ch - 2) * 4 + v) * 2048, h4.x, h4.y, h4.z, h4.w);
                    }
                }
            }
            if (stage == 0) {
                uint32_t q[32];
#pragma unroll
                for (int i = 0; i < 32; i++) q[i] = pack_bf16(d[2 * i], d[2 * i + 1]);
                PROF(5);
                PROFG(23);
                if (wg == 0) bar_arrive(6, 160);
                {
                    float o[64], sa[32], sb[32];
                    uint32_t pa[16], pb[16];
#pragma unroll
                    for (int i = 0; i < 64; i++) o[i] = 0.f;
                    float n0 = 0.f, n1 = 0.f, l0 = 1.f, l1 = 1.f;
                    bool shifted = false;
                    const uint64_t dbase = desc_of(sbase);
                    const uint64_t dbk = dbase - (511u << 16);
                    const int my_bar = 1 + wg, other_bar = 2 - wg;

                    auto softmax_a = [&](bool first, float& s0, float& s1) {
                        if (first) {
                            shifted = false;
                            n0 = n1 = 0.f;
                            l0 = l1 = 0.f;
                        }
                        if (shifted)
                            exp_step<true>(sa, pa, n0, n1, s0, s1);
                        else
                            exp_step<false>(sa, pa, n0, n1, s0, s1);
                    };
                    auto softmax_b = [&](bool first, float s0, float s1) {
                        float u0, u1;
                        if (shifted)
                            exp_step<true>(sb, pb, n0, n1, u0, u1);
                        else
                            exp_step<false>(sb, pb, n0, n1, u0, u1);
                        s0 += u0;
                        s1 += u1;
                        bool bad = !(fmaxf(s0, s1) <= SM_HI);
                        if (first) {
                            float r0 = s0 + __shfl_xor_sync(0xffffffffu, s0, 1), r1 = s1 + __shfl_xor_sync(0xffffffffu, s1, 1);
                            r0 += __shfl_xor_sync(0xffffffffu, r0, 2);
                            r1 += __shfl_xor_sync(0xffffffffu, r1, 2);
                            bad = bad || !(fminf(r0, r1) >= SM_LO);
                        }
                        if (__any_sync(0xffffffffu, bad)) {
                            float x0, x1;
                            row_max(sa, sb, x0, x1);
                            x0 = -x0;
                            x1 = -x1;
                            if (!first) {
                                x0 = fminf(x0, n0);
                                x1 = fminf(x1, n1);
                                const float al0 = ex2(x0 - n0), al1 = ex2(x1 - n1);
                                l0 *= al0;
                                l1 *= al1;
#pragma unroll
                                for (int i = 0; i < 16; i++) {
                                    o[4 * i] *= al0;
                                    o[4 * i + 1] *= al0;
                                    o[4 * i + 2] *= al1;
                                    o[4 * i + 3] *= al1;
                                }
                            }
                            n0 = x0;
                            n1 = x1;
                            shifted = true;
                            exp_step<true>(sa, pa, n0, n1, s0, s1);
                            exp_step<true>(sb, pb, n0, n1, u0, u1);
                            s0 += u0;
                            s1 += u1;
                        }
                        l0 += s0;
                        l1 += s1;
                    };

                    cx.wait_full(4, 0);
                    if (wg == 1) bar_sync(my_bar, 256);
                    wg_fence();
                    qk_step(sa, q, dbk + 4 * 1024);
                    qk_step(sb, q, dbk + 5 * 1024);
                    wg_commit();
                    bar_arrive(other_bar, 256);
                    wg_wait<0>();
                    pin(sa);
                    pin(sb);
                    cx.release(4);
                    cx.wait_full(6, 0);
                    {
                        float s0, s1;
                        softmax_a(true, s0, s1);
                        softmax_b(true, s0, s1);
                    }
                    uint32_t alo = (uint32_t)dbase + 6 * 1024, blo = (uint32_t)dbase;
                    const uint32_t dhi = (uint32_t)(dbase >> 32);
#pragma unroll 1
                    for (int t = 1; t < 64; t++) {
                        const int j = t & 15;
                        const uint32_t sA = 2 + 4 * (t & 1), sB = 4 - 4 * (t & 1);
                        const uint64_t da = ((uint64_t)dhi << 32) | alo, db = ((uint64_t)dhi << 32) | blo;
                        TL(0);
                        bar_sync(my_bar, 256);
                        TL(2);
                        wg_fence();
                        pv_step(o, pa, da + 1024, j != 1);
                        qk_step(sa, q, da - (511u << 16));
                        wg_commit();
                        cx.wait_full(sB, ((36 + 4 * t) >> 3) & 1);
                        wg_fence();
                        qk_step(sb, q, db - (511u << 16));
                        pv_step(o, pb, db + 1024, 1);
                        wg_commit();
                        bar_arrive(other_bar, 256);
                        alo ^= 4096;
                        blo ^= 4096;
                        asm volatile("" : "+r"(alo), "+r"(blo));
                        TL(3);
                        wg_wait<1>();
                        pin(sa);
                        pin(pa);
                        TL(4);
                        cx.release(sA);
                        const float lp0 = l0, lp1 = l1;
                        float s0, s1;
                        softmax_a(j == 0, s0, s1);
                        TL(5);
                        wg_wait<0>();
                        pin(o);
                        pin(sb);
                        pin(pb);
                        TL(6);
                        cx.release(sB);
                        if (j == 0) {
                            float i0, i1;
                            inv_row_sums(lp0, lp1, i0, i1);
                            const uint32_t dst = spill + ((t >> 4) - 1) * 16384;
#pragma unroll
                            for (int v = 0; v < 8; v++)
                                sts128(dst + v * 2048, pack_bf16(o[8 * v] * i0, o[8 * v + 1] * i0),
                                       pack_bf16(o[8 * v + 2] * i1, o[8 * v + 3] * i1),
                                       pack_bf16(o[8 * v + 4] * i0, o[8 * v + 5] * i0),
                                       pack_bf16(o[8 * v + 6] * i1, o[8 * v + 7] * i1));
                        }
                        const uint32_t bn = sbase + OFF_FULL + (8 - sA) * 8, pn = ((38 + 4 * t) >> 3) & 1;
                        const bool okn = mbar_try(bn, pn);
                        TL(1);
                        softmax_b(j == 0, s0, s1);
                        if (!okn || j == 15) {
                            mbar_wait(bn, pn);
                            if (j == 15 && t < 63) {
                                const uint32_t src = spill + (t >> 4) * 16384;
#pragma unroll
                                for (int v = 0; v < 8; v++)
                                    lds128(src + v * 2048, q[4 * v], q[4 * v + 1], q[4 * v + 2], q[4 * v + 3]);
                            }
                        }
                        TL(7);
                    }
                    bar_sync(my_bar, 256);
                    wg_fence();
                    pv_step(o, pa, dbase + 2 * 1024, 1);
                    pv_step(o, pb, dbase + 3 * 1024, 1);
                    wg_commit();
                    if (wg == 0) bar_arrive(other_bar, 256);
                    float i0, i1;
                    inv_row_sums(l0, l1, i0, i1);
                    wg_wait<0>();
                    pin(o);
                    cx.release(2);
#pragma unroll
                    for (int i = 0; i < 16; i++) {
                        a[96 + 2 * i] = pack_bf16(o[4 * i] * i0, o[4 * i + 1] * i0);
                        a[96 + 2 * i + 1] = pack_bf16(o[4 * i + 2] * i1, o[4 * i + 3] * i1);
                    }
#pragma unroll
                    for (int i = 128; i < 144; i++) a[i] = 0;
                }
                ring.slot = 4;
                ring.phase = 0;
                PROF(6);
                PROFG(24);
            } else {
#pragma unroll
                for (int v = 0; v < 8; v++) {
                    const uint4 t = __ldcg(hhbuf + v * 256);
                    a[112 + 4 * v] = t.x;
                    a[113 + 4 * v] = t.y;
                    a[114 + 4 * v] = t.z;
                    a[115 + 4 * v] = t.w;
                }
#pragma unroll
                for (int i = 0; i < 16; i++) a[96 + i] = pack_bf16(d[2 * i], d[2 * i + 1]);
                PROF(13);
            }
#pragma unroll
            for (int v = 0; v < 24; v++) lds128(spill + v * 2048, a[4 * v], a[4 * v + 1], a[4 * v + 2], a[4 * v + 3]);

            {
                uint4* dst = sc_->part + ((size_t)wown * 8 + g) * 36 * 32 + lane;
                const uint32_t ptag = (stage + 1) & 1;
#pragma unroll 1
                for (int p = 0; p < 4; p++) {
                    TG(stage * 32 + 18 + p * 2);
                    gemm_n128(d, a, cx, ring, stage != 0);
                    TG(stage * 32 + 19 + p * 2);
#pragma unroll
                    for (int u = 0; u < 8; u++)
                        st128(dst + (p * 8 + u) * 32, (pack_bf16(d[8 * u], d[8 * u + 1]) & ~1u) | ptag,
                              pack_bf16(d[8 * u + 2], d[8 * u + 3]), pack_bf16(d[8 * u + 4], d[8 * u + 5]),
                              pack_bf16(d[8 * u + 6], d[8 * u + 7]));
                    if (p == 0 && wg == 0) bar_arrive(7, 160);
                }
                float e[32];
                TG(stage * 32 + 26);
                gemm_n64(e, a, cx, ring, stage != 0);
                TG(stage * 32 + 27);
                uint2* dst2 = reinterpret_cast<uint2*>(dst - lane + 32 * 32) + lane;
#pragma unroll
                for (int j = 0; j < 8; j++)
                    st64(dst2 + j * 32, (pack_bf16(e[4 * j], e[4 * j + 1]) & ~1u) | ptag, pack_bf16(e[4 * j + 2], e[4 * j + 3]));
            }
            PROF(stage == 0 ? 7 : 14);
            if (stage == 1) {
                PROFG(26);
                asm volatile("barrier.cluster.arrive.relaxed.aligned;" ::: "memory");
            }
        }
        if (wg == 0) bar_sync(8, 256);
        bar_sync(3, 256);
        if (tid == 0) {
            rows_store(sbase, &maps.rout, own * 16);
            if (b == 0) sc_->epoch = epoch + 1;
            rows_store_wait();
        }
        __syncwarp();
        PROF(16);
        PROFG(31);
        asm volatile("barrier.cluster.wait.aligned;" ::: "memory");
    }
}

typedef CUresult (*EncodeFn)(CUtensorMap*, CUtensorMapDataType, cuuint32_t, void*, const cuuint64_t*, const cuuint64_t*,
                             const cuuint32_t*, const cuuint32_t*, CUtensorMapInterleave, CUtensorMapSwizzle,
                             CUtensorMapL2promotion, CUtensorMapFloatOOBfill);

void make_map(EncodeFn enc, CUtensorMap* m, const void* ptr, uint64_t rows, uint64_t cols, bool narrow = false) {
    cuuint64_t gdim[2] = {cols, rows};
    cuuint64_t gstr[1] = {cols * 2};
    cuuint32_t box[2] = {narrow ? 16u : 64u, narrow ? 192u : 64u};
    cuuint32_t estr[2] = {1, 1};
    enc(m, CU_TENSOR_MAP_DATA_TYPE_BFLOAT16, 2, const_cast<void*>(ptr), gdim, gstr, box, estr,
        CU_TENSOR_MAP_INTERLEAVE_NONE, narrow ? CU_TENSOR_MAP_SWIZZLE_NONE : CU_TENSOR_MAP_SWIZZLE_128B,
        CU_TENSOR_MAP_L2_PROMOTION_L2_128B,
        CU_TENSOR_MAP_FLOAT_OOB_FILL_NONE);
}

void make_rows_map(EncodeFn enc, CUtensorMap* m, const void* ptr) {
    cuuint64_t gdim[3] = {64, 9, 2048};
    cuuint64_t gstr[2] = {128, DM * 2};
    cuuint32_t box[3] = {64, 9, 16};
    cuuint32_t estr[3] = {1, 1, 1};
    enc(m, CU_TENSOR_MAP_DATA_TYPE_BFLOAT16, 3, const_cast<void*>(ptr), gdim, gstr, box, estr,
        CU_TENSOR_MAP_INTERLEAVE_NONE, CU_TENSOR_MAP_SWIZZLE_128B, CU_TENSOR_MAP_L2_PROMOTION_L2_128B,
        CU_TENSOR_MAP_FLOAT_OOB_FILL_NONE);
}

}

extern "C" void kernel_launch(void* const* d_in, const int* in_sizes, int n_in, void* d_out, int out_size) {
    (void)in_sizes;
    (void)n_in;
    (void)out_size;
    void* fn = nullptr;
    cudaDriverEntryPointQueryResult qr;
    cudaGetDriverEntryPoint("cuTensorMapEncodeTiled", &fn, cudaEnableDefault, &qr);
    EncodeFn enc = (EncodeFn)fn;
    Params maps;
    maps.x = (const __nv_bfloat16*)d_in[0];
    maps.cvec = (const __nv_bfloat16*)d_in[9];
    maps.wmod = (const __nv_bfloat16*)d_in[10];
    maps.kc = (const __nv_bfloat16*)d_in[1];
    maps.vc = (const __nv_bfloat16*)d_in[2];
    maps.wq_p = (const __nv_bfloat16*)d_in[3];
    maps.wo_p = (const __nv_bfloat16*)d_in[4];
    maps.wg_p = (const __nv_bfloat16*)d_in[6];
    maps.wu_p = (const __nv_bfloat16*)d_in[7];
    maps.wd_p = (const __nv_bfloat16*)d_in[8];
    maps.out = (__nv_bfloat16*)d_out;
    void* scp = nullptr;
    cudaGetSymbolAddress(&scp, g_scratch);
    maps.sc = (Scratch*)scp;
    make_map(enc, &maps.k, d_in[1], 32 * 2048, 128);
    make_map(enc, &maps.v, d_in[2], 32 * 2048, 128);
    make_map(enc, &maps.wq, d_in[3], 576, 4096);
    make_map(enc, &maps.wo, d_in[4], 4096, 576);
    make_map(enc, &maps.wg, d_in[6], 576, 4608);
    make_map(enc, &maps.wu, d_in[7], 576, 4608);
    make_map(enc, &maps.wd, d_in[8], 4608, 576);
    make_map(enc, &maps.wm, d_in[10], 576, 3456, true);
    make_rows_map(enc, &maps.rx, d_in[0]);
    make_rows_map(enc, &maps.rx2, (char*)scp + offsetof(Scratch, x2));
    make_rows_map(enc, &maps.rout, d_out);
    cudaFuncSetAttribute(fused_block_kernel, cudaFuncAttributeMaxDynamicSharedMemorySize, SMEM_BYTES);
    fused_block_kernel<<<128, 384, SMEM_BYTES>>>(maps);
}
```

```cpp
#include <cuda_runtime.h>
#include <cuda_bf16.h>
#include <cuda.h>
#include <stdint.h>
#include <stddef.h>

namespace {

constexpr int DM = 576;
constexpr int SLOT_BYTES = 16384;
constexpr int BOX_BYTES = 8192;
constexpr int NUNITS = 14;
constexpr int SMEM_TAIL = NUNITS * SLOT_BYTES;
constexpr int SMEM_BYTES = SMEM_TAIL + 2048 + 1024;
constexpr int OFF_FULL = SMEM_TAIL;
constexpr int OFF_EMPTY = SMEM_TAIL + 64;
constexpr int OFF_RED = SMEM_TAIL + 128;

constexpr int KV_AHEAD = 16;
#define GATE_SLOT 4
constexpr int OFF_XBAR = SMEM_TAIL + 1792;
constexpr int OFF_ROWS = 8 * SLOT_BYTES;
constexpr int OFF_MODT = OFF_ROWS + 20480;
constexpr int OFF_WBLK = OFF_ROWS + 28672;
constexpr int OFF_WBAR = SMEM_TAIL + 1800;

struct Scratch {
    unsigned epoch[32];
    uint32_t mod[6 * DM];
    uint4 h[2][2][128 * 36 * 32];
    uint4 part[128 * 8 * 36 * 32];
    uint4 hh[128 * 8 * 256];
    __nv_bfloat16 x2[2048 * DM];
};
__device__ Scratch g_scratch;

#define TG(i)
#define TL(i)
#define PROFR(i)
#define PROF(i)
#define PROFG(i)

struct Params {
    const __nv_bfloat16 *x, *cvec, *wmod, *kc, *vc, *wq_p, *wo_p, *wg_p, *wu_p, *wd_p;
    __nv_bfloat16* out;
    Scratch* sc;
    CUtensorMap k, v, wq, wo, wg, wu, wd, wm, rx, rx2, rout;
};

__device__ __forceinline__ uint32_t smem_u32(const void* p) { return (uint32_t)__cvta_generic_to_shared(p); }
__device__ __forceinline__ void mbar_init(uint32_t a, uint32_t c) {
    asm volatile("mbarrier.init.shared::cta.b64 [%0], %1;" ::"r"(a), "r"(c) : "memory");
}
__device__ __forceinline__ void mbar_expect_tx(uint32_t a, uint32_t bytes) {
    asm volatile("mbarrier.arrive.expect_tx.shared::cta.b64 _, [%0], %1;" ::"r"(a), "r"(bytes) : "memory");
}
__device__ __forceinline__ bool mbar_try(uint32_t a, uint32_t ph) {
    uint32_t ok;
    asm volatile(
        "{\n.reg .pred p;\nmbarrier.try_wait.parity.shared::cta.b64 p, [%1], %2;\nselp.u32 %0, 1, 0, p;\n}"
        : "=r"(ok)
        : "r"(a), "r"(ph)
        : "memory");
    return ok != 0;
}
__device__ __forceinline__ uint32_t clk32() {
    uint32_t c;
    asm volatile("mov.u32 %0, %%clock;" : "=r"(c));
    return c;
}
constexpr uint32_t WAIT_LIMIT = 1u << 30;
__device__ __forceinline__ void mbar_wait(uint32_t a, uint32_t ph) {
    if (mbar_try(a, ph)) return;
    uint32_t t0 = clk32();
    while (!mbar_try(a, ph)) {
        if (clk32() - t0 > WAIT_LIMIT) break;
    }
}
__device__ __forceinline__ void mbar_arrive_cluster(uint32_t a, uint32_t cta) {
    asm volatile(
        "{\n.reg .b32 ra;\nmapa.shared::cluster.u32 ra, %0, %1;\nmbarrier.arrive.shared::cluster.b64 _, [ra];\n}" ::"r"(a),
        "r"(cta)
        : "memory");
}
__device__ __forceinline__ void tma_mc(uint32_t dst, const CUtensorMap* m, int c0, int c1, uint32_t bar) {
    asm volatile(
        "cp.async.bulk.tensor.2d.shared::cluster.global.mbarrier::complete_tx::bytes.multicast::cluster"
        " [%0], [%1, {%3, %4}], [%2], %5;" ::"r"(dst),
        "l"(m), "r"(bar), "r"(c0), "r"(c1), "h"((uint16_t)3)
        : "memory");
}
__device__ __forceinline__ void l2_prefetch(const void* p, uint32_t bytes) {
    asm volatile("cp.async.bulk.prefetch.L2.global [%0], %1;" ::"l"(p), "r"(bytes) : "memory");
}
__device__ __forceinline__ void bar_sync(int id, int n) { asm volatile("bar.sync %0, %1;" ::"r"(id), "r"(n) : "memory"); }
__device__ __forceinline__ void bar_arrive(int id, int n) {
    asm volatile("bar.arrive %0, %1;" ::"r"(id), "r"(n) : "memory");
}
__device__ __forceinline__ void wg_fence() { asm volatile("wgmma.fence.sync.aligned;" ::: "memory"); }
__device__ __forceinline__ void wg_commit() { asm volatile("wgmma.commit_group.sync.aligned;" ::: "memory"); }
template <int N>
__device__ __forceinline__ void wg_wait() {
    asm volatile("wgmma.wait_group.sync.aligned %0;" ::"n"(N) : "memory");
}
template <int N>
__device__ __forceinline__ void pin(float (&d)[N]) {
#pragma unroll
    for (int i = 0; i < N; i++) asm volatile("" : "+f"(d[i])::"memory");
}
template <int N>
__device__ __forceinline__ void pin(uint32_t (&d)[N]) {
#pragma unroll
    for (int i = 0; i < N; i++) asm volatile("" : "+r"(d[i])::"memory");
}
__device__ __forceinline__ uint32_t pack_bf16(float lo, float hi) {
    uint32_t r;
    asm("cvt.rn.bf16x2.f32 %0, %1, %2;" : "=r"(r) : "f"(hi), "f"(lo));
    return r;
}
__device__ __forceinline__ float bf_lo(uint32_t v) { return __uint_as_float(v << 16); }
__device__ __forceinline__ float bf_hi(uint32_t v) { return __uint_as_float(v & 0xffff0000u); }
__device__ __forceinline__ float round_bf16(float v) { return __bfloat162float(__float2bfloat16_rn(v)); }
__device__ __forceinline__ float ex2(float x) {
    float y;
    asm("ex2.approx.ftz.f32 %0, %1;" : "=f"(y) : "f"(x));
    return y;
}
__device__ __forceinline__ float rcp(float x) {
    float y;
    asm("rcp.approx.ftz.f32 %0, %1;" : "=f"(y) : "f"(x));
    return y;
}
__device__ __forceinline__ float tanh_fast(float x) {
    float y;
    asm("tanh.approx.f32 %0, %1;" : "=f"(y) : "f"(x));
    return y;
}
__device__ __forceinline__ void sts128(uint32_t a, uint32_t x, uint32_t y, uint32_t z, uint32_t w) {
    asm volatile("st.shared.v4.b32 [%0], {%1,%2,%3,%4};" ::"r"(a), "r"(x), "r"(y), "r"(z), "r"(w) : "memory");
}
__device__ __forceinline__ void lds128(uint32_t a, uint32_t& x, uint32_t& y, uint32_t& z, uint32_t& w) {
    asm volatile("ld.shared.v4.b32 {%0,%1,%2,%3}, [%4];" : "=r"(x), "=r"(y), "=r"(z), "=r"(w) : "r"(a) : "memory");
}
__device__ __forceinline__ void sts32f(uint32_t a, float v) {
    asm volatile("st.shared.f32 [%0], %1;" ::"r"(a), "f"(v) : "memory");
}
__device__ __forceinline__ float lds32f(uint32_t a) {
    float v;
    asm volatile("ld.shared.f32 %0, [%1];" : "=f"(v) : "r"(a) : "memory");
    return v;
}
#define F8(d, b) \
    "+f"(d[b]), "+f"(d[b + 1]), "+f"(d[b + 2]), "+f"(d[b + 3]), "+f"(d[b + 4]), "+f"(d[b + 5]), "+f"(d[b + 6]), "+f"(d[b + 7])

template <int TB>
__device__ __forceinline__ void wgmma_n128(float (&d)[64], uint32_t a0, uint32_t a1, uint32_t a2, uint32_t a3,
                                           uint64_t db, int sc) {
    asm volatile(
        "{\n.reg .pred p;\nsetp.ne.b32 p, %69, 0;\n"
        "wgmma.mma_async.sync.aligned.m64n128k16.f32.bf16.bf16 "
        "{%0,%1,%2,%3,%4,%5,%6,%7,%8,%9,%10,%11,%12,%13,%14,%15,%16,%17,%18,%19,%20,%21,%22,%23,%24,%25,%26,%27,%28,%29,%30,%31,"
        "%32,%33,%34,%35,%36,%37,%38,%39,%40,%41,%42,%43,%44,%45,%46,%47,%48,%49,%50,%51,%52,%53,%54,%55,%56,%57,%58,%59,%60,%61,%62,%63},"
        "{%64,%65,%66,%67}, %68, p, 1, 1, %70;\n}"
        : F8(d, 0), F8(d, 8), F8(d, 16), F8(d, 24), F8(d, 32), F8(d, 40), F8(d, 48), F8(d, 56)
        : "r"(a0), "r"(a1), "r"(a2), "r"(a3), "l"(db), "r"(sc), "n"(TB));
}
#define O8(d, b) \
    "=f"(d[b]), "=f"(d[b + 1]), "=f"(d[b + 2]), "=f"(d[b + 3]), "=f"(d[b + 4]), "=f"(d[b + 5]), "=f"(d[b + 6]), "=f"(d[b + 7])
template <int TB>
__device__ __forceinline__ void wgmma_n128_z(float (&d)[64], uint32_t a0, uint32_t a1, uint32_t a2, uint32_t a3,
                                             uint64_t db) {
    asm volatile(
        "wgmma.mma_async.sync.aligned.m64n128k16.f32.bf16.bf16 "
        "{%0,%1,%2,%3,%4,%5,%6,%7,%8,%9,%10,%11,%12,%13,%14,%15,%16,%17,%18,%19,%20,%21,%22,%23,%24,%25,%26,%27,%28,%29,%30,%31,"
        "%32,%33,%34,%35,%36,%37,%38,%39,%40,%41,%42,%43,%44,%45,%46,%47,%48,%49,%50,%51,%52,%53,%54,%55,%56,%57,%58,%59,%60,%61,%62,%63},"
        "{%64,%65,%66,%67}, %68, 0, 1, 1, %69;"
        : O8(d, 0), O8(d, 8), O8(d, 16), O8(d, 24), O8(d, 32), O8(d, 40), O8(d, 48), O8(d, 56)
        : "r"(a0), "r"(a1), "r"(a2), "r"(a3), "l"(db), "n"(TB));
}
template <int TB>
__device__ __forceinline__ void wgmma_n64_z(float (&d)[32], uint32_t a0, uint32_t a1, uint32_t a2, uint32_t a3,
                                            uint64_t db) {
    asm volatile(
        "wgmma.mma_async.sync.aligned.m64n64k16.f32.bf16.bf16 "
        "{%0,%1,%2,%3,%4,%5,%6,%7,%8,%9,%10,%11,%12,%13,%14,%15,%16,%17,%18,%19,%20,%21,%22,%23,%24,%25,%26,%27,%28,%29,%30,%31},"
        "{%32,%33,%34,%35}, %36, 0, 1, 1, %37;"
        : O8(d, 0), O8(d, 8), O8(d, 16), O8(d, 24)
        : "r"(a0), "r"(a1), "r"(a2), "r"(a3), "l"(db), "n"(TB));
}
template <int TB>
__device__ __forceinline__ void wgmma_n64(float (&d)[32], uint32_t a0, uint32_t a1, uint32_t a2, uint32_t a3,
                                          uint64_t db) {
    asm volatile(
        "wgmma.mma_async.sync.aligned.m64n64k16.f32.bf16.bf16 "
        "{%0,%1,%2,%3,%4,%5,%6,%7,%8,%9,%10,%11,%12,%13,%14,%15,%16,%17,%18,%19,%20,%21,%22,%23,%24,%25,%26,%27,%28,%29,%30,%31},"
        "{%32,%33,%34,%35}, %36, 1, 1, 1, %37;"
        : F8(d, 0), F8(d, 8), F8(d, 16), F8(d, 24)
        : "r"(a0), "r"(a1), "r"(a2), "r"(a3), "l"(db), "n"(TB));
}

__device__ __forceinline__ uint64_t desc_of(uint32_t saddr) {
    return (uint64_t)(((saddr >> 4) & 0x3FFFu) | (512u << 16)) | ((uint64_t)(64u | (1u << 30)) << 32);
}

struct Ring {
    uint32_t slot;
    uint32_t phase;
    __device__ __forceinline__ void next() {
        if (++slot == 8) {
            slot = 0;
            phase ^= 1;
        }
    }
};

struct Ctx {
    uint32_t sbase;
    int wg;
    uint32_t rel_cta;
    __device__ __forceinline__ void wait_full(uint32_t slot, uint32_t phase) const {
        mbar_wait(sbase + OFF_FULL + slot * 8, phase);
    }
    __device__ __forceinline__ void release(uint32_t slot) const {
        if (rel_cta < 2) mbar_arrive_cluster(sbase + OFF_EMPTY + slot * 8, rel_cta);
    }
};

__device__ __forceinline__ void gemm_n128(float (&d)[64], const uint32_t (&a)[144], const Ctx& c, Ring& r, bool nine) {
    uint32_t prev = 0;
#pragma unroll
    for (int s = 0; s < 9; s++) {
        if (s < 8 || nine) {
            if (s == GATE_SLOT) bar_sync(8 + c.wg, 256);
            c.wait_full(r.slot, r.phase);
            uint64_t db = desc_of(c.sbase + r.slot * SLOT_BYTES);
            wg_fence();
#pragma unroll
            for (int k = 0; k < 4; k++) {
                if ((s | k) == 0)
                    wgmma_n128_z<1>(d, a[0], a[1], a[2], a[3], db);
                else
                    wgmma_n128<1>(d, a[s * 16 + k * 4], a[s * 16 + k * 4 + 1], a[s * 16 + k * 4 + 2],
                                  a[s * 16 + k * 4 + 3], db + k * 128, 1);
            }
            wg_commit();
            if (s == 8 || (s == 7 && !nine)) bar_arrive(9 - c.wg, 256);
            if (s > 0) {
                wg_wait<1>();
                c.release(prev);
            }
            prev = r.slot;
            r.next();
        }
    }
    wg_wait<0>();
    c.release(prev);
    pin(d);
}
__device__ __forceinline__ void gemm_n64(float (&d)[32], const uint32_t (&a)[144], const Ctx& c, Ring& r, bool nine) {
    uint32_t prev = 0;
#pragma unroll
    for (int s = 0; s < 5; s++) {
        if (s < 4 || nine) {
            c.wait_full(r.slot, r.phase);
            uint64_t db = desc_of(c.sbase + r.slot * SLOT_BYTES);
            wg_fence();
#pragma unroll
            for (int k = 0; k < 8; k++) {
                if ((s | k) == 0)
                    wgmma_n64_z<1>(d, a[0], a[1], a[2], a[3], db);
                else if (s * 8 + k < 36)
                    wgmma_n64<1>(d, a[s * 32 + k * 4], a[s * 32 + k * 4 + 1], a[s * 32 + k * 4 + 2],
                                 a[s * 32 + k * 4 + 3], db + k * 128);
            }
            wg_commit();
            if (s > 0) {
                wg_wait<1>();
                c.release(prev);
            }
            prev = r.slot;
            r.next();
        }
    }
    wg_wait<0>();
    c.release(prev);
    pin(d);
}
__device__ __forceinline__ void st128(uint4* p, uint32_t x, uint32_t y, uint32_t z, uint32_t w) {
    asm volatile(
        "{\n.reg .b64 lo, hi;\n.reg .b128 t;\nmov.b64 lo, {%1, %2};\nmov.b64 hi, {%3, %4};\nmov.b128 t, {lo, hi};\n"
        "st.relaxed.gpu.global.b128 [%0], t;\n}" ::"l"(p),
        "r"(x), "r"(y), "r"(z), "r"(w)
        : "memory");
}
__device__ __forceinline__ uint4 ld128(const uint4* p) {
    uint4 r;
    asm volatile(
        "{\n.reg .b64 lo, hi;\n.reg .b128 t;\nld.relaxed.gpu.global.b128 t, [%4];\nmov.b128 {lo, hi}, t;\n"
        "mov.b64 {%0, %1}, lo;\nmov.b64 {%2, %3}, hi;\n}"
        : "=r"(r.x), "=r"(r.y), "=r"(r.z), "=r"(r.w)
        : "l"(p));
    return r;
}
__device__ __forceinline__ void st64(void* p, uint32_t x, uint32_t y) {
    asm volatile("{\n.reg .b64 t;\nmov.b64 t, {%1, %2};\nst.relaxed.gpu.global.b64 [%0], t;\n}" ::"l"(p), "r"(x), "r"(y)
                 : "memory");
}
__device__ __forceinline__ uint2 ld64(const void* p) {
    uint2 r;
    asm volatile("{\n.reg .b64 t;\nld.relaxed.gpu.global.b64 t, [%2];\nmov.b64 {%0, %1}, t;\n}"
                 : "=r"(r.x), "=r"(r.y)
                 : "l"(p));
    return r;
}
__device__ __forceinline__ void rows_load(uint32_t sbase, const CUtensorMap* m, int row0) {
    mbar_expect_tx(sbase + OFF_XBAR, 16 * DM * 2);
    asm volatile(
        "cp.async.bulk.tensor.3d.shared::cluster.global.mbarrier::complete_tx::bytes [%0], [%1, {%3, %3, %4}], [%2];" ::"r"(
            sbase + OFF_ROWS),
        "l"(m), "r"(sbase + OFF_XBAR), "r"(0), "r"(row0)
        : "memory");
}
__device__ __forceinline__ void rows_store(uint32_t sbase, const CUtensorMap* m, int row0) {
    asm volatile("cp.async.bulk.tensor.3d.global.shared::cta.bulk_group [%0, {%2, %2, %3}], [%1];" ::"l"(m),
                 "r"(sbase + OFF_ROWS), "r"(0), "r"(row0)
                 : "memory");
    asm volatile("cp.async.bulk.commit_group;" ::: "memory");
}
__device__ __forceinline__ void rows_store_wait() { asm volatile("cp.async.bulk.wait_group 0;" ::: "memory"); }

__device__ __forceinline__ constexpr int own_col(int j) { return j < 8 ? (j >> 1) * 128 + (j & 1) * 8 : 512; }
__device__ __forceinline__ void row_reduce(float& s0, float& s1, uint32_t red, int warp, int lane) {
    s0 += __shfl_xor_sync(0xffffffffu, s0, 1);
    s1 += __shfl_xor_sync(0xffffffffu, s1, 1);
    s0 += __shfl_xor_sync(0xffffffffu, s0, 2);
    s1 += __shfl_xor_sync(0xffffffffu, s1, 2);
    if ((lane & 3) == 0) {
        sts32f(red + (warp * 16 + (lane >> 2)) * 4, s0);
        sts32f(red + (warp * 16 + 8 + (lane >> 2)) * 4, s1);
    }
    bar_sync(3, 256);
    s0 = 0.f;
    s1 = 0.f;
#pragma unroll
    for (int w = 0; w < 8; w++) {
        s0 += lds32f(red + (w * 16 + (lane >> 2)) * 4);
        s1 += lds32f(red + (w * 16 + 8 + (lane >> 2)) * 4);
    }
}
__device__ __forceinline__ void layernorm_rows(float (&v)[36], uint32_t red, int warp, int lane) {
    float s0 = 0.f, s1 = 0.f;
#pragma unroll
    for (int j = 0; j < 9; j++) {
        s0 += v[4 * j] + v[4 * j + 1];
        s1 += v[4 * j + 2] + v[4 * j + 3];
    }
    row_reduce(s0, s1, red, warp, lane);
    const float m0 = s0 * (1.f / DM), m1 = s1 * (1.f / DM);
    s0 = 0.f;
    s1 = 0.f;
#pragma unroll
    for (int j = 0; j < 9; j++) {
        v[4 * j] -= m0;
        v[4 * j + 1] -= m0;
        v[4 * j + 2] -= m1;
        v[4 * j + 3] -= m1;
        s0 += v[4 * j] * v[4 * j] + v[4 * j + 1] * v[4 * j + 1];
        s1 += v[4 * j + 2] * v[4 * j + 2] + v[4 * j + 3] * v[4 * j + 3];
    }
    row_reduce(s0, s1, red + 512, warp, lane);
    const float r0 = rsqrtf(s0 * (1.f / DM) + 1e-5f), r1 = rsqrtf(s1 * (1.f / DM) + 1e-5f);
#pragma unroll
    for (int j = 0; j < 9; j++) {
        v[4 * j] *= r0;
        v[4 * j + 1] *= r0;
        v[4 * j + 2] *= r1;
        v[4 * j + 3] *= r1;
    }
}
__device__ __forceinline__ void mod_to_smem(uint32_t dst, const uint32_t* src, uint32_t tag) {
    const uint32_t t0 = clk32();
    uint4 u;
    while (true) {
        u = ld128(reinterpret_cast<const uint4*>(src));
        const uint32_t bad = ((u.x ^ tag) | (u.y ^ tag) | (u.z ^ tag) | (u.w ^ tag)) & 0xffffu;
        if (__all_sync(0xffffffffu, bad == 0) || clk32() - t0 > WAIT_LIMIT) break;
        __nanosleep(64);
    }
    sts128(dst, u.x & 0xffff0000u, u.y & 0xffff0000u, u.z & 0xffff0000u, u.w & 0xffff0000u);
}
__device__ __forceinline__ void lds_mod(float (&m)[18], uint32_t src  , int warp) {
#pragma unroll
    for (int j = 0; j < 9; j++)
        asm volatile("ld.shared.v2.f32 {%0,%1}, [%2];"
                     : "=f"(m[2 * j]), "=f"(m[2 * j + 1])
                     : "r"(src + own_col(j) * 4 - (j == 8 ? warp * 32 : 0))
                     : "memory");
}
__device__ __forceinline__ void modulate_store(const float (&v)[36], const float (&shift)[18], const float (&scale)[18],
                                               uint4* hbuf  , int warp, int lane) {
    uint32_t o[18];
#pragma unroll
    for (int j = 0; j < 9; j++) {
        const uint32_t cc = pack_bf16(1.f + scale[2 * j], 1.f + scale[2 * j + 1]);
        const float c0 = bf_lo(cc), c1 = bf_hi(cc);
        o[2 * j] = max(pack_bf16(fmaf(v[4 * j], c0, shift[2 * j]), fmaf(v[4 * j + 1], c1, shift[2 * j + 1])), 1u);
        o[2 * j + 1] = max(pack_bf16(fmaf(v[4 * j + 2], c0, shift[2 * j]), fmaf(v[4 * j + 3], c1, shift[2 * j + 1])), 1u);
    }
#pragma unroll
    for (int i = 0; i < 4; i++) st128(hbuf + (i * 8 + warp) * 32 + lane, o[4 * i], o[4 * i + 1], o[4 * i + 2], o[4 * i + 3]);
    st64(reinterpret_cast<uint2*>(hbuf + 32 * 32) + warp * 32 + lane, o[16], o[17]);
}
__device__ __forceinline__ void sum_partials(float (&v)[36], const uint4* src  , uint32_t tag) {
    const uint32_t t0 = clk32();
    while (true) {
        uint4 t[8][4];
#pragma unroll
        for (int s = 0; s < 8; s++)
#pragma unroll
            for (int i = 0; i < 4; i++) t[s][i] = ld128(src + (s * 36 + i * 8) * 32);
        uint32_t bad = 0;
#pragma unroll
        for (int i = 0; i < 32; i++) v[i] = 0.f;
#pragma unroll
        for (int s = 0; s < 8; s++)
#pragma unroll
            for (int i = 0; i < 4; i++) {
                bad |= t[s][i].x ^ tag;
                v[8 * i] += bf_lo(t[s][i].x);
                v[8 * i + 1] += bf_hi(t[s][i].x);
                v[8 * i + 2] += bf_lo(t[s][i].y);
                v[8 * i + 3] += bf_hi(t[s][i].y);
                v[8 * i + 4] += bf_lo(t[s][i].z);
                v[8 * i + 5] += bf_hi(t[s][i].z);
                v[8 * i + 6] += bf_lo(t[s][i].w);
                v[8 * i + 7] += bf_hi(t[s][i].w);
            }
        if (__all_sync(0xffffffffu, (bad & 1u) == 0) || clk32() - t0 > WAIT_LIMIT) break;
    }
}
__device__ __forceinline__ void sum_tail(float (&v)[36], const uint2* src  , uint32_t tag) {
    const uint32_t t0 = clk32();
    while (true) {
        uint2 t[8];
#pragma unroll
        for (int s = 0; s < 8; s++) t[s] = ld64(src + s * 72 * 32);
        uint32_t bad = 0;
        v[32] = v[33] = v[34] = v[35] = 0.f;
#pragma unroll
        for (int s = 0; s < 8; s++) {
            bad |= t[s].x ^ tag;
            v[32] += bf_lo(t[s].x);
            v[33] += bf_hi(t[s].x);
            v[34] += bf_lo(t[s].y);
            v[35] += bf_hi(t[s].y);
        }
        if (__all_sync(0xffffffffu, (bad & 1u) == 0) || clk32() - t0 > WAIT_LIMIT) break;
    }
}
__device__ __forceinline__ void poll_tail(uint32_t (&a)[144], const uint2* src  ) {
    const uint32_t t0 = clk32();
    while (true) {
        uint32_t m = 0xffffffffu;
#pragma unroll
        for (int j = 0; j < 8; j++) {
            const uint2 t = ld64(src + j * 32);
            a[128 + 2 * j] = t.x;
            a[129 + 2 * j] = t.y;
        }
#pragma unroll
        for (int j = 0; j < 16; j++) m = min(m, a[128 + j]);
        if (__all_sync(0xffffffffu, m != 0) || clk32() - t0 > WAIT_LIMIT) break;
    }
}
template <int K0, int K1>
__device__ __forceinline__ void poll_frags(uint32_t (&a)[144], const uint4* src  , bool kick) {
    const uint32_t t0 = clk32();
    while (true) {
#pragma unroll
        for (int k = K0; k < K1; k++)
            asm volatile("ld.relaxed.gpu.global.v4.u32 {%0,%1,%2,%3}, [%4];"
                         : "=r"(a[4 * k]), "=r"(a[4 * k + 1]), "=r"(a[4 * k + 2]), "=r"(a[4 * k + 3])
                         : "l"(src + k * 32));
        if (kick) bar_arrive(5, 256);
        kick = false;
        uint32_t m0 = a[4 * K0], m1 = a[4 * K0 + 1];
#pragma unroll
        for (int i = 4 * K0 + 2; i < 4 * K1; i += 2) {
            m0 = min(m0, a[i]);
            m1 = min(m1, a[i + 1]);
        }
        if (__all_sync(0xffffffffu, min(m0, m1) != 0) || clk32() - t0 > WAIT_LIMIT) break;
    }
}

constexpr float SM_SCALE = 0.08838834764831845f * 1.4426950408889634f;
constexpr float SM_HI = 1.2089258e24f;
constexpr float SM_LO = 9.0949470e-13f;
__device__ __forceinline__ void qk_step(float (&s)[32], const uint32_t (&q)[32], uint64_t dk) {
#pragma unroll
    for (int k = 0; k < 8; k++) {
        if (k == 0)
            wgmma_n64_z<0>(s, q[0], q[1], q[2], q[3], dk);
        else
            wgmma_n64<0>(s, q[4 * k], q[4 * k + 1], q[4 * k + 2], q[4 * k + 3], dk + (k >> 2) * 512 + (k & 3) * 2);
    }
}
__device__ __forceinline__ void pv_step(float (&o)[64], const uint32_t (&p)[16], uint64_t dv, int acc) {
#pragma unroll
    for (int k = 0; k < 4; k++)
        wgmma_n128<1>(o, p[4 * k], p[4 * k + 1], p[4 * k + 2], p[4 * k + 3], dv + k * 128, k != 0 ? 1 : acc);
}
template <bool SHIFT>
__device__ __forceinline__ void exp_step(const float (&s)[32], uint32_t (&p)[16], float n0, float n1, float& s0,
                                         float& s1) {
#pragma unroll
    for (int i = 0; i < 8; i++) {
        const float e0 = ex2(SHIFT ? s[4 * i] + n0 : s[4 * i]), e1 = ex2(SHIFT ? s[4 * i + 1] + n0 : s[4 * i + 1]);
        const float e2 = ex2(SHIFT ? s[4 * i + 2] + n1 : s[4 * i + 2]), e3 = ex2(SHIFT ? s[4 * i + 3] + n1 : s[4 * i + 3]);
        if (i == 0) {
            s0 = e0 + e1;
            s1 = e2 + e3;
        } else {
            s0 += e0 + e1;
            s1 += e2 + e3;
        }
        p[2 * i] = pack_bf16(e0, e1);
        p[2 * i + 1] = pack_bf16(e2, e3);
    }
}
__device__ __forceinline__ void row_max(const float (&sa)[32], const float (&sb)[32], float& x0, float& x1) {
    float xa[8];
#pragma unroll
    for (int i = 0; i < 8; i++) xa[i] = fmaxf(sa[i], sb[i]);
#pragma unroll
    for (int k = 1; k < 4; k++)
#pragma unroll
        for (int i = 0; i < 8; i++) xa[i] = fmaxf(xa[i], fmaxf(sa[8 * k + i], sb[8 * k + i]));
    x0 = fmaxf(fmaxf(xa[0], xa[1]), fmaxf(xa[4], xa[5]));
    x1 = fmaxf(fmaxf(xa[2], xa[3]), fmaxf(xa[6], xa[7]));
    x0 = fmaxf(x0, __shfl_xor_sync(0xffffffffu, x0, 1));
    x1 = fmaxf(x1, __shfl_xor_sync(0xffffffffu, x1, 1));
    x0 = fmaxf(x0, __shfl_xor_sync(0xffffffffu, x0, 2));
    x1 = fmaxf(x1, __shfl_xor_sync(0xffffffffu, x1, 2));
}
__device__ __forceinline__ void inv_row_sums(float l0, float l1, float& i0, float& i1) {
    l0 += __shfl_xor_sync(0xffffffffu, l0, 1);
    l1 += __shfl_xor_sync(0xffffffffu, l1, 1);
    l0 += __shfl_xor_sync(0xffffffffu, l0, 2);
    l1 += __shfl_xor_sync(0xffffffffu, l1, 2);
    i0 = rcp(l0);
    i1 = rcp(l1);
}

__device__ __forceinline__ float silu_bf16(unsigned short c) {
    const float cv = bf_lo(c);
    return round_bf16(cv * rcp(1.f + ex2(-1.4426950408889634f * cv)));
}
__device__ __forceinline__ void st_mod(uint32_t* p, float v, uint32_t tag) {
    asm volatile("st.relaxed.gpu.global.u32 [%0], %1;" ::"l"(p), "r"(__float_as_uint(round_bf16(v)) | tag)
                 : "memory");
}
__device__ __forceinline__ void mod_block(const uint4 (&w)[5], const float (&sc)[5], uint32_t* dst, uint32_t red,
                                          int warp, int lane, uint32_t tag) {
    float acc[8];
#pragma unroll
    for (int e = 0; e < 8; e++) acc[e] = 0.f;
#pragma unroll
    for (int i = 0; i < 5; i++) {
        acc[0] = fmaf(sc[i], bf_lo(w[i].x), acc[0]);
        acc[1] = fmaf(sc[i], bf_hi(w[i].x), acc[1]);
        acc[2] = fmaf(sc[i], bf_lo(w[i].y), acc[2]);
        acc[3] = fmaf(sc[i], bf_hi(w[i].y), acc[3]);
        acc[4] = fmaf(sc[i], bf_lo(w[i].z), acc[4]);
        acc[5] = fmaf(sc[i], bf_hi(w[i].z), acc[5]);
        acc[6] = fmaf(sc[i], bf_lo(w[i].w), acc[6]);
        acc[7] = fmaf(sc[i], bf_hi(w[i].w), acc[7]);
    }
#pragma unroll
    for (int o = 2; o < 32; o <<= 1)
#pragma unroll
        for (int e = 0; e < 8; e++) acc[e] += __shfl_xor_sync(0xffffffffu, acc[e], o);
    if (lane < 2) {
#pragma unroll
        for (int e = 0; e < 8; e++) sts32f(red + (warp * 16 + lane * 8 + e) * 4, acc[e]);
    }
    bar_sync(3, 256);
    if (warp == 0 && lane < 16) {
        float s = 0.f;
#pragma unroll
        for (int w8 = 0; w8 < 8; w8++) s += lds32f(red + (w8 * 16 + lane) * 4);
        st_mod(dst + lane, s, tag);
    }
}

__global__ void __cluster_dims__(2, 1, 1) __launch_bounds__(384, 1)
    fused_block_kernel(const __grid_constant__ Params maps) {
    extern __shared__ uint8_t smem_raw[];
    uint32_t sbase = (smem_u32(smem_raw) + 1023u) & ~1023u;
    asm volatile("" : "+r"(sbase));
    const int b = blockIdx.x;
    const int rank = b & 1;
    const int mt = ((b >> 1) & 7) * 2 + rank;
    const int g = b >> 4;
    const int warp = __shfl_sync(0xffffffffu, threadIdx.x >> 5, 0);
    const int lane = threadIdx.x & 31;
    Scratch* const sc_ = maps.sc;
    const __nv_bfloat16* const wmod = maps.wmod;
    const __nv_bfloat16* const cvec = maps.cvec;

    if (threadIdx.x == 0) {
        mbar_init(sbase + OFF_WBAR, 1);
        asm volatile("fence.mbarrier_init.release.cluster;" ::: "memory");
        if (b < 72) {
            mbar_expect_tx(sbase + OFF_WBAR, DM * 32);
#pragma unroll
            for (int i = 0; i < 3; i++)
                asm volatile(
                    "cp.async.bulk.tensor.2d.shared::cluster.global.mbarrier::complete_tx::bytes"
                    " [%0], [%1, {%3, %4}], [%2];" ::"r"(sbase + OFF_WBLK + i * 192 * 32),
                    "l"(&maps.wm), "r"(sbase + OFF_WBAR), "r"(b * 16), "r"(i * 192)
                    : "memory");
        }
    } else if (threadIdx.x == 32) {
        mbar_init(sbase + OFF_XBAR, 1);
        asm volatile("fence.mbarrier_init.release.cluster;" ::: "memory");
        rows_load(sbase, &maps.rx, (mt * 8 + g) * 16);
    } else if (threadIdx.x >= 64 && threadIdx.x < 64 + 81) {
        const int li = b * 81 + threadIdx.x - 64;
        asm volatile("prefetch.global.L2 [%0];" ::"l"((const char*)wmod + (size_t)(li / 18) * (12 * DM) + (li % 18) * 128));
    }
    __syncwarp();
    unsigned short cu[5];
#pragma unroll
    for (int i = 0; i < 5; i++)
        asm volatile("ld.global.nc.u16 %0, [%1];"
                     : "=h"(cu[i])
                     : "l"(cvec + min((int)(threadIdx.x >> 1) + 128 * i, DM - 1)));
    uint32_t epoch;
    asm volatile("ld.relaxed.gpu.global.u32 %0, [%1];" : "=r"(epoch) : "l"(&sc_->epoch[lane]));

    if (warp >= 8) {
        asm volatile("setmaxnreg.dec.sync.aligned.u32 24;");
        if (warp == 8 && lane == 0) {
#pragma unroll
            for (int i = 0; i < 8; i++) {
                mbar_init(sbase + OFF_FULL + i * 8, 1);
                mbar_init(sbase + OFF_EMPTY + i * 8, 4);
            }
            asm volatile("fence.mbarrier_init.release.cluster;" ::: "memory");
            asm volatile("barrier.cluster.arrive.relaxed;\nbarrier.cluster.wait;" ::: "memory");
            uint32_t slot = 0, phase = 1;
            const uint32_t dst0 = sbase + rank * BOX_BYTES;
            auto acquire = [&](uint32_t bytes) {
                mbar_wait(sbase + OFF_EMPTY + slot * 8, phase);
                mbar_expect_tx(sbase + OFF_FULL + slot * 8, bytes);
            };
            auto adv8 = [&]() {
                if (++slot == 8) {
                    slot = 0;
                    phase ^= 1;
                }
            };
#pragma unroll 1
            for (int hq = 0; hq < 4; hq++) {
                const int col = (g * 4 + ((hq + 1) & 3)) * 128 + rank * 64;
                if (hq == 2) {
                    l2_prefetch(maps.kc + (size_t)(g * 4 * 2048 + (b & 15) * 64) * 128, SLOT_BYTES);
                    l2_prefetch(maps.vc + (size_t)(g * 4 * 2048 + (b & 15) * 64) * 128, SLOT_BYTES);
                }
#pragma unroll 1
                for (int kc = 0; kc < 9; kc++) {
                    acquire(SLOT_BYTES);
                    tma_mc(dst0 + slot * SLOT_BYTES, &maps.wq, col, kc * 64, sbase + OFF_FULL + slot * 8);
                    adv8();
                }
            }
            const int row0 = g * 4 * 2048;
#pragma unroll 1
            for (int n = 0; n < 128; n++) {
                if (n < 4) mbar_wait(sbase + OFF_EMPTY + (slot + 1) * 8, phase);
                acquire(2 * SLOT_BYTES);
                const uint32_t bar = sbase + OFF_FULL + slot * 8;
                const int r0 = n == 0 ? 0 : (n == 127 ? 126 : n + 1);
                const int r1 = n == 0 ? 1 : (n == 127 ? 127 : n - 1);
                tma_mc(dst0 + slot * SLOT_BYTES, n == 127 ? &maps.v : &maps.k, rank * 64, row0 + r0 * 64, bar);
                tma_mc(dst0 + (slot + 1) * SLOT_BYTES, n == 0 ? &maps.k : &maps.v, rank * 64, row0 + r1 * 64, bar);
                adv8();
                adv8();
                if (n >= 96 && n < 96 + 10) {
                    const int i = n - 96;
                    if (i < 9) {
                        l2_prefetch((const char*)maps.wg_p + (size_t)b * 41472 + i * 4608, 4608);
                        l2_prefetch((const char*)maps.wu_p + (size_t)b * 41472 + i * 4608, 4608);
                        l2_prefetch((const char*)maps.wd_p + (size_t)b * 41472 + i * 4608, 4608);
                        l2_prefetch((const char*)maps.wo_p + (size_t)b * 36864 + i * 4096, 4096);
                    }
                }
                const int u = n + KV_AHEAD;
                if (u < 128 && (u & 15) == (b & 15)) {
                    l2_prefetch(maps.kc + (size_t)(row0 + u * 64) * 128, SLOT_BYTES);
                    l2_prefetch(maps.vc + (size_t)(row0 + u * 64) * 128, SLOT_BYTES);
                }
            }
#pragma unroll 1
            for (int p = 0; p < 4; p++)
#pragma unroll 1
                for (int kc = 0; kc < 8; kc++) {
                    acquire(SLOT_BYTES);
                    tma_mc(dst0 + slot * SLOT_BYTES, &maps.wo, p * 128 + rank * 64, g * 512 + kc * 64,
                           sbase + OFF_FULL + slot * 8);
                    adv8();
                }
#pragma unroll 1
            for (int kc = 0; kc < 4; kc++) {
                acquire(SLOT_BYTES);
                tma_mc(dst0 + slot * SLOT_BYTES, &maps.wo, 512, g * 512 + kc * 128 + rank * 64,
                       sbase + OFF_FULL + slot * 8);
                adv8();
            }
            const CUtensorMap* mg = rank ? &maps.wu : &maps.wg;
#pragma unroll 1
            for (int ch = 0; ch < 9; ch++)
#pragma unroll 1
                for (int kc = 0; kc < 9; kc++) {
                    acquire(SLOT_BYTES);
                    tma_mc(dst0 + slot * SLOT_BYTES, mg, g * 576 + ch * 64, kc * 64, sbase + OFF_FULL + slot * 8);
                    adv8();
                }
#pragma unroll 1
            for (int p = 0; p < 4; p++)
#pragma unroll 1
                for (int kc = 2; kc < 11; kc++) {
                    acquire(SLOT_BYTES);
                    tma_mc(dst0 + slot * SLOT_BYTES, &maps.wd, p * 128 + rank * 64, g * 576 + (kc < 9 ? kc : kc - 9) * 64,
                           sbase + OFF_FULL + slot * 8);
                    adv8();
                }
#pragma unroll 1
            for (int i = 0; i < 5; i++) {
                acquire(i < 4 ? SLOT_BYTES : BOX_BYTES);
                const int kc = 2 * i + rank + 2;
                if (i < 4 || rank == 0)
                    tma_mc(dst0 + slot * SLOT_BYTES, &maps.wd, 512, g * 576 + (kc < 9 ? kc : kc - 9) * 64,
                           sbase + OFF_FULL + slot * 8);
                adv8();
            }
        } else if (warp == 11) {
            asm volatile("barrier.cluster.arrive.relaxed.aligned;" ::: "memory");
            uint4* hz = sc_->h[(epoch & 1) ^ 1][0] + (size_t)b * 72 * 32 + lane;
            bar_sync(6, 160);
#pragma unroll 1
            for (int i = 0; i < 72; i++) {
                hz[i * 32] = make_uint4(0, 0, 0, 0);
                __nanosleep(200);
            }
        } else if (warp == 9 || warp == 10) {
            asm volatile("barrier.cluster.arrive.relaxed.aligned;" ::: "memory");
            const uint32_t tag = (epoch + 1) & 0xffffu;
            bar_sync(4, 320);
            if (warp == 10 && lane < 9) l2_prefetch((const char*)maps.wq_p + (size_t)b * 36864 + lane * 4096, 4096);
            const int blk = warp == 9 ? 72 + b : 200 + b;
            if (blk < 216) {
                float acc[8];
#pragma unroll
                for (int e = 0; e < 8; e++) acc[e] = 0.f;
                const uint4* wp = reinterpret_cast<const uint4*>(wmod + (size_t)(lane >> 1) * (6 * DM) + blk * 16) + (lane & 1);
                const unsigned short* cp = reinterpret_cast<const unsigned short*>(cvec) + (lane >> 1);
#pragma unroll 1
                for (int i = 0; i < 36; i++) {
                    const uint4 w = __ldg(wp + (size_t)i * (16 * 6 * DM / 8));
                    const float sc = silu_bf16(__ldg(cp + i * 16));
                    acc[0] = fmaf(sc, bf_lo(w.x), acc[0]);
                    acc[1] = fmaf(sc, bf_hi(w.x), acc[1]);
                    acc[2] = fmaf(sc, bf_lo(w.y), acc[2]);
                    acc[3] = fmaf(sc, bf_hi(w.y), acc[3]);
                    acc[4] = fmaf(sc, bf_lo(w.z), acc[4]);
                    acc[5] = fmaf(sc, bf_hi(w.z), acc[5]);
                    acc[6] = fmaf(sc, bf_lo(w.w), acc[6]);
                    acc[7] = fmaf(sc, bf_hi(w.w), acc[7]);
                }
#pragma unroll
                for (int o = 2; o < 32; o <<= 1)
#pragma unroll
                    for (int e = 0; e < 8; e++) acc[e] += __shfl_xor_sync(0xffffffffu, acc[e], o);
                if (lane < 2) {
#pragma unroll
                    for (int e = 0; e < 8; e++) st_mod(sc_->mod + blk * 16 + lane * 8 + e, acc[e], tag);
                }
            }
            if (warp == 9) {
#pragma unroll 1
                for (int st = 1; st <= 2; st++) {
                    bar_sync(7, 160);
                    const uint32_t* src = sc_->mod + (st * 3 - 1) * DM;
                    const int n = st == 1 ? 3 * DM : DM;
#pragma unroll 1
                    for (int i = lane * 4; i < n + 127 - ((n + 127) & 127); i += 128)
                        mod_to_smem(sbase + OFF_MODT + min(i, n - 4) * 4, src + min(i, n - 4), tag);
                    __syncwarp();
                    if (lane == 0) rows_load(sbase, st == 1 ? &maps.rx : &maps.rx2, (mt * 8 + g) * 16);
                    if (st == 1) {
                        bar_sync(7, 160);
                        if (lane == 0) {
                            rows_store(sbase, &maps.rx2, (mt * 8 + g) * 16);
                            rows_store_wait();
                        }
                        __syncwarp();
                        bar_arrive(10, 160);
                    }
                }
            }
        }
    } else {
        asm volatile("setmaxnreg.inc.sync.aligned.u32 240;");
        const int wg = warp >> 2;
        const int tid = threadIdx.x;
        Ctx cx;
        cx.sbase = sbase;
        cx.wg = wg;
        if (wg == 1) bar_arrive(8, 256);
        cx.rel_cta = (lane == 0 && (warp & 3) < 2) ? (warp & 3) : 2;
        const uint32_t red = sbase + OFF_RED;
        const int own = mt * 8 + g;
        const int wown = mt * 8 + warp;
        PROF(0);
        PROFG(30);
        PROFR(17);
        {
            const int r0 = tid >> 1;
            PROFR(18);
            asm volatile("barrier.cluster.arrive.relaxed.aligned;" ::: "memory");
            bar_sync(3, 256);
            if (b < 72) {
                float sc[5];
                uint4 w1[5];
#pragma unroll
                for (int i = 0; i < 5; i++) sc[i] = (r0 + 128 * i < DM) ? silu_bf16(cu[i]) : 0.f;
                PROFR(19);
                mbar_wait(sbase + OFF_WBAR, 0);
                PROFR(20);
#pragma unroll
                for (int i = 0; i < 5; i++)
                    lds128(sbase + OFF_WBLK + (i < 4 ? tid + i * 256 : 1024 + (tid & 127)) * 16, w1[i].x, w1[i].y, w1[i].z, w1[i].w);
                mod_block(w1, sc, sc_->mod + b * 16, red + 1024, warp, lane, (epoch + 1) & 0xffffu);
            }
            PROFR(21);
        }

        Ring ring{0u, 0u};
        int stage = 0;
        asm volatile("" : "+r"(stage));
#pragma unroll 1
        for (;; stage++) {
            int tid, lane;
            asm volatile("mov.u32 %0, %%tid.x;" : "=r"(tid));
            lane = tid & 31;
            {
                float v[36];
                const uint32_t modt = sbase + OFF_MODT + (warp * 16 + (lane & 3) * 2) * 4;
                if (stage == 0) {
#pragma unroll
                    for (int i = 0; i < 36; i++) v[i] = 0.f;
                } else {
                    const uint4* psrc = sc_->part + (size_t)own * 8 * 36 * 32;
                    sum_partials(v, psrc + tid, stage & 1);
                    PROF(stage == 1 ? 8 : 15);
                    sum_tail(v, reinterpret_cast<const uint2*>(psrc + 32 * 32) + tid, stage & 1);
                }
                mbar_wait(sbase + OFF_XBAR, stage & 1);
                if (stage == 0) PROFR(22);
                {
                    const float gs = stage == 2 ? 0.5f : 1.f;
                    float gate[18];
                    lds_mod(gate, modt, warp);
                    const int r = lane >> 2;
                    const uint32_t rows = sbase + OFF_ROWS + r * (DM * 2) + (lane & 3) * 4;
#pragma unroll
                    for (int j = 0; j < 9; j++) {
                        const int ch = j < 8 ? (j >> 1) * 2 + (warp >> 2) : 8, c16 = j < 8 ? (warp & 3) * 2 + (j & 1) : warp;
                        const uint32_t ad = rows + ch * 128 + ((c16 ^ ((r + ch) & 7)) << 4);
                        const uint32_t u0 = __float_as_uint(lds32f(ad)), u1 = __float_as_uint(lds32f(ad + 8 * DM * 2));
                        const float g0 = stage ? gate[2 * j] * gs : 0.f, g1 = stage ? gate[2 * j + 1] * gs : 0.f;
                        v[4 * j] = fmaf(g0, v[4 * j], bf_lo(u0));
                        v[4 * j + 1] = fmaf(g1, v[4 * j + 1], bf_hi(u0));
                        v[4 * j + 2] = fmaf(g0, v[4 * j + 2], bf_lo(u1));
                        v[4 * j + 3] = fmaf(g1, v[4 * j + 3], bf_hi(u1));
                        sts32f(ad, __uint_as_float(pack_bf16(v[4 * j], v[4 * j + 1])));
                        sts32f(ad + 8 * DM * 2, __uint_as_float(pack_bf16(v[4 * j + 2], v[4 * j + 3])));
                    }
                    asm volatile("fence.proxy.async.shared::cta;" ::: "memory");
                }
                if (stage == 2) break;
                PROF(stage == 0 ? 1 : 9);
                layernorm_rows(v, red, warp, lane);
                if (stage == 0) PROFR(27);
                if (stage == 0) {
                    const uint32_t tag = (epoch + 1) & 0xffffu;
                    mod_to_smem(sbase + OFF_MODT + (DM + tid * 4) * 4, sc_->mod + tid * 4, tag);
                    if (warp == 7) mod_to_smem(sbase + OFF_MODT + (DM + 1024 + lane * 4) * 4, sc_->mod + 1024 + lane * 4, tag);
                    bar_sync(3, 256);
                    bar_arrive(4, 320);
                }
                float shift[18], scale[18];
                lds_mod(shift, modt + DM * 4, warp);
                lds_mod(scale, modt + 2 * DM * 4, warp);
                if (stage == 0) PROFR(28);
                PROF(stage == 0 ? 2 : 10);
                modulate_store(v, shift, scale, sc_->h[epoch & 1][stage] + (size_t)own * 36 * 32, warp, lane);
                if (stage == 0) asm volatile("barrier.cluster.wait.aligned;" ::: "memory");
            }

            const uint32_t spill = sbase + 8 * SLOT_BYTES + wg * 3 * SLOT_BYTES + (tid & 127) * 16;
            uint32_t a[144];
            PROF(stage == 0 ? 3 : 11);
            {
                const uint4* hsrc = sc_->h[epoch & 1][stage] + (size_t)wown * 36 * 32 + lane;
                poll_tail(a, reinterpret_cast<const uint2*>(hsrc - lane + 32 * 32) + lane);
                PROF(stage == 0 ? 4 : 12);
                if (stage == 1) PROFG(25);
                TG(stage * 32 + 30);
                if (wg == 1) bar_sync(5, 256);
                poll_frags<0, 32>(a, hsrc, wg == 0);
            }
            uint4* hhbuf = sc_->hh + (size_t)b * 8 * 256 + tid;
            float d[64];
#pragma unroll 1
            for (int ch = 0;; ch++) {
                TG(stage * 32 + ch * 2);
                gemm_n128(d, a, cx, ring, true);
                TG(stage * 32 + ch * 2 + 1);
                if (stage == 0) {
#pragma unroll
                    for (int i = 0; i < 64; i++) d[i] *= SM_SCALE;
                    if (ch == 3) break;
#pragma unroll
                    for (int v = 0; v < 8; v++)
                        sts128(spill + (ch * 8 + v) * 2048, pack_bf16(d[8 * v], d[8 * v + 1]),
                               pack_bf16(d[8 * v + 2], d[8 * v + 3]), pack_bf16(d[8 * v + 4], d[8 * v + 5]),
                               pack_bf16(d[8 * v + 6], d[8 * v + 7]));
                } else {
#pragma unroll
                    for (int i = 0; i < 32; i++) {
                        const float gv = d[i], gu = gv * d[32 + i];
                        const float z = gv * fmaf(gv * gv, 0.7978845608028654f * 0.044715f, 0.7978845608028654f);
                        d[i] = fmaf(gu, tanh_fast(z), gu);
                    }
                    if (ch == 8) break;
                    if (wg == 0) {
                        if (ch == 0) bar_arrive(7, 160);
                        if (ch == 2) bar_sync(10, 160);
                    }
#pragma unroll
                    for (int v = 0; v < 4; v++) {
                        const uint4 h4 = make_uint4(pack_bf16(d[8 * v], d[8 * v + 1]), pack_bf16(d[8 * v + 2], d[8 * v + 3]),
                                                    pack_bf16(d[8 * v + 4], d[8 * v + 5]), pack_bf16(d[8 * v + 6], d[8 * v + 7]));
                        if (ch < 2)
                            __stcg(hhbuf + (ch * 4 + v) * 256, h4);
                        else
                            sts128(spill + ((ch - 2) * 4 + v) * 2048, h4.x, h4.y, h4.z, h4.w);
                    }
                }
            }
            if (stage == 0) {
                uint32_t q[32];
#pragma unroll
                for (int i = 0; i < 32; i++) q[i] = pack_bf16(d[2 * i], d[2 * i + 1]);
                PROF(5);
                PROFG(23);
                if (wg == 0) bar_arrive(6, 160);
                {
                    float o[64], sa[32], sb[32];
                    uint32_t pa[16], pb[16];
#pragma unroll
                    for (int i = 0; i < 64; i++) o[i] = 0.f;
                    float n0 = 0.f, n1 = 0.f, l0 = 1.f, l1 = 1.f;
                    bool shifted = false;
                    const uint64_t dbase = desc_of(sbase);
                    const uint64_t dbk = dbase - (511u << 16);
                    const int my_bar = 1 + wg, other_bar = 2 - wg;

                    auto softmax_a = [&](bool first, float& s0, float& s1) {
                        if (first) {
                            shifted = false;
                            n0 = n1 = 0.f;
                            l0 = l1 = 0.f;
                        }
                        if (shifted)
                            exp_step<true>(sa, pa, n0, n1, s0, s1);
                        else
                            exp_step<false>(sa, pa, n0, n1, s0, s1);
                    };
                    auto softmax_b = [&](bool first, float s0, float s1) {
                        float u0, u1;
                        if (shifted)
                            exp_step<true>(sb, pb, n0, n1, u0, u1);
                        else
                            exp_step<false>(sb, pb, n0, n1, u0, u1);
                        s0 += u0;
                        s1 += u1;
                        bool bad = !(fmaxf(s0, s1) <= SM_HI);
                        if (first) {
                            float r0 = s0 + __shfl_xor_sync(0xffffffffu, s0, 1), r1 = s1 + __shfl_xor_sync(0xffffffffu, s1, 1);
                            r0 += __shfl_xor_sync(0xffffffffu, r0, 2);
                            r1 += __shfl_xor_sync(0xffffffffu, r1, 2);
                            bad = bad || !(fminf(r0, r1) >= SM_LO);
                        }
                        if (__any_sync(0xffffffffu, bad)) {
                            float x0, x1;
                            row_max(sa, sb, x0, x1);
                            x0 = -x0;
                            x1 = -x1;
                            if (!first) {
                                x0 = fminf(x0, n0);
                                x1 = fminf(x1, n1);
                                const float al0 = ex2(x0 - n0), al1 = ex2(x1 - n1);
                                l0 *= al0;
                                l1 *= al1;
#pragma unroll
                                for (int i = 0; i < 16; i++) {
                                    o[4 * i] *= al0;
                                    o[4 * i + 1] *= al0;
                                    o[4 * i + 2] *= al1;
                                    o[4 * i + 3] *= al1;
                                }
                            }
                            n0 = x0;
                            n1 = x1;
                            shifted = true;
                            exp_step<true>(sa, pa, n0, n1, s0, s1);
                            exp_step<true>(sb, pb, n0, n1, u0, u1);
                            s0 += u0;
                            s1 += u1;
                        }
                        l0 += s0;
                        l1 += s1;
                    };

                    cx.wait_full(4, 0);
                    if (wg == 1) bar_sync(my_bar, 256);
                    wg_fence();
                    qk_step(sa, q, dbk + 4 * 1024);
                    qk_step(sb, q, dbk + 5 * 1024);
                    wg_commit();
                    bar_arrive(other_bar, 256);
                    wg_wait<0>();
                    pin(sa);
                    pin(sb);
                    cx.release(4);
                    cx.wait_full(6, 0);
                    {
                        float s0, s1;
                        softmax_a(true, s0, s1);
                        softmax_b(true, s0, s1);
                    }
                    uint32_t alo = (uint32_t)dbase + 6 * 1024, blo = (uint32_t)dbase;
                    const uint32_t dhi = (uint32_t)(dbase >> 32);
#pragma unroll 1
                    for (int t = 1; t < 64; t++) {
                        const int j = t & 15;
                        const uint32_t sA = 2 + 4 * (t & 1), sB = 4 - 4 * (t & 1);
                        const uint64_t da = ((uint64_t)dhi << 32) | alo, db = ((uint64_t)dhi << 32) | blo;
                        TL(0);
                        bar_sync(my_bar, 256);
                        TL(2);
                        wg_fence();
                        pv_step(o, pa, da + 1024, j != 1);
                        qk_step(sa, q, da - (511u << 16));
                        wg_commit();
                        cx.wait_full(sB, ((36 + 4 * t) >> 3) & 1);
                        wg_fence();
                        qk_step(sb, q, db - (511u << 16));
                        pv_step(o, pb, db + 1024, 1);
                        wg_commit();
                        bar_arrive(other_bar, 256);
                        alo ^= 4096;
                        blo ^= 4096;
                        asm volatile("" : "+r"(alo), "+r"(blo));
                        TL(3);
                        wg_wait<1>();
                        pin(sa);
                        pin(pa);
                        TL(4);
                        cx.release(sA);
                        const float lp0 = l0, lp1 = l1;
                        float s0, s1;
                        softmax_a(j == 0, s0, s1);
                        TL(5);
                        wg_wait<0>();
                        pin(o);
                        pin(sb);
                        pin(pb);
                        TL(6);
                        cx.release(sB);
                        if (j == 0) {
                            float i0, i1;
                            inv_row_sums(lp0, lp1, i0, i1);
                            const uint32_t dst = spill + ((t >> 4) - 1) * 16384;
#pragma unroll
                            for (int v = 0; v < 8; v++)
                                sts128(dst + v * 2048, pack_bf16(o[8 * v] * i0, o[8 * v + 1] * i0),
                                       pack_bf16(o[8 * v + 2] * i1, o[8 * v + 3] * i1),
                                       pack_bf16(o[8 * v + 4] * i0, o[8 * v + 5] * i0),
                                       pack_bf16(o[8 * v + 6] * i1, o[8 * v + 7] * i1));
                        }
                        const uint32_t bn = sbase + OFF_FULL + (8 - sA) * 8, pn = ((38 + 4 * t) >> 3) & 1;
                        const bool okn = mbar_try(bn, pn);
                        TL(1);
                        softmax_b(j == 0, s0, s1);
                        if (!okn || j == 15) {
                            mbar_wait(bn, pn);
                            if (j == 15 && t < 63) {
                                const uint32_t src = spill + (t >> 4) * 16384;
#pragma unroll
                                for (int v = 0; v < 8; v++)
                                    lds128(src + v * 2048, q[4 * v], q[4 * v + 1], q[4 * v + 2], q[4 * v + 3]);
                            }
                        }
                        TL(7);
                    }
                    bar_sync(my_bar, 256);
                    wg_fence();
                    pv_step(o, pa, dbase + 2 * 1024, 1);
                    pv_step(o, pb, dbase + 3 * 1024, 1);
                    wg_commit();
                    if (wg == 0) bar_arrive(other_bar, 256);
                    float i0, i1;
                    inv_row_sums(l0, l1, i0, i1);
                    wg_wait<0>();
                    pin(o);
                    cx.release(2);
#pragma unroll
                    for (int i = 0; i < 16; i++) {
                        a[96 + 2 * i] = pack_bf16(o[4 * i] * i0, o[4 * i + 1] * i0);
                        a[96 + 2 * i + 1] = pack_bf16(o[4 * i + 2] * i1, o[4 * i + 3] * i1);
                    }
#pragma unroll
                    for (int i = 128; i < 144; i++) a[i] = 0;
                }
                ring.slot = 4;
                ring.phase = 0;
                PROF(6);
                PROFG(24);
            } else {
#pragma unroll
                for (int v = 0; v < 8; v++) {
                    const uint4 t = __ldcg(hhbuf + v * 256);
                    a[112 + 4 * v] = t.x;
                    a[113 + 4 * v] = t.y;
                    a[114 + 4 * v] = t.z;
                    a[115 + 4 * v] = t.w;
                }
#pragma unroll
                for (int i = 0; i < 16; i++) a[96 + i] = pack_bf16(d[2 * i], d[2 * i + 1]);
                PROF(13);
            }
#pragma unroll
            for (int v = 0; v < 24; v++) lds128(spill + v * 2048, a[4 * v], a[4 * v + 1], a[4 * v + 2], a[4 * v + 3]);

            {
                uint4* dst = sc_->part + ((size_t)wown * 8 + g) * 36 * 32 + lane;
                const uint32_t ptag = (stage + 1) & 1;
#pragma unroll 1
                for (int p = 0; p < 4; p++) {
                    TG(stage * 32 + 18 + p * 2);
                    gemm_n128(d, a, cx, ring, stage != 0);
                    TG(stage * 32 + 19 + p * 2);
#pragma unroll
                    for (int u = 0; u < 8; u++)
                        st128(dst + (p * 8 + u) * 32, (pack_bf16(d[8 * u], d[8 * u + 1]) & ~1u) | ptag,
                              pack_bf16(d[8 * u + 2], d[8 * u + 3]), pack_bf16(d[8 * u + 4], d[8 * u + 5]),
                              pack_bf16(d[8 * u + 6], d[8 * u + 7]));
                    if (p == 0 && wg == 0) bar_arrive(7, 160);
                }
                float e[32];
                TG(stage * 32 + 26);
                gemm_n64(e, a, cx, ring, stage != 0);
                TG(stage * 32 + 27);
                uint2* dst2 = reinterpret_cast<uint2*>(dst - lane + 32 * 32) + lane;
#pragma unroll
                for (int j = 0; j < 8; j++)
                    st64(dst2 + j * 32, (pack_bf16(e[4 * j], e[4 * j + 1]) & ~1u) | ptag, pack_bf16(e[4 * j + 2], e[4 * j + 3]));
            }
            PROF(stage == 0 ? 7 : 14);
            if (stage == 1) {
                PROFG(26);
                asm volatile("barrier.cluster.arrive.relaxed.aligned;" ::: "memory");
            }
        }
        if (wg == 0) bar_sync(8, 256);
        bar_sync(3, 256);
        if (b == 0 && warp == 1) sc_->epoch[lane] = epoch + 1;
        if (tid == 0) {
            rows_store(sbase, &maps.rout, own * 16);
            rows_store_wait();
        }
        __syncwarp();
        PROF(16);
        PROFG(31);
        asm volatile("barrier.cluster.wait.aligned;" ::: "memory");
    }
}

typedef CUresult (*EncodeFn)(CUtensorMap*, CUtensorMapDataType, cuuint32_t, void*, const cuuint64_t*, const cuuint64_t*,
                             const cuuint32_t*, const cuuint32_t*, CUtensorMapInterleave, CUtensorMapSwizzle,
                             CUtensorMapL2promotion, CUtensorMapFloatOOBfill);

void make_map(EncodeFn enc, CUtensorMap* m, const void* ptr, uint64_t rows, uint64_t cols, bool narrow = false) {
    cuuint64_t gdim[2] = {cols, rows};
    cuuint64_t gstr[1] = {cols * 2};
    cuuint32_t box[2] = {narrow ? 16u : 64u, narrow ? 192u : 64u};
    cuuint32_t estr[2] = {1, 1};
    enc(m, CU_TENSOR_MAP_DATA_TYPE_BFLOAT16, 2, const_cast<void*>(ptr), gdim, gstr, box, estr,
        CU_TENSOR_MAP_INTERLEAVE_NONE, narrow ? CU_TENSOR_MAP_SWIZZLE_NONE : CU_TENSOR_MAP_SWIZZLE_128B,
        CU_TENSOR_MAP_L2_PROMOTION_L2_128B,
        CU_TENSOR_MAP_FLOAT_OOB_FILL_NONE);
}

void make_rows_map(EncodeFn enc, CUtensorMap* m, const void* ptr) {
    cuuint64_t gdim[3] = {64, 9, 2048};
    cuuint64_t gstr[2] = {128, DM * 2};
    cuuint32_t box[3] = {64, 9, 16};
    cuuint32_t estr[3] = {1, 1, 1};
    enc(m, CU_TENSOR_MAP_DATA_TYPE_BFLOAT16, 3, const_cast<void*>(ptr), gdim, gstr, box, estr,
        CU_TENSOR_MAP_INTERLEAVE_NONE, CU_TENSOR_MAP_SWIZZLE_128B, CU_TENSOR_MAP_L2_PROMOTION_L2_128B,
        CU_TENSOR_MAP_FLOAT_OOB_FILL_NONE);
}

}

extern "C" void kernel_launch(void* const* d_in, const int* in_sizes, int n_in, void* d_out, int out_size) {
    (void)in_sizes;
    (void)n_in;
    (void)out_size;
    void* fn = nullptr;
    cudaDriverEntryPointQueryResult qr;
    cudaGetDriverEntryPoint("cuTensorMapEncodeTiled", &fn, cudaEnableDefault, &qr);
    EncodeFn enc = (EncodeFn)fn;
    Params maps;
    maps.x = (const __nv_bfloat16*)d_in[0];
    maps.cvec = (const __nv_bfloat16*)d_in[9];
    maps.wmod = (const __nv_bfloat16*)d_in[10];
    maps.kc = (const __nv_bfloat16*)d_in[1];
    maps.vc = (const __nv_bfloat16*)d_in[2];
    maps.wq_p = (const __nv_bfloat16*)d_in[3];
    maps.wo_p = (const __nv_bfloat16*)d_in[4];
    maps.wg_p = (const __nv_bfloat16*)d_in[6];
    maps.wu_p = (const __nv_bfloat16*)d_in[7];
    maps.wd_p = (const __nv_bfloat16*)d_in[8];
    maps.out = (__nv_bfloat16*)d_out;
    void* scp = nullptr;
    cudaGetSymbolAddress(&scp, g_scratch);
    maps.sc = (Scratch*)scp;
    make_map(enc, &maps.k, d_in[1], 32 * 2048, 128);
    make_map(enc, &maps.v, d_in[2], 32 * 2048, 128);
    make_map(enc, &maps.wq, d_in[3], 576, 4096);
    make_map(enc, &maps.wo, d_in[4], 4096, 576);
    make_map(enc, &maps.wg, d_in[6], 576, 4608);
    make_map(enc, &maps.wu, d_in[7], 576, 4608);
    make_map(enc, &maps.wd, d_in[8], 4608, 576);
    make_map(enc, &maps.wm, d_in[10], 576, 3456, true);
    make_rows_map(enc, &maps.rx, d_in[0]);
    make_rows_map(enc, &maps.rx2, (char*)scp + offsetof(Scratch, x2));
    make_rows_map(enc, &maps.rout, d_out);
    cudaFuncSetAttribute(fused_block_kernel, cudaFuncAttributeMaxDynamicSharedMemorySize, SMEM_BYTES);
    fused_block_kernel<<<128, 384, SMEM_BYTES>>>(maps);
}
```

```cpp
#include <cuda_runtime.h>
#include <cuda_bf16.h>
#include <cuda.h>
#include <stdint.h>
#include <stddef.h>

namespace {

constexpr int DM = 576;
constexpr int SLOT_BYTES = 16384;
constexpr int BOX_BYTES = 8192;
constexpr int NUNITS = 14;
constexpr int SMEM_TAIL = NUNITS * SLOT_BYTES;
constexpr int SMEM_BYTES = SMEM_TAIL + 2048 + 1024;
constexpr int OFF_FULL = SMEM_TAIL;
constexpr int OFF_EMPTY = SMEM_TAIL + 64;
constexpr int OFF_RED = SMEM_TAIL + 128;

constexpr int KV_AHEAD = 16;
#define GATE_SLOT 4
constexpr int OFF_XBAR = SMEM_TAIL + 1792;
constexpr int OFF_ROWS = 8 * SLOT_BYTES;
constexpr int OFF_MODT = OFF_ROWS + 20480;
constexpr int OFF_WBLK = OFF_ROWS + 28672;
constexpr int OFF_WBAR = SMEM_TAIL + 1800;
constexpr int OFF_EPOCH = SMEM_TAIL + 1808;
constexpr int OFF_CVEC = OFF_WBLK + DM * 32;

struct Scratch {
    unsigned epoch[128 * 32];
    uint32_t mod[6 * DM];
    uint4 h[2][2][128 * 36 * 32];
    uint4 part[128 * 8 * 36 * 32];
    uint4 hh[128 * 8 * 256];
    __nv_bfloat16 x2[2048 * DM];
};
__device__ Scratch g_scratch;

#define TG(i)
#define TL(i)
#define PROFR(i)
#define PROF(i)
#define PROFG(i)

struct Params {
    const __nv_bfloat16 *x, *cvec, *wmod, *kc, *vc, *wq_p, *wo_p, *wg_p, *wu_p, *wd_p;
    __nv_bfloat16* out;
    Scratch* sc;
    CUtensorMap k, v, wq, wo, wg, wu, wd, wm, rx, rx2, rout;
};

__device__ __forceinline__ uint32_t smem_u32(const void* p) { return (uint32_t)__cvta_generic_to_shared(p); }
__device__ __forceinline__ void mbar_init(uint32_t a, uint32_t c) {
    asm volatile("mbarrier.init.shared::cta.b64 [%0], %1;" ::"r"(a), "r"(c) : "memory");
}
__device__ __forceinline__ void mbar_expect_tx(uint32_t a, uint32_t bytes) {
    asm volatile("mbarrier.arrive.expect_tx.shared::cta.b64 _, [%0], %1;" ::"r"(a), "r"(bytes) : "memory");
}
__device__ __forceinline__ bool mbar_try(uint32_t a, uint32_t ph) {
    uint32_t ok;
    asm volatile(
        "{\n.reg .pred p;\nmbarrier.try_wait.parity.shared::cta.b64 p, [%1], %2;\nselp.u32 %0, 1, 0, p;\n}"
        : "=r"(ok)
        : "r"(a), "r"(ph)
        : "memory");
    return ok != 0;
}
__device__ __forceinline__ uint32_t clk32() {
    uint32_t c;
    asm volatile("mov.u32 %0, %%clock;" : "=r"(c));
    return c;
}
constexpr uint32_t WAIT_LIMIT = 1u << 30;
__device__ __forceinline__ void mbar_wait(uint32_t a, uint32_t ph) {
    if (mbar_try(a, ph)) return;
    uint32_t t0 = clk32();
    while (!mbar_try(a, ph)) {
        if (clk32() - t0 > WAIT_LIMIT) break;
    }
}
__device__ __forceinline__ void mbar_arrive_cluster(uint32_t a, uint32_t cta) {
    asm volatile(
        "{\n.reg .b32 ra;\nmapa.shared::cluster.u32 ra, %0, %1;\nmbarrier.arrive.shared::cluster.b64 _, [ra];\n}" ::"r"(a),
        "r"(cta)
        : "memory");
}
__device__ __forceinline__ void tma_mc(uint32_t dst, const CUtensorMap* m, int c0, int c1, uint32_t bar) {
    asm volatile(
        "cp.async.bulk.tensor.2d.shared::cluster.global.mbarrier::complete_tx::bytes.multicast::cluster"
        " [%0], [%1, {%3, %4}], [%2], %5;" ::"r"(dst),
        "l"(m), "r"(bar), "r"(c0), "r"(c1), "h"((uint16_t)3)
        : "memory");
}
__device__ __forceinline__ void bulk_load(uint32_t dst, const void* src, uint32_t bytes, uint32_t bar) {
    asm volatile("cp.async.bulk.shared::cluster.global.mbarrier::complete_tx::bytes [%0], [%1], %2, [%3];" ::"r"(dst),
                 "l"(src), "r"(bytes), "r"(bar)
                 : "memory");
}
__device__ __forceinline__ void l2_prefetch(const void* p, uint32_t bytes) {
    asm volatile("cp.async.bulk.prefetch.L2.global [%0], %1;" ::"l"(p), "r"(bytes) : "memory");
}
__device__ __forceinline__ void bar_sync(int id, int n) { asm volatile("bar.sync %0, %1;" ::"r"(id), "r"(n) : "memory"); }
__device__ __forceinline__ void bar_arrive(int id, int n) {
    asm volatile("bar.arrive %0, %1;" ::"r"(id), "r"(n) : "memory");
}
__device__ __forceinline__ void wg_fence() { asm volatile("wgmma.fence.sync.aligned;" ::: "memory"); }
__device__ __forceinline__ void wg_commit() { asm volatile("wgmma.commit_group.sync.aligned;" ::: "memory"); }
template <int N>
__device__ __forceinline__ void wg_wait() {
    asm volatile("wgmma.wait_group.sync.aligned %0;" ::"n"(N) : "memory");
}
template <int N>
__device__ __forceinline__ void pin(float (&d)[N]) {
#pragma unroll
    for (int i = 0; i < N; i++) asm volatile("" : "+f"(d[i])::"memory");
}
template <int N>
__device__ __forceinline__ void pin(uint32_t (&d)[N]) {
#pragma unroll
    for (int i = 0; i < N; i++) asm volatile("" : "+r"(d[i])::"memory");
}
__device__ __forceinline__ uint32_t pack_bf16(float lo, float hi) {
    uint32_t r;
    asm("cvt.rn.bf16x2.f32 %0, %1, %2;" : "=r"(r) : "f"(hi), "f"(lo));
    return r;
}
__device__ __forceinline__ float bf_lo(uint32_t v) { return __uint_as_float(v << 16); }
__device__ __forceinline__ float bf_hi(uint32_t v) { return __uint_as_float(v & 0xffff0000u); }
__device__ __forceinline__ float round_bf16(float v) { return __bfloat162float(__float2bfloat16_rn(v)); }
__device__ __forceinline__ float ex2(float x) {
    float y;
    asm("ex2.approx.ftz.f32 %0, %1;" : "=f"(y) : "f"(x));
    return y;
}
__device__ __forceinline__ float rcp(float x) {
    float y;
    asm("rcp.approx.ftz.f32 %0, %1;" : "=f"(y) : "f"(x));
    return y;
}
__device__ __forceinline__ float tanh_fast(float x) {
    float y;
    asm("tanh.approx.f32 %0, %1;" : "=f"(y) : "f"(x));
    return y;
}
__device__ __forceinline__ void sts128(uint32_t a, uint32_t x, uint32_t y, uint32_t z, uint32_t w) {
    asm volatile("st.shared.v4.b32 [%0], {%1,%2,%3,%4};" ::"r"(a), "r"(x), "r"(y), "r"(z), "r"(w) : "memory");
}
__device__ __forceinline__ void lds128(uint32_t a, uint32_t& x, uint32_t& y, uint32_t& z, uint32_t& w) {
    asm volatile("ld.shared.v4.b32 {%0,%1,%2,%3}, [%4];" : "=r"(x), "=r"(y), "=r"(z), "=r"(w) : "r"(a) : "memory");
}
__device__ __forceinline__ void sts32f(uint32_t a, float v) {
    asm volatile("st.shared.f32 [%0], %1;" ::"r"(a), "f"(v) : "memory");
}
__device__ __forceinline__ float lds32f(uint32_t a) {
    float v;
    asm volatile("ld.shared.f32 %0, [%1];" : "=f"(v) : "r"(a) : "memory");
    return v;
}
#define F8(d, b) \
    "+f"(d[b]), "+f"(d[b + 1]), "+f"(d[b + 2]), "+f"(d[b + 3]), "+f"(d[b + 4]), "+f"(d[b + 5]), "+f"(d[b + 6]), "+f"(d[b + 7])

template <int TB>
__device__ __forceinline__ void wgmma_n128(float (&d)[64], uint32_t a0, uint32_t a1, uint32_t a2, uint32_t a3,
                                           uint64_t db, int sc) {
    asm volatile(
        "{\n.reg .pred p;\nsetp.ne.b32 p, %69, 0;\n"
        "wgmma.mma_async.sync.aligned.m64n128k16.f32.bf16.bf16 "
        "{%0,%1,%2,%3,%4,%5,%6,%7,%8,%9,%10,%11,%12,%13,%14,%15,%16,%17,%18,%19,%20,%21,%22,%23,%24,%25,%26,%27,%28,%29,%30,%31,"
        "%32,%33,%34,%35,%36,%37,%38,%39,%40,%41,%42,%43,%44,%45,%46,%47,%48,%49,%50,%51,%52,%53,%54,%55,%56,%57,%58,%59,%60,%61,%62,%63},"
        "{%64,%65,%66,%67}, %68, p, 1, 1, %70;\n}"
        : F8(d, 0), F8(d, 8), F8(d, 16), F8(d, 24), F8(d, 32), F8(d, 40), F8(d, 48), F8(d, 56)
        : "r"(a0), "r"(a1), "r"(a2), "r"(a3), "l"(db), "r"(sc), "n"(TB));
}
#define O8(d, b) \
    "=f"(d[b]), "=f"(d[b + 1]), "=f"(d[b + 2]), "=f"(d[b + 3]), "=f"(d[b + 4]), "=f"(d[b + 5]), "=f"(d[b + 6]), "=f"(d[b + 7])
template <int TB>
__device__ __forceinline__ void wgmma_n128_z(float (&d)[64], uint32_t a0, uint32_t a1, uint32_t a2, uint32_t a3,
                                             uint64_t db) {
    asm volatile(
        "wgmma.mma_async.sync.aligned.m64n128k16.f32.bf16.bf16 "
        "{%0,%1,%2,%3,%4,%5,%6,%7,%8,%9,%10,%11,%12,%13,%14,%15,%16,%17,%18,%19,%20,%21,%22,%23,%24,%25,%26,%27,%28,%29,%30,%31,"
        "%32,%33,%34,%35,%36,%37,%38,%39,%40,%41,%42,%43,%44,%45,%46,%47,%48,%49,%50,%51,%52,%53,%54,%55,%56,%57,%58,%59,%60,%61,%62,%63},"
        "{%64,%65,%66,%67}, %68, 0, 1, 1, %69;"
        : O8(d, 0), O8(d, 8), O8(d, 16), O8(d, 24), O8(d, 32), O8(d, 40), O8(d, 48), O8(d, 56)
        : "r"(a0), "r"(a1), "r"(a2), "r"(a3), "l"(db), "n"(TB));
}
template <int TB>
__device__ __forceinline__ void wgmma_n64_z(float (&d)[32], uint32_t a0, uint32_t a1, uint32_t a2, uint32_t a3,
                                            uint64_t db) {
    asm volatile(
        "wgmma.mma_async.sync.aligned.m64n64k16.f32.bf16.bf16 "
        "{%0,%1,%2,%3,%4,%5,%6,%7,%8,%9,%10,%11,%12,%13,%14,%15,%16,%17,%18,%19,%20,%21,%22,%23,%24,%25,%26,%27,%28,%29,%30,%31},"
        "{%32,%33,%34,%35}, %36, 0, 1, 1, %37;"
        : O8(d, 0), O8(d, 8), O8(d, 16), O8(d, 24)
        : "r"(a0), "r"(a1), "r"(a2), "r"(a3), "l"(db), "n"(TB));
}
template <int TB>
__device__ __forceinline__ void wgmma_n64(float (&d)[32], uint32_t a0, uint32_t a1, uint32_t a2, uint32_t a3,
                                          uint64_t db) {
    asm volatile(
        "wgmma.mma_async.sync.aligned.m64n64k16.f32.bf16.bf16 "
        "{%0,%1,%2,%3,%4,%5,%6,%7,%8,%9,%10,%11,%12,%13,%14,%15,%16,%17,%18,%19,%20,%21,%22,%23,%24,%25,%26,%27,%28,%29,%30,%31},"
        "{%32,%33,%34,%35}, %36, 1, 1, 1, %37;"
        : F8(d, 0), F8(d, 8), F8(d, 16), F8(d, 24)
        : "r"(a0), "r"(a1), "r"(a2), "r"(a3), "l"(db), "n"(TB));
}

__device__ __forceinline__ uint64_t desc_of(uint32_t saddr) {
    return (uint64_t)(((saddr >> 4) & 0x3FFFu) | (512u << 16)) | ((uint64_t)(64u | (1u << 30)) << 32);
}

struct Ring {
    uint32_t slot;
    uint32_t phase;
    __device__ __forceinline__ void next() {
        if (++slot == 8) {
            slot = 0;
            phase ^= 1;
        }
    }
};

struct Ctx {
    uint32_t sbase;
    int wg;
    uint32_t rel_cta;
    __device__ __forceinline__ void wait_full(uint32_t slot, uint32_t phase) const {
        mbar_wait(sbase + OFF_FULL + slot * 8, phase);
    }
    __device__ __forceinline__ void release(uint32_t slot) const {
        if (rel_cta < 2) mbar_arrive_cluster(sbase + OFF_EMPTY + slot * 8, rel_cta);
    }
};

__device__ __forceinline__ void gemm_n128(float (&d)[64], const uint32_t (&a)[144], const Ctx& c, Ring& r, bool nine) {
    uint32_t prev = 0;
#pragma unroll
    for (int s = 0; s < 9; s++) {
        if (s < 8 || nine) {
            if (s == GATE_SLOT) bar_sync(8 + c.wg, 256);
            c.wait_full(r.slot, r.phase);
            uint64_t db = desc_of(c.sbase + r.slot * SLOT_BYTES);
            wg_fence();
#pragma unroll
            for (int k = 0; k < 4; k++) {
                if ((s | k) == 0)
                    wgmma_n128_z<1>(d, a[0], a[1], a[2], a[3], db);
                else
                    wgmma_n128<1>(d, a[s * 16 + k * 4], a[s * 16 + k * 4 + 1], a[s * 16 + k * 4 + 2],
                                  a[s * 16 + k * 4 + 3], db + k * 128, 1);
            }
            wg_commit();
            if (s == 8 || (s == 7 && !nine)) bar_arrive(9 - c.wg, 256);
            if (s > 0) {
                wg_wait<1>();
                c.release(prev);
            }
            prev = r.slot;
            r.next();
        }
    }
    wg_wait<0>();
    c.release(prev);
    pin(d);
}
__device__ __forceinline__ void gemm_n64(float (&d)[32], const uint32_t (&a)[144], const Ctx& c, Ring& r, bool nine) {
    uint32_t prev = 0;
#pragma unroll
    for (int s = 0; s < 5; s++) {
        if (s < 4 || nine) {
            c.wait_full(r.slot, r.phase);
            uint64_t db = desc_of(c.sbase + r.slot * SLOT_BYTES);
            wg_fence();
#pragma unroll
            for (int k = 0; k < 8; k++) {
                if ((s | k) == 0)
                    wgmma_n64_z<1>(d, a[0], a[1], a[2], a[3], db);
                else if (s * 8 + k < 36)
                    wgmma_n64<1>(d, a[s * 32 + k * 4], a[s * 32 + k * 4 + 1], a[s * 32 + k * 4 + 2],
                                 a[s * 32 + k * 4 + 3], db + k * 128);
            }
            wg_commit();
            if (s > 0) {
                wg_wait<1>();
                c.release(prev);
            }
            prev = r.slot;
            r.next();
        }
    }
    wg_wait<0>();
    c.release(prev);
    pin(d);
}
__device__ __forceinline__ void st128(uint4* p, uint32_t x, uint32_t y, uint32_t z, uint32_t w) {
    asm volatile(
        "{\n.reg .b64 lo, hi;\n.reg .b128 t;\nmov.b64 lo, {%1, %2};\nmov.b64 hi, {%3, %4};\nmov.b128 t, {lo, hi};\n"
        "st.relaxed.gpu.global.b128 [%0], t;\n}" ::"l"(p),
        "r"(x), "r"(y), "r"(z), "r"(w)
        : "memory");
}
__device__ __forceinline__ uint4 ld128(const uint4* p) {
    uint4 r;
    asm volatile(
        "{\n.reg .b64 lo, hi;\n.reg .b128 t;\nld.relaxed.gpu.global.b128 t, [%4];\nmov.b128 {lo, hi}, t;\n"
        "mov.b64 {%0, %1}, lo;\nmov.b64 {%2, %3}, hi;\n}"
        : "=r"(r.x), "=r"(r.y), "=r"(r.z), "=r"(r.w)
        : "l"(p));
    return r;
}
__device__ __forceinline__ void st64(void* p, uint32_t x, uint32_t y) {
    asm volatile("{\n.reg .b64 t;\nmov.b64 t, {%1, %2};\nst.relaxed.gpu.global.b64 [%0], t;\n}" ::"l"(p), "r"(x), "r"(y)
                 : "memory");
}
__device__ __forceinline__ uint2 ld64(const void* p) {
    uint2 r;
    asm volatile("{\n.reg .b64 t;\nld.relaxed.gpu.global.b64 t, [%2];\nmov.b64 {%0, %1}, t;\n}"
                 : "=r"(r.x), "=r"(r.y)
                 : "l"(p));
    return r;
}
__device__ __forceinline__ void rows_load(uint32_t sbase, const CUtensorMap* m, int row0) {
    mbar_expect_tx(sbase + OFF_XBAR, 16 * DM * 2);
    asm volatile(
        "cp.async.bulk.tensor.3d.shared::cluster.global.mbarrier::complete_tx::bytes [%0], [%1, {%3, %3, %4}], [%2];" ::"r"(
            sbase + OFF_ROWS),
        "l"(m), "r"(sbase + OFF_XBAR), "r"(0), "r"(row0)
        : "memory");
}
__device__ __forceinline__ void rows_store(uint32_t sbase, const CUtensorMap* m, int row0) {
    asm volatile("cp.async.bulk.tensor.3d.global.shared::cta.bulk_group [%0, {%2, %2, %3}], [%1];" ::"l"(m),
                 "r"(sbase + OFF_ROWS), "r"(0), "r"(row0)
                 : "memory");
    asm volatile("cp.async.bulk.commit_group;" ::: "memory");
}
__device__ __forceinline__ void rows_store_wait() { asm volatile("cp.async.bulk.wait_group 0;" ::: "memory"); }

__device__ __forceinline__ constexpr int own_col(int j) { return j < 8 ? (j >> 1) * 128 + (j & 1) * 8 : 512; }
__device__ __forceinline__ void row_reduce(float& s0, float& s1, uint32_t red, int warp, int lane) {
    s0 += __shfl_xor_sync(0xffffffffu, s0, 1);
    s1 += __shfl_xor_sync(0xffffffffu, s1, 1);
    s0 += __shfl_xor_sync(0xffffffffu, s0, 2);
    s1 += __shfl_xor_sync(0xffffffffu, s1, 2);
    if ((lane & 3) == 0) {
        sts32f(red + (warp * 16 + (lane >> 2)) * 4, s0);
        sts32f(red + (warp * 16 + 8 + (lane >> 2)) * 4, s1);
    }
    bar_sync(3, 256);
    s0 = 0.f;
    s1 = 0.f;
#pragma unroll
    for (int w = 0; w < 8; w++) {
        s0 += lds32f(red + (w * 16 + (lane >> 2)) * 4);
        s1 += lds32f(red + (w * 16 + 8 + (lane >> 2)) * 4);
    }
}
__device__ __forceinline__ void layernorm_rows(float (&v)[36], uint32_t red, int warp, int lane) {
    float s0 = 0.f, s1 = 0.f;
#pragma unroll
    for (int j = 0; j < 9; j++) {
        s0 += v[4 * j] + v[4 * j + 1];
        s1 += v[4 * j + 2] + v[4 * j + 3];
    }
    row_reduce(s0, s1, red, warp, lane);
    const float m0 = s0 * (1.f / DM), m1 = s1 * (1.f / DM);
    s0 = 0.f;
    s1 = 0.f;
#pragma unroll
    for (int j = 0; j < 9; j++) {
        v[4 * j] -= m0;
        v[4 * j + 1] -= m0;
        v[4 * j + 2] -= m1;
        v[4 * j + 3] -= m1;
        s0 += v[4 * j] * v[4 * j] + v[4 * j + 1] * v[4 * j + 1];
        s1 += v[4 * j + 2] * v[4 * j + 2] + v[4 * j + 3] * v[4 * j + 3];
    }
    row_reduce(s0, s1, red + 512, warp, lane);
    const float r0 = rsqrtf(s0 * (1.f / DM) + 1e-5f), r1 = rsqrtf(s1 * (1.f / DM) + 1e-5f);
#pragma unroll
    for (int j = 0; j < 9; j++) {
        v[4 * j] *= r0;
        v[4 * j + 1] *= r0;
        v[4 * j + 2] *= r1;
        v[4 * j + 3] *= r1;
    }
}
__device__ __forceinline__ void mod_to_smem(uint32_t dst, const uint32_t* src, uint32_t tag) {
    const uint32_t t0 = clk32();
    uint4 u;
    while (true) {
        u = ld128(reinterpret_cast<const uint4*>(src));
        const uint32_t bad = ((u.x ^ tag) | (u.y ^ tag) | (u.z ^ tag) | (u.w ^ tag)) & 0xffffu;
        if (__all_sync(0xffffffffu, bad == 0) || clk32() - t0 > WAIT_LIMIT) break;
        __nanosleep(64);
    }
    sts128(dst, u.x & 0xffff0000u, u.y & 0xffff0000u, u.z & 0xffff0000u, u.w & 0xffff0000u);
}
__device__ __forceinline__ void lds_mod(float (&m)[18], uint32_t src  , int warp) {
#pragma unroll
    for (int j = 0; j < 9; j++)
        asm volatile("ld.shared.v2.f32 {%0,%1}, [%2];"
                     : "=f"(m[2 * j]), "=f"(m[2 * j + 1])
                     : "r"(src + own_col(j) * 4 - (j == 8 ? warp * 32 : 0))
                     : "memory");
}
__device__ __forceinline__ void modulate_store(const float (&v)[36], const float (&shift)[18], const float (&scale)[18],
                                               uint4* hbuf  , int warp, int lane) {
    uint32_t o[18];
#pragma unroll
    for (int j = 0; j < 9; j++) {
        const uint32_t cc = pack_bf16(1.f + scale[2 * j], 1.f + scale[2 * j + 1]);
        const float c0 = bf_lo(cc), c1 = bf_hi(cc);
        o[2 * j] = max(pack_bf16(fmaf(v[4 * j], c0, shift[2 * j]), fmaf(v[4 * j + 1], c1, shift[2 * j + 1])), 1u);
        o[2 * j + 1] = max(pack_bf16(fmaf(v[4 * j + 2], c0, shift[2 * j]), fmaf(v[4 * j + 3], c1, shift[2 * j + 1])), 1u);
    }
#pragma unroll
    for (int i = 0; i < 4; i++) st128(hbuf + (i * 8 + warp) * 32 + lane, o[4 * i], o[4 * i + 1], o[4 * i + 2], o[4 * i + 3]);
    st64(reinterpret_cast<uint2*>(hbuf + 32 * 32) + warp * 32 + lane, o[16], o[17]);
}
__device__ __forceinline__ void sum_partials(float (&v)[36], const uint4* src  , uint32_t tag) {
    const uint32_t t0 = clk32();
    while (true) {
        uint4 t[8][4];
#pragma unroll
        for (int s = 0; s < 8; s++)
#pragma unroll
            for (int i = 0; i < 4; i++) t[s][i] = ld128(src + (s * 36 + i * 8) * 32);
        uint32_t bad = 0;
#pragma unroll
        for (int i = 0; i < 32; i++) v[i] = 0.f;
#pragma unroll
        for (int s = 0; s < 8; s++)
#pragma unroll
            for (int i = 0; i < 4; i++) {
                bad |= t[s][i].x ^ tag;
                v[8 * i] += bf_lo(t[s][i].x);
                v[8 * i + 1] += bf_hi(t[s][i].x);
                v[8 * i + 2] += bf_lo(t[s][i].y);
                v[8 * i + 3] += bf_hi(t[s][i].y);
                v[8 * i + 4] += bf_lo(t[s][i].z);
                v[8 * i + 5] += bf_hi(t[s][i].z);
                v[8 * i + 6] += bf_lo(t[s][i].w);
                v[8 * i + 7] += bf_hi(t[s][i].w);
            }
        if (__all_sync(0xffffffffu, (bad & 1u) == 0) || clk32() - t0 > WAIT_LIMIT) break;
    }
}
__device__ __forceinline__ void sum_tail(float (&v)[36], const uint2* src  , uint32_t tag) {
    const uint32_t t0 = clk32();
    while (true) {
        uint2 t[8];
#pragma unroll
        for (int s = 0; s < 8; s++) t[s] = ld64(src + s * 72 * 32);
        uint32_t bad = 0;
        v[32] = v[33] = v[34] = v[35] = 0.f;
#pragma unroll
        for (int s = 0; s < 8; s++) {
            bad |= t[s].x ^ tag;
            v[32] += bf_lo(t[s].x);
            v[33] += bf_hi(t[s].x);
            v[34] += bf_lo(t[s].y);
            v[35] += bf_hi(t[s].y);
        }
        if (__all_sync(0xffffffffu, (bad & 1u) == 0) || clk32() - t0 > WAIT_LIMIT) break;
    }
}
__device__ __forceinline__ void poll_tail(uint32_t (&a)[144], const uint2* src  ) {
    const uint32_t t0 = clk32();
    while (true) {
        uint32_t m = 0xffffffffu;
#pragma unroll
        for (int j = 0; j < 8; j++) {
            const uint2 t = ld64(src + j * 32);
            a[128 + 2 * j] = t.x;
            a[129 + 2 * j] = t.y;
        }
#pragma unroll
        for (int j = 0; j < 16; j++) m = min(m, a[128 + j]);
        if (__all_sync(0xffffffffu, m != 0) || clk32() - t0 > WAIT_LIMIT) break;
    }
}
template <int K0, int K1>
__device__ __forceinline__ void poll_frags(uint32_t (&a)[144], const uint4* src  , bool kick) {
    const uint32_t t0 = clk32();
    while (true) {
#pragma unroll
        for (int k = K0; k < K1; k++)
            asm volatile("ld.relaxed.gpu.global.v4.u32 {%0,%1,%2,%3}, [%4];"
                         : "=r"(a[4 * k]), "=r"(a[4 * k + 1]), "=r"(a[4 * k + 2]), "=r"(a[4 * k + 3])
                         : "l"(src + k * 32));
        if (kick) bar_arrive(5, 256);
        kick = false;
        uint32_t m0 = a[4 * K0], m1 = a[4 * K0 + 1];
#pragma unroll
        for (int i = 4 * K0 + 2; i < 4 * K1; i += 2) {
            m0 = min(m0, a[i]);
            m1 = min(m1, a[i + 1]);
        }
        if (__all_sync(0xffffffffu, min(m0, m1) != 0) || clk32() - t0 > WAIT_LIMIT) break;
    }
}

constexpr float SM_SCALE = 0.08838834764831845f * 1.4426950408889634f;
constexpr float SM_HI = 1.2089258e24f;
constexpr float SM_LO = 9.0949470e-13f;
__device__ __forceinline__ void qk_step(float (&s)[32], const uint32_t (&q)[32], uint64_t dk) {
#pragma unroll
    for (int k = 0; k < 8; k++) {
        if (k == 0)
            wgmma_n64_z<0>(s, q[0], q[1], q[2], q[3], dk);
        else
            wgmma_n64<0>(s, q[4 * k], q[4 * k + 1], q[4 * k + 2], q[4 * k + 3], dk + (k >> 2) * 512 + (k & 3) * 2);
    }
}
__device__ __forceinline__ void pv_step(float (&o)[64], const uint32_t (&p)[16], uint64_t dv, int acc) {
#pragma unroll
    for (int k = 0; k < 4; k++)
        wgmma_n128<1>(o, p[4 * k], p[4 * k + 1], p[4 * k + 2], p[4 * k + 3], dv + k * 128, k != 0 ? 1 : acc);
}
template <bool SHIFT>
__device__ __forceinline__ void exp_step(const float (&s)[32], uint32_t (&p)[16], float n0, float n1, float& s0,
                                         float& s1) {
#pragma unroll
    for (int i = 0; i < 8; i++) {
        const float e0 = ex2(SHIFT ? s[4 * i] + n0 : s[4 * i]), e1 = ex2(SHIFT ? s[4 * i + 1] + n0 : s[4 * i + 1]);
        const float e2 = ex2(SHIFT ? s[4 * i + 2] + n1 : s[4 * i + 2]), e3 = ex2(SHIFT ? s[4 * i + 3] + n1 : s[4 * i + 3]);
        if (i == 0) {
            s0 = e0 + e1;
            s1 = e2 + e3;
        } else {
            s0 += e0 + e1;
            s1 += e2 + e3;
        }
        p[2 * i] = pack_bf16(e0, e1);
        p[2 * i + 1] = pack_bf16(e2, e3);
    }
}
__device__ __forceinline__ void row_max(const float (&sa)[32], const float (&sb)[32], float& x0, float& x1) {
    float xa[8];
#pragma unroll
    for (int i = 0; i < 8; i++) xa[i] = fmaxf(sa[i], sb[i]);
#pragma unroll
    for (int k = 1; k < 4; k++)
#pragma unroll
        for (int i = 0; i < 8; i++) xa[i] = fmaxf(xa[i], fmaxf(sa[8 * k + i], sb[8 * k + i]));
    x0 = fmaxf(fmaxf(xa[0], xa[1]), fmaxf(xa[4], xa[5]));
    x1 = fmaxf(fmaxf(xa[2], xa[3]), fmaxf(xa[6], xa[7]));
    x0 = fmaxf(x0, __shfl_xor_sync(0xffffffffu, x0, 1));
    x1 = fmaxf(x1, __shfl_xor_sync(0xffffffffu, x1, 1));
    x0 = fmaxf(x0, __shfl_xor_sync(0xffffffffu, x0, 2));
    x1 = fmaxf(x1, __shfl_xor_sync(0xffffffffu, x1, 2));
}
__device__ __forceinline__ void inv_row_sums(float l0, float l1, float& i0, float& i1) {
    l0 += __shfl_xor_sync(0xffffffffu, l0, 1);
    l1 += __shfl_xor_sync(0xffffffffu, l1, 1);
    l0 += __shfl_xor_sync(0xffffffffu, l0, 2);
    l1 += __shfl_xor_sync(0xffffffffu, l1, 2);
    i0 = rcp(l0);
    i1 = rcp(l1);
}

__device__ __forceinline__ uint32_t get_epoch(uint32_t sbase) { return __float_as_uint(lds32f(sbase + OFF_EPOCH)); }
__device__ __forceinline__ float silu_bf16(unsigned short c) {
    const float cv = bf_lo(c);
    return round_bf16(cv * rcp(1.f + ex2(-1.4426950408889634f * cv)));
}
__device__ __forceinline__ void st_mod(uint32_t* p, float v, uint32_t tag) {
    asm volatile("st.relaxed.gpu.global.u32 [%0], %1;" ::"l"(p), "r"(__float_as_uint(round_bf16(v)) | tag)
                 : "memory");
}
__device__ __forceinline__ void mod_block(const uint4 (&w)[5], const float (&sc)[5], uint32_t* dst, uint32_t red,
                                          int warp, int lane, uint32_t tag) {
    float acc[8];
#pragma unroll
    for (int e = 0; e < 8; e++) acc[e] = 0.f;
#pragma unroll
    for (int i = 0; i < 5; i++) {
        acc[0] = fmaf(sc[i], bf_lo(w[i].x), acc[0]);
        acc[1] = fmaf(sc[i], bf_hi(w[i].x), acc[1]);
        acc[2] = fmaf(sc[i], bf_lo(w[i].y), acc[2]);
        acc[3] = fmaf(sc[i], bf_hi(w[i].y), acc[3]);
        acc[4] = fmaf(sc[i], bf_lo(w[i].z), acc[4]);
        acc[5] = fmaf(sc[i], bf_hi(w[i].z), acc[5]);
        acc[6] = fmaf(sc[i], bf_lo(w[i].w), acc[6]);
        acc[7] = fmaf(sc[i], bf_hi(w[i].w), acc[7]);
    }
#pragma unroll
    for (int o = 2; o < 32; o <<= 1)
#pragma unroll
        for (int e = 0; e < 8; e++) acc[e] += __shfl_xor_sync(0xffffffffu, acc[e], o);
    if (lane < 2) {
#pragma unroll
        for (int e = 0; e < 8; e++) sts32f(red + (warp * 16 + lane * 8 + e) * 4, acc[e]);
    }
    bar_sync(3, 256);
    if (warp == 0 && lane < 16) {
        float s = 0.f;
#pragma unroll
        for (int w8 = 0; w8 < 8; w8++) s += lds32f(red + (w8 * 16 + lane) * 4);
        st_mod(dst + lane, s, tag);
    }
}

__global__ void __cluster_dims__(2, 1, 1) __launch_bounds__(384, 1)
    fused_block_kernel(const __grid_constant__ Params maps) {
    extern __shared__ uint8_t smem_raw[];
    uint32_t sbase = (smem_u32(smem_raw) + 1023u) & ~1023u;
    asm volatile("" : "+r"(sbase));
    const int b = blockIdx.x;
    const int rank = b & 1;
    const int mt = ((b >> 1) & 7) * 2 + rank;
    const int g = b >> 4;
    const int warp = __shfl_sync(0xffffffffu, threadIdx.x >> 5, 0);
    const int lane = threadIdx.x & 31;
    Scratch* const sc_ = maps.sc;
    const __nv_bfloat16* const wmod = maps.wmod;
    const __nv_bfloat16* const cvec = maps.cvec;

    if (threadIdx.x == 0) {
        mbar_init(sbase + OFF_WBAR, 1);
        asm volatile("fence.mbarrier_init.release.cluster;" ::: "memory");
        mbar_expect_tx(sbase + OFF_WBAR, b < 72 ? 16 + DM * 34 : 16);
        bulk_load(sbase + OFF_EPOCH, &sc_->epoch[b * 32], 16, sbase + OFF_WBAR);
        if (b < 72) {
            bulk_load(sbase + OFF_CVEC, cvec, DM * 2, sbase + OFF_WBAR);
#pragma unroll
            for (int i = 0; i < 3; i++)
                asm volatile(
                    "cp.async.bulk.tensor.2d.shared::cluster.global.mbarrier::complete_tx::bytes"
                    " [%0], [%1, {%3, %4}], [%2];" ::"r"(sbase + OFF_WBLK + i * 192 * 32),
                    "l"(&maps.wm), "r"(sbase + OFF_WBAR), "r"(b * 16), "r"(i * 192)
                    : "memory");
        }
    } else if (threadIdx.x == 32) {
        mbar_init(sbase + OFF_XBAR, 1);
        asm volatile("fence.mbarrier_init.release.cluster;" ::: "memory");
        rows_load(sbase, &maps.rx, (mt * 8 + g) * 16);
    } else if (threadIdx.x >= 64 && threadIdx.x < 64 + 81) {
        const int li = b * 81 + threadIdx.x - 64;
        asm volatile("prefetch.global.L2 [%0];" ::"l"((const char*)wmod + (size_t)(li / 18) * (12 * DM) + (li % 18) * 128));
    }
    __syncwarp();

    if (warp >= 8) {
        asm volatile("setmaxnreg.dec.sync.aligned.u32 24;");
        if (warp == 8 && lane == 0) {
#pragma unroll
            for (int i = 0; i < 8; i++) {
                mbar_init(sbase + OFF_FULL + i * 8, 1);
                mbar_init(sbase + OFF_EMPTY + i * 8, 4);
            }
            asm volatile("fence.mbarrier_init.release.cluster;" ::: "memory");
            asm volatile("barrier.cluster.arrive.relaxed;\nbarrier.cluster.wait;" ::: "memory");
            uint32_t slot = 0, phase = 1;
            const uint32_t dst0 = sbase + rank * BOX_BYTES;
            auto acquire = [&](uint32_t bytes) {
                mbar_wait(sbase + OFF_EMPTY + slot * 8, phase);
                mbar_expect_tx(sbase + OFF_FULL + slot * 8, bytes);
            };
            auto adv8 = [&]() {
                if (++slot == 8) {
                    slot = 0;
                    phase ^= 1;
                }
            };
#pragma unroll 1
            for (int hq = 0; hq < 4; hq++) {
                const int col = (g * 4 + ((hq + 1) & 3)) * 128 + rank * 64;
                if (hq == 2) {
                    l2_prefetch(maps.kc + (size_t)(g * 4 * 2048 + (b & 15) * 64) * 128, SLOT_BYTES);
                    l2_prefetch(maps.vc + (size_t)(g * 4 * 2048 + (b & 15) * 64) * 128, SLOT_BYTES);
                }
#pragma unroll 1
                for (int kc = 0; kc < 9; kc++) {
                    acquire(SLOT_BYTES);
                    tma_mc(dst0 + slot * SLOT_BYTES, &maps.wq, col, kc * 64, sbase + OFF_FULL + slot * 8);
                    adv8();
                }
            }
            const int row0 = g * 4 * 2048;
#pragma unroll 1
            for (int n = 0; n < 128; n++) {
                if (n < 4) mbar_wait(sbase + OFF_EMPTY + (slot + 1) * 8, phase);
                acquire(2 * SLOT_BYTES);
                const uint32_t bar = sbase + OFF_FULL + slot * 8;
                const int r0 = n == 0 ? 0 : (n == 127 ? 126 : n + 1);
                const int r1 = n == 0 ? 1 : (n == 127 ? 127 : n - 1);
                tma_mc(dst0 + slot * SLOT_BYTES, n == 127 ? &maps.v : &maps.k, rank * 64, row0 + r0 * 64, bar);
                tma_mc(dst0 + (slot + 1) * SLOT_BYTES, n == 0 ? &maps.k : &maps.v, rank * 64, row0 + r1 * 64, bar);
                adv8();
                adv8();
                if (n >= 96 && n < 96 + 10) {
                    const int i = n - 96;
                    if (i < 9) {
                        l2_prefetch((const char*)maps.wg_p + (size_t)b * 41472 + i * 4608, 4608);
                        l2_prefetch((const char*)maps.wu_p + (size_t)b * 41472 + i * 4608, 4608);
                        l2_prefetch((const char*)maps.wd_p + (size_t)b * 41472 + i * 4608, 4608);
                        l2_prefetch((const char*)maps.wo_p + (size_t)b * 36864 + i * 4096, 4096);
                    }
                }
                const int u = n + KV_AHEAD;
                if (u < 128 && (u & 15) == (b & 15)) {
                    l2_prefetch(maps.kc + (size_t)(row0 + u * 64) * 128, SLOT_BYTES);
                    l2_prefetch(maps.vc + (size_t)(row0 + u * 64) * 128, SLOT_BYTES);
                }
            }
#pragma unroll 1
            for (int p = 0; p < 4; p++)
#pragma unroll 1
                for (int kc = 0; kc < 8; kc++) {
                    acquire(SLOT_BYTES);
                    tma_mc(dst0 + slot * SLOT_BYTES, &maps.wo, p * 128 + rank * 64, g * 512 + kc * 64,
                           sbase + OFF_FULL + slot * 8);
                    adv8();
                }
#pragma unroll 1
            for (int kc = 0; kc < 4; kc++) {
                acquire(SLOT_BYTES);
                tma_mc(dst0 + slot * SLOT_BYTES, &maps.wo, 512, g * 512 + kc * 128 + rank * 64,
                       sbase + OFF_FULL + slot * 8);
                adv8();
            }
            const CUtensorMap* mg = rank ? &maps.wu : &maps.wg;
#pragma unroll 1
            for (int ch = 0; ch < 9; ch++)
#pragma unroll 1
                for (int kc = 0; kc < 9; kc++) {
                    acquire(SLOT_BYTES);
                    tma_mc(dst0 + slot * SLOT_BYTES, mg, g * 576 + ch * 64, kc * 64, sbase + OFF_FULL + slot * 8);
                    adv8();
                }
#pragma unroll 1
            for (int p = 0; p < 4; p++)
#pragma unroll 1
                for (int kc = 2; kc < 11; kc++) {
                    acquire(SLOT_BYTES);
                    tma_mc(dst0 + slot * SLOT_BYTES, &maps.wd, p * 128 + rank * 64, g * 576 + (kc < 9 ? kc : kc - 9) * 64,
                           sbase + OFF_FULL + slot * 8);
                    adv8();
                }
#pragma unroll 1
            for (int i = 0; i < 5; i++) {
                acquire(i < 4 ? SLOT_BYTES : BOX_BYTES);
                const int kc = 2 * i + rank + 2;
                if (i < 4 || rank == 0)
                    tma_mc(dst0 + slot * SLOT_BYTES, &maps.wd, 512, g * 576 + (kc < 9 ? kc : kc - 9) * 64,
                           sbase + OFF_FULL + slot * 8);
                adv8();
            }
        } else if (warp == 11) {
            asm volatile("barrier.cluster.arrive.relaxed.aligned;" ::: "memory");
            bar_sync(6, 160);
            uint4* hz = sc_->h[(get_epoch(sbase) & 1) ^ 1][0] + (size_t)b * 72 * 32 + lane;
#pragma unroll 1
            for (int i = 0; i < 72; i++) {
                hz[i * 32] = make_uint4(0, 0, 0, 0);
                __nanosleep(200);
            }
        } else if (warp == 9 || warp == 10) {
            asm volatile("barrier.cluster.arrive.relaxed.aligned;" ::: "memory");
            bar_sync(4, 320);
            const uint32_t tag = (get_epoch(sbase) + 1) & 0xffffu;
            if (warp == 10 && lane < 9) l2_prefetch((const char*)maps.wq_p + (size_t)b * 36864 + lane * 4096, 4096);
            const int blk = warp == 9 ? 72 + b : 200 + b;
            if (blk < 216) {
                float acc[8];
#pragma unroll
                for (int e = 0; e < 8; e++) acc[e] = 0.f;
                const uint4* wp = reinterpret_cast<const uint4*>(wmod + (size_t)(lane >> 1) * (6 * DM) + blk * 16) + (lane & 1);
                const unsigned short* cp = reinterpret_cast<const unsigned short*>(cvec) + (lane >> 1);
#pragma unroll 1
                for (int i = 0; i < 36; i++) {
                    const uint4 w = __ldg(wp + (size_t)i * (16 * 6 * DM / 8));
                    const float sc = silu_bf16(__ldg(cp + i * 16));
                    acc[0] = fmaf(sc, bf_lo(w.x), acc[0]);
                    acc[1] = fmaf(sc, bf_hi(w.x), acc[1]);
                    acc[2] = fmaf(sc, bf_lo(w.y), acc[2]);
                    acc[3] = fmaf(sc, bf_hi(w.y), acc[3]);
                    acc[4] = fmaf(sc, bf_lo(w.z), acc[4]);
                    acc[5] = fmaf(sc, bf_hi(w.z), acc[5]);
                    acc[6] = fmaf(sc, bf_lo(w.w), acc[6]);
                    acc[7] = fmaf(sc, bf_hi(w.w), acc[7]);
                }
#pragma unroll
                for (int o = 2; o < 32; o <<= 1)
#pragma unroll
                    for (int e = 0; e < 8; e++) acc[e] += __shfl_xor_sync(0xffffffffu, acc[e], o);
                if (lane < 2) {
#pragma unroll
                    for (int e = 0; e < 8; e++) st_mod(sc_->mod + blk * 16 + lane * 8 + e, acc[e], tag);
                }
            }
            if (warp == 9) {
#pragma unroll 1
                for (int st = 1; st <= 2; st++) {
                    bar_sync(7, 160);
                    const uint32_t* src = sc_->mod + (st * 3 - 1) * DM;
                    const int n = st == 1 ? 3 * DM : DM;
#pragma unroll 1
                    for (int i = lane * 4; i < n + 127 - ((n + 127) & 127); i += 128)
                        mod_to_smem(sbase + OFF_MODT + min(i, n - 4) * 4, src + min(i, n - 4), tag);
                    __syncwarp();
                    if (lane == 0) rows_load(sbase, st == 1 ? &maps.rx : &maps.rx2, (mt * 8 + g) * 16);
                    if (st == 1) {
                        bar_sync(7, 160);
                        if (lane == 0) {
                            rows_store(sbase, &maps.rx2, (mt * 8 + g) * 16);
                            rows_store_wait();
                        }
                        __syncwarp();
                        bar_arrive(10, 160);
                    }
                }
            }
        }
    } else {
        asm volatile("setmaxnreg.inc.sync.aligned.u32 240;");
        const int wg = warp >> 2;
        const int tid = threadIdx.x;
        Ctx cx;
        cx.sbase = sbase;
        cx.wg = wg;
        if (wg == 1) bar_arrive(8, 256);
        cx.rel_cta = (lane == 0 && (warp & 3) < 2) ? (warp & 3) : 2;
        const uint32_t red = sbase + OFF_RED;
        const int own = mt * 8 + g;
        const int wown = mt * 8 + warp;
        PROF(0);
        PROFG(30);
        PROFR(17);
        {
            const int r0 = tid >> 1;
            PROFR(18);
            asm volatile("barrier.cluster.arrive.relaxed.aligned;" ::: "memory");
            bar_sync(3, 256);
            PROFR(19);
            mbar_wait(sbase + OFF_WBAR, 0);
            PROFR(20);
            if (b < 72) {
                float sc[5];
                uint4 w1[5];
#pragma unroll
                for (int i = 0; i < 5; i++) {
                    unsigned short cu;
                    asm volatile("ld.shared.u16 %0, [%1];" : "=h"(cu) : "r"(sbase + OFF_CVEC + min(r0 + 128 * i, DM - 1) * 2));
                    sc[i] = (r0 + 128 * i < DM) ? silu_bf16(cu) : 0.f;
                }
#pragma unroll
                for (int i = 0; i < 5; i++)
                    lds128(sbase + OFF_WBLK + (i < 4 ? tid + i * 256 : 1024 + (tid & 127)) * 16, w1[i].x, w1[i].y, w1[i].z, w1[i].w);
                mod_block(w1, sc, sc_->mod + b * 16, red + 1024, warp, lane, (get_epoch(sbase) + 1) & 0xffffu);
            }
            PROFR(21);
        }

        Ring ring{0u, 0u};
        int stage = 0;
        asm volatile("" : "+r"(stage));
#pragma unroll 1
        for (;; stage++) {
            int tid, lane;
            asm volatile("mov.u32 %0, %%tid.x;" : "=r"(tid));
            lane = tid & 31;
            const uint32_t epoch = get_epoch(sbase);
            {
                float v[36];
                const uint32_t modt = sbase + OFF_MODT + (warp * 16 + (lane & 3) * 2) * 4;
                if (stage == 0) {
#pragma unroll
                    for (int i = 0; i < 36; i++) v[i] = 0.f;
                } else {
                    const uint4* psrc = sc_->part + (size_t)own * 8 * 36 * 32;
                    sum_partials(v, psrc + tid, stage & 1);
                    PROF(stage == 1 ? 8 : 15);
                    sum_tail(v, reinterpret_cast<const uint2*>(psrc + 32 * 32) + tid, stage & 1);
                }
                mbar_wait(sbase + OFF_XBAR, stage & 1);
                if (stage == 0) PROFR(22);
                {
                    const float gs = stage == 2 ? 0.5f : 1.f;
                    float gate[18];
                    lds_mod(gate, modt, warp);
                    const int r = lane >> 2;
                    const uint32_t rows = sbase + OFF_ROWS + r * (DM * 2) + (lane & 3) * 4;
#pragma unroll
                    for (int j = 0; j < 9; j++) {
                        const int ch = j < 8 ? (j >> 1) * 2 + (warp >> 2) : 8, c16 = j < 8 ? (warp & 3) * 2 + (j & 1) : warp;
                        const uint32_t ad = rows + ch * 128 + ((c16 ^ ((r + ch) & 7)) << 4);
                        const uint32_t u0 = __float_as_uint(lds32f(ad)), u1 = __float_as_uint(lds32f(ad + 8 * DM * 2));
                        const float g0 = stage ? gate[2 * j] * gs : 0.f, g1 = stage ? gate[2 * j + 1] * gs : 0.f;
                        v[4 * j] = fmaf(g0, v[4 * j], bf_lo(u0));
                        v[4 * j + 1] = fmaf(g1, v[4 * j + 1], bf_hi(u0));
                        v[4 * j + 2] = fmaf(g0, v[4 * j + 2], bf_lo(u1));
                        v[4 * j + 3] = fmaf(g1, v[4 * j + 3], bf_hi(u1));
                        sts32f(ad, __uint_as_float(pack_bf16(v[4 * j], v[4 * j + 1])));
                        sts32f(ad + 8 * DM * 2, __uint_as_float(pack_bf16(v[4 * j + 2], v[4 * j + 3])));
                    }
                    asm volatile("fence.proxy.async.shared::cta;" ::: "memory");
                }
                if (stage == 2) break;
                PROF(stage == 0 ? 1 : 9);
                layernorm_rows(v, red, warp, lane);
                if (stage == 0) PROFR(27);
                if (stage == 0) {
                    const uint32_t tag = (epoch + 1) & 0xffffu;
                    mod_to_smem(sbase + OFF_MODT + (DM + tid * 4) * 4, sc_->mod + tid * 4, tag);
                    if (warp == 7) mod_to_smem(sbase + OFF_MODT + (DM + 1024 + lane * 4) * 4, sc_->mod + 1024 + lane * 4, tag);
                    bar_sync(3, 256);
                    bar_arrive(4, 320);
                }
                float shift[18], scale[18];
                lds_mod(shift, modt + DM * 4, warp);
                lds_mod(scale, modt + 2 * DM * 4, warp);
                if (stage == 0) PROFR(28);
                PROF(stage == 0 ? 2 : 10);
                modulate_store(v, shift, scale, sc_->h[epoch & 1][stage] + (size_t)own * 36 * 32, warp, lane);
                if (stage == 0) asm volatile("barrier.cluster.wait.aligned;" ::: "memory");
            }

            const uint32_t spill = sbase + 8 * SLOT_BYTES + wg * 3 * SLOT_BYTES + (tid & 127) * 16;
            uint32_t a[144];
            PROF(stage == 0 ? 3 : 11);
            {
                const uint4* hsrc = sc_->h[epoch & 1][stage] + (size_t)wown * 36 * 32 + lane;
                poll_tail(a, reinterpret_cast<const uint2*>(hsrc - lane + 32 * 32) + lane);
                PROF(stage == 0 ? 4 : 12);
                if (stage == 1) PROFG(25);
                TG(stage * 32 + 30);
                if (wg == 1) bar_sync(5, 256);
                poll_frags<0, 32>(a, hsrc, wg == 0);
            }
            uint4* hhbuf = sc_->hh + (size_t)b * 8 * 256 + tid;
            float d[64];
#pragma unroll 1
            for (int ch = 0;; ch++) {
                TG(stage * 32 + ch * 2);
                gemm_n128(d, a, cx, ring, true);
                TG(stage * 32 + ch * 2 + 1);
                if (stage == 0) {
#pragma unroll
                    for (int i = 0; i < 64; i++) d[i] *= SM_SCALE;
                    if (ch == 3) break;
#pragma unroll
                    for (int v = 0; v < 8; v++)
                        sts128(spill + (ch * 8 + v) * 2048, pack_bf16(d[8 * v], d[8 * v + 1]),
                               pack_bf16(d[8 * v + 2], d[8 * v + 3]), pack_bf16(d[8 * v + 4], d[8 * v + 5]),
                               pack_bf16(d[8 * v + 6], d[8 * v + 7]));
                } else {
#pragma unroll
                    for (int i = 0; i < 32; i++) {
                        const float gv = d[i], gu = gv * d[32 + i];
                        const float z = gv * fmaf(gv * gv, 0.7978845608028654f * 0.044715f, 0.7978845608028654f);
                        d[i] = fmaf(gu, tanh_fast(z), gu);
                    }
                    if (ch == 8) break;
                    if (wg == 0) {
                        if (ch == 0) bar_arrive(7, 160);
                        if (ch == 2) bar_sync(10, 160);
                    }
#pragma unroll
                    for (int v = 0; v < 4; v++) {
                        const uint4 h4 = make_uint4(pack_bf16(d[8 * v], d[8 * v + 1]), pack_bf16(d[8 * v + 2], d[8 * v + 3]),
                                                    pack_bf16(d[8 * v + 4], d[8 * v + 5]), pack_bf16(d[8 * v + 6], d[8 * v + 7]));
                        if (ch < 2)
                            __stcg(hhbuf + (ch * 4 + v) * 256, h4);
                        else
                            sts128(spill + ((ch - 2) * 4 + v) * 2048, h4.x, h4.y, h4.z, h4.w);
                    }
                }
            }
            if (stage == 0) {
                uint32_t q[32];
#pragma unroll
                for (int i = 0; i < 32; i++) q[i] = pack_bf16(d[2 * i], d[2 * i + 1]);
                PROF(5);
                PROFG(23);
                if (wg == 0) bar_arrive(6, 160);
                {
                    float o[64], sa[32], sb[32];
                    uint32_t pa[16], pb[16];
#pragma unroll
                    for (int i = 0; i < 64; i++) o[i] = 0.f;
                    float n0 = 0.f, n1 = 0.f, l0 = 1.f, l1 = 1.f;
                    bool shifted = false;
                    const uint64_t dbase = desc_of(sbase);
                    const uint64_t dbk = dbase - (511u << 16);
                    const int my_bar = 1 + wg, other_bar = 2 - wg;

                    auto softmax_a = [&](bool first, float& s0, float& s1) {
                        if (first) {
                            shifted = false;
                            n0 = n1 = 0.f;
                            l0 = l1 = 0.f;
                        }
                        if (shifted)
                            exp_step<true>(sa, pa, n0, n1, s0, s1);
                        else
                            exp_step<false>(sa, pa, n0, n1, s0, s1);
                    };
                    auto softmax_b = [&](bool first, float s0, float s1) {
                        float u0, u1;
                        if (shifted)
                            exp_step<true>(sb, pb, n0, n1, u0, u1);
                        else
                            exp_step<false>(sb, pb, n0, n1, u0, u1);
                        s0 += u0;
                        s1 += u1;
                        bool bad = !(fmaxf(s0, s1) <= SM_HI);
                        if (first) {
                            float r0 = s0 + __shfl_xor_sync(0xffffffffu, s0, 1), r1 = s1 + __shfl_xor_sync(0xffffffffu, s1, 1);
                            r0 += __shfl_xor_sync(0xffffffffu, r0, 2);
                            r1 += __shfl_xor_sync(0xffffffffu, r1, 2);
                            bad = bad || !(fminf(r0, r1) >= SM_LO);
                        }
                        if (__any_sync(0xffffffffu, bad)) {
                            float x0, x1;
                            row_max(sa, sb, x0, x1);
                            x0 = -x0;
                            x1 = -x1;
                            if (!first) {
                                x0 = fminf(x0, n0);
                                x1 = fminf(x1, n1);
                                const float al0 = ex2(x0 - n0), al1 = ex2(x1 - n1);
                                l0 *= al0;
                                l1 *= al1;
#pragma unroll
                                for (int i = 0; i < 16; i++) {
                                    o[4 * i] *= al0;
                                    o[4 * i + 1] *= al0;
                                    o[4 * i + 2] *= al1;
                                    o[4 * i + 3] *= al1;
                                }
                            }
                            n0 = x0;
                            n1 = x1;
                            shifted = true;
                            exp_step<true>(sa, pa, n0, n1, s0, s1);
                            exp_step<true>(sb, pb, n0, n1, u0, u1);
                            s0 += u0;
                            s1 += u1;
                        }
                        l0 += s0;
                        l1 += s1;
                    };

                    cx.wait_full(4, 0);
                    if (wg == 1) bar_sync(my_bar, 256);
                    wg_fence();
                    qk_step(sa, q, dbk + 4 * 1024);
                    qk_step(sb, q, dbk + 5 * 1024);
                    wg_commit();
                    bar_arrive(other_bar, 256);
                    wg_wait<0>();
                    pin(sa);
                    pin(sb);
                    cx.release(4);
                    cx.wait_full(6, 0);
                    {
                        float s0, s1;
                        softmax_a(true, s0, s1);
                        softmax_b(true, s0, s1);
                    }
                    uint32_t alo = (uint32_t)dbase + 6 * 1024, blo = (uint32_t)dbase;
                    const uint32_t dhi = (uint32_t)(dbase >> 32);
#pragma unroll 1
                    for (int t = 1; t < 64; t++) {
                        const int j = t & 15;
                        const uint32_t sA = 2 + 4 * (t & 1), sB = 4 - 4 * (t & 1);
                        const uint64_t da = ((uint64_t)dhi << 32) | alo, db = ((uint64_t)dhi << 32) | blo;
                        TL(0);
                        bar_sync(my_bar, 256);
                        TL(2);
                        wg_fence();
                        pv_step(o, pa, da + 1024, j != 1);
                        qk_step(sa, q, da - (511u << 16));
                        wg_commit();
                        cx.wait_full(sB, ((36 + 4 * t) >> 3) & 1);
                        wg_fence();
                        qk_step(sb, q, db - (511u << 16));
                        pv_step(o, pb, db + 1024, 1);
                        wg_commit();
                        bar_arrive(other_bar, 256);
                        alo ^= 4096;
                        blo ^= 4096;
                        asm volatile("" : "+r"(alo), "+r"(blo));
                        TL(3);
                        wg_wait<1>();
                        pin(sa);
                        pin(pa);
                        TL(4);
                        cx.release(sA);
                        const float lp0 = l0, lp1 = l1;
                        float s0, s1;
                        softmax_a(j == 0, s0, s1);
                        TL(5);
                        wg_wait<0>();
                        pin(o);
                        pin(sb);
                        pin(pb);
                        TL(6);
                        cx.release(sB);
                        if (j == 0) {
                            float i0, i1;
                            inv_row_sums(lp0, lp1, i0, i1);
                            const uint32_t dst = spill + ((t >> 4) - 1) * 16384;
#pragma unroll
                            for (int v = 0; v < 8; v++)
                                sts128(dst + v * 2048, pack_bf16(o[8 * v] * i0, o[8 * v + 1] * i0),
                                       pack_bf16(o[8 * v + 2] * i1, o[8 * v + 3] * i1),
                                       pack_bf16(o[8 * v + 4] * i0, o[8 * v + 5] * i0),
                                       pack_bf16(o[8 * v + 6] * i1, o[8 * v + 7] * i1));
                        }
                        const uint32_t bn = sbase + OFF_FULL + (8 - sA) * 8, pn = ((38 + 4 * t) >> 3) & 1;
                        const bool okn = mbar_try(bn, pn);
                        TL(1);
                        softmax_b(j == 0, s0, s1);
                        if (!okn || j == 15) {
                            mbar_wait(bn, pn);
                            if (j == 15 && t < 63) {
                                const uint32_t src = spill + (t >> 4) * 16384;
#pragma unroll
                                for (int v = 0; v < 8; v++)
                                    lds128(src + v * 2048, q[4 * v], q[4 * v + 1], q[4 * v + 2], q[4 * v + 3]);
                            }
                        }
                        TL(7);
                    }
                    bar_sync(my_bar, 256);
                    wg_fence();
                    pv_step(o, pa, dbase + 2 * 1024, 1);
                    pv_step(o, pb, dbase + 3 * 1024, 1);
                    wg_commit();
                    if (wg == 0) bar_arrive(other_bar, 256);
                    float i0, i1;
                    inv_row_sums(l0, l1, i0, i1);
                    wg_wait<0>();
                    pin(o);
                    cx.release(2);
#pragma unroll
                    for (int i = 0; i < 16; i++) {
                        a[96 + 2 * i] = pack_bf16(o[4 * i] * i0, o[4 * i + 1] * i0);
                        a[96 + 2 * i + 1] = pack_bf16(o[4 * i + 2] * i1, o[4 * i + 3] * i1);
                    }
#pragma unroll
                    for (int i = 128; i < 144; i++) a[i] = 0;
                }
                ring.slot = 4;
                ring.phase = 0;
                PROF(6);
                PROFG(24);
            } else {
#pragma unroll
                for (int v = 0; v < 8; v++) {
                    const uint4 t = __ldcg(hhbuf + v * 256);
                    a[112 + 4 * v] = t.x;
                    a[113 + 4 * v] = t.y;
                    a[114 + 4 * v] = t.z;
                    a[115 + 4 * v] = t.w;
                }
#pragma unroll
                for (int i = 0; i < 16; i++) a[96 + i] = pack_bf16(d[2 * i], d[2 * i + 1]);
                PROF(13);
            }
#pragma unroll
            for (int v = 0; v < 24; v++) lds128(spill + v * 2048, a[4 * v], a[4 * v + 1], a[4 * v + 2], a[4 * v + 3]);

            {
                uint4* dst = sc_->part + ((size_t)wown * 8 + g) * 36 * 32 + lane;
                const uint32_t ptag = (stage + 1) & 1;
#pragma unroll 1
                for (int p = 0; p < 4; p++) {
                    TG(stage * 32 + 18 + p * 2);
                    gemm_n128(d, a, cx, ring, stage != 0);
                    TG(stage * 32 + 19 + p * 2);
#pragma unroll
                    for (int u = 0; u < 8; u++)
                        st128(dst + (p * 8 + u) * 32, (pack_bf16(d[8 * u], d[8 * u + 1]) & ~1u) | ptag,
                              pack_bf16(d[8 * u + 2], d[8 * u + 3]), pack_bf16(d[8 * u + 4], d[8 * u + 5]),
                              pack_bf16(d[8 * u + 6], d[8 * u + 7]));
                    if (p == 0 && wg == 0) bar_arrive(7, 160);
                }
                float e[32];
                TG(stage * 32 + 26);
                gemm_n64(e, a, cx, ring, stage != 0);
                TG(stage * 32 + 27);
                uint2* dst2 = reinterpret_cast<uint2*>(dst - lane + 32 * 32) + lane;
#pragma unroll
                for (int j = 0; j < 8; j++)
                    st64(dst2 + j * 32, (pack_bf16(e[4 * j], e[4 * j + 1]) & ~1u) | ptag, pack_bf16(e[4 * j + 2], e[4 * j + 3]));
            }
            PROF(stage == 0 ? 7 : 14);
            if (stage == 1) {
                PROFG(26);
                asm volatile("barrier.cluster.arrive.relaxed.aligned;" ::: "memory");
            }
        }
        if (wg == 0) bar_sync(8, 256);
        bar_sync(3, 256);
        if (tid == 32) sc_->epoch[b * 32] = get_epoch(sbase) + 1;
        if (tid == 0) {
            rows_store(sbase, &maps.rout, own * 16);
            rows_store_wait();
        }
        __syncwarp();
        PROF(16);
        PROFG(31);
        asm volatile("barrier.cluster.wait.aligned;" ::: "memory");
    }
}

typedef CUresult (*EncodeFn)(CUtensorMap*, CUtensorMapDataType, cuuint32_t, void*, const cuuint64_t*, const cuuint64_t*,
                             const cuuint32_t*, const cuuint32_t*, CUtensorMapInterleave, CUtensorMapSwizzle,
                             CUtensorMapL2promotion, CUtensorMapFloatOOBfill);

void make_map(EncodeFn enc, CUtensorMap* m, const void* ptr, uint64_t rows, uint64_t cols, bool narrow = false) {
    cuuint64_t gdim[2] = {cols, rows};
    cuuint64_t gstr[1] = {cols * 2};
    cuuint32_t box[2] = {narrow ? 16u : 64u, narrow ? 192u : 64u};
    cuuint32_t estr[2] = {1, 1};
    enc(m, CU_TENSOR_MAP_DATA_TYPE_BFLOAT16, 2, const_cast<void*>(ptr), gdim, gstr, box, estr,
        CU_TENSOR_MAP_INTERLEAVE_NONE, narrow ? CU_TENSOR_MAP_SWIZZLE_NONE : CU_TENSOR_MAP_SWIZZLE_128B,
        CU_TENSOR_MAP_L2_PROMOTION_L2_128B,
        CU_TENSOR_MAP_FLOAT_OOB_FILL_NONE);
}

void make_rows_map(EncodeFn enc, CUtensorMap* m, const void* ptr) {
    cuuint64_t gdim[3] = {64, 9, 2048};
    cuuint64_t gstr[2] = {128, DM * 2};
    cuuint32_t box[3] = {64, 9, 16};
    cuuint32_t estr[3] = {1, 1, 1};
    enc(m, CU_TENSOR_MAP_DATA_TYPE_BFLOAT16, 3, const_cast<void*>(ptr), gdim, gstr, box, estr,
        CU_TENSOR_MAP_INTERLEAVE_NONE, CU_TENSOR_MAP_SWIZZLE_128B, CU_TENSOR_MAP_L2_PROMOTION_L2_128B,
        CU_TENSOR_MAP_FLOAT_OOB_FILL_NONE);
}

}

extern "C" void kernel_launch(void* const* d_in, const int* in_sizes, int n_in, void* d_out, int out_size) {
    (void)in_sizes;
    (void)n_in;
    (void)out_size;
    void* fn = nullptr;
    cudaDriverEntryPointQueryResult qr;
    cudaGetDriverEntryPoint("cuTensorMapEncodeTiled", &fn, cudaEnableDefault, &qr);
    EncodeFn enc = (EncodeFn)fn;
    Params maps;
    maps.x = (const __nv_bfloat16*)d_in[0];
    maps.cvec = (const __nv_bfloat16*)d_in[9];
    maps.wmod = (const __nv_bfloat16*)d_in[10];
    maps.kc = (const __nv_bfloat16*)d_in[1];
    maps.vc = (const __nv_bfloat16*)d_in[2];
    maps.wq_p = (const __nv_bfloat16*)d_in[3];
    maps.wo_p = (const __nv_bfloat16*)d_in[4];
    maps.wg_p = (const __nv_bfloat16*)d_in[6];
    maps.wu_p = (const __nv_bfloat16*)d_in[7];
    maps.wd_p = (const __nv_bfloat16*)d_in[8];
    maps.out = (__nv_bfloat16*)d_out;
    void* scp = nullptr;
    cudaGetSymbolAddress(&scp, g_scratch);
    maps.sc = (Scratch*)scp;
    make_map(enc, &maps.k, d_in[1], 32 * 2048, 128);
    make_map(enc, &maps.v, d_in[2], 32 * 2048, 128);
    make_map(enc, &maps.wq, d_in[3], 576, 4096);
    make_map(enc, &maps.wo, d_in[4], 4096, 576);
    make_map(enc, &maps.wg, d_in[6], 576, 4608);
    make_map(enc, &maps.wu, d_in[7], 576, 4608);
    make_map(enc, &maps.wd, d_in[8], 4608, 576);
    make_map(enc, &maps.wm, d_in[10], 576, 3456, true);
    make_rows_map(enc, &maps.rx, d_in[0]);
    make_rows_map(enc, &maps.rx2, (char*)scp + offsetof(Scratch, x2));
    make_rows_map(enc, &maps.rout, d_out);
    cudaFuncSetAttribute(fused_block_kernel, cudaFuncAttributeMaxDynamicSharedMemorySize, SMEM_BYTES);
    fused_block_kernel<<<128, 384, SMEM_BYTES>>>(maps);
}
```

```cpp
#include <cuda_runtime.h>
#include <cuda_bf16.h>
#include <cuda.h>
#include <stdint.h>
#include <stddef.h>

namespace {

constexpr int DM = 576;
constexpr int SLOT_BYTES = 16384;
constexpr int BOX_BYTES = 8192;
constexpr int NUNITS = 14;
constexpr int SMEM_TAIL = NUNITS * SLOT_BYTES;
constexpr int SMEM_BYTES = SMEM_TAIL + 2048 + 1024;
constexpr int OFF_FULL = SMEM_TAIL;
constexpr int OFF_EMPTY = SMEM_TAIL + 64;
constexpr int OFF_RED = SMEM_TAIL + 128;

constexpr int KV_AHEAD = 16;
#define GATE_SLOT 4
constexpr int OFF_XBAR = SMEM_TAIL + 1792;
constexpr int OFF_ROWS = 8 * SLOT_BYTES;
constexpr int OFF_MODT = OFF_ROWS + 20480;
constexpr int OFF_EPOCH = SMEM_TAIL + 1808;
constexpr int OFF_CVEC = OFF_ROWS + 28672;

struct Scratch {
    unsigned epoch[128 * 32];
    uint32_t mod[6 * DM];
    uint4 h[2][2][128 * 36 * 32];
    uint4 part[128 * 8 * 36 * 32];
    uint4 hh[128 * 8 * 256];
    __nv_bfloat16 x2[2048 * DM];
};
__device__ Scratch g_scratch;

#define TG(i)
#define TL(i)
#define PROFR(i)
#define PROF(i)
#define PROFG(i)

struct Params {
    const __nv_bfloat16 *x, *cvec, *wmod, *kc, *vc, *wq_p, *wo_p, *wg_p, *wu_p, *wd_p;
    __nv_bfloat16* out;
    Scratch* sc;
    CUtensorMap k, v, wq, wo, wg, wu, wd, rx, rx2, rout;
};

__device__ __forceinline__ uint32_t smem_u32(const void* p) { return (uint32_t)__cvta_generic_to_shared(p); }
__device__ __forceinline__ void mbar_init(uint32_t a, uint32_t c) {
    asm volatile("mbarrier.init.shared::cta.b64 [%0], %1;" ::"r"(a), "r"(c) : "memory");
}
__device__ __forceinline__ void mbar_expect_tx(uint32_t a, uint32_t bytes) {
    asm volatile("mbarrier.arrive.expect_tx.shared::cta.b64 _, [%0], %1;" ::"r"(a), "r"(bytes) : "memory");
}
__device__ __forceinline__ bool mbar_try(uint32_t a, uint32_t ph) {
    uint32_t ok;
    asm volatile(
        "{\n.reg .pred p;\nmbarrier.try_wait.parity.shared::cta.b64 p, [%1], %2;\nselp.u32 %0, 1, 0, p;\n}"
        : "=r"(ok)
        : "r"(a), "r"(ph)
        : "memory");
    return ok != 0;
}
__device__ __forceinline__ uint32_t clk32() {
    uint32_t c;
    asm volatile("mov.u32 %0, %%clock;" : "=r"(c));
    return c;
}
constexpr uint32_t WAIT_LIMIT = 1u << 30;
__device__ __forceinline__ void mbar_wait(uint32_t a, uint32_t ph) {
    if (mbar_try(a, ph)) return;
    uint32_t t0 = clk32();
    while (!mbar_try(a, ph)) {
        if (clk32() - t0 > WAIT_LIMIT) break;
    }
}
__device__ __forceinline__ void mbar_arrive_cluster(uint32_t a, uint32_t cta) {
    asm volatile(
        "{\n.reg .b32 ra;\nmapa.shared::cluster.u32 ra, %0, %1;\nmbarrier.arrive.shared::cluster.b64 _, [ra];\n}" ::"r"(a),
        "r"(cta)
        : "memory");
}
__device__ __forceinline__ void tma_mc(uint32_t dst, const CUtensorMap* m, int c0, int c1, uint32_t bar) {
    asm volatile(
        "cp.async.bulk.tensor.2d.shared::cluster.global.mbarrier::complete_tx::bytes.multicast::cluster"
        " [%0], [%1, {%3, %4}], [%2], %5;" ::"r"(dst),
        "l"(m), "r"(bar), "r"(c0), "r"(c1), "h"((uint16_t)3)
        : "memory");
}
__device__ __forceinline__ void bulk_load(uint32_t dst, const void* src, uint32_t bytes, uint32_t bar) {
    asm volatile("cp.async.bulk.shared::cluster.global.mbarrier::complete_tx::bytes [%0], [%1], %2, [%3];" ::"r"(dst),
                 "l"(src), "r"(bytes), "r"(bar)
                 : "memory");
}
__device__ __forceinline__ void l2_prefetch(const void* p, uint32_t bytes) {
    asm volatile("cp.async.bulk.prefetch.L2.global [%0], %1;" ::"l"(p), "r"(bytes) : "memory");
}
__device__ __forceinline__ void bar_sync(int id, int n) { asm volatile("bar.sync %0, %1;" ::"r"(id), "r"(n) : "memory"); }
__device__ __forceinline__ void bar_arrive(int id, int n) {
    asm volatile("bar.arrive %0, %1;" ::"r"(id), "r"(n) : "memory");
}
__device__ __forceinline__ void wg_fence() { asm volatile("wgmma.fence.sync.aligned;" ::: "memory"); }
__device__ __forceinline__ void wg_commit() { asm volatile("wgmma.commit_group.sync.aligned;" ::: "memory"); }
template <int N>
__device__ __forceinline__ void wg_wait() {
    asm volatile("wgmma.wait_group.sync.aligned %0;" ::"n"(N) : "memory");
}
template <int N>
__device__ __forceinline__ void pin(float (&d)[N]) {
#pragma unroll
    for (int i = 0; i < N; i++) asm volatile("" : "+f"(d[i])::"memory");
}
template <int N>
__device__ __forceinline__ void pin(uint32_t (&d)[N]) {
#pragma unroll
    for (int i = 0; i < N; i++) asm volatile("" : "+r"(d[i])::"memory");
}
__device__ __forceinline__ uint32_t pack_bf16(float lo, float hi) {
    uint32_t r;
    asm("cvt.rn.bf16x2.f32 %0, %1, %2;" : "=r"(r) : "f"(hi), "f"(lo));
    return r;
}
__device__ __forceinline__ float bf_lo(uint32_t v) { return __uint_as_float(v << 16); }
__device__ __forceinline__ float bf_hi(uint32_t v) { return __uint_as_float(v & 0xffff0000u); }
__device__ __forceinline__ float round_bf16(float v) { return __bfloat162float(__float2bfloat16_rn(v)); }
__device__ __forceinline__ float ex2(float x) {
    float y;
    asm("ex2.approx.ftz.f32 %0, %1;" : "=f"(y) : "f"(x));
    return y;
}
__device__ __forceinline__ float rcp(float x) {
    float y;
    asm("rcp.approx.ftz.f32 %0, %1;" : "=f"(y) : "f"(x));
    return y;
}
__device__ __forceinline__ float tanh_fast(float x) {
    float y;
    asm("tanh.approx.f32 %0, %1;" : "=f"(y) : "f"(x));
    return y;
}
__device__ __forceinline__ void sts128(uint32_t a, uint32_t x, uint32_t y, uint32_t z, uint32_t w) {
    asm volatile("st.shared.v4.b32 [%0], {%1,%2,%3,%4};" ::"r"(a), "r"(x), "r"(y), "r"(z), "r"(w) : "memory");
}
__device__ __forceinline__ void lds128(uint32_t a, uint32_t& x, uint32_t& y, uint32_t& z, uint32_t& w) {
    asm volatile("ld.shared.v4.b32 {%0,%1,%2,%3}, [%4];" : "=r"(x), "=r"(y), "=r"(z), "=r"(w) : "r"(a) : "memory");
}
__device__ __forceinline__ void sts32f(uint32_t a, float v) {
    asm volatile("st.shared.f32 [%0], %1;" ::"r"(a), "f"(v) : "memory");
}
__device__ __forceinline__ float lds32f(uint32_t a) {
    float v;
    asm volatile("ld.shared.f32 %0, [%1];" : "=f"(v) : "r"(a) : "memory");
    return v;
}
#define F8(d, b) \
    "+f"(d[b]), "+f"(d[b + 1]), "+f"(d[b + 2]), "+f"(d[b + 3]), "+f"(d[b + 4]), "+f"(d[b + 5]), "+f"(d[b + 6]), "+f"(d[b + 7])

template <int TB>
__device__ __forceinline__ void wgmma_n128(float (&d)[64], uint32_t a0, uint32_t a1, uint32_t a2, uint32_t a3,
                                           uint64_t db, int sc) {
    asm volatile(
        "{\n.reg .pred p;\nsetp.ne.b32 p, %69, 0;\n"
        "wgmma.mma_async.sync.aligned.m64n128k16.f32.bf16.bf16 "
        "{%0,%1,%2,%3,%4,%5,%6,%7,%8,%9,%10,%11,%12,%13,%14,%15,%16,%17,%18,%19,%20,%21,%22,%23,%24,%25,%26,%27,%28,%29,%30,%31,"
        "%32,%33,%34,%35,%36,%37,%38,%39,%40,%41,%42,%43,%44,%45,%46,%47,%48,%49,%50,%51,%52,%53,%54,%55,%56,%57,%58,%59,%60,%61,%62,%63},"
        "{%64,%65,%66,%67}, %68, p, 1, 1, %70;\n}"
        : F8(d, 0), F8(d, 8), F8(d, 16), F8(d, 24), F8(d, 32), F8(d, 40), F8(d, 48), F8(d, 56)
        : "r"(a0), "r"(a1), "r"(a2), "r"(a3), "l"(db), "r"(sc), "n"(TB));
}
#define O8(d, b) \
    "=f"(d[b]), "=f"(d[b + 1]), "=f"(d[b + 2]), "=f"(d[b + 3]), "=f"(d[b + 4]), "=f"(d[b + 5]), "=f"(d[b + 6]), "=f"(d[b + 7])
template <int TB>
__device__ __forceinline__ void wgmma_n128_z(float (&d)[64], uint32_t a0, uint32_t a1, uint32_t a2, uint32_t a3,
                                             uint64_t db) {
    asm volatile(
        "wgmma.mma_async.sync.aligned.m64n128k16.f32.bf16.bf16 "
        "{%0,%1,%2,%3,%4,%5,%6,%7,%8,%9,%10,%11,%12,%13,%14,%15,%16,%17,%18,%19,%20,%21,%22,%23,%24,%25,%26,%27,%28,%29,%30,%31,"
        "%32,%33,%34,%35,%36,%37,%38,%39,%40,%41,%42,%43,%44,%45,%46,%47,%48,%49,%50,%51,%52,%53,%54,%55,%56,%57,%58,%59,%60,%61,%62,%63},"
        "{%64,%65,%66,%67}, %68, 0, 1, 1, %69;"
        : O8(d, 0), O8(d, 8), O8(d, 16), O8(d, 24), O8(d, 32), O8(d, 40), O8(d, 48), O8(d, 56)
        : "r"(a0), "r"(a1), "r"(a2), "r"(a3), "l"(db), "n"(TB));
}
template <int TB>
__device__ __forceinline__ void wgmma_n64_z(float (&d)[32], uint32_t a0, uint32_t a1, uint32_t a2, uint32_t a3,
                                            uint64_t db) {
    asm volatile(
        "wgmma.mma_async.sync.aligned.m64n64k16.f32.bf16.bf16 "
        "{%0,%1,%2,%3,%4,%5,%6,%7,%8,%9,%10,%11,%12,%13,%14,%15,%16,%17,%18,%19,%20,%21,%22,%23,%24,%25,%26,%27,%28,%29,%30,%31},"
        "{%32,%33,%34,%35}, %36, 0, 1, 1, %37;"
        : O8(d, 0), O8(d, 8), O8(d, 16), O8(d, 24)
        : "r"(a0), "r"(a1), "r"(a2), "r"(a3), "l"(db), "n"(TB));
}
template <int TB>
__device__ __forceinline__ void wgmma_n64(float (&d)[32], uint32_t a0, uint32_t a1, uint32_t a2, uint32_t a3,
                                          uint64_t db) {
    asm volatile(
        "wgmma.mma_async.sync.aligned.m64n64k16.f32.bf16.bf16 "
        "{%0,%1,%2,%3,%4,%5,%6,%7,%8,%9,%10,%11,%12,%13,%14,%15,%16,%17,%18,%19,%20,%21,%22,%23,%24,%25,%26,%27,%28,%29,%30,%31},"
        "{%32,%33,%34,%35}, %36, 1, 1, 1, %37;"
        : F8(d, 0), F8(d, 8), F8(d, 16), F8(d, 24)
        : "r"(a0), "r"(a1), "r"(a2), "r"(a3), "l"(db), "n"(TB));
}

__device__ __forceinline__ uint64_t desc_of(uint32_t saddr) {
    return (uint64_t)(((saddr >> 4) & 0x3FFFu) | (512u << 16)) | ((uint64_t)(64u | (1u << 30)) << 32);
}

struct Ring {
    uint32_t slot;
    uint32_t phase;
    __device__ __forceinline__ void next() {
        if (++slot == 8) {
            slot = 0;
            phase ^= 1;
        }
    }
};

struct Ctx {
    uint32_t sbase;
    int wg;
    uint32_t rel_cta;
    __device__ __forceinline__ void wait_full(uint32_t slot, uint32_t phase) const {
        mbar_wait(sbase + OFF_FULL + slot * 8, phase);
    }
    __device__ __forceinline__ void release(uint32_t slot) const {
        if (rel_cta < 2) mbar_arrive_cluster(sbase + OFF_EMPTY + slot * 8, rel_cta);
    }
};

__device__ __forceinline__ void gemm_n128(float (&d)[64], const uint32_t (&a)[144], const Ctx& c, Ring& r, bool nine) {
    uint32_t prev = 0;
#pragma unroll
    for (int s = 0; s < 9; s++) {
        if (s < 8 || nine) {
            if (s == GATE_SLOT) bar_sync(8 + c.wg, 256);
            c.wait_full(r.slot, r.phase);
            uint64_t db = desc_of(c.sbase + r.slot * SLOT_BYTES);
            wg_fence();
#pragma unroll
            for (int k = 0; k < 4; k++) {
                if ((s | k) == 0)
                    wgmma_n128_z<1>(d, a[0], a[1], a[2], a[3], db);
                else
                    wgmma_n128<1>(d, a[s * 16 + k * 4], a[s * 16 + k * 4 + 1], a[s * 16 + k * 4 + 2],
                                  a[s * 16 + k * 4 + 3], db + k * 128, 1);
            }
            wg_commit();
            if (s == 8 || (s == 7 && !nine)) bar_arrive(9 - c.wg, 256);
            if (s > 0) {
                wg_wait<1>();
                c.release(prev);
            }
            prev = r.slot;
            r.next();
        }
    }
    wg_wait<0>();
    c.release(prev);
    pin(d);
}
__device__ __forceinline__ void gemm_n64(float (&d)[32], const uint32_t (&a)[144], const Ctx& c, Ring& r, bool nine) {
    uint32_t prev = 0;
#pragma unroll
    for (int s = 0; s < 5; s++) {
        if (s < 4 || nine) {
            c.wait_full(r.slot, r.phase);
            uint64_t db = desc_of(c.sbase + r.slot * SLOT_BYTES);
            wg_fence();
#pragma unroll
            for (int k = 0; k < 8; k++) {
                if ((s | k) == 0)
                    wgmma_n64_z<1>(d, a[0], a[1], a[2], a[3], db);
                else if (s * 8 + k < 36)
                    wgmma_n64<1>(d, a[s * 32 + k * 4], a[s * 32 + k * 4 + 1], a[s * 32 + k * 4 + 2],
                                 a[s * 32 + k * 4 + 3], db + k * 128);
            }
            wg_commit();
            if (s > 0) {
                wg_wait<1>();
                c.release(prev);
            }
            prev = r.slot;
            r.next();
        }
    }
    wg_wait<0>();
    c.release(prev);
    pin(d);
}
__device__ __forceinline__ void st128(uint4* p, uint32_t x, uint32_t y, uint32_t z, uint32_t w) {
    asm volatile(
        "{\n.reg .b64 lo, hi;\n.reg .b128 t;\nmov.b64 lo, {%1, %2};\nmov.b64 hi, {%3, %4};\nmov.b128 t, {lo, hi};\n"
        "st.relaxed.gpu.global.b128 [%0], t;\n}" ::"l"(p),
        "r"(x), "r"(y), "r"(z), "r"(w)
        : "memory");
}
__device__ __forceinline__ uint4 ld128(const uint4* p) {
    uint4 r;
    asm volatile(
        "{\n.reg .b64 lo, hi;\n.reg .b128 t;\nld.relaxed.gpu.global.b128 t, [%4];\nmov.b128 {lo, hi}, t;\n"
        "mov.b64 {%0, %1}, lo;\nmov.b64 {%2, %3}, hi;\n}"
        : "=r"(r.x), "=r"(r.y), "=r"(r.z), "=r"(r.w)
        : "l"(p));
    return r;
}
__device__ __forceinline__ uint4 ldg128(const uint4* p) {
    uint4 r;
    asm volatile("ld.global.nc.v4.u32 {%0,%1,%2,%3}, [%4];" : "=r"(r.x), "=r"(r.y), "=r"(r.z), "=r"(r.w) : "l"(p));
    return r;
}
__device__ __forceinline__ void st64(void* p, uint32_t x, uint32_t y) {
    asm volatile("{\n.reg .b64 t;\nmov.b64 t, {%1, %2};\nst.relaxed.gpu.global.b64 [%0], t;\n}" ::"l"(p), "r"(x), "r"(y)
                 : "memory");
}
__device__ __forceinline__ uint2 ld64(const void* p) {
    uint2 r;
    asm volatile("{\n.reg .b64 t;\nld.relaxed.gpu.global.b64 t, [%2];\nmov.b64 {%0, %1}, t;\n}"
                 : "=r"(r.x), "=r"(r.y)
                 : "l"(p));
    return r;
}
__device__ __forceinline__ void rows_load(uint32_t sbase, const CUtensorMap* m, int row0) {
    mbar_expect_tx(sbase + OFF_XBAR, 16 * DM * 2);
    asm volatile(
        "cp.async.bulk.tensor.3d.shared::cluster.global.mbarrier::complete_tx::bytes [%0], [%1, {%3, %3, %4}], [%2];" ::"r"(
            sbase + OFF_ROWS),
        "l"(m), "r"(sbase + OFF_XBAR), "r"(0), "r"(row0)
        : "memory");
}
__device__ __forceinline__ void rows_store(uint32_t sbase, const CUtensorMap* m, int row0) {
    asm volatile("cp.async.bulk.tensor.3d.global.shared::cta.bulk_group [%0, {%2, %2, %3}], [%1];" ::"l"(m),
                 "r"(sbase + OFF_ROWS), "r"(0), "r"(row0)
                 : "memory");
    asm volatile("cp.async.bulk.commit_group;" ::: "memory");
}
__device__ __forceinline__ void rows_store_wait() { asm volatile("cp.async.bulk.wait_group 0;" ::: "memory"); }

__device__ __forceinline__ constexpr int own_col(int j) { return j < 8 ? (j >> 1) * 128 + (j & 1) * 8 : 512; }
__device__ __forceinline__ void row_reduce(float& s0, float& s1, uint32_t red, int warp, int lane) {
    s0 += __shfl_xor_sync(0xffffffffu, s0, 1);
    s1 += __shfl_xor_sync(0xffffffffu, s1, 1);
    s0 += __shfl_xor_sync(0xffffffffu, s0, 2);
    s1 += __shfl_xor_sync(0xffffffffu, s1, 2);
    if ((lane & 3) == 0) {
        sts32f(red + (warp * 16 + (lane >> 2)) * 4, s0);
        sts32f(red + (warp * 16 + 8 + (lane >> 2)) * 4, s1);
    }
    bar_sync(3, 256);
    s0 = 0.f;
    s1 = 0.f;
#pragma unroll
    for (int w = 0; w < 8; w++) {
        s0 += lds32f(red + (w * 16 + (lane >> 2)) * 4);
        s1 += lds32f(red + (w * 16 + 8 + (lane >> 2)) * 4);
    }
}
__device__ __forceinline__ void layernorm_rows(float (&v)[36], uint32_t red, int warp, int lane) {
    float s0 = 0.f, s1 = 0.f;
#pragma unroll
    for (int j = 0; j < 9; j++) {
        s0 += v[4 * j] + v[4 * j + 1];
        s1 += v[4 * j + 2] + v[4 * j + 3];
    }
    row_reduce(s0, s1, red, warp, lane);
    const float m0 = s0 * (1.f / DM), m1 = s1 * (1.f / DM);
    s0 = 0.f;
    s1 = 0.f;
#pragma unroll
    for (int j = 0; j < 9; j++) {
        v[4 * j] -= m0;
        v[4 * j + 1] -= m0;
        v[4 * j + 2] -= m1;
        v[4 * j + 3] -= m1;
        s0 += v[4 * j] * v[4 * j] + v[4 * j + 1] * v[4 * j + 1];
        s1 += v[4 * j + 2] * v[4 * j + 2] + v[4 * j + 3] * v[4 * j + 3];
    }
    row_reduce(s0, s1, red + 512, warp, lane);
    const float r0 = rsqrtf(s0 * (1.f / DM) + 1e-5f), r1 = rsqrtf(s1 * (1.f / DM) + 1e-5f);
#pragma unroll
    for (int j = 0; j < 9; j++) {
        v[4 * j] *= r0;
        v[4 * j + 1] *= r0;
        v[4 * j + 2] *= r1;
        v[4 * j + 3] *= r1;
    }
}
__device__ __forceinline__ void mod_to_smem(uint32_t dst, const uint32_t* src, uint32_t tag) {
    const uint32_t t0 = clk32();
    uint4 u;
    while (true) {
        u = ld128(reinterpret_cast<const uint4*>(src));
        const uint32_t bad = ((u.x ^ tag) | (u.y ^ tag) | (u.z ^ tag) | (u.w ^ tag)) & 0xffffu;
        if (__all_sync(0xffffffffu, bad == 0) || clk32() - t0 > WAIT_LIMIT) break;
        __nanosleep(64);
    }
    sts128(dst, u.x & 0xffff0000u, u.y & 0xffff0000u, u.z & 0xffff0000u, u.w & 0xffff0000u);
}
__device__ __forceinline__ void lds_mod(float (&m)[18], uint32_t src  , int warp) {
#pragma unroll
    for (int j = 0; j < 9; j++)
        asm volatile("ld.shared.v2.f32 {%0,%1}, [%2];"
                     : "=f"(m[2 * j]), "=f"(m[2 * j + 1])
                     : "r"(src + own_col(j) * 4 - (j == 8 ? warp * 32 : 0))
                     : "memory");
}
__device__ __forceinline__ void modulate_store(const float (&v)[36], const float (&shift)[18], const float (&scale)[18],
                                               uint4* hbuf  , int warp, int lane) {
    uint32_t o[18];
#pragma unroll
    for (int j = 0; j < 9; j++) {
        const uint32_t cc = pack_bf16(1.f + scale[2 * j], 1.f + scale[2 * j + 1]);
        const float c0 = bf_lo(cc), c1 = bf_hi(cc);
        o[2 * j] = max(pack_bf16(fmaf(v[4 * j], c0, shift[2 * j]), fmaf(v[4 * j + 1], c1, shift[2 * j + 1])), 1u);
        o[2 * j + 1] = max(pack_bf16(fmaf(v[4 * j + 2], c0, shift[2 * j]), fmaf(v[4 * j + 3], c1, shift[2 * j + 1])), 1u);
    }
#pragma unroll
    for (int i = 0; i < 4; i++) st128(hbuf + (i * 8 + warp) * 32 + lane, o[4 * i], o[4 * i + 1], o[4 * i + 2], o[4 * i + 3]);
    st64(reinterpret_cast<uint2*>(hbuf + 32 * 32) + warp * 32 + lane, o[16], o[17]);
}
__device__ __forceinline__ void sum_partials(float (&v)[36], const uint4* src  , uint32_t tag) {
    const uint32_t t0 = clk32();
    while (true) {
        uint4 t[8][4];
#pragma unroll
        for (int s = 0; s < 8; s++)
#pragma unroll
            for (int i = 0; i < 4; i++) t[s][i] = ld128(src + (s * 36 + i * 8) * 32);
        uint32_t bad = 0;
#pragma unroll
        for (int i = 0; i < 32; i++) v[i] = 0.f;
#pragma unroll
        for (int s = 0; s < 8; s++)
#pragma unroll
            for (int i = 0; i < 4; i++) {
                bad |= t[s][i].x ^ tag;
                v[8 * i] += bf_lo(t[s][i].x);
                v[8 * i + 1] += bf_hi(t[s][i].x);
                v[8 * i + 2] += bf_lo(t[s][i].y);
                v[8 * i + 3] += bf_hi(t[s][i].y);
                v[8 * i + 4] += bf_lo(t[s][i].z);
                v[8 * i + 5] += bf_hi(t[s][i].z);
                v[8 * i + 6] += bf_lo(t[s][i].w);
                v[8 * i + 7] += bf_hi(t[s][i].w);
            }
        if (__all_sync(0xffffffffu, (bad & 1u) == 0) || clk32() - t0 > WAIT_LIMIT) break;
    }
}
__device__ __forceinline__ void sum_tail(float (&v)[36], const uint2* src  , uint32_t tag) {
    const uint32_t t0 = clk32();
    while (true) {
        uint2 t[8];
#pragma unroll
        for (int s = 0; s < 8; s++) t[s] = ld64(src + s * 72 * 32);
        uint32_t bad = 0;
        v[32] = v[33] = v[34] = v[35] = 0.f;
#pragma unroll
        for (int s = 0; s < 8; s++) {
            bad |= t[s].x ^ tag;
            v[32] += bf_lo(t[s].x);
            v[33] += bf_hi(t[s].x);
            v[34] += bf_lo(t[s].y);
            v[35] += bf_hi(t[s].y);
        }
        if (__all_sync(0xffffffffu, (bad & 1u) == 0) || clk32() - t0 > WAIT_LIMIT) break;
    }
}
__device__ __forceinline__ void poll_tail(uint32_t (&a)[144], const uint2* src  ) {
    const uint32_t t0 = clk32();
    while (true) {
        uint32_t m = 0xffffffffu;
#pragma unroll
        for (int j = 0; j < 8; j++) {
            const uint2 t = ld64(src + j * 32);
            a[128 + 2 * j] = t.x;
            a[129 + 2 * j] = t.y;
        }
#pragma unroll
        for (int j = 0; j < 16; j++) m = min(m, a[128 + j]);
        if (__all_sync(0xffffffffu, m != 0) || clk32() - t0 > WAIT_LIMIT) break;
    }
}
template <int K0, int K1>
__device__ __forceinline__ void poll_frags(uint32_t (&a)[144], const uint4* src  , bool kick) {
    const uint32_t t0 = clk32();
    while (true) {
#pragma unroll
        for (int k = K0; k < K1; k++)
            asm volatile("ld.relaxed.gpu.global.v4.u32 {%0,%1,%2,%3}, [%4];"
                         : "=r"(a[4 * k]), "=r"(a[4 * k + 1]), "=r"(a[4 * k + 2]), "=r"(a[4 * k + 3])
                         : "l"(src + k * 32));
        if (kick) bar_arrive(5, 256);
        kick = false;
        uint32_t m0 = a[4 * K0], m1 = a[4 * K0 + 1];
#pragma unroll
        for (int i = 4 * K0 + 2; i < 4 * K1; i += 2) {
            m0 = min(m0, a[i]);
            m1 = min(m1, a[i + 1]);
        }
        if (__all_sync(0xffffffffu, min(m0, m1) != 0) || clk32() - t0 > WAIT_LIMIT) break;
    }
}

constexpr float SM_SCALE = 0.08838834764831845f * 1.4426950408889634f;
constexpr float SM_HI = 1.2089258e24f;
constexpr float SM_LO = 9.0949470e-13f;
__device__ __forceinline__ void qk_step(float (&s)[32], const uint32_t (&q)[32], uint64_t dk) {
#pragma unroll
    for (int k = 0; k < 8; k++) {
        if (k == 0)
            wgmma_n64_z<0>(s, q[0], q[1], q[2], q[3], dk);
        else
            wgmma_n64<0>(s, q[4 * k], q[4 * k + 1], q[4 * k + 2], q[4 * k + 3], dk + (k >> 2) * 512 + (k & 3) * 2);
    }
}
__device__ __forceinline__ void pv_step(float (&o)[64], const uint32_t (&p)[16], uint64_t dv, int acc) {
#pragma unroll
    for (int k = 0; k < 4; k++)
        wgmma_n128<1>(o, p[4 * k], p[4 * k + 1], p[4 * k + 2], p[4 * k + 3], dv + k * 128, k != 0 ? 1 : acc);
}
template <bool SHIFT>
__device__ __forceinline__ void exp_step(const float (&s)[32], uint32_t (&p)[16], float n0, float n1, float& s0,
                                         float& s1) {
#pragma unroll
    for (int i = 0; i < 8; i++) {
        const float e0 = ex2(SHIFT ? s[4 * i] + n0 : s[4 * i]), e1 = ex2(SHIFT ? s[4 * i + 1] + n0 : s[4 * i + 1]);
        const float e2 = ex2(SHIFT ? s[4 * i + 2] + n1 : s[4 * i + 2]), e3 = ex2(SHIFT ? s[4 * i + 3] + n1 : s[4 * i + 3]);
        if (i == 0) {
            s0 = e0 + e1;
            s1 = e2 + e3;
        } else {
            s0 += e0 + e1;
            s1 += e2 + e3;
        }
        p[2 * i] = pack_bf16(e0, e1);
        p[2 * i + 1] = pack_bf16(e2, e3);
    }
}
__device__ __forceinline__ void row_max(const float (&sa)[32], const float (&sb)[32], float& x0, float& x1) {
    float xa[8];
#pragma unroll
    for (int i = 0; i < 8; i++) xa[i] = fmaxf(sa[i], sb[i]);
#pragma unroll
    for (int k = 1; k < 4; k++)
#pragma unroll
        for (int i = 0; i < 8; i++) xa[i] = fmaxf(xa[i], fmaxf(sa[8 * k + i], sb[8 * k + i]));
    x0 = fmaxf(fmaxf(xa[0], xa[1]), fmaxf(xa[4], xa[5]));
    x1 = fmaxf(fmaxf(xa[2], xa[3]), fmaxf(xa[6], xa[7]));
    x0 = fmaxf(x0, __shfl_xor_sync(0xffffffffu, x0, 1));
    x1 = fmaxf(x1, __shfl_xor_sync(0xffffffffu, x1, 1));
    x0 = fmaxf(x0, __shfl_xor_sync(0xffffffffu, x0, 2));
    x1 = fmaxf(x1, __shfl_xor_sync(0xffffffffu, x1, 2));
}
__device__ __forceinline__ void inv_row_sums(float l0, float l1, float& i0, float& i1) {
    l0 += __shfl_xor_sync(0xffffffffu, l0, 1);
    l1 += __shfl_xor_sync(0xffffffffu, l1, 1);
    l0 += __shfl_xor_sync(0xffffffffu, l0, 2);
    l1 += __shfl_xor_sync(0xffffffffu, l1, 2);
    i0 = rcp(l0);
    i1 = rcp(l1);
}

__device__ __forceinline__ uint32_t get_epoch(uint32_t sbase) { return __float_as_uint(lds32f(sbase + OFF_EPOCH)); }
__device__ __forceinline__ float silu_bf16(unsigned short c) {
    const float cv = bf_lo(c);
    return round_bf16(cv * rcp(1.f + ex2(-1.4426950408889634f * cv)));
}
__device__ __forceinline__ void st_mod(uint32_t* p, float v, uint32_t tag) {
    asm volatile("st.relaxed.gpu.global.u32 [%0], %1;" ::"l"(p), "r"(__float_as_uint(round_bf16(v)) | tag)
                 : "memory");
}
__device__ __forceinline__ void mod_block(const uint4 (&w)[5], const float (&sc)[5], uint32_t* dst, uint32_t red,
                                          int warp, int lane, uint32_t tag) {
    float acc[8];
#pragma unroll
    for (int e = 0; e < 8; e++) acc[e] = 0.f;
#pragma unroll
    for (int i = 0; i < 5; i++) {
        acc[0] = fmaf(sc[i], bf_lo(w[i].x), acc[0]);
        acc[1] = fmaf(sc[i], bf_hi(w[i].x), acc[1]);
        acc[2] = fmaf(sc[i], bf_lo(w[i].y), acc[2]);
        acc[3] = fmaf(sc[i], bf_hi(w[i].y), acc[3]);
        acc[4] = fmaf(sc[i], bf_lo(w[i].z), acc[4]);
        acc[5] = fmaf(sc[i], bf_hi(w[i].z), acc[5]);
        acc[6] = fmaf(sc[i], bf_lo(w[i].w), acc[6]);
        acc[7] = fmaf(sc[i], bf_hi(w[i].w), acc[7]);
    }
#pragma unroll
    for (int o = 2; o < 32; o <<= 1)
#pragma unroll
        for (int e = 0; e < 8; e++) acc[e] += __shfl_xor_sync(0xffffffffu, acc[e], o);
    if (lane < 2) {
#pragma unroll
        for (int e = 0; e < 8; e++) sts32f(red + (warp * 16 + lane * 8 + e) * 4, acc[e]);
    }
    bar_sync(3, 256);
    if (warp == 0 && lane < 16) {
        float s = 0.f;
#pragma unroll
        for (int w8 = 0; w8 < 8; w8++) s += lds32f(red + (w8 * 16 + lane) * 4);
        st_mod(dst + lane, s, tag);
    }
}

__global__ void __cluster_dims__(2, 1, 1) __launch_bounds__(384, 1)
    fused_block_kernel(const __grid_constant__ Params maps) {
    extern __shared__ uint8_t smem_raw[];
    uint32_t sbase = (smem_u32(smem_raw) + 1023u) & ~1023u;
    asm volatile("" : "+r"(sbase));
    const int b = blockIdx.x;
    const int rank = b & 1;
    const int mt = ((b >> 1) & 7) * 2 + rank;
    const int g = b >> 4;
    const int warp = __shfl_sync(0xffffffffu, threadIdx.x >> 5, 0);
    const int lane = threadIdx.x & 31;
    Scratch* const sc_ = maps.sc;
    const __nv_bfloat16* const wmod = maps.wmod;
    const __nv_bfloat16* const cvec = maps.cvec;

#define SPROF(i)

    if (warp >= 8) {
        if (threadIdx.x >= 288 && threadIdx.x < 288 + 81) {
            const int li = b * 81 + threadIdx.x - 288;
            asm volatile("prefetch.global.L2 [%0];" ::"l"((const char*)wmod + (size_t)(li / 18) * (12 * DM) + (li % 18) * 128));
        }
        asm volatile("setmaxnreg.dec.sync.aligned.u32 24;");
        if (warp == 8 && lane == 0) {
#pragma unroll
            for (int i = 0; i < 8; i++) {
                mbar_init(sbase + OFF_FULL + i * 8, 1);
                mbar_init(sbase + OFF_EMPTY + i * 8, 4);
            }
            mbar_init(sbase + OFF_XBAR, 1);
            asm volatile("fence.mbarrier_init.release.cluster;" ::: "memory");
            asm volatile("barrier.cluster.arrive.relaxed;\nbarrier.cluster.wait;" ::: "memory");
            uint32_t slot = 0, phase = 1;
            const uint32_t dst0 = sbase + rank * BOX_BYTES;
            auto acquire = [&](uint32_t bytes) {
                mbar_wait(sbase + OFF_EMPTY + slot * 8, phase);
                mbar_expect_tx(sbase + OFF_FULL + slot * 8, bytes);
            };
            auto adv8 = [&]() {
                if (++slot == 8) {
                    slot = 0;
                    phase ^= 1;
                }
            };
#pragma unroll 1
            for (int hq = 0; hq < 4; hq++) {
                const int col = (g * 4 + ((hq + 1) & 3)) * 128 + rank * 64;
                if (hq == 2) {
                    l2_prefetch(maps.kc + (size_t)(g * 4 * 2048 + (b & 15) * 64) * 128, SLOT_BYTES);
                    l2_prefetch(maps.vc + (size_t)(g * 4 * 2048 + (b & 15) * 64) * 128, SLOT_BYTES);
                }
#pragma unroll 1
                for (int kc = 0; kc < 9; kc++) {
                    acquire(SLOT_BYTES);
                    tma_mc(dst0 + slot * SLOT_BYTES, &maps.wq, col, kc * 64, sbase + OFF_FULL + slot * 8);
                    adv8();
                }
            }
            const int row0 = g * 4 * 2048;
#pragma unroll 1
            for (int n = 0; n < 128; n++) {
                if (n < 4) mbar_wait(sbase + OFF_EMPTY + (slot + 1) * 8, phase);
                acquire(2 * SLOT_BYTES);
                const uint32_t bar = sbase + OFF_FULL + slot * 8;
                const int r0 = n == 0 ? 0 : (n == 127 ? 126 : n + 1);
                const int r1 = n == 0 ? 1 : (n == 127 ? 127 : n - 1);
                tma_mc(dst0 + slot * SLOT_BYTES, n == 127 ? &maps.v : &maps.k, rank * 64, row0 + r0 * 64, bar);
                tma_mc(dst0 + (slot + 1) * SLOT_BYTES, n == 0 ? &maps.k : &maps.v, rank * 64, row0 + r1 * 64, bar);
                adv8();
                adv8();
                if (n >= 96 && n < 96 + 10) {
                    const int i = n - 96;
                    if (i < 9) {
                        l2_prefetch((const char*)maps.wg_p + (size_t)b * 41472 + i * 4608, 4608);
                        l2_prefetch((const char*)maps.wu_p + (size_t)b * 41472 + i * 4608, 4608);
                        l2_prefetch((const char*)maps.wd_p + (size_t)b * 41472 + i * 4608, 4608);
                        l2_prefetch((const char*)maps.wo_p + (size_t)b * 36864 + i * 4096, 4096);
                    }
                }
                const int u = n + KV_AHEAD;
                if (u < 128 && (u & 15) == (b & 15)) {
                    l2_prefetch(maps.kc + (size_t)(row0 + u * 64) * 128, SLOT_BYTES);
                    l2_prefetch(maps.vc + (size_t)(row0 + u * 64) * 128, SLOT_BYTES);
                }
            }
#pragma unroll 1
            for (int p = 0; p < 4; p++)
#pragma unroll 1
                for (int kc = 0; kc < 8; kc++) {
                    acquire(SLOT_BYTES);
                    tma_mc(dst0 + slot * SLOT_BYTES, &maps.wo, p * 128 + rank * 64, g * 512 + kc * 64,
                           sbase + OFF_FULL + slot * 8);
                    adv8();
                }
#pragma unroll 1
            for (int kc = 0; kc < 4; kc++) {
                acquire(SLOT_BYTES);
                tma_mc(dst0 + slot * SLOT_BYTES, &maps.wo, 512, g * 512 + kc * 128 + rank * 64,
                       sbase + OFF_FULL + slot * 8);
                adv8();
            }
            const CUtensorMap* mg = rank ? &maps.wu : &maps.wg;
#pragma unroll 1
            for (int ch = 0; ch < 9; ch++)
#pragma unroll 1
                for (int kc = 0; kc < 9; kc++) {
                    acquire(SLOT_BYTES);
                    tma_mc(dst0 + slot * SLOT_BYTES, mg, g * 576 + ch * 64, kc * 64, sbase + OFF_FULL + slot * 8);
                    adv8();
                }
#pragma unroll 1
            for (int p = 0; p < 4; p++)
#pragma unroll 1
                for (int kc = 2; kc < 11; kc++) {
                    acquire(SLOT_BYTES);
                    tma_mc(dst0 + slot * SLOT_BYTES, &maps.wd, p * 128 + rank * 64, g * 576 + (kc < 9 ? kc : kc - 9) * 64,
                           sbase + OFF_FULL + slot * 8);
                    adv8();
                }
#pragma unroll 1
            for (int i = 0; i < 5; i++) {
                acquire(i < 4 ? SLOT_BYTES : BOX_BYTES);
                const int kc = 2 * i + rank + 2;
                if (i < 4 || rank == 0)
                    tma_mc(dst0 + slot * SLOT_BYTES, &maps.wd, 512, g * 576 + (kc < 9 ? kc : kc - 9) * 64,
                           sbase + OFF_FULL + slot * 8);
                adv8();
            }
        } else if (warp == 11) {
            asm volatile("barrier.cluster.arrive.relaxed.aligned;" ::: "memory");
            bar_sync(6, 160);
            uint4* hz = sc_->h[(get_epoch(sbase) & 1) ^ 1][0] + (size_t)b * 72 * 32 + lane;
#pragma unroll 1
            for (int i = 0; i < 72; i++) {
                hz[i * 32] = make_uint4(0, 0, 0, 0);
                __nanosleep(200);
            }
        } else if (warp == 9 || warp == 10) {
            asm volatile("barrier.cluster.arrive.relaxed.aligned;" ::: "memory");
            bar_sync(4, 320);
            const uint32_t tag = (get_epoch(sbase) + 1) & 0xffffu;
            if (warp == 10 && lane < 9) l2_prefetch((const char*)maps.wq_p + (size_t)b * 36864 + lane * 4096, 4096);
            const int blk = warp == 9 ? 72 + b : 200 + b;
            if (blk < 216) {
                float acc[8];
#pragma unroll
                for (int e = 0; e < 8; e++) acc[e] = 0.f;
                const uint4* wp = reinterpret_cast<const uint4*>(wmod + (size_t)(lane >> 1) * (6 * DM) + blk * 16) + (lane & 1);
                const unsigned short* cp = reinterpret_cast<const unsigned short*>(cvec) + (lane >> 1);
#pragma unroll 1
                for (int i = 0; i < 36; i++) {
                    const uint4 w = __ldg(wp + (size_t)i * (16 * 6 * DM / 8));
                    const float sc = silu_bf16(__ldg(cp + i * 16));
                    acc[0] = fmaf(sc, bf_lo(w.x), acc[0]);
                    acc[1] = fmaf(sc, bf_hi(w.x), acc[1]);
                    acc[2] = fmaf(sc, bf_lo(w.y), acc[2]);
                    acc[3] = fmaf(sc, bf_hi(w.y), acc[3]);
                    acc[4] = fmaf(sc, bf_lo(w.z), acc[4]);
                    acc[5] = fmaf(sc, bf_hi(w.z), acc[5]);
                    acc[6] = fmaf(sc, bf_lo(w.w), acc[6]);
                    acc[7] = fmaf(sc, bf_hi(w.w), acc[7]);
                }
#pragma unroll
                for (int o = 2; o < 32; o <<= 1)
#pragma unroll
                    for (int e = 0; e < 8; e++) acc[e] += __shfl_xor_sync(0xffffffffu, acc[e], o);
                if (lane < 2) {
#pragma unroll
                    for (int e = 0; e < 8; e++) st_mod(sc_->mod + blk * 16 + lane * 8 + e, acc[e], tag);
                }
            }
            if (warp == 9) {
#pragma unroll 1
                for (int st = 1; st <= 2; st++) {
                    bar_sync(7, 160);
                    const uint32_t* src = sc_->mod + (st * 3 - 1) * DM;
                    const int n = st == 1 ? 3 * DM : DM;
#pragma unroll 1
                    for (int i = lane * 4; i < n + 127 - ((n + 127) & 127); i += 128)
                        mod_to_smem(sbase + OFF_MODT + min(i, n - 4) * 4, src + min(i, n - 4), tag);
                    __syncwarp();
                    if (lane == 0) rows_load(sbase, st == 1 ? &maps.rx : &maps.rx2, (mt * 8 + g) * 16);
                    if (st == 1) {
                        bar_sync(7, 160);
                        if (lane == 0) {
                            rows_store(sbase, &maps.rx2, (mt * 8 + g) * 16);
                            rows_store_wait();
                        }
                        __syncwarp();
                        bar_arrive(10, 160);
                    }
                }
            }
        }
    } else {
        uint4 cw = make_uint4(0, 0, 0, 0), w1[5], xw[5];
        {
            const int t = threadIdx.x;
            if (t < 72) cw = ldg128(reinterpret_cast<const uint4*>(cvec) + t);
            if (t == 96) cw = ld128(reinterpret_cast<const uint4*>(&sc_->epoch[b * 32]));
            const int bw = min(b, 71);
            if (b < 72) {
#pragma unroll
                for (int i = 0; i < 5; i++)
                    w1[i] = ldg128(reinterpret_cast<const uint4*>(wmod + (size_t)min((t >> 1) + 128 * i, DM - 1) * (6 * DM)) +
                                   bw * 2 + (t & 1));
            } else {
#pragma unroll
                for (int i = 0; i < 5; i++) w1[i] = make_uint4(0, 0, 0, 0);
            }
#pragma unroll
            for (int i = 0; i < 5; i++)
                xw[i] = ldg128(reinterpret_cast<const uint4*>(maps.x + (size_t)(mt * 8 + g) * 16 * DM) + min(t + 256 * i, 1151));
        }
        if (threadIdx.x == 160) SPROF(5);
        asm volatile("setmaxnreg.inc.sync.aligned.u32 240;");
        if (threadIdx.x == 160) SPROF(6);
        const int wg = warp >> 2;
        const int tid = threadIdx.x;
        Ctx cx;
        cx.sbase = sbase;
        cx.wg = wg;
        if (wg == 1) bar_arrive(8, 256);
        cx.rel_cta = (lane == 0 && (warp & 3) < 2) ? (warp & 3) : 2;
        const uint32_t red = sbase + OFF_RED;
        const int own = mt * 8 + g;
        const int wown = mt * 8 + warp;
        PROF(0);
        PROFG(30);
        PROFR(17);
        {
            const int r0 = tid >> 1;
            PROFR(18);
            asm volatile("barrier.cluster.arrive.relaxed.aligned;" ::: "memory");
            if (tid < 72) sts128(sbase + OFF_CVEC + tid * 16, cw.x, cw.y, cw.z, cw.w);
            if (tid == 96) sts128(sbase + OFF_EPOCH, cw.x, cw.y, cw.z, cw.w);
            bar_sync(3, 256);
            PROFR(19);
            if (b < 72) {
                float sc[5];
#pragma unroll
                for (int i = 0; i < 5; i++) {
                    unsigned short cu;
                    asm volatile("ld.shared.u16 %0, [%1];" : "=h"(cu) : "r"(sbase + OFF_CVEC + min(r0 + 128 * i, DM - 1) * 2));
                    sc[i] = (r0 + 128 * i < DM) ? silu_bf16(cu) : 0.f;
                }
                mod_block(w1, sc, sc_->mod + b * 16, red + 1024, warp, lane, (get_epoch(sbase) + 1) & 0xffffu);
            }
            PROFR(21);
#pragma unroll
            for (int i = 0; i < 5; i++) {
                const int vi = min(tid + 256 * i, 1151), ln = vi >> 3;
                sts128(sbase + OFF_ROWS + ln * 128 + (((vi & 7) ^ (ln & 7)) << 4), xw[i].x, xw[i].y, xw[i].z, xw[i].w);
            }
            bar_sync(3, 256);
        }

        Ring ring{0u, 0u};
        int stage = 0;
        asm volatile("" : "+r"(stage));
#pragma unroll 1
        for (;; stage++) {
            int tid, lane;
            asm volatile("mov.u32 %0, %%tid.x;" : "=r"(tid));
            lane = tid & 31;
            const uint32_t epoch = get_epoch(sbase);
            {
                float v[36];
                const uint32_t modt = sbase + OFF_MODT + (warp * 16 + (lane & 3) * 2) * 4;
                if (stage == 0) {
#pragma unroll
                    for (int i = 0; i < 36; i++) v[i] = 0.f;
                } else {
                    const uint4* psrc = sc_->part + (size_t)own * 8 * 36 * 32;
                    sum_partials(v, psrc + tid, stage & 1);
                    PROF(stage == 1 ? 8 : 15);
                    sum_tail(v, reinterpret_cast<const uint2*>(psrc + 32 * 32) + tid, stage & 1);
                }
                if (stage) mbar_wait(sbase + OFF_XBAR, stage - 1);
                if (stage == 0) PROFR(22);
                {
                    const float gs = stage == 2 ? 0.5f : 1.f;
                    float gate[18];
                    lds_mod(gate, modt, warp);
                    const int r = lane >> 2;
                    const uint32_t rows = sbase + OFF_ROWS + r * (DM * 2) + (lane & 3) * 4;
#pragma unroll
                    for (int j = 0; j < 9; j++) {
                        const int ch = j < 8 ? (j >> 1) * 2 + (warp >> 2) : 8, c16 = j < 8 ? (warp & 3) * 2 + (j & 1) : warp;
                        const uint32_t ad = rows + ch * 128 + ((c16 ^ ((r + ch) & 7)) << 4);
                        const uint32_t u0 = __float_as_uint(lds32f(ad)), u1 = __float_as_uint(lds32f(ad + 8 * DM * 2));
                        const float g0 = stage ? gate[2 * j] * gs : 0.f, g1 = stage ? gate[2 * j + 1] * gs : 0.f;
                        v[4 * j] = fmaf(g0, v[4 * j], bf_lo(u0));
                        v[4 * j + 1] = fmaf(g1, v[4 * j + 1], bf_hi(u0));
                        v[4 * j + 2] = fmaf(g0, v[4 * j + 2], bf_lo(u1));
                        v[4 * j + 3] = fmaf(g1, v[4 * j + 3], bf_hi(u1));
                        sts32f(ad, __uint_as_float(pack_bf16(v[4 * j], v[4 * j + 1])));
                        sts32f(ad + 8 * DM * 2, __uint_as_float(pack_bf16(v[4 * j + 2], v[4 * j + 3])));
                    }
                    asm volatile("fence.proxy.async.shared::cta;" ::: "memory");
                }
                if (stage == 2) break;
                PROF(stage == 0 ? 1 : 9);
                layernorm_rows(v, red, warp, lane);
                if (stage == 0) PROFR(27);
                if (stage == 0) {
                    const uint32_t tag = (epoch + 1) & 0xffffu;
                    mod_to_smem(sbase + OFF_MODT + (DM + tid * 4) * 4, sc_->mod + tid * 4, tag);
                    if (warp == 7) mod_to_smem(sbase + OFF_MODT + (DM + 1024 + lane * 4) * 4, sc_->mod + 1024 + lane * 4, tag);
                    bar_sync(3, 256);
                    bar_arrive(4, 320);
                }
                float shift[18], scale[18];
                lds_mod(shift, modt + DM * 4, warp);
                lds_mod(scale, modt + 2 * DM * 4, warp);
                if (stage == 0) PROFR(28);
                PROF(stage == 0 ? 2 : 10);
                modulate_store(v, shift, scale, sc_->h[epoch & 1][stage] + (size_t)own * 36 * 32, warp, lane);
                if (stage == 0) asm volatile("barrier.cluster.wait.aligned;" ::: "memory");
            }

            const uint32_t spill = sbase + 8 * SLOT_BYTES + wg * 3 * SLOT_BYTES + (tid & 127) * 16;
            uint32_t a[144];
            PROF(stage == 0 ? 3 : 11);
            {
                const uint4* hsrc = sc_->h[epoch & 1][stage] + (size_t)wown * 36 * 32 + lane;
                poll_tail(a, reinterpret_cast<const uint2*>(hsrc - lane + 32 * 32) + lane);
                PROF(stage == 0 ? 4 : 12);
                if (stage == 1) PROFG(25);
                TG(stage * 32 + 30);
                if (wg == 1) bar_sync(5, 256);
                poll_frags<0, 32>(a, hsrc, wg == 0);
            }
            uint4* hhbuf = sc_->hh + (size_t)b * 8 * 256 + tid;
            float d[64];
#pragma unroll 1
            for (int ch = 0;; ch++) {
                TG(stage * 32 + ch * 2);
                gemm_n128(d, a, cx, ring, true);
                TG(stage * 32 + ch * 2 + 1);
                if (stage == 0) {
#pragma unroll
                    for (int i = 0; i < 64; i++) d[i] *= SM_SCALE;
                    if (ch == 3) break;
#pragma unroll
                    for (int v = 0; v < 8; v++)
                        sts128(spill + (ch * 8 + v) * 2048, pack_bf16(d[8 * v], d[8 * v + 1]),
                               pack_bf16(d[8 * v + 2], d[8 * v + 3]), pack_bf16(d[8 * v + 4], d[8 * v + 5]),
                               pack_bf16(d[8 * v + 6], d[8 * v + 7]));
                } else {
#pragma unroll
                    for (int i = 0; i < 32; i++) {
                        const float gv = d[i], gu = gv * d[32 + i];
                        const float z = gv * fmaf(gv * gv, 0.7978845608028654f * 0.044715f, 0.7978845608028654f);
                        d[i] = fmaf(gu, tanh_fast(z), gu);
                    }
                    if (ch == 8) break;
                    if (wg == 0) {
                        if (ch == 0) bar_arrive(7, 160);
                        if (ch == 2) bar_sync(10, 160);
                    }
#pragma unroll
                    for (int v = 0; v < 4; v++) {
                        const uint4 h4 = make_uint4(pack_bf16(d[8 * v], d[8 * v + 1]), pack_bf16(d[8 * v + 2], d[8 * v + 3]),
                                                    pack_bf16(d[8 * v + 4], d[8 * v + 5]), pack_bf16(d[8 * v + 6], d[8 * v + 7]));
                        if (ch < 2)
                            __stcg(hhbuf + (ch * 4 + v) * 256, h4);
                        else
                            sts128(spill + ((ch - 2) * 4 + v) * 2048, h4.x, h4.y, h4.z, h4.w);
                    }
                }
            }
            if (stage == 0) {
                uint32_t q[32];
#pragma unroll
                for (int i = 0; i < 32; i++) q[i] = pack_bf16(d[2 * i], d[2 * i + 1]);
                PROF(5);
                PROFG(23);
                if (wg == 0) bar_arrive(6, 160);
                {
                    float o[64], sa[32], sb[32];
                    uint32_t pa[16], pb[16];
#pragma unroll
                    for (int i = 0; i < 64; i++) o[i] = 0.f;
                    float n0 = 0.f, n1 = 0.f, l0 = 1.f, l1 = 1.f;
                    bool shifted = false;
                    const uint64_t dbase = desc_of(sbase);
                    const uint64_t dbk = dbase - (511u << 16);
                    const int my_bar = 1 + wg, other_bar = 2 - wg;

                    auto softmax_a = [&](bool first, float& s0, float& s1) {
                        if (first) {
                            shifted = false;
                            n0 = n1 = 0.f;
                            l0 = l1 = 0.f;
                        }
                        if (shifted)
                            exp_step<true>(sa, pa, n0, n1, s0, s1);
                        else
                            exp_step<false>(sa, pa, n0, n1, s0, s1);
                    };
                    auto softmax_b = [&](bool first, float s0, float s1) {
                        float u0, u1;
                        if (shifted)
                            exp_step<true>(sb, pb, n0, n1, u0, u1);
                        else
                            exp_step<false>(sb, pb, n0, n1, u0, u1);
                        s0 += u0;
                        s1 += u1;
                        bool bad = !(fmaxf(s0, s1) <= SM_HI);
                        if (first) {
                            float r0 = s0 + __shfl_xor_sync(0xffffffffu, s0, 1), r1 = s1 + __shfl_xor_sync(0xffffffffu, s1, 1);
                            r0 += __shfl_xor_sync(0xffffffffu, r0, 2);
                            r1 += __shfl_xor_sync(0xffffffffu, r1, 2);
                            bad = bad || !(fminf(r0, r1) >= SM_LO);
                        }
                        if (__any_sync(0xffffffffu, bad)) {
                            float x0, x1;
                            row_max(sa, sb, x0, x1);
                            x0 = -x0;
                            x1 = -x1;
                            if (!first) {
                                x0 = fminf(x0, n0);
                                x1 = fminf(x1, n1);
                                const float al0 = ex2(x0 - n0), al1 = ex2(x1 - n1);
                                l0 *= al0;
                                l1 *= al1;
#pragma unroll
                                for (int i = 0; i < 16; i++) {
                                    o[4 * i] *= al0;
                                    o[4 * i + 1] *= al0;
                                    o[4 * i + 2] *= al1;
                                    o[4 * i + 3] *= al1;
                                }
                            }
                            n0 = x0;
                            n1 = x1;
                            shifted = true;
                            exp_step<true>(sa, pa, n0, n1, s0, s1);
                            exp_step<true>(sb, pb, n0, n1, u0, u1);
                            s0 += u0;
                            s1 += u1;
                        }
                        l0 += s0;
                        l1 += s1;
                    };

                    cx.wait_full(4, 0);
                    if (wg == 1) bar_sync(my_bar, 256);
                    wg_fence();
                    qk_step(sa, q, dbk + 4 * 1024);
                    qk_step(sb, q, dbk + 5 * 1024);
                    wg_commit();
                    bar_arrive(other_bar, 256);
                    wg_wait<0>();
                    pin(sa);
                    pin(sb);
                    cx.release(4);
                    cx.wait_full(6, 0);
                    {
                        float s0, s1;
                        softmax_a(true, s0, s1);
                        softmax_b(true, s0, s1);
                    }
                    uint32_t alo = (uint32_t)dbase + 6 * 1024, blo = (uint32_t)dbase;
                    const uint32_t dhi = (uint32_t)(dbase >> 32);
#pragma unroll 1
                    for (int t = 1; t < 64; t++) {
                        const int j = t & 15;
                        const uint32_t sA = 2 + 4 * (t & 1), sB = 4 - 4 * (t & 1);
                        const uint64_t da = ((uint64_t)dhi << 32) | alo, db = ((uint64_t)dhi << 32) | blo;
                        TL(0);
                        bar_sync(my_bar, 256);
                        TL(2);
                        wg_fence();
                        pv_step(o, pa, da + 1024, j != 1);
                        qk_step(sa, q, da - (511u << 16));
                        wg_commit();
                        cx.wait_full(sB, ((36 + 4 * t) >> 3) & 1);
                        wg_fence();
                        qk_step(sb, q, db - (511u << 16));
                        pv_step(o, pb, db + 1024, 1);
                        wg_commit();
                        bar_arrive(other_bar, 256);
                        alo ^= 4096;
                        blo ^= 4096;
                        asm volatile("" : "+r"(alo), "+r"(blo));
                        TL(3);
                        wg_wait<1>();
                        pin(sa);
                        pin(pa);
                        TL(4);
                        cx.release(sA);
                        const float lp0 = l0, lp1 = l1;
                        float s0, s1;
                        softmax_a(j == 0, s0, s1);
                        TL(5);
                        wg_wait<0>();
                        pin(o);
                        pin(sb);
                        pin(pb);
                        TL(6);
                        cx.release(sB);
                        if (j == 0) {
                            float i0, i1;
                            inv_row_sums(lp0, lp1, i0, i1);
                            const uint32_t dst = spill + ((t >> 4) - 1) * 16384;
#pragma unroll
                            for (int v = 0; v < 8; v++)
                                sts128(dst + v * 2048, pack_bf16(o[8 * v] * i0, o[8 * v + 1] * i0),
                                       pack_bf16(o[8 * v + 2] * i1, o[8 * v + 3] * i1),
                                       pack_bf16(o[8 * v + 4] * i0, o[8 * v + 5] * i0),
                                       pack_bf16(o[8 * v + 6] * i1, o[8 * v + 7] * i1));
                        }
                        const uint32_t bn = sbase + OFF_FULL + (8 - sA) * 8, pn = ((38 + 4 * t) >> 3) & 1;
                        const bool okn = mbar_try(bn, pn);
                        TL(1);
                        softmax_b(j == 0, s0, s1);
                        if (!okn || j == 15) {
                            mbar_wait(bn, pn);
                            if (j == 15 && t < 63) {
                                const uint32_t src = spill + (t >> 4) * 16384;
#pragma unroll
                                for (int v = 0; v < 8; v++)
                                    lds128(src + v * 2048, q[4 * v], q[4 * v + 1], q[4 * v + 2], q[4 * v + 3]);
                            }
                        }
                        TL(7);
                    }
                    bar_sync(my_bar, 256);
                    wg_fence();
                    pv_step(o, pa, dbase + 2 * 1024, 1);
                    pv_step(o, pb, dbase + 3 * 1024, 1);
                    wg_commit();
                    if (wg == 0) bar_arrive(other_bar, 256);
                    float i0, i1;
                    inv_row_sums(l0, l1, i0, i1);
                    wg_wait<0>();
                    pin(o);
                    cx.release(2);
#pragma unroll
                    for (int i = 0; i < 16; i++) {
                        a[96 + 2 * i] = pack_bf16(o[4 * i] * i0, o[4 * i + 1] * i0);
                        a[96 + 2 * i + 1] = pack_bf16(o[4 * i + 2] * i1, o[4 * i + 3] * i1);
                    }
#pragma unroll
                    for (int i = 128; i < 144; i++) a[i] = 0;
                }
                ring.slot = 4;
                ring.phase = 0;
                PROF(6);
                PROFG(24);
            } else {
#pragma unroll
                for (int v = 0; v < 8; v++) {
                    const uint4 t = __ldcg(hhbuf + v * 256);
                    a[112 + 4 * v] = t.x;
                    a[113 + 4 * v] = t.y;
                    a[114 + 4 * v] = t.z;
                    a[115 + 4 * v] = t.w;
                }
#pragma unroll
                for (int i = 0; i < 16; i++) a[96 + i] = pack_bf16(d[2 * i], d[2 * i + 1]);
                PROF(13);
            }
#pragma unroll
            for (int v = 0; v < 24; v++) lds128(spill + v * 2048, a[4 * v], a[4 * v + 1], a[4 * v + 2], a[4 * v + 3]);

            {
                uint4* dst = sc_->part + ((size_t)wown * 8 + g) * 36 * 32 + lane;
                const uint32_t ptag = (stage + 1) & 1;
#pragma unroll 1
                for (int p = 0; p < 4; p++) {
                    TG(stage * 32 + 18 + p * 2);
                    gemm_n128(d, a, cx, ring, stage != 0);
                    TG(stage * 32 + 19 + p * 2);
#pragma unroll
                    for (int u = 0; u < 8; u++)
                        st128(dst + (p * 8 + u) * 32, (pack_bf16(d[8 * u], d[8 * u + 1]) & ~1u) | ptag,
                              pack_bf16(d[8 * u + 2], d[8 * u + 3]), pack_bf16(d[8 * u + 4], d[8 * u + 5]),
                              pack_bf16(d[8 * u + 6], d[8 * u + 7]));
                    if (p == 0 && wg == 0) bar_arrive(7, 160);
                }
                float e[32];
                TG(stage * 32 + 26);
                gemm_n64(e, a, cx, ring, stage != 0);
                TG(stage * 32 + 27);
                uint2* dst2 = reinterpret_cast<uint2*>(dst - lane + 32 * 32) + lane;
#pragma unroll
                for (int j = 0; j < 8; j++)
                    st64(dst2 + j * 32, (pack_bf16(e[4 * j], e[4 * j + 1]) & ~1u) | ptag, pack_bf16(e[4 * j + 2], e[4 * j + 3]));
            }
            PROF(stage == 0 ? 7 : 14);
            if (stage == 1) {
                PROFG(26);
                asm volatile("barrier.cluster.arrive.relaxed.aligned;" ::: "memory");
            }
        }
        if (wg == 0) bar_sync(8, 256);
        bar_sync(3, 256);
        if (tid == 32) sc_->epoch[b * 32] = get_epoch(sbase) + 1;
        if (tid == 0) {
            rows_store(sbase, &maps.rout, own * 16);
            rows_store_wait();
        }
        __syncwarp();
        PROF(16);
        PROFG(31);
        asm volatile("barrier.cluster.wait.aligned;" ::: "memory");
    }
}

typedef CUresult (*EncodeFn)(CUtensorMap*, CUtensorMapDataType, cuuint32_t, void*, const cuuint64_t*, const cuuint64_t*,
                             const cuuint32_t*, const cuuint32_t*, CUtensorMapInterleave, CUtensorMapSwizzle,
                             CUtensorMapL2promotion, CUtensorMapFloatOOBfill);

void make_map(EncodeFn enc, CUtensorMap* m, const void* ptr, uint64_t rows, uint64_t cols, bool narrow = false) {
    cuuint64_t gdim[2] = {cols, rows};
    cuuint64_t gstr[1] = {cols * 2};
    cuuint32_t box[2] = {narrow ? 16u : 64u, narrow ? 192u : 64u};
    cuuint32_t estr[2] = {1, 1};
    enc(m, CU_TENSOR_MAP_DATA_TYPE_BFLOAT16, 2, const_cast<void*>(ptr), gdim, gstr, box, estr,
        CU_TENSOR_MAP_INTERLEAVE_NONE, narrow ? CU_TENSOR_MAP_SWIZZLE_NONE : CU_TENSOR_MAP_SWIZZLE_128B,
        CU_TENSOR_MAP_L2_PROMOTION_L2_128B,
        CU_TENSOR_MAP_FLOAT_OOB_FILL_NONE);
}

void make_rows_map(EncodeFn enc, CUtensorMap* m, const void* ptr) {
    cuuint64_t gdim[3] = {64, 9, 2048};
    cuuint64_t gstr[2] = {128, DM * 2};
    cuuint32_t box[3] = {64, 9, 16};
    cuuint32_t estr[3] = {1, 1, 1};
    enc(m, CU_TENSOR_MAP_DATA_TYPE_BFLOAT16, 3, const_cast<void*>(ptr), gdim, gstr, box, estr,
        CU_TENSOR_MAP_INTERLEAVE_NONE, CU_TENSOR_MAP_SWIZZLE_128B, CU_TENSOR_MAP_L2_PROMOTION_L2_128B,
        CU_TENSOR_MAP_FLOAT_OOB_FILL_NONE);
}

}

extern "C" void kernel_launch(void* const* d_in, const int* in_sizes, int n_in, void* d_out, int out_size) {
    (void)in_sizes;
    (void)n_in;
    (void)out_size;
    void* fn = nullptr;
    cudaDriverEntryPointQueryResult qr;
    cudaGetDriverEntryPoint("cuTensorMapEncodeTiled", &fn, cudaEnableDefault, &qr);
    EncodeFn enc = (EncodeFn)fn;
    Params maps;
    maps.x = (const __nv_bfloat16*)d_in[0];
    maps.cvec = (const __nv_bfloat16*)d_in[9];
    maps.wmod = (const __nv_bfloat16*)d_in[10];
    maps.kc = (const __nv_bfloat16*)d_in[1];
    maps.vc = (const __nv_bfloat16*)d_in[2];
    maps.wq_p = (const __nv_bfloat16*)d_in[3];
    maps.wo_p = (const __nv_bfloat16*)d_in[4];
    maps.wg_p = (const __nv_bfloat16*)d_in[6];
    maps.wu_p = (const __nv_bfloat16*)d_in[7];
    maps.wd_p = (const __nv_bfloat16*)d_in[8];
    maps.out = (__nv_bfloat16*)d_out;
    void* scp = nullptr;
    cudaGetSymbolAddress(&scp, g_scratch);
    maps.sc = (Scratch*)scp;
    make_map(enc, &maps.k, d_in[1], 32 * 2048, 128);
    make_map(enc, &maps.v, d_in[2], 32 * 2048, 128);
    make_map(enc, &maps.wq, d_in[3], 576, 4096);
    make_map(enc, &maps.wo, d_in[4], 4096, 576);
    make_map(enc, &maps.wg, d_in[6], 576, 4608);
    make_map(enc, &maps.wu, d_in[7], 576, 4608);
    make_map(enc, &maps.wd, d_in[8], 4608, 576);
    make_rows_map(enc, &maps.rx, d_in[0]);
    make_rows_map(enc, &maps.rx2, (char*)scp + offsetof(Scratch, x2));
    make_rows_map(enc, &maps.rout, d_out);
    cudaFuncSetAttribute(fused_block_kernel, cudaFuncAttributeMaxDynamicSharedMemorySize, SMEM_BYTES);
    fused_block_kernel<<<128, 384, SMEM_BYTES>>>(maps);
}
```

```cpp
#include <cuda_runtime.h>
#include <cuda_bf16.h>
#include <cuda.h>
#include <stdint.h>
#include <stddef.h>

namespace {

constexpr int DM = 576;
constexpr int SLOT_BYTES = 16384;
constexpr int BOX_BYTES = 8192;
constexpr int NUNITS = 14;
constexpr int SMEM_TAIL = NUNITS * SLOT_BYTES;
constexpr int SMEM_BYTES = SMEM_TAIL + 2048 + 1024;
constexpr int OFF_FULL = SMEM_TAIL;
constexpr int OFF_EMPTY = SMEM_TAIL + 64;
constexpr int OFF_RED = SMEM_TAIL + 128;

constexpr int KV_AHEAD = 16;
#define GATE_SLOT 4
#define X_DELAY 1200
constexpr int OFF_XBAR = SMEM_TAIL + 1792;
constexpr int OFF_ROWS = 8 * SLOT_BYTES;
constexpr int OFF_MODT = OFF_ROWS + 20480;
constexpr int OFF_EPOCH = SMEM_TAIL + 1808;
constexpr int OFF_CVEC = OFF_ROWS + 28672;

struct Scratch {
    unsigned epoch[128 * 32];
    uint32_t mod[6 * DM];
    uint4 h[2][2][128 * 36 * 32];
    uint4 part[128 * 8 * 36 * 32];
    uint4 hh[128 * 8 * 256];
    __nv_bfloat16 x2[2048 * DM];
};
__device__ Scratch g_scratch;

#define TG(i)
#define TL(i)
#define PROFR(i)
#define PROF(i)
#define PROFG(i)

struct Params {
    const __nv_bfloat16 *x, *cvec, *wmod, *kc, *vc, *wq_p, *wo_p, *wg_p, *wu_p, *wd_p;
    __nv_bfloat16* out;
    Scratch* sc;
    CUtensorMap k, v, wq, wo, wg, wu, wd, rx, rx2, rout;
};

__device__ __forceinline__ uint32_t smem_u32(const void* p) { return (uint32_t)__cvta_generic_to_shared(p); }
__device__ __forceinline__ void mbar_init(uint32_t a, uint32_t c) {
    asm volatile("mbarrier.init.shared::cta.b64 [%0], %1;" ::"r"(a), "r"(c) : "memory");
}
__device__ __forceinline__ void mbar_expect_tx(uint32_t a, uint32_t bytes) {
    asm volatile("mbarrier.arrive.expect_tx.shared::cta.b64 _, [%0], %1;" ::"r"(a), "r"(bytes) : "memory");
}
__device__ __forceinline__ bool mbar_try(uint32_t a, uint32_t ph) {
    uint32_t ok;
    asm volatile(
        "{\n.reg .pred p;\nmbarrier.try_wait.parity.shared::cta.b64 p, [%1], %2;\nselp.u32 %0, 1, 0, p;\n}"
        : "=r"(ok)
        : "r"(a), "r"(ph)
        : "memory");
    return ok != 0;
}
__device__ __forceinline__ uint32_t clk32() {
    uint32_t c;
    asm volatile("mov.u32 %0, %%clock;" : "=r"(c));
    return c;
}
constexpr uint32_t WAIT_LIMIT = 1u << 30;
__device__ __forceinline__ void mbar_wait(uint32_t a, uint32_t ph) {
    if (mbar_try(a, ph)) return;
    uint32_t t0 = clk32();
    while (!mbar_try(a, ph)) {
        if (clk32() - t0 > WAIT_LIMIT) break;
    }
}
__device__ __forceinline__ void mbar_arrive_cluster(uint32_t a, uint32_t cta) {
    asm volatile(
        "{\n.reg .b32 ra;\nmapa.shared::cluster.u32 ra, %0, %1;\nmbarrier.arrive.shared::cluster.b64 _, [ra];\n}" ::"r"(a),
        "r"(cta)
        : "memory");
}
__device__ __forceinline__ void tma_mc(uint32_t dst, const CUtensorMap* m, int c0, int c1, uint32_t bar) {
    asm volatile(
        "cp.async.bulk.tensor.2d.shared::cluster.global.mbarrier::complete_tx::bytes.multicast::cluster"
        " [%0], [%1, {%3, %4}], [%2], %5;" ::"r"(dst),
        "l"(m), "r"(bar), "r"(c0), "r"(c1), "h"((uint16_t)3)
        : "memory");
}
__device__ __forceinline__ void bulk_load(uint32_t dst, const void* src, uint32_t bytes, uint32_t bar) {
    asm volatile("cp.async.bulk.shared::cluster.global.mbarrier::complete_tx::bytes [%0], [%1], %2, [%3];" ::"r"(dst),
                 "l"(src), "r"(bytes), "r"(bar)
                 : "memory");
}
__device__ __forceinline__ void l2_prefetch(const void* p, uint32_t bytes) {
    asm volatile("cp.async.bulk.prefetch.L2.global [%0], %1;" ::"l"(p), "r"(bytes) : "memory");
}
__device__ __forceinline__ void bar_sync(int id, int n) { asm volatile("bar.sync %0, %1;" ::"r"(id), "r"(n) : "memory"); }
__device__ __forceinline__ void bar_arrive(int id, int n) {
    asm volatile("bar.arrive %0, %1;" ::"r"(id), "r"(n) : "memory");
}
__device__ __forceinline__ void wg_fence() { asm volatile("wgmma.fence.sync.aligned;" ::: "memory"); }
__device__ __forceinline__ void wg_commit() { asm volatile("wgmma.commit_group.sync.aligned;" ::: "memory"); }
template <int N>
__device__ __forceinline__ void wg_wait() {
    asm volatile("wgmma.wait_group.sync.aligned %0;" ::"n"(N) : "memory");
}
template <int N>
__device__ __forceinline__ void pin(float (&d)[N]) {
#pragma unroll
    for (int i = 0; i < N; i++) asm volatile("" : "+f"(d[i])::"memory");
}
template <int N>
__device__ __forceinline__ void pin(uint32_t (&d)[N]) {
#pragma unroll
    for (int i = 0; i < N; i++) asm volatile("" : "+r"(d[i])::"memory");
}
__device__ __forceinline__ uint32_t pack_bf16(float lo, float hi) {
    uint32_t r;
    asm("cvt.rn.bf16x2.f32 %0, %1, %2;" : "=r"(r) : "f"(hi), "f"(lo));
    return r;
}
__device__ __forceinline__ float bf_lo(uint32_t v) { return __uint_as_float(v << 16); }
__device__ __forceinline__ float bf_hi(uint32_t v) { return __uint_as_float(v & 0xffff0000u); }
__device__ __forceinline__ float round_bf16(float v) { return __bfloat162float(__float2bfloat16_rn(v)); }
__device__ __forceinline__ float ex2(float x) {
    float y;
    asm("ex2.approx.ftz.f32 %0, %1;" : "=f"(y) : "f"(x));
    return y;
}
__device__ __forceinline__ float rcp(float x) {
    float y;
    asm("rcp.approx.ftz.f32 %0, %1;" : "=f"(y) : "f"(x));
    return y;
}
__device__ __forceinline__ float tanh_fast(float x) {
    float y;
    asm("tanh.approx.f32 %0, %1;" : "=f"(y) : "f"(x));
    return y;
}
__device__ __forceinline__ void sts128(uint32_t a, uint32_t x, uint32_t y, uint32_t z, uint32_t w) {
    asm volatile("st.shared.v4.b32 [%0], {%1,%2,%3,%4};" ::"r"(a), "r"(x), "r"(y), "r"(z), "r"(w) : "memory");
}
__device__ __forceinline__ void lds128(uint32_t a, uint32_t& x, uint32_t& y, uint32_t& z, uint32_t& w) {
    asm volatile("ld.shared.v4.b32 {%0,%1,%2,%3}, [%4];" : "=r"(x), "=r"(y), "=r"(z), "=r"(w) : "r"(a) : "memory");
}
__device__ __forceinline__ void sts32f(uint32_t a, float v) {
    asm volatile("st.shared.f32 [%0], %1;" ::"r"(a), "f"(v) : "memory");
}
__device__ __forceinline__ float lds32f(uint32_t a) {
    float v;
    asm volatile("ld.shared.f32 %0, [%1];" : "=f"(v) : "r"(a) : "memory");
    return v;
}
#define F8(d, b) \
    "+f"(d[b]), "+f"(d[b + 1]), "+f"(d[b + 2]), "+f"(d[b + 3]), "+f"(d[b + 4]), "+f"(d[b + 5]), "+f"(d[b + 6]), "+f"(d[b + 7])

template <int TB>
__device__ __forceinline__ void wgmma_n128(float (&d)[64], uint32_t a0, uint32_t a1, uint32_t a2, uint32_t a3,
                                           uint64_t db, int sc) {
    asm volatile(
        "{\n.reg .pred p;\nsetp.ne.b32 p, %69, 0;\n"
        "wgmma.mma_async.sync.aligned.m64n128k16.f32.bf16.bf16 "
        "{%0,%1,%2,%3,%4,%5,%6,%7,%8,%9,%10,%11,%12,%13,%14,%15,%16,%17,%18,%19,%20,%21,%22,%23,%24,%25,%26,%27,%28,%29,%30,%31,"
        "%32,%33,%34,%35,%36,%37,%38,%39,%40,%41,%42,%43,%44,%45,%46,%47,%48,%49,%50,%51,%52,%53,%54,%55,%56,%57,%58,%59,%60,%61,%62,%63},"
        "{%64,%65,%66,%67}, %68, p, 1, 1, %70;\n}"
        : F8(d, 0), F8(d, 8), F8(d, 16), F8(d, 24), F8(d, 32), F8(d, 40), F8(d, 48), F8(d, 56)
        : "r"(a0), "r"(a1), "r"(a2), "r"(a3), "l"(db), "r"(sc), "n"(TB));
}
#define O8(d, b) \
    "=f"(d[b]), "=f"(d[b + 1]), "=f"(d[b + 2]), "=f"(d[b + 3]), "=f"(d[b + 4]), "=f"(d[b + 5]), "=f"(d[b + 6]), "=f"(d[b + 7])
template <int TB>
__device__ __forceinline__ void wgmma_n128_z(float (&d)[64], uint32_t a0, uint32_t a1, uint32_t a2, uint32_t a3,
                                             uint64_t db) {
    asm volatile(
        "wgmma.mma_async.sync.aligned.m64n128k16.f32.bf16.bf16 "
        "{%0,%1,%2,%3,%4,%5,%6,%7,%8,%9,%10,%11,%12,%13,%14,%15,%16,%17,%18,%19,%20,%21,%22,%23,%24,%25,%26,%27,%28,%29,%30,%31,"
        "%32,%33,%34,%35,%36,%37,%38,%39,%40,%41,%42,%43,%44,%45,%46,%47,%48,%49,%50,%51,%52,%53,%54,%55,%56,%57,%58,%59,%60,%61,%62,%63},"
        "{%64,%65,%66,%67}, %68, 0, 1, 1, %69;"
        : O8(d, 0), O8(d, 8), O8(d, 16), O8(d, 24), O8(d, 32), O8(d, 40), O8(d, 48), O8(d, 56)
        : "r"(a0), "r"(a1), "r"(a2), "r"(a3), "l"(db), "n"(TB));
}
template <int TB>
__device__ __forceinline__ void wgmma_n64_z(float (&d)[32], uint32_t a0, uint32_t a1, uint32_t a2, uint32_t a3,
                                            uint64_t db) {
    asm volatile(
        "wgmma.mma_async.sync.aligned.m64n64k16.f32.bf16.bf16 "
        "{%0,%1,%2,%3,%4,%5,%6,%7,%8,%9,%10,%11,%12,%13,%14,%15,%16,%17,%18,%19,%20,%21,%22,%23,%24,%25,%26,%27,%28,%29,%30,%31},"
        "{%32,%33,%34,%35}, %36, 0, 1, 1, %37;"
        : O8(d, 0), O8(d, 8), O8(d, 16), O8(d, 24)
        : "r"(a0), "r"(a1), "r"(a2), "r"(a3), "l"(db), "n"(TB));
}
template <int TB>
__device__ __forceinline__ void wgmma_n64(float (&d)[32], uint32_t a0, uint32_t a1, uint32_t a2, uint32_t a3,
                                          uint64_t db) {
    asm volatile(
        "wgmma.mma_async.sync.aligned.m64n64k16.f32.bf16.bf16 "
        "{%0,%1,%2,%3,%4,%5,%6,%7,%8,%9,%10,%11,%12,%13,%14,%15,%16,%17,%18,%19,%20,%21,%22,%23,%24,%25,%26,%27,%28,%29,%30,%31},"
        "{%32,%33,%34,%35}, %36, 1, 1, 1, %37;"
        : F8(d, 0), F8(d, 8), F8(d, 16), F8(d, 24)
        : "r"(a0), "r"(a1), "r"(a2), "r"(a3), "l"(db), "n"(TB));
}

__device__ __forceinline__ uint64_t desc_of(uint32_t saddr) {
    return (uint64_t)(((saddr >> 4) & 0x3FFFu) | (512u << 16)) | ((uint64_t)(64u | (1u << 30)) << 32);
}

struct Ring {
    uint32_t slot;
    uint32_t phase;
    __device__ __forceinline__ void next() {
        if (++slot == 8) {
            slot = 0;
            phase ^= 1;
        }
    }
};

struct Ctx {
    uint32_t sbase;
    int wg;
    uint32_t rel_cta;
    __device__ __forceinline__ void wait_full(uint32_t slot, uint32_t phase) const {
        mbar_wait(sbase + OFF_FULL + slot * 8, phase);
    }
    __device__ __forceinline__ void release(uint32_t slot) const {
        if (rel_cta < 2) mbar_arrive_cluster(sbase + OFF_EMPTY + slot * 8, rel_cta);
    }
};

__device__ __forceinline__ void gemm_n128(float (&d)[64], const uint32_t (&a)[144], const Ctx& c, Ring& r, bool nine) {
    uint32_t prev = 0;
#pragma unroll
    for (int s = 0; s < 9; s++) {
        if (s < 8 || nine) {
            if (s == GATE_SLOT) bar_sync(8 + c.wg, 256);
            c.wait_full(r.slot, r.phase);
            uint64_t db = desc_of(c.sbase + r.slot * SLOT_BYTES);
            wg_fence();
#pragma unroll
            for (int k = 0; k < 4; k++) {
                if ((s | k) == 0)
                    wgmma_n128_z<1>(d, a[0], a[1], a[2], a[3], db);
                else
                    wgmma_n128<1>(d, a[s * 16 + k * 4], a[s * 16 + k * 4 + 1], a[s * 16 + k * 4 + 2],
                                  a[s * 16 + k * 4 + 3], db + k * 128, 1);
            }
            wg_commit();
            if (s == 8 || (s == 7 && !nine)) bar_arrive(9 - c.wg, 256);
            if (s > 0) {
                wg_wait<1>();
                c.release(prev);
            }
            prev = r.slot;
            r.next();
        }
    }
    wg_wait<0>();
    c.release(prev);
    pin(d);
}
__device__ __forceinline__ void gemm_n64(float (&d)[32], const uint32_t (&a)[144], const Ctx& c, Ring& r, bool nine) {
    uint32_t prev = 0;
#pragma unroll
    for (int s = 0; s < 5; s++) {
        if (s < 4 || nine) {
            c.wait_full(r.slot, r.phase);
            uint64_t db = desc_of(c.sbase + r.slot * SLOT_BYTES);
            wg_fence();
#pragma unroll
            for (int k = 0; k < 8; k++) {
                if ((s | k) == 0)
                    wgmma_n64_z<1>(d, a[0], a[1], a[2], a[3], db);
                else if (s * 8 + k < 36)
                    wgmma_n64<1>(d, a[s * 32 + k * 4], a[s * 32 + k * 4 + 1], a[s * 32 + k * 4 + 2],
                                 a[s * 32 + k * 4 + 3], db + k * 128);
            }
            wg_commit();
            if (s > 0) {
                wg_wait<1>();
                c.release(prev);
            }
            prev = r.slot;
            r.next();
        }
    }
    wg_wait<0>();
    c.release(prev);
    pin(d);
}
__device__ __forceinline__ void st128(uint4* p, uint32_t x, uint32_t y, uint32_t z, uint32_t w) {
    asm volatile(
        "{\n.reg .b64 lo, hi;\n.reg .b128 t;\nmov.b64 lo, {%1, %2};\nmov.b64 hi, {%3, %4};\nmov.b128 t, {lo, hi};\n"
        "st.relaxed.gpu.global.b128 [%0], t;\n}" ::"l"(p),
        "r"(x), "r"(y), "r"(z), "r"(w)
        : "memory");
}
__device__ __forceinline__ uint4 ld128(const uint4* p) {
    uint4 r;
    asm volatile(
        "{\n.reg .b64 lo, hi;\n.reg .b128 t;\nld.relaxed.gpu.global.b128 t, [%4];\nmov.b128 {lo, hi}, t;\n"
        "mov.b64 {%0, %1}, lo;\nmov.b64 {%2, %3}, hi;\n}"
        : "=r"(r.x), "=r"(r.y), "=r"(r.z), "=r"(r.w)
        : "l"(p));
    return r;
}
__device__ __forceinline__ uint4 ldg128(const uint4* p) {
    uint4 r;
    asm volatile("ld.global.nc.v4.u32 {%0,%1,%2,%3}, [%4];" : "=r"(r.x), "=r"(r.y), "=r"(r.z), "=r"(r.w) : "l"(p));
    return r;
}
__device__ __forceinline__ void st64(void* p, uint32_t x, uint32_t y) {
    asm volatile("{\n.reg .b64 t;\nmov.b64 t, {%1, %2};\nst.relaxed.gpu.global.b64 [%0], t;\n}" ::"l"(p), "r"(x), "r"(y)
                 : "memory");
}
__device__ __forceinline__ uint2 ld64(const void* p) {
    uint2 r;
    asm volatile("{\n.reg .b64 t;\nld.relaxed.gpu.global.b64 t, [%2];\nmov.b64 {%0, %1}, t;\n}"
                 : "=r"(r.x), "=r"(r.y)
                 : "l"(p));
    return r;
}
__device__ __forceinline__ void rows_load(uint32_t sbase, const CUtensorMap* m, int row0) {
    mbar_expect_tx(sbase + OFF_XBAR, 16 * DM * 2);
    asm volatile(
        "cp.async.bulk.tensor.3d.shared::cluster.global.mbarrier::complete_tx::bytes [%0], [%1, {%3, %3, %4}], [%2];" ::"r"(
            sbase + OFF_ROWS),
        "l"(m), "r"(sbase + OFF_XBAR), "r"(0), "r"(row0)
        : "memory");
}
__device__ __forceinline__ void rows_store(uint32_t sbase, const CUtensorMap* m, int row0) {
    asm volatile("cp.async.bulk.tensor.3d.global.shared::cta.bulk_group [%0, {%2, %2, %3}], [%1];" ::"l"(m),
                 "r"(sbase + OFF_ROWS), "r"(0), "r"(row0)
                 : "memory");
    asm volatile("cp.async.bulk.commit_group;" ::: "memory");
}
__device__ __forceinline__ void rows_store_wait() { asm volatile("cp.async.bulk.wait_group 0;" ::: "memory"); }

__device__ __forceinline__ constexpr int own_col(int j) { return j < 8 ? (j >> 1) * 128 + (j & 1) * 8 : 512; }
__device__ __forceinline__ void row_reduce(float& s0, float& s1, uint32_t red, int warp, int lane) {
    s0 += __shfl_xor_sync(0xffffffffu, s0, 1);
    s1 += __shfl_xor_sync(0xffffffffu, s1, 1);
    s0 += __shfl_xor_sync(0xffffffffu, s0, 2);
    s1 += __shfl_xor_sync(0xffffffffu, s1, 2);
    if ((lane & 3) == 0) {
        sts32f(red + (warp * 16 + (lane >> 2)) * 4, s0);
        sts32f(red + (warp * 16 + 8 + (lane >> 2)) * 4, s1);
    }
    bar_sync(3, 256);
    s0 = 0.f;
    s1 = 0.f;
#pragma unroll
    for (int w = 0; w < 8; w++) {
        s0 += lds32f(red + (w * 16 + (lane >> 2)) * 4);
        s1 += lds32f(red + (w * 16 + 8 + (lane >> 2)) * 4);
    }
}
__device__ __forceinline__ void layernorm_rows(float (&v)[36], uint32_t red, int warp, int lane) {
    float s0 = 0.f, s1 = 0.f;
#pragma unroll
    for (int j = 0; j < 9; j++) {
        s0 += v[4 * j] + v[4 * j + 1];
        s1 += v[4 * j + 2] + v[4 * j + 3];
    }
    row_reduce(s0, s1, red, warp, lane);
    const float m0 = s0 * (1.f / DM), m1 = s1 * (1.f / DM);
    s0 = 0.f;
    s1 = 0.f;
#pragma unroll
    for (int j = 0; j < 9; j++) {
        v[4 * j] -= m0;
        v[4 * j + 1] -= m0;
        v[4 * j + 2] -= m1;
        v[4 * j + 3] -= m1;
        s0 += v[4 * j] * v[4 * j] + v[4 * j + 1] * v[4 * j + 1];
        s1 += v[4 * j + 2] * v[4 * j + 2] + v[4 * j + 3] * v[4 * j + 3];
    }
    row_reduce(s0, s1, red + 512, warp, lane);
    const float r0 = rsqrtf(s0 * (1.f / DM) + 1e-5f), r1 = rsqrtf(s1 * (1.f / DM) + 1e-5f);
#pragma unroll
    for (int j = 0; j < 9; j++) {
        v[4 * j] *= r0;
        v[4 * j + 1] *= r0;
        v[4 * j + 2] *= r1;
        v[4 * j + 3] *= r1;
    }
}
__device__ __forceinline__ void mod_to_smem(uint32_t dst, const uint32_t* src, uint32_t tag) {
    const uint32_t t0 = clk32();
    uint4 u;
    while (true) {
        u = ld128(reinterpret_cast<const uint4*>(src));
        const uint32_t bad = ((u.x ^ tag) | (u.y ^ tag) | (u.z ^ tag) | (u.w ^ tag)) & 0xffffu;
        if (__all_sync(0xffffffffu, bad == 0) || clk32() - t0 > WAIT_LIMIT) break;
        __nanosleep(64);
    }
    sts128(dst, u.x & 0xffff0000u, u.y & 0xffff0000u, u.z & 0xffff0000u, u.w & 0xffff0000u);
}
__device__ __forceinline__ void lds_mod(float (&m)[18], uint32_t src  , int warp) {
#pragma unroll
    for (int j = 0; j < 9; j++)
        asm volatile("ld.shared.v2.f32 {%0,%1}, [%2];"
                     : "=f"(m[2 * j]), "=f"(m[2 * j + 1])
                     : "r"(src + own_col(j) * 4 - (j == 8 ? warp * 32 : 0))
                     : "memory");
}
__device__ __forceinline__ void modulate_store(const float (&v)[36], const float (&shift)[18], const float (&scale)[18],
                                               uint4* hbuf  , int warp, int lane) {
    uint32_t o[18];
#pragma unroll
    for (int j = 0; j < 9; j++) {
        const uint32_t cc = pack_bf16(1.f + scale[2 * j], 1.f + scale[2 * j + 1]);
        const float c0 = bf_lo(cc), c1 = bf_hi(cc);
        o[2 * j] = max(pack_bf16(fmaf(v[4 * j], c0, shift[2 * j]), fmaf(v[4 * j + 1], c1, shift[2 * j + 1])), 1u);
        o[2 * j + 1] = max(pack_bf16(fmaf(v[4 * j + 2], c0, shift[2 * j]), fmaf(v[4 * j + 3], c1, shift[2 * j + 1])), 1u);
    }
#pragma unroll
    for (int i = 0; i < 4; i++) st128(hbuf + (i * 8 + warp) * 32 + lane, o[4 * i], o[4 * i + 1], o[4 * i + 2], o[4 * i + 3]);
    st64(reinterpret_cast<uint2*>(hbuf + 32 * 32) + warp * 32 + lane, o[16], o[17]);
}
__device__ __forceinline__ void sum_partials(float (&v)[36], const uint4* src  , uint32_t tag) {
    const uint32_t t0 = clk32();
    while (true) {
        uint4 t[8][4];
#pragma unroll
        for (int s = 0; s < 8; s++)
#pragma unroll
            for (int i = 0; i < 4; i++) t[s][i] = ld128(src + (s * 36 + i * 8) * 32);
        uint32_t bad = 0;
#pragma unroll
        for (int i = 0; i < 32; i++) v[i] = 0.f;
#pragma unroll
        for (int s = 0; s < 8; s++)
#pragma unroll
            for (int i = 0; i < 4; i++) {
                bad |= t[s][i].x ^ tag;
                v[8 * i] += bf_lo(t[s][i].x);
                v[8 * i + 1] += bf_hi(t[s][i].x);
                v[8 * i + 2] += bf_lo(t[s][i].y);
                v[8 * i + 3] += bf_hi(t[s][i].y);
                v[8 * i + 4] += bf_lo(t[s][i].z);
                v[8 * i + 5] += bf_hi(t[s][i].z);
                v[8 * i + 6] += bf_lo(t[s][i].w);
                v[8 * i + 7] += bf_hi(t[s][i].w);
            }
        if (__all_sync(0xffffffffu, (bad & 1u) == 0) || clk32() - t0 > WAIT_LIMIT) break;
    }
}
__device__ __forceinline__ void sum_tail(float (&v)[36], const uint2* src  , uint32_t tag) {
    const uint32_t t0 = clk32();
    while (true) {
        uint2 t[8];
#pragma unroll
        for (int s = 0; s < 8; s++) t[s] = ld64(src + s * 72 * 32);
        uint32_t bad = 0;
        v[32] = v[33] = v[34] = v[35] = 0.f;
#pragma unroll
        for (int s = 0; s < 8; s++) {
            bad |= t[s].x ^ tag;
            v[32] += bf_lo(t[s].x);
            v[33] += bf_hi(t[s].x);
            v[34] += bf_lo(t[s].y);
            v[35] += bf_hi(t[s].y);
        }
        if (__all_sync(0xffffffffu, (bad & 1u) == 0) || clk32() - t0 > WAIT_LIMIT) break;
    }
}
__device__ __forceinline__ void poll_tail(uint32_t (&a)[144], const uint2* src  ) {
    const uint32_t t0 = clk32();
    while (true) {
        uint32_t m = 0xffffffffu;
#pragma unroll
        for (int j = 0; j < 8; j++) {
            const uint2 t = ld64(src + j * 32);
            a[128 + 2 * j] = t.x;
            a[129 + 2 * j] = t.y;
        }
#pragma unroll
        for (int j = 0; j < 16; j++) m = min(m, a[128 + j]);
        if (__all_sync(0xffffffffu, m != 0) || clk32() - t0 > WAIT_LIMIT) break;
    }
}
template <int K0, int K1>
__device__ __forceinline__ void poll_frags(uint32_t (&a)[144], const uint4* src  , bool kick) {
    const uint32_t t0 = clk32();
    while (true) {
#pragma unroll
        for (int k = K0; k < K1; k++)
            asm volatile("ld.relaxed.gpu.global.v4.u32 {%0,%1,%2,%3}, [%4];"
                         : "=r"(a[4 * k]), "=r"(a[4 * k + 1]), "=r"(a[4 * k + 2]), "=r"(a[4 * k + 3])
                         : "l"(src + k * 32));
        if (kick) bar_arrive(5, 256);
        kick = false;
        uint32_t m0 = a[4 * K0], m1 = a[4 * K0 + 1];
#pragma unroll
        for (int i = 4 * K0 + 2; i < 4 * K1; i += 2) {
            m0 = min(m0, a[i]);
            m1 = min(m1, a[i + 1]);
        }
        if (__all_sync(0xffffffffu, min(m0, m1) != 0) || clk32() - t0 > WAIT_LIMIT) break;
    }
}

constexpr float SM_SCALE = 0.08838834764831845f * 1.4426950408889634f;
constexpr float SM_HI = 1.2089258e24f;
constexpr float SM_LO = 9.0949470e-13f;
__device__ __forceinline__ void qk_step(float (&s)[32], const uint32_t (&q)[32], uint64_t dk) {
#pragma unroll
    for (int k = 0; k < 8; k++) {
        if (k == 0)
            wgmma_n64_z<0>(s, q[0], q[1], q[2], q[3], dk);
        else
            wgmma_n64<0>(s, q[4 * k], q[4 * k + 1], q[4 * k + 2], q[4 * k + 3], dk + (k >> 2) * 512 + (k & 3) * 2);
    }
}
__device__ __forceinline__ void pv_step(float (&o)[64], const uint32_t (&p)[16], uint64_t dv, int acc) {
#pragma unroll
    for (int k = 0; k < 4; k++)
        wgmma_n128<1>(o, p[4 * k], p[4 * k + 1], p[4 * k + 2], p[4 * k + 3], dv + k * 128, k != 0 ? 1 : acc);
}
template <bool SHIFT>
__device__ __forceinline__ void exp_step(const float (&s)[32], uint32_t (&p)[16], float n0, float n1, float& s0,
                                         float& s1) {
#pragma unroll
    for (int i = 0; i < 8; i++) {
        const float e0 = ex2(SHIFT ? s[4 * i] + n0 : s[4 * i]), e1 = ex2(SHIFT ? s[4 * i + 1] + n0 : s[4 * i + 1]);
        const float e2 = ex2(SHIFT ? s[4 * i + 2] + n1 : s[4 * i + 2]), e3 = ex2(SHIFT ? s[4 * i + 3] + n1 : s[4 * i + 3]);
        if (i == 0) {
            s0 = e0 + e1;
            s1 = e2 + e3;
        } else {
            s0 += e0 + e1;
            s1 += e2 + e3;
        }
        p[2 * i] = pack_bf16(e0, e1);
        p[2 * i + 1] = pack_bf16(e2, e3);
    }
}
__device__ __forceinline__ void row_max(const float (&sa)[32], const float (&sb)[32], float& x0, float& x1) {
    float xa[8];
#pragma unroll
    for (int i = 0; i < 8; i++) xa[i] = fmaxf(sa[i], sb[i]);
#pragma unroll
    for (int k = 1; k < 4; k++)
#pragma unroll
        for (int i = 0; i < 8; i++) xa[i] = fmaxf(xa[i], fmaxf(sa[8 * k + i], sb[8 * k + i]));
    x0 = fmaxf(fmaxf(xa[0], xa[1]), fmaxf(xa[4], xa[5]));
    x1 = fmaxf(fmaxf(xa[2], xa[3]), fmaxf(xa[6], xa[7]));
    x0 = fmaxf(x0, __shfl_xor_sync(0xffffffffu, x0, 1));
    x1 = fmaxf(x1, __shfl_xor_sync(0xffffffffu, x1, 1));
    x0 = fmaxf(x0, __shfl_xor_sync(0xffffffffu, x0, 2));
    x1 = fmaxf(x1, __shfl_xor_sync(0xffffffffu, x1, 2));
}
__device__ __forceinline__ void inv_row_sums(float l0, float l1, float& i0, float& i1) {
    l0 += __shfl_xor_sync(0xffffffffu, l0, 1);
    l1 += __shfl_xor_sync(0xffffffffu, l1, 1);
    l0 += __shfl_xor_sync(0xffffffffu, l0, 2);
    l1 += __shfl_xor_sync(0xffffffffu, l1, 2);
    i0 = rcp(l0);
    i1 = rcp(l1);
}

__device__ __forceinline__ uint32_t get_epoch(uint32_t sbase) { return __float_as_uint(lds32f(sbase + OFF_EPOCH)); }
__device__ __forceinline__ float silu_bf16(unsigned short c) {
    const float cv = bf_lo(c);
    return round_bf16(cv * rcp(1.f + ex2(-1.4426950408889634f * cv)));
}
__device__ __forceinline__ void st_mod(uint32_t* p, float v, uint32_t tag) {
    asm volatile("st.relaxed.gpu.global.u32 [%0], %1;" ::"l"(p), "r"(__float_as_uint(round_bf16(v)) | tag)
                 : "memory");
}
__device__ __forceinline__ void mod_fma(float (&acc)[8], const uint4 (&w)[5], const float (&sc)[5]) {
#pragma unroll
    for (int e = 0; e < 8; e++) acc[e] = 0.f;
#pragma unroll
    for (int i = 0; i < 5; i++) {
        acc[0] = fmaf(sc[i], bf_lo(w[i].x), acc[0]);
        acc[1] = fmaf(sc[i], bf_hi(w[i].x), acc[1]);
        acc[2] = fmaf(sc[i], bf_lo(w[i].y), acc[2]);
        acc[3] = fmaf(sc[i], bf_hi(w[i].y), acc[3]);
        acc[4] = fmaf(sc[i], bf_lo(w[i].z), acc[4]);
        acc[5] = fmaf(sc[i], bf_hi(w[i].z), acc[5]);
        acc[6] = fmaf(sc[i], bf_lo(w[i].w), acc[6]);
        acc[7] = fmaf(sc[i], bf_hi(w[i].w), acc[7]);
    }
}
__device__ __forceinline__ void mod_reduce(float (&acc)[8], uint32_t* dst, uint32_t red, int warp, int lane,
                                           uint32_t tag) {
#pragma unroll
    for (int o = 2; o < 32; o <<= 1)
#pragma unroll
        for (int e = 0; e < 8; e++) acc[e] += __shfl_xor_sync(0xffffffffu, acc[e], o);
    if (lane < 2) {
#pragma unroll
        for (int e = 0; e < 8; e++) sts32f(red + (warp * 16 + lane * 8 + e) * 4, acc[e]);
    }
    bar_sync(3, 256);
    if (warp == 0 && lane < 16) {
        float s = 0.f;
#pragma unroll
        for (int w8 = 0; w8 < 8; w8++) s += lds32f(red + (w8 * 16 + lane) * 4);
        st_mod(dst + lane, s, tag);
    }
}

__global__ void __cluster_dims__(2, 1, 1) __launch_bounds__(384, 1)
    fused_block_kernel(const __grid_constant__ Params maps) {
    extern __shared__ uint8_t smem_raw[];
    const uint32_t t_entry = clk32();
    if (threadIdx.x >= 288 && threadIdx.x < 288 + 81) {
        const int li = blockIdx.x * 81 + threadIdx.x - 288;
        asm volatile("prefetch.global.L2 [%0];" ::"l"((const char*)maps.wmod + (size_t)(li / 18) * (12 * DM) + (li % 18) * 128));
    }
    uint32_t sbase = (smem_u32(smem_raw) + 1023u) & ~1023u;
    asm volatile("" : "+r"(sbase));
    const int b = blockIdx.x;
    const int rank = b & 1;
    const int mt = ((b >> 1) & 7) * 2 + rank;
    const int g = b >> 4;
    const int warp = __shfl_sync(0xffffffffu, threadIdx.x >> 5, 0);
    const int lane = threadIdx.x & 31;
    Scratch* const sc_ = maps.sc;
    const __nv_bfloat16* const wmod = maps.wmod;
    const __nv_bfloat16* const cvec = maps.cvec;

#define SPROF(i)

    if (warp >= 8) {
        asm volatile("setmaxnreg.dec.sync.aligned.u32 24;");
        if (warp == 8 && lane == 0) {
#pragma unroll
            for (int i = 0; i < 8; i++) {
                mbar_init(sbase + OFF_FULL + i * 8, 1);
                mbar_init(sbase + OFF_EMPTY + i * 8, 4);
            }
            mbar_init(sbase + OFF_XBAR, 1);
            asm volatile("fence.mbarrier_init.release.cluster;" ::: "memory");
            asm volatile("barrier.cluster.arrive.relaxed;\nbarrier.cluster.wait;" ::: "memory");
            uint32_t slot = 0, phase = 1;
            const uint32_t dst0 = sbase + rank * BOX_BYTES;
            auto acquire = [&](uint32_t bytes) {
                mbar_wait(sbase + OFF_EMPTY + slot * 8, phase);
                mbar_expect_tx(sbase + OFF_FULL + slot * 8, bytes);
            };
            auto adv8 = [&]() {
                if (++slot == 8) {
                    slot = 0;
                    phase ^= 1;
                }
            };
#pragma unroll 1
            for (int hq = 0; hq < 4; hq++) {
                const int col = (g * 4 + ((hq + 1) & 3)) * 128 + rank * 64;
                if (hq == 2) {
                    l2_prefetch(maps.kc + (size_t)(g * 4 * 2048 + (b & 15) * 64) * 128, SLOT_BYTES);
                    l2_prefetch(maps.vc + (size_t)(g * 4 * 2048 + (b & 15) * 64) * 128, SLOT_BYTES);
                }
#pragma unroll 1
                for (int kc = 0; kc < 9; kc++) {
                    acquire(SLOT_BYTES);
                    tma_mc(dst0 + slot * SLOT_BYTES, &maps.wq, col, kc * 64, sbase + OFF_FULL + slot * 8);
                    adv8();
                }
            }
            const int row0 = g * 4 * 2048;
#pragma unroll 1
            for (int n = 0; n < 128; n++) {
                if (n < 4) mbar_wait(sbase + OFF_EMPTY + (slot + 1) * 8, phase);
                acquire(2 * SLOT_BYTES);
                const uint32_t bar = sbase + OFF_FULL + slot * 8;
                const int r0 = n == 0 ? 0 : (n == 127 ? 126 : n + 1);
                const int r1 = n == 0 ? 1 : (n == 127 ? 127 : n - 1);
                tma_mc(dst0 + slot * SLOT_BYTES, n == 127 ? &maps.v : &maps.k, rank * 64, row0 + r0 * 64, bar);
                tma_mc(dst0 + (slot + 1) * SLOT_BYTES, n == 0 ? &maps.k : &maps.v, rank * 64, row0 + r1 * 64, bar);
                adv8();
                adv8();
                if (n >= 96 && n < 96 + 10) {
                    const int i = n - 96;
                    if (i < 9) {
                        l2_prefetch((const char*)maps.wg_p + (size_t)b * 41472 + i * 4608, 4608);
                        l2_prefetch((const char*)maps.wu_p + (size_t)b * 41472 + i * 4608, 4608);
                        l2_prefetch((const char*)maps.wd_p + (size_t)b * 41472 + i * 4608, 4608);
                        l2_prefetch((const char*)maps.wo_p + (size_t)b * 36864 + i * 4096, 4096);
                    }
                }
                const int u = n + KV_AHEAD;
                if (u < 128 && (u & 15) == (b & 15)) {
                    l2_prefetch(maps.kc + (size_t)(row0 + u * 64) * 128, SLOT_BYTES);
                    l2_prefetch(maps.vc + (size_t)(row0 + u * 64) * 128, SLOT_BYTES);
                }
            }
#pragma unroll 1
            for (int p = 0; p < 4; p++)
#pragma unroll 1
                for (int kc = 0; kc < 8; kc++) {
                    acquire(SLOT_BYTES);
                    tma_mc(dst0 + slot * SLOT_BYTES, &maps.wo, p * 128 + rank * 64, g * 512 + kc * 64,
                           sbase + OFF_FULL + slot * 8);
                    adv8();
                }
#pragma unroll 1
            for (int kc = 0; kc < 4; kc++) {
                acquire(SLOT_BYTES);
                tma_mc(dst0 + slot * SLOT_BYTES, &maps.wo, 512, g * 512 + kc * 128 + rank * 64,
                       sbase + OFF_FULL + slot * 8);
                adv8();
            }
            const CUtensorMap* mg = rank ? &maps.wu : &maps.wg;
#pragma unroll 1
            for (int ch = 0; ch < 9; ch++)
#pragma unroll 1
                for (int kc = 0; kc < 9; kc++) {
                    acquire(SLOT_BYTES);
                    tma_mc(dst0 + slot * SLOT_BYTES, mg, g * 576 + ch * 64, kc * 64, sbase + OFF_FULL + slot * 8);
                    adv8();
                }
#pragma unroll 1
            for (int p = 0; p < 4; p++)
#pragma unroll 1
                for (int kc = 2; kc < 11; kc++) {
                    acquire(SLOT_BYTES);
                    tma_mc(dst0 + slot * SLOT_BYTES, &maps.wd, p * 128 + rank * 64, g * 576 + (kc < 9 ? kc : kc - 9) * 64,
                           sbase + OFF_FULL + slot * 8);
                    adv8();
                }
#pragma unroll 1
            for (int i = 0; i < 5; i++) {
                acquire(i < 4 ? SLOT_BYTES : BOX_BYTES);
                const int kc = 2 * i + rank + 2;
                if (i < 4 || rank == 0)
                    tma_mc(dst0 + slot * SLOT_BYTES, &maps.wd, 512, g * 576 + (kc < 9 ? kc : kc - 9) * 64,
                           sbase + OFF_FULL + slot * 8);
                adv8();
            }
        } else if (warp == 11) {
            asm volatile("barrier.cluster.arrive.relaxed.aligned;" ::: "memory");
            bar_sync(6, 160);
            uint4* hz = sc_->h[(get_epoch(sbase) & 1) ^ 1][0] + (size_t)b * 72 * 32 + lane;
#pragma unroll 1
            for (int i = 0; i < 72; i++) {
                hz[i * 32] = make_uint4(0, 0, 0, 0);
                __nanosleep(200);
            }
        } else if (warp == 9 || warp == 10) {
            asm volatile("barrier.cluster.arrive.relaxed.aligned;" ::: "memory");
            bar_sync(4, 320);
            const uint32_t tag = (get_epoch(sbase) + 1) & 0xffffu;
            if (warp == 10 && lane < 9) l2_prefetch((const char*)maps.wq_p + (size_t)b * 36864 + lane * 4096, 4096);
            const int blk = warp == 9 ? 72 + b : 200 + b;
            if (blk < 216) {
                float acc[8];
#pragma unroll
                for (int e = 0; e < 8; e++) acc[e] = 0.f;
                const uint4* wp = reinterpret_cast<const uint4*>(wmod + (size_t)(lane >> 1) * (6 * DM) + blk * 16) + (lane & 1);
                const unsigned short* cp = reinterpret_cast<const unsigned short*>(cvec) + (lane >> 1);
#pragma unroll 1
                for (int i = 0; i < 36; i++) {
                    const uint4 w = __ldg(wp + (size_t)i * (16 * 6 * DM / 8));
                    const float sc = silu_bf16(__ldg(cp + i * 16));
                    acc[0] = fmaf(sc, bf_lo(w.x), acc[0]);
                    acc[1] = fmaf(sc, bf_hi(w.x), acc[1]);
                    acc[2] = fmaf(sc, bf_lo(w.y), acc[2]);
                    acc[3] = fmaf(sc, bf_hi(w.y), acc[3]);
                    acc[4] = fmaf(sc, bf_lo(w.z), acc[4]);
                    acc[5] = fmaf(sc, bf_hi(w.z), acc[5]);
                    acc[6] = fmaf(sc, bf_lo(w.w), acc[6]);
                    acc[7] = fmaf(sc, bf_hi(w.w), acc[7]);
                }
#pragma unroll
                for (int o = 2; o < 32; o <<= 1)
#pragma unroll
                    for (int e = 0; e < 8; e++) acc[e] += __shfl_xor_sync(0xffffffffu, acc[e], o);
                if (lane < 2) {
#pragma unroll
                    for (int e = 0; e < 8; e++) st_mod(sc_->mod + blk * 16 + lane * 8 + e, acc[e], tag);
                }
            }
            if (warp == 9) {
#pragma unroll 1
                for (int st = 1; st <= 2; st++) {
                    bar_sync(7, 160);
                    const uint32_t* src = sc_->mod + (st * 3 - 1) * DM;
                    const int n = st == 1 ? 3 * DM : DM;
#pragma unroll 1
                    for (int i = lane * 4; i < n + 127 - ((n + 127) & 127); i += 128)
                        mod_to_smem(sbase + OFF_MODT + min(i, n - 4) * 4, src + min(i, n - 4), tag);
                    __syncwarp();
                    if (lane == 0) rows_load(sbase, st == 1 ? &maps.rx : &maps.rx2, (mt * 8 + g) * 16);
                    if (st == 1) {
                        bar_sync(7, 160);
                        if (lane == 0) {
                            rows_store(sbase, &maps.rx2, (mt * 8 + g) * 16);
                            rows_store_wait();
                        }
                        __syncwarp();
                        bar_arrive(10, 160);
                    }
                }
            }
        }
    } else {
        uint4 cw = make_uint4(0, 0, 0, 0), w1[5];
        {
            const int t = threadIdx.x;
            if (t < 72 && b < 72) cw = ldg128(reinterpret_cast<const uint4*>(cvec) + t);
            if (t == 96) cw = ld128(reinterpret_cast<const uint4*>(&sc_->epoch[b * 32]));
            const int bw = min(b, 71);
            if (b < 72) {
#pragma unroll
                for (int i = 0; i < 5; i++)
                    w1[i] = ldg128(reinterpret_cast<const uint4*>(wmod + (size_t)min((t >> 1) + 128 * i, DM - 1) * (6 * DM)) +
                                   bw * 2 + (t & 1));
            } else {
#pragma unroll
                for (int i = 0; i < 5; i++) w1[i] = make_uint4(0, 0, 0, 0);
            }
        }
        if (threadIdx.x == 160) SPROF(5);
        asm volatile("setmaxnreg.inc.sync.aligned.u32 240;");
        if (threadIdx.x == 160) SPROF(6);
        const int wg = warp >> 2;
        const int tid = threadIdx.x;
        Ctx cx;
        cx.sbase = sbase;
        cx.wg = wg;
        if (wg == 1) bar_arrive(8, 256);
        cx.rel_cta = (lane == 0 && (warp & 3) < 2) ? (warp & 3) : 2;
        const uint32_t red = sbase + OFF_RED;
        const int own = mt * 8 + g;
        const int wown = mt * 8 + warp;
        PROF(0);
        PROFG(30);
        PROFR(17);
        {
            const int r0 = tid >> 1;
            PROFR(18);
            asm volatile("barrier.cluster.arrive.relaxed.aligned;" ::: "memory");
            if (tid < 72) sts128(sbase + OFF_CVEC + tid * 16, cw.x, cw.y, cw.z, cw.w);
            if (tid == 96) sts128(sbase + OFF_EPOCH, cw.x, cw.y, cw.z, cw.w);
            bar_sync(3, 256);
            PROFR(19);
            float acc[8];
            {
                float sc[5];
#pragma unroll
                for (int i = 0; i < 5; i++) {
                    unsigned short cu;
                    asm volatile("ld.shared.u16 %0, [%1];" : "=h"(cu) : "r"(sbase + OFF_CVEC + min(r0 + 128 * i, DM - 1) * 2));
                    sc[i] = (r0 + 128 * i < DM) ? silu_bf16(cu) : 0.f;
                }
                mod_fma(acc, w1, sc);
            }
            uint4 xw[5];
            {
                const uint4* xs = reinterpret_cast<const uint4*>(maps.x + (size_t)own * 16 * DM);
                if (acc[0] == 1.2345678e-30f && acc[7] == 1.2345678e-30f) xs += 1;
                xs -= (acc[0] == 1.2345678e-30f && acc[7] == 1.2345678e-30f) ? 1 : 0;
                asm volatile("" : "+l"(xs), "+f"(acc[0]), "+f"(acc[7]));
#pragma unroll
                for (int i = 0; i < 5; i++) xw[i] = ldg128(xs + min(tid + 256 * i, 1151));
            }
            PROFR(20);
            if (b < 72) mod_reduce(acc, sc_->mod + b * 16, red + 1024, warp, lane, (get_epoch(sbase) + 1) & 0xffffu);
            PROFR(21);
#pragma unroll
            for (int i = 0; i < 5; i++) {
                const int vi = min(tid + 256 * i, 1151), ln = vi >> 3;
                sts128(sbase + OFF_ROWS + ln * 128 + (((vi & 7) ^ (ln & 7)) << 4), xw[i].x, xw[i].y, xw[i].z, xw[i].w);
            }
            bar_sync(3, 256);
        }

        Ring ring{0u, 0u};
        int stage = 0;
        asm volatile("" : "+r"(stage));
#pragma unroll 1
        for (;; stage++) {
            int tid, lane;
            asm volatile("mov.u32 %0, %%tid.x;" : "=r"(tid));
            lane = tid & 31;
            const uint32_t epoch = get_epoch(sbase);
            {
                float v[36];
                const uint32_t modt = sbase + OFF_MODT + (warp * 16 + (lane & 3) * 2) * 4;
                if (stage == 0) {
#pragma unroll
                    for (int i = 0; i < 36; i++) v[i] = 0.f;
                } else {
                    const uint4* psrc = sc_->part + (size_t)own * 8 * 36 * 32;
                    sum_partials(v, psrc + tid, stage & 1);
                    PROF(stage == 1 ? 8 : 15);
                    sum_tail(v, reinterpret_cast<const uint2*>(psrc + 32 * 32) + tid, stage & 1);
                }
                if (stage) mbar_wait(sbase + OFF_XBAR, stage - 1);
                if (stage == 0) PROFR(22);
                {
                    const float gs = stage == 2 ? 0.5f : 1.f;
                    float gate[18];
                    lds_mod(gate, modt, warp);
                    const int r = lane >> 2;
                    const uint32_t rows = sbase + OFF_ROWS + r * (DM * 2) + (lane & 3) * 4;
#pragma unroll
                    for (int j = 0; j < 9; j++) {
                        const int ch = j < 8 ? (j >> 1) * 2 + (warp >> 2) : 8, c16 = j < 8 ? (warp & 3) * 2 + (j & 1) : warp;
                        const uint32_t ad = rows + ch * 128 + ((c16 ^ ((r + ch) & 7)) << 4);
                        const uint32_t u0 = __float_as_uint(lds32f(ad)), u1 = __float_as_uint(lds32f(ad + 8 * DM * 2));
                        const float g0 = stage ? gate[2 * j] * gs : 0.f, g1 = stage ? gate[2 * j + 1] * gs : 0.f;
                        v[4 * j] = fmaf(g0, v[4 * j], bf_lo(u0));
                        v[4 * j + 1] = fmaf(g1, v[4 * j + 1], bf_hi(u0));
                        v[4 * j + 2] = fmaf(g0, v[4 * j + 2], bf_lo(u1));
                        v[4 * j + 3] = fmaf(g1, v[4 * j + 3], bf_hi(u1));
                        sts32f(ad, __uint_as_float(pack_bf16(v[4 * j], v[4 * j + 1])));
                        sts32f(ad + 8 * DM * 2, __uint_as_float(pack_bf16(v[4 * j + 2], v[4 * j + 3])));
                    }
                    asm volatile("fence.proxy.async.shared::cta;" ::: "memory");
                }
                if (stage == 2) break;
                PROF(stage == 0 ? 1 : 9);
                layernorm_rows(v, red, warp, lane);
                if (stage == 0) PROFR(27);
                if (stage == 0) {
                    const uint32_t tag = (epoch + 1) & 0xffffu;
                    mod_to_smem(sbase + OFF_MODT + (DM + tid * 4) * 4, sc_->mod + tid * 4, tag);
                    if (warp == 7) mod_to_smem(sbase + OFF_MODT + (DM + 1024 + lane * 4) * 4, sc_->mod + 1024 + lane * 4, tag);
                    bar_sync(3, 256);
                    bar_arrive(4, 320);
                }
                float shift[18], scale[18];
                lds_mod(shift, modt + DM * 4, warp);
                lds_mod(scale, modt + 2 * DM * 4, warp);
                if (stage == 0) PROFR(28);
                PROF(stage == 0 ? 2 : 10);
                modulate_store(v, shift, scale, sc_->h[epoch & 1][stage] + (size_t)own * 36 * 32, warp, lane);
                if (stage == 0) asm volatile("barrier.cluster.wait.aligned;" ::: "memory");
            }

            const uint32_t spill = sbase + 8 * SLOT_BYTES + wg * 3 * SLOT_BYTES + (tid & 127) * 16;
            uint32_t a[144];
            PROF(stage == 0 ? 3 : 11);
            {
                const uint4* hsrc = sc_->h[epoch & 1][stage] + (size_t)wown * 36 * 32 + lane;
                poll_tail(a, reinterpret_cast<const uint2*>(hsrc - lane + 32 * 32) + lane);
                PROF(stage == 0 ? 4 : 12);
                if (stage == 1) PROFG(25);
                TG(stage * 32 + 30);
                if (wg == 1) bar_sync(5, 256);
                poll_frags<0, 32>(a, hsrc, wg == 0);
            }
            uint4* hhbuf = sc_->hh + (size_t)b * 8 * 256 + tid;
            float d[64];
#pragma unroll 1
            for (int ch = 0;; ch++) {
                TG(stage * 32 + ch * 2);
                gemm_n128(d, a, cx, ring, true);
                TG(stage * 32 + ch * 2 + 1);
                if (stage == 0) {
#pragma unroll
                    for (int i = 0; i < 64; i++) d[i] *= SM_SCALE;
                    if (ch == 3) break;
#pragma unroll
                    for (int v = 0; v < 8; v++)
                        sts128(spill + (ch * 8 + v) * 2048, pack_bf16(d[8 * v], d[8 * v + 1]),
                               pack_bf16(d[8 * v + 2], d[8 * v + 3]), pack_bf16(d[8 * v + 4], d[8 * v + 5]),
                               pack_bf16(d[8 * v + 6], d[8 * v + 7]));
                } else {
#pragma unroll
                    for (int i = 0; i < 32; i++) {
                        const float gv = d[i], gu = gv * d[32 + i];
                        const float z = gv * fmaf(gv * gv, 0.7978845608028654f * 0.044715f, 0.7978845608028654f);
                        d[i] = fmaf(gu, tanh_fast(z), gu);
                    }
                    if (ch == 8) break;
                    if (wg == 0) {
                        if (ch == 0) bar_arrive(7, 160);
                        if (ch == 2) bar_sync(10, 160);
                    }
#pragma unroll
                    for (int v = 0; v < 4; v++) {
                        const uint4 h4 = make_uint4(pack_bf16(d[8 * v], d[8 * v + 1]), pack_bf16(d[8 * v + 2], d[8 * v + 3]),
                                                    pack_bf16(d[8 * v + 4], d[8 * v + 5]), pack_bf16(d[8 * v + 6], d[8 * v + 7]));
                        if (ch < 2)
                            __stcg(hhbuf + (ch * 4 + v) * 256, h4);
                        else
                            sts128(spill + ((ch - 2) * 4 + v) * 2048, h4.x, h4.y, h4.z, h4.w);
                    }
                }
            }
            if (stage == 0) {
                uint32_t q[32];
#pragma unroll
                for (int i = 0; i < 32; i++) q[i] = pack_bf16(d[2 * i], d[2 * i + 1]);
                PROF(5);
                PROFG(23);
                if (wg == 0) bar_arrive(6, 160);
                {
                    float o[64], sa[32], sb[32];
                    uint32_t pa[16], pb[16];
#pragma unroll
                    for (int i = 0; i < 64; i++) o[i] = 0.f;
                    float n0 = 0.f, n1 = 0.f, l0 = 1.f, l1 = 1.f;
                    bool shifted = false;
                    const uint64_t dbase = desc_of(sbase);
                    const uint64_t dbk = dbase - (511u << 16);
                    const int my_bar = 1 + wg, other_bar = 2 - wg;

                    auto softmax_a = [&](bool first, float& s0, float& s1) {
                        if (first) {
                            shifted = false;
                            n0 = n1 = 0.f;
                            l0 = l1 = 0.f;
                        }
                        if (shifted)
                            exp_step<true>(sa, pa, n0, n1, s0, s1);
                        else
                            exp_step<false>(sa, pa, n0, n1, s0, s1);
                    };
                    auto softmax_b = [&](bool first, float s0, float s1) {
                        float u0, u1;
                        if (shifted)
                            exp_step<true>(sb, pb, n0, n1, u0, u1);
                        else
                            exp_step<false>(sb, pb, n0, n1, u0, u1);
                        s0 += u0;
                        s1 += u1;
                        bool bad = !(fmaxf(s0, s1) <= SM_HI);
                        if (first) {
                            float r0 = s0 + __shfl_xor_sync(0xffffffffu, s0, 1), r1 = s1 + __shfl_xor_sync(0xffffffffu, s1, 1);
                            r0 += __shfl_xor_sync(0xffffffffu, r0, 2);
                            r1 += __shfl_xor_sync(0xffffffffu, r1, 2);
                            bad = bad || !(fminf(r0, r1) >= SM_LO);
                        }
                        if (__any_sync(0xffffffffu, bad)) {
                            float x0, x1;
                            row_max(sa, sb, x0, x1);
                            x0 = -x0;
                            x1 = -x1;
                            if (!first) {
                                x0 = fminf(x0, n0);
                                x1 = fminf(x1, n1);
                                const float al0 = ex2(x0 - n0), al1 = ex2(x1 - n1);
                                l0 *= al0;
                                l1 *= al1;
#pragma unroll
                                for (int i = 0; i < 16; i++) {
                                    o[4 * i] *= al0;
                                    o[4 * i + 1] *= al0;
                                    o[4 * i + 2] *= al1;
                                    o[4 * i + 3] *= al1;
                                }
                            }
                            n0 = x0;
                            n1 = x1;
                            shifted = true;
                            exp_step<true>(sa, pa, n0, n1, s0, s1);
                            exp_step<true>(sb, pb, n0, n1, u0, u1);
                            s0 += u0;
                            s1 += u1;
                        }
                        l0 += s0;
                        l1 += s1;
                    };

                    cx.wait_full(4, 0);
                    if (wg == 1) bar_sync(my_bar, 256);
                    wg_fence();
                    qk_step(sa, q, dbk + 4 * 1024);
                    qk_step(sb, q, dbk + 5 * 1024);
                    wg_commit();
                    bar_arrive(other_bar, 256);
                    wg_wait<0>();
                    pin(sa);
                    pin(sb);
                    cx.release(4);
                    cx.wait_full(6, 0);
                    {
                        float s0, s1;
                        softmax_a(true, s0, s1);
                        softmax_b(true, s0, s1);
                    }
                    uint32_t alo = (uint32_t)dbase + 6 * 1024, blo = (uint32_t)dbase;
                    const uint32_t dhi = (uint32_t)(dbase >> 32);
#pragma unroll 1
                    for (int t = 1; t < 64; t++) {
                        const int j = t & 15;
                        const uint32_t sA = 2 + 4 * (t & 1), sB = 4 - 4 * (t & 1);
                        const uint64_t da = ((uint64_t)dhi << 32) | alo, db = ((uint64_t)dhi << 32) | blo;
                        TL(0);
                        bar_sync(my_bar, 256);
                        TL(2);
                        wg_fence();
                        pv_step(o, pa, da + 1024, j != 1);
                        qk_step(sa, q, da - (511u << 16));
                        wg_commit();
                        cx.wait_full(sB, ((36 + 4 * t) >> 3) & 1);
                        wg_fence();
                        qk_step(sb, q, db - (511u << 16));
                        pv_step(o, pb, db + 1024, 1);
                        wg_commit();
                        bar_arrive(other_bar, 256);
                        alo ^= 4096;
                        blo ^= 4096;
                        asm volatile("" : "+r"(alo), "+r"(blo));
                        TL(3);
                        wg_wait<1>();
                        pin(sa);
                        pin(pa);
                        TL(4);
                        cx.release(sA);
                        const float lp0 = l0, lp1 = l1;
                        float s0, s1;
                        softmax_a(j == 0, s0, s1);
                        TL(5);
                        wg_wait<0>();
                        pin(o);
                        pin(sb);
                        pin(pb);
                        TL(6);
                        cx.release(sB);
                        if (j == 0) {
                            float i0, i1;
                            inv_row_sums(lp0, lp1, i0, i1);
                            const uint32_t dst = spill + ((t >> 4) - 1) * 16384;
#pragma unroll
                            for (int v = 0; v < 8; v++)
                                sts128(dst + v * 2048, pack_bf16(o[8 * v] * i0, o[8 * v + 1] * i0),
                                       pack_bf16(o[8 * v + 2] * i1, o[8 * v + 3] * i1),
                                       pack_bf16(o[8 * v + 4] * i0, o[8 * v + 5] * i0),
                                       pack_bf16(o[8 * v + 6] * i1, o[8 * v + 7] * i1));
                        }
                        const uint32_t bn = sbase + OFF_FULL + (8 - sA) * 8, pn = ((38 + 4 * t) >> 3) & 1;
                        const bool okn = mbar_try(bn, pn);
                        TL(1);
                        softmax_b(j == 0, s0, s1);
                        if (!okn || j == 15) {
                            mbar_wait(bn, pn);
                            if (j == 15 && t < 63) {
                                const uint32_t src = spill + (t >> 4) * 16384;
#pragma unroll
                                for (int v = 0; v < 8; v++)
                                    lds128(src + v * 2048, q[4 * v], q[4 * v + 1], q[4 * v + 2], q[4 * v + 3]);
                            }
                        }
                        TL(7);
                    }
                    bar_sync(my_bar, 256);
                    wg_fence();
                    pv_step(o, pa, dbase + 2 * 1024, 1);
                    pv_step(o, pb, dbase + 3 * 1024, 1);
                    wg_commit();
                    if (wg == 0) bar_arrive(other_bar, 256);
                    float i0, i1;
                    inv_row_sums(l0, l1, i0, i1);
                    wg_wait<0>();
                    pin(o);
                    cx.release(2);
#pragma unroll
                    for (int i = 0; i < 16; i++) {
                        a[96 + 2 * i] = pack_bf16(o[4 * i] * i0, o[4 * i + 1] * i0);
                        a[96 + 2 * i + 1] = pack_bf16(o[4 * i + 2] * i1, o[4 * i + 3] * i1);
                    }
#pragma unroll
                    for (int i = 128; i < 144; i++) a[i] = 0;
                }
                ring.slot = 4;
                ring.phase = 0;
                PROF(6);
                PROFG(24);
            } else {
#pragma unroll
                for (int v = 0; v < 8; v++) {
                    const uint4 t = __ldcg(hhbuf + v * 256);
                    a[112 + 4 * v] = t.x;
                    a[113 + 4 * v] = t.y;
                    a[114 + 4 * v] = t.z;
                    a[115 + 4 * v] = t.w;
                }
#pragma unroll
                for (int i = 0; i < 16; i++) a[96 + i] = pack_bf16(d[2 * i], d[2 * i + 1]);
                PROF(13);
            }
#pragma unroll
            for (int v = 0; v < 24; v++) lds128(spill + v * 2048, a[4 * v], a[4 * v + 1], a[4 * v + 2], a[4 * v + 3]);

            {
                uint4* dst = sc_->part + ((size_t)wown * 8 + g) * 36 * 32 + lane;
                const uint32_t ptag = (stage + 1) & 1;
#pragma unroll 1
                for (int p = 0; p < 4; p++) {
                    TG(stage * 32 + 18 + p * 2);
                    gemm_n128(d, a, cx, ring, stage != 0);
                    TG(stage * 32 + 19 + p * 2);
#pragma unroll
                    for (int u = 0; u < 8; u++)
                        st128(dst + (p * 8 + u) * 32, (pack_bf16(d[8 * u], d[8 * u + 1]) & ~1u) | ptag,
                              pack_bf16(d[8 * u + 2], d[8 * u + 3]), pack_bf16(d[8 * u + 4], d[8 * u + 5]),
                              pack_bf16(d[8 * u + 6], d[8 * u + 7]));
                    if (p == 0 && wg == 0) bar_arrive(7, 160);
                }
                float e[32];
                TG(stage * 32 + 26);
                gemm_n64(e, a, cx, ring, stage != 0);
                TG(stage * 32 + 27);
                uint2* dst2 = reinterpret_cast<uint2*>(dst - lane + 32 * 32) + lane;
#pragma unroll
                for (int j = 0; j < 8; j++)
                    st64(dst2 + j * 32, (pack_bf16(e[4 * j], e[4 * j + 1]) & ~1u) | ptag, pack_bf16(e[4 * j + 2], e[4 * j + 3]));
            }
            PROF(stage == 0 ? 7 : 14);
            if (stage == 1) {
                PROFG(26);
                asm volatile("barrier.cluster.arrive.relaxed.aligned;" ::: "memory");
            }
        }
        if (wg == 0) bar_sync(8, 256);
        bar_sync(3, 256);
        if (tid == 32) sc_->epoch[b * 32] = get_epoch(sbase) + 1;
        if (tid == 0) {
            rows_store(sbase, &maps.rout, own * 16);
            rows_store_wait();
        }
        __syncwarp();
        PROF(16);
        PROFG(31);
        asm volatile("barrier.cluster.wait.aligned;" ::: "memory");
    }
}

typedef CUresult (*EncodeFn)(CUtensorMap*, CUtensorMapDataType, cuuint32_t, void*, const cuuint64_t*, const cuuint64_t*,
                             const cuuint32_t*, const cuuint32_t*, CUtensorMapInterleave, CUtensorMapSwizzle,
                             CUtensorMapL2promotion, CUtensorMapFloatOOBfill);

void make_map(EncodeFn enc, CUtensorMap* m, const void* ptr, uint64_t rows, uint64_t cols, bool narrow = false) {
    cuuint64_t gdim[2] = {cols, rows};
    cuuint64_t gstr[1] = {cols * 2};
    cuuint32_t box[2] = {narrow ? 16u : 64u, narrow ? 192u : 64u};
    cuuint32_t estr[2] = {1, 1};
    enc(m, CU_TENSOR_MAP_DATA_TYPE_BFLOAT16, 2, const_cast<void*>(ptr), gdim, gstr, box, estr,
        CU_TENSOR_MAP_INTERLEAVE_NONE, narrow ? CU_TENSOR_MAP_SWIZZLE_NONE : CU_TENSOR_MAP_SWIZZLE_128B,
        CU_TENSOR_MAP_L2_PROMOTION_L2_128B,
        CU_TENSOR_MAP_FLOAT_OOB_FILL_NONE);
}

void make_rows_map(EncodeFn enc, CUtensorMap* m, const void* ptr) {
    cuuint64_t gdim[3] = {64, 9, 2048};
    cuuint64_t gstr[2] = {128, DM * 2};
    cuuint32_t box[3] = {64, 9, 16};
    cuuint32_t estr[3] = {1, 1, 1};
    enc(m, CU_TENSOR_MAP_DATA_TYPE_BFLOAT16, 3, const_cast<void*>(ptr), gdim, gstr, box, estr,
        CU_TENSOR_MAP_INTERLEAVE_NONE, CU_TENSOR_MAP_SWIZZLE_128B, CU_TENSOR_MAP_L2_PROMOTION_L2_128B,
        CU_TENSOR_MAP_FLOAT_OOB_FILL_NONE);
}

}

extern "C" void kernel_launch(void* const* d_in, const int* in_sizes, int n_in, void* d_out, int out_size) {
    (void)in_sizes;
    (void)n_in;
    (void)out_size;
    void* fn = nullptr;
    cudaDriverEntryPointQueryResult qr;
    cudaGetDriverEntryPoint("cuTensorMapEncodeTiled", &fn, cudaEnableDefault, &qr);
    EncodeFn enc = (EncodeFn)fn;
    Params maps;
    maps.x = (const __nv_bfloat16*)d_in[0];
    maps.cvec = (const __nv_bfloat16*)d_in[9];
    maps.wmod = (const __nv_bfloat16*)d_in[10];
    maps.kc = (const __nv_bfloat16*)d_in[1];
    maps.vc = (const __nv_bfloat16*)d_in[2];
    maps.wq_p = (const __nv_bfloat16*)d_in[3];
    maps.wo_p = (const __nv_bfloat16*)d_in[4];
    maps.wg_p = (const __nv_bfloat16*)d_in[6];
    maps.wu_p = (const __nv_bfloat16*)d_in[7];
    maps.wd_p = (const __nv_bfloat16*)d_in[8];
    maps.out = (__nv_bfloat16*)d_out;
    void* scp = nullptr;
    cudaGetSymbolAddress(&scp, g_scratch);
    maps.sc = (Scratch*)scp;
    make_map(enc, &maps.k, d_in[1], 32 * 2048, 128);
    make_map(enc, &maps.v, d_in[2], 32 * 2048, 128);
    make_map(enc, &maps.wq, d_in[3], 576, 4096);
    make_map(enc, &maps.wo, d_in[4], 4096, 576);
    make_map(enc, &maps.wg, d_in[6], 576, 4608);
    make_map(enc, &maps.wu, d_in[7], 576, 4608);
    make_map(enc, &maps.wd, d_in[8], 4608, 576);
    make_rows_map(enc, &maps.rx, d_in[0]);
    make_rows_map(enc, &maps.rx2, (char*)scp + offsetof(Scratch, x2));
    make_rows_map(enc, &maps.rout, d_out);
    cudaFuncSetAttribute(fused_block_kernel, cudaFuncAttributeMaxDynamicSharedMemorySize, SMEM_BYTES);
    fused_block_kernel<<<128, 384, SMEM_BYTES>>>(maps);
}
```

```cpp
#include <cuda_runtime.h>
#include <cuda_bf16.h>
#include <cuda.h>
#include <stdint.h>
#include <stddef.h>

namespace {

constexpr int DM = 576;
constexpr int SLOT_BYTES = 16384;
constexpr int BOX_BYTES = 8192;
constexpr int NUNITS = 14;
constexpr int SMEM_TAIL = NUNITS * SLOT_BYTES;
constexpr int SMEM_BYTES = SMEM_TAIL + 2048 + 1024;
constexpr int OFF_FULL = SMEM_TAIL;
constexpr int OFF_EMPTY = SMEM_TAIL + 64;
constexpr int OFF_RED = SMEM_TAIL + 128;

constexpr int KV_AHEAD = 16;
#define GATE_SLOT 4
constexpr int OFF_XBAR = SMEM_TAIL + 1792;
constexpr int OFF_ROWS = 8 * SLOT_BYTES;
constexpr int OFF_MODT = OFF_ROWS + 20480;
constexpr int OFF_EPOCH = SMEM_TAIL + 1808;
constexpr int OFF_MRED = OFF_ROWS + 28672;

struct Scratch {
    unsigned epoch[128 * 32];
    uint32_t mod[6 * DM];
    uint32_t modp[6][2 * DM];
    uint4 h[2][2][128 * 36 * 32];
    uint4 part[128 * 8 * 36 * 32];
    uint4 hh[128 * 8 * 256];
    __nv_bfloat16 x2[2048 * DM];
};
__device__ Scratch g_scratch;

#define TG(i)
#define TL(i)
#define PROFR(i)
#define PROF(i)
#define PROFG(i)

struct Params {
    const __nv_bfloat16 *x, *cvec, *wmod, *kc, *vc, *wq_p, *wo_p, *wg_p, *wu_p, *wd_p;
    __nv_bfloat16* out;
    Scratch* sc;
    CUtensorMap k, v, wq, wo, wg, wu, wd, rx, rx2, rout;
};

__device__ __forceinline__ uint32_t smem_u32(const void* p) { return (uint32_t)__cvta_generic_to_shared(p); }
__device__ __forceinline__ void mbar_init(uint32_t a, uint32_t c) {
    asm volatile("mbarrier.init.shared::cta.b64 [%0], %1;" ::"r"(a), "r"(c) : "memory");
}
__device__ __forceinline__ void mbar_expect_tx(uint32_t a, uint32_t bytes) {
    asm volatile("mbarrier.arrive.expect_tx.shared::cta.b64 _, [%0], %1;" ::"r"(a), "r"(bytes) : "memory");
}
__device__ __forceinline__ bool mbar_try(uint32_t a, uint32_t ph) {
    uint32_t ok;
    asm volatile(
        "{\n.reg .pred p;\nmbarrier.try_wait.parity.shared::cta.b64 p, [%1], %2;\nselp.u32 %0, 1, 0, p;\n}"
        : "=r"(ok)
        : "r"(a), "r"(ph)
        : "memory");
    return ok != 0;
}
__device__ __forceinline__ uint32_t clk32() {
    uint32_t c;
    asm volatile("mov.u32 %0, %%clock;" : "=r"(c));
    return c;
}
constexpr uint32_t WAIT_LIMIT = 1u << 30;
__device__ __forceinline__ void mbar_wait(uint32_t a, uint32_t ph) {
    if (mbar_try(a, ph)) return;
    uint32_t t0 = clk32();
    while (!mbar_try(a, ph)) {
        if (clk32() - t0 > WAIT_LIMIT) break;
    }
}
__device__ __forceinline__ void mbar_arrive_cluster(uint32_t a, uint32_t cta) {
    asm volatile(
        "{\n.reg .b32 ra;\nmapa.shared::cluster.u32 ra, %0, %1;\nmbarrier.arrive.shared::cluster.b64 _, [ra];\n}" ::"r"(a),
        "r"(cta)
        : "memory");
}
__device__ __forceinline__ void tma_mc(uint32_t dst, const CUtensorMap* m, int c0, int c1, uint32_t bar) {
    asm volatile(
        "cp.async.bulk.tensor.2d.shared::cluster.global.mbarrier::complete_tx::bytes.multicast::cluster"
        " [%0], [%1, {%3, %4}], [%2], %5;" ::"r"(dst),
        "l"(m), "r"(bar), "r"(c0), "r"(c1), "h"((uint16_t)3)
        : "memory");
}
__device__ __forceinline__ void bulk_load(uint32_t dst, const void* src, uint32_t bytes, uint32_t bar) {
    asm volatile("cp.async.bulk.shared::cluster.global.mbarrier::complete_tx::bytes [%0], [%1], %2, [%3];" ::"r"(dst),
                 "l"(src), "r"(bytes), "r"(bar)
                 : "memory");
}
__device__ __forceinline__ void l2_prefetch(const void* p, uint32_t bytes) {
    asm volatile("cp.async.bulk.prefetch.L2.global [%0], %1;" ::"l"(p), "r"(bytes) : "memory");
}
__device__ __forceinline__ void bar_sync(int id, int n) { asm volatile("bar.sync %0, %1;" ::"r"(id), "r"(n) : "memory"); }
__device__ __forceinline__ void bar_arrive(int id, int n) {
    asm volatile("bar.arrive %0, %1;" ::"r"(id), "r"(n) : "memory");
}
__device__ __forceinline__ void wg_fence() { asm volatile("wgmma.fence.sync.aligned;" ::: "memory"); }
__device__ __forceinline__ void wg_commit() { asm volatile("wgmma.commit_group.sync.aligned;" ::: "memory"); }
template <int N>
__device__ __forceinline__ void wg_wait() {
    asm volatile("wgmma.wait_group.sync.aligned %0;" ::"n"(N) : "memory");
}
template <int N>
__device__ __forceinline__ void pin(float (&d)[N]) {
#pragma unroll
    for (int i = 0; i < N; i++) asm volatile("" : "+f"(d[i])::"memory");
}
template <int N>
__device__ __forceinline__ void pin(uint32_t (&d)[N]) {
#pragma unroll
    for (int i = 0; i < N; i++) asm volatile("" : "+r"(d[i])::"memory");
}
__device__ __forceinline__ uint32_t pack_bf16(float lo, float hi) {
    uint32_t r;
    asm("cvt.rn.bf16x2.f32 %0, %1, %2;" : "=r"(r) : "f"(hi), "f"(lo));
    return r;
}
__device__ __forceinline__ float bf_lo(uint32_t v) { return __uint_as_float(v << 16); }
__device__ __forceinline__ float bf_hi(uint32_t v) { return __uint_as_float(v & 0xffff0000u); }
__device__ __forceinline__ float round_bf16(float v) { return __bfloat162float(__float2bfloat16_rn(v)); }
__device__ __forceinline__ float ex2(float x) {
    float y;
    asm("ex2.approx.ftz.f32 %0, %1;" : "=f"(y) : "f"(x));
    return y;
}
__device__ __forceinline__ float rcp(float x) {
    float y;
    asm("rcp.approx.ftz.f32 %0, %1;" : "=f"(y) : "f"(x));
    return y;
}
__device__ __forceinline__ float tanh_fast(float x) {
    float y;
    asm("tanh.approx.f32 %0, %1;" : "=f"(y) : "f"(x));
    return y;
}
__device__ __forceinline__ void sts128(uint32_t a, uint32_t x, uint32_t y, uint32_t z, uint32_t w) {
    asm volatile("st.shared.v4.b32 [%0], {%1,%2,%3,%4};" ::"r"(a), "r"(x), "r"(y), "r"(z), "r"(w) : "memory");
}
__device__ __forceinline__ void lds128(uint32_t a, uint32_t& x, uint32_t& y, uint32_t& z, uint32_t& w) {
    asm volatile("ld.shared.v4.b32 {%0,%1,%2,%3}, [%4];" : "=r"(x), "=r"(y), "=r"(z), "=r"(w) : "r"(a) : "memory");
}
__device__ __forceinline__ void sts32f(uint32_t a, float v) {
    asm volatile("st.shared.f32 [%0], %1;" ::"r"(a), "f"(v) : "memory");
}
__device__ __forceinline__ float lds32f(uint32_t a) {
    float v;
    asm volatile("ld.shared.f32 %0, [%1];" : "=f"(v) : "r"(a) : "memory");
    return v;
}
#define F8(d, b) \
    "+f"(d[b]), "+f"(d[b + 1]), "+f"(d[b + 2]), "+f"(d[b + 3]), "+f"(d[b + 4]), "+f"(d[b + 5]), "+f"(d[b + 6]), "+f"(d[b + 7])

template <int TB>
__device__ __forceinline__ void wgmma_n128(float (&d)[64], uint32_t a0, uint32_t a1, uint32_t a2, uint32_t a3,
                                           uint64_t db, int sc) {
    asm volatile(
        "{\n.reg .pred p;\nsetp.ne.b32 p, %69, 0;\n"
        "wgmma.mma_async.sync.aligned.m64n128k16.f32.bf16.bf16 "
        "{%0,%1,%2,%3,%4,%5,%6,%7,%8,%9,%10,%11,%12,%13,%14,%15,%16,%17,%18,%19,%20,%21,%22,%23,%24,%25,%26,%27,%28,%29,%30,%31,"
        "%32,%33,%34,%35,%36,%37,%38,%39,%40,%41,%42,%43,%44,%45,%46,%47,%48,%49,%50,%51,%52,%53,%54,%55,%56,%57,%58,%59,%60,%61,%62,%63},"
        "{%64,%65,%66,%67}, %68, p, 1, 1, %70;\n}"
        : F8(d, 0), F8(d, 8), F8(d, 16), F8(d, 24), F8(d, 32), F8(d, 40), F8(d, 48), F8(d, 56)
        : "r"(a0), "r"(a1), "r"(a2), "r"(a3), "l"(db), "r"(sc), "n"(TB));
}
#define O8(d, b) \
    "=f"(d[b]), "=f"(d[b + 1]), "=f"(d[b + 2]), "=f"(d[b + 3]), "=f"(d[b + 4]), "=f"(d[b + 5]), "=f"(d[b + 6]), "=f"(d[b + 7])
template <int TB>
__device__ __forceinline__ void wgmma_n128_z(float (&d)[64], uint32_t a0, uint32_t a1, uint32_t a2, uint32_t a3,
                                             uint64_t db) {
    asm volatile(
        "wgmma.mma_async.sync.aligned.m64n128k16.f32.bf16.bf16 "
        "{%0,%1,%2,%3,%4,%5,%6,%7,%8,%9,%10,%11,%12,%13,%14,%15,%16,%17,%18,%19,%20,%21,%22,%23,%24,%25,%26,%27,%28,%29,%30,%31,"
        "%32,%33,%34,%35,%36,%37,%38,%39,%40,%41,%42,%43,%44,%45,%46,%47,%48,%49,%50,%51,%52,%53,%54,%55,%56,%57,%58,%59,%60,%61,%62,%63},"
        "{%64,%65,%66,%67}, %68, 0, 1, 1, %69;"
        : O8(d, 0), O8(d, 8), O8(d, 16), O8(d, 24), O8(d, 32), O8(d, 40), O8(d, 48), O8(d, 56)
        : "r"(a0), "r"(a1), "r"(a2), "r"(a3), "l"(db), "n"(TB));
}
template <int TB>
__device__ __forceinline__ void wgmma_n64_z(float (&d)[32], uint32_t a0, uint32_t a1, uint32_t a2, uint32_t a3,
                                            uint64_t db) {
    asm volatile(
        "wgmma.mma_async.sync.aligned.m64n64k16.f32.bf16.bf16 "
        "{%0,%1,%2,%3,%4,%5,%6,%7,%8,%9,%10,%11,%12,%13,%14,%15,%16,%17,%18,%19,%20,%21,%22,%23,%24,%25,%26,%27,%28,%29,%30,%31},"
        "{%32,%33,%34,%35}, %36, 0, 1, 1, %37;"
        : O8(d, 0), O8(d, 8), O8(d, 16), O8(d, 24)
        : "r"(a0), "r"(a1), "r"(a2), "r"(a3), "l"(db), "n"(TB));
}
template <int TB>
__device__ __forceinline__ void wgmma_n64(float (&d)[32], uint32_t a0, uint32_t a1, uint32_t a2, uint32_t a3,
                                          uint64_t db) {
    asm volatile(
        "wgmma.mma_async.sync.aligned.m64n64k16.f32.bf16.bf16 "
        "{%0,%1,%2,%3,%4,%5,%6,%7,%8,%9,%10,%11,%12,%13,%14,%15,%16,%17,%18,%19,%20,%21,%22,%23,%24,%25,%26,%27,%28,%29,%30,%31},"
        "{%32,%33,%34,%35}, %36, 1, 1, 1, %37;"
        : F8(d, 0), F8(d, 8), F8(d, 16), F8(d, 24)
        : "r"(a0), "r"(a1), "r"(a2), "r"(a3), "l"(db), "n"(TB));
}

__device__ __forceinline__ uint64_t desc_of(uint32_t saddr) {
    return (uint64_t)(((saddr >> 4) & 0x3FFFu) | (512u << 16)) | ((uint64_t)(64u | (1u << 30)) << 32);
}

struct Ring {
    uint32_t slot;
    uint32_t phase;
    __device__ __forceinline__ void next() {
        if (++slot == 8) {
            slot = 0;
            phase ^= 1;
        }
    }
};

struct Ctx {
    uint32_t sbase;
    int wg;
    uint32_t rel_cta;
    __device__ __forceinline__ void wait_full(uint32_t slot, uint32_t phase) const {
        mbar_wait(sbase + OFF_FULL + slot * 8, phase);
    }
    __device__ __forceinline__ void release(uint32_t slot) const {
        if (rel_cta < 2) mbar_arrive_cluster(sbase + OFF_EMPTY + slot * 8, rel_cta);
    }
};

__device__ __forceinline__ void gemm_n128(float (&d)[64], const uint32_t (&a)[144], const Ctx& c, Ring& r, bool nine) {
    uint32_t prev = 0;
#pragma unroll
    for (int s = 0; s < 9; s++) {
        if (s < 8 || nine) {
            if (s == GATE_SLOT) bar_sync(8 + c.wg, 256);
            c.wait_full(r.slot, r.phase);
            uint64_t db = desc_of(c.sbase + r.slot * SLOT_BYTES);
            wg_fence();
#pragma unroll
            for (int k = 0; k < 4; k++) {
                if ((s | k) == 0)
                    wgmma_n128_z<1>(d, a[0], a[1], a[2], a[3], db);
                else
                    wgmma_n128<1>(d, a[s * 16 + k * 4], a[s * 16 + k * 4 + 1], a[s * 16 + k * 4 + 2],
                                  a[s * 16 + k * 4 + 3], db + k * 128, 1);
            }
            wg_commit();
            if (s == 8 || (s == 7 && !nine)) bar_arrive(9 - c.wg, 256);
            if (s > 0) {
                wg_wait<1>();
                c.release(prev);
            }
            prev = r.slot;
            r.next();
        }
    }
    wg_wait<0>();
    c.release(prev);
    pin(d);
}
__device__ __forceinline__ void gemm_n64(float (&d)[32], const uint32_t (&a)[144], const Ctx& c, Ring& r, bool nine) {
    uint32_t prev = 0;
#pragma unroll
    for (int s = 0; s < 5; s++) {
        if (s < 4 || nine) {
            c.wait_full(r.slot, r.phase);
            uint64_t db = desc_of(c.sbase + r.slot * SLOT_BYTES);
            wg_fence();
#pragma unroll
            for (int k = 0; k < 8; k++) {
                if ((s | k) == 0)
                    wgmma_n64_z<1>(d, a[0], a[1], a[2], a[3], db);
                else if (s * 8 + k < 36)
                    wgmma_n64<1>(d, a[s * 32 + k * 4], a[s * 32 + k * 4 + 1], a[s * 32 + k * 4 + 2],
                                 a[s * 32 + k * 4 + 3], db + k * 128);
            }
            wg_commit();
            if (s > 0) {
                wg_wait<1>();
                c.release(prev);
            }
            prev = r.slot;
            r.next();
        }
    }
    wg_wait<0>();
    c.release(prev);
    pin(d);
}
__device__ __forceinline__ void st128(uint4* p, uint32_t x, uint32_t y, uint32_t z, uint32_t w) {
    asm volatile(
        "{\n.reg .b64 lo, hi;\n.reg .b128 t;\nmov.b64 lo, {%1, %2};\nmov.b64 hi, {%3, %4};\nmov.b128 t, {lo, hi};\n"
        "st.relaxed.gpu.global.b128 [%0], t;\n}" ::"l"(p),
        "r"(x), "r"(y), "r"(z), "r"(w)
        : "memory");
}
__device__ __forceinline__ uint4 ld128(const uint4* p) {
    uint4 r;
    asm volatile(
        "{\n.reg .b64 lo, hi;\n.reg .b128 t;\nld.relaxed.gpu.global.b128 t, [%4];\nmov.b128 {lo, hi}, t;\n"
        "mov.b64 {%0, %1}, lo;\nmov.b64 {%2, %3}, hi;\n}"
        : "=r"(r.x), "=r"(r.y), "=r"(r.z), "=r"(r.w)
        : "l"(p));
    return r;
}
__device__ __forceinline__ uint4 ldg128(const uint4* p) {
    uint4 r;
    asm volatile("ld.global.nc.v4.u32 {%0,%1,%2,%3}, [%4];" : "=r"(r.x), "=r"(r.y), "=r"(r.z), "=r"(r.w) : "l"(p));
    return r;
}
__device__ __forceinline__ void st64(void* p, uint32_t x, uint32_t y) {
    asm volatile("{\n.reg .b64 t;\nmov.b64 t, {%1, %2};\nst.relaxed.gpu.global.b64 [%0], t;\n}" ::"l"(p), "r"(x), "r"(y)
                 : "memory");
}
__device__ __forceinline__ uint2 ld64(const void* p) {
    uint2 r;
    asm volatile("{\n.reg .b64 t;\nld.relaxed.gpu.global.b64 t, [%2];\nmov.b64 {%0, %1}, t;\n}"
                 : "=r"(r.x), "=r"(r.y)
                 : "l"(p));
    return r;
}
__device__ __forceinline__ void rows_load(uint32_t sbase, const CUtensorMap* m, int row0) {
    mbar_expect_tx(sbase + OFF_XBAR, 16 * DM * 2);
    asm volatile(
        "cp.async.bulk.tensor.3d.shared::cluster.global.mbarrier::complete_tx::bytes [%0], [%1, {%3, %3, %4}], [%2];" ::"r"(
            sbase + OFF_ROWS),
        "l"(m), "r"(sbase + OFF_XBAR), "r"(0), "r"(row0)
        : "memory");
}
__device__ __forceinline__ void rows_store(uint32_t sbase, const CUtensorMap* m, int row0) {
    asm volatile("cp.async.bulk.tensor.3d.global.shared::cta.bulk_group [%0, {%2, %2, %3}], [%1];" ::"l"(m),
                 "r"(sbase + OFF_ROWS), "r"(0), "r"(row0)
                 : "memory");
    asm volatile("cp.async.bulk.commit_group;" ::: "memory");
}
__device__ __forceinline__ void rows_store_wait() { asm volatile("cp.async.bulk.wait_group 0;" ::: "memory"); }

__device__ __forceinline__ constexpr int own_col(int j) { return j < 8 ? (j >> 1) * 128 + (j & 1) * 8 : 512; }
__device__ __forceinline__ void row_reduce(float& s0, float& s1, uint32_t red, int warp, int lane) {
    s0 += __shfl_xor_sync(0xffffffffu, s0, 1);
    s1 += __shfl_xor_sync(0xffffffffu, s1, 1);
    s0 += __shfl_xor_sync(0xffffffffu, s0, 2);
    s1 += __shfl_xor_sync(0xffffffffu, s1, 2);
    if ((lane & 3) == 0) {
        sts32f(red + (warp * 16 + (lane >> 2)) * 4, s0);
        sts32f(red + (warp * 16 + 8 + (lane >> 2)) * 4, s1);
    }
    bar_sync(3, 256);
    s0 = 0.f;
    s1 = 0.f;
#pragma unroll
    for (int w = 0; w < 8; w++) {
        s0 += lds32f(red + (w * 16 + (lane >> 2)) * 4);
        s1 += lds32f(red + (w * 16 + 8 + (lane >> 2)) * 4);
    }
}
__device__ __forceinline__ void layernorm_rows(float (&v)[36], uint32_t red, int warp, int lane) {
    float s0 = 0.f, s1 = 0.f;
#pragma unroll
    for (int j = 0; j < 9; j++) {
        s0 += v[4 * j] + v[4 * j + 1];
        s1 += v[4 * j + 2] + v[4 * j + 3];
    }
    row_reduce(s0, s1, red, warp, lane);
    const float m0 = s0 * (1.f / DM), m1 = s1 * (1.f / DM);
    s0 = 0.f;
    s1 = 0.f;
#pragma unroll
    for (int j = 0; j < 9; j++) {
        v[4 * j] -= m0;
        v[4 * j + 1] -= m0;
        v[4 * j + 2] -= m1;
        v[4 * j + 3] -= m1;
        s0 += v[4 * j] * v[4 * j] + v[4 * j + 1] * v[4 * j + 1];
        s1 += v[4 * j + 2] * v[4 * j + 2] + v[4 * j + 3] * v[4 * j + 3];
    }
    row_reduce(s0, s1, red + 512, warp, lane);
    const float r0 = rsqrtf(s0 * (1.f / DM) + 1e-5f), r1 = rsqrtf(s1 * (1.f / DM) + 1e-5f);
#pragma unroll
    for (int j = 0; j < 9; j++) {
        v[4 * j] *= r0;
        v[4 * j + 1] *= r0;
        v[4 * j + 2] *= r1;
        v[4 * j + 3] *= r1;
    }
}
__device__ __forceinline__ void mod_to_smem(uint32_t dst, const uint32_t* src, uint32_t tag) {
    const uint32_t t0 = clk32();
    uint4 u;
    while (true) {
        u = ld128(reinterpret_cast<const uint4*>(src));
        const uint32_t bad = ((u.x ^ tag) | (u.y ^ tag) | (u.z ^ tag) | (u.w ^ tag)) & 0xffffu;
        if (__all_sync(0xffffffffu, bad == 0) || clk32() - t0 > WAIT_LIMIT) break;
        __nanosleep(64);
    }
    sts128(dst, u.x & 0xffff0000u, u.y & 0xffff0000u, u.z & 0xffff0000u, u.w & 0xffff0000u);
}
__device__ __forceinline__ void lds_mod(float (&m)[18], uint32_t src  , int warp) {
#pragma unroll
    for (int j = 0; j < 9; j++)
        asm volatile("ld.shared.v2.f32 {%0,%1}, [%2];"
                     : "=f"(m[2 * j]), "=f"(m[2 * j + 1])
                     : "r"(src + own_col(j) * 4 - (j == 8 ? warp * 32 : 0))
                     : "memory");
}
__device__ __forceinline__ void modulate_store(const float (&v)[36], const float (&shift)[18], const float (&scale)[18],
                                               uint4* hbuf  , int warp, int lane) {
    uint32_t o[18];
#pragma unroll
    for (int j = 0; j < 9; j++) {
        const uint32_t cc = pack_bf16(1.f + scale[2 * j], 1.f + scale[2 * j + 1]);
        const float c0 = bf_lo(cc), c1 = bf_hi(cc);
        o[2 * j] = max(pack_bf16(fmaf(v[4 * j], c0, shift[2 * j]), fmaf(v[4 * j + 1], c1, shift[2 * j + 1])), 1u);
        o[2 * j + 1] = max(pack_bf16(fmaf(v[4 * j + 2], c0, shift[2 * j]), fmaf(v[4 * j + 3], c1, shift[2 * j + 1])), 1u);
    }
#pragma unroll
    for (int i = 0; i < 4; i++) st128(hbuf + (i * 8 + warp) * 32 + lane, o[4 * i], o[4 * i + 1], o[4 * i + 2], o[4 * i + 3]);
    st64(reinterpret_cast<uint2*>(hbuf + 32 * 32) + warp * 32 + lane, o[16], o[17]);
}
__device__ __forceinline__ void sum_partials(float (&v)[36], const uint4* src  , uint32_t tag) {
    const uint32_t t0 = clk32();
    while (true) {
        uint4 t[8][4];
#pragma unroll
        for (int s = 0; s < 8; s++)
#pragma unroll
            for (int i = 0; i < 4; i++) t[s][i] = ld128(src + (s * 36 + i * 8) * 32);
        uint32_t bad = 0;
#pragma unroll
        for (int i = 0; i < 32; i++) v[i] = 0.f;
#pragma unroll
        for (int s = 0; s < 8; s++)
#pragma unroll
            for (int i = 0; i < 4; i++) {
                bad |= t[s][i].x ^ tag;
                v[8 * i] += bf_lo(t[s][i].x);
                v[8 * i + 1] += bf_hi(t[s][i].x);
                v[8 * i + 2] += bf_lo(t[s][i].y);
                v[8 * i + 3] += bf_hi(t[s][i].y);
                v[8 * i + 4] += bf_lo(t[s][i].z);
                v[8 * i + 5] += bf_hi(t[s][i].z);
                v[8 * i + 6] += bf_lo(t[s][i].w);
                v[8 * i + 7] += bf_hi(t[s][i].w);
            }
        if (__all_sync(0xffffffffu, (bad & 1u) == 0) || clk32() - t0 > WAIT_LIMIT) break;
    }
}
__device__ __forceinline__ void sum_tail(float (&v)[36], const uint2* src  , uint32_t tag) {
    const uint32_t t0 = clk32();
    while (true) {
        uint2 t[8];
#pragma unroll
        for (int s = 0; s < 8; s++) t[s] = ld64(src + s * 72 * 32);
        uint32_t bad = 0;
        v[32] = v[33] = v[34] = v[35] = 0.f;
#pragma unroll
        for (int s = 0; s < 8; s++) {
            bad |= t[s].x ^ tag;
            v[32] += bf_lo(t[s].x);
            v[33] += bf_hi(t[s].x);
            v[34] += bf_lo(t[s].y);
            v[35] += bf_hi(t[s].y);
        }
        if (__all_sync(0xffffffffu, (bad & 1u) == 0) || clk32() - t0 > WAIT_LIMIT) break;
    }
}
__device__ __forceinline__ void poll_tail(uint32_t (&a)[144], const uint2* src  ) {
    const uint32_t t0 = clk32();
    while (true) {
        uint32_t m = 0xffffffffu;
#pragma unroll
        for (int j = 0; j < 8; j++) {
            const uint2 t = ld64(src + j * 32);
            a[128 + 2 * j] = t.x;
            a[129 + 2 * j] = t.y;
        }
#pragma unroll
        for (int j = 0; j < 16; j++) m = min(m, a[128 + j]);
        if (__all_sync(0xffffffffu, m != 0) || clk32() - t0 > WAIT_LIMIT) break;
    }
}
template <int K0, int K1>
__device__ __forceinline__ void poll_frags(uint32_t (&a)[144], const uint4* src  , bool kick) {
    const uint32_t t0 = clk32();
    while (true) {
#pragma unroll
        for (int k = K0; k < K1; k++)
            asm volatile("ld.relaxed.gpu.global.v4.u32 {%0,%1,%2,%3}, [%4];"
                         : "=r"(a[4 * k]), "=r"(a[4 * k + 1]), "=r"(a[4 * k + 2]), "=r"(a[4 * k + 3])
                         : "l"(src + k * 32));
        if (kick) bar_arrive(5, 256);
        kick = false;
        uint32_t m0 = a[4 * K0], m1 = a[4 * K0 + 1];
#pragma unroll
        for (int i = 4 * K0 + 2; i < 4 * K1; i += 2) {
            m0 = min(m0, a[i]);
            m1 = min(m1, a[i + 1]);
        }
        if (__all_sync(0xffffffffu, min(m0, m1) != 0) || clk32() - t0 > WAIT_LIMIT) break;
    }
}

constexpr float SM_SCALE = 0.08838834764831845f * 1.4426950408889634f;
constexpr float SM_HI = 1.2089258e24f;
constexpr float SM_LO = 9.0949470e-13f;
__device__ __forceinline__ void qk_step(float (&s)[32], const uint32_t (&q)[32], uint64_t dk) {
#pragma unroll
    for (int k = 0; k < 8; k++) {
        if (k == 0)
            wgmma_n64_z<0>(s, q[0], q[1], q[2], q[3], dk);
        else
            wgmma_n64<0>(s, q[4 * k], q[4 * k + 1], q[4 * k + 2], q[4 * k + 3], dk + (k >> 2) * 512 + (k & 3) * 2);
    }
}
__device__ __forceinline__ void pv_step(float (&o)[64], const uint32_t (&p)[16], uint64_t dv, int acc) {
#pragma unroll
    for (int k = 0; k < 4; k++)
        wgmma_n128<1>(o, p[4 * k], p[4 * k + 1], p[4 * k + 2], p[4 * k + 3], dv + k * 128, k != 0 ? 1 : acc);
}
template <bool SHIFT>
__device__ __forceinline__ void exp_step(const float (&s)[32], uint32_t (&p)[16], float n0, float n1, float& s0,
                                         float& s1) {
#pragma unroll
    for (int i = 0; i < 8; i++) {
        const float e0 = ex2(SHIFT ? s[4 * i] + n0 : s[4 * i]), e1 = ex2(SHIFT ? s[4 * i + 1] + n0 : s[4 * i + 1]);
        const float e2 = ex2(SHIFT ? s[4 * i + 2] + n1 : s[4 * i + 2]), e3 = ex2(SHIFT ? s[4 * i + 3] + n1 : s[4 * i + 3]);
        if (i == 0) {
            s0 = e0 + e1;
            s1 = e2 + e3;
        } else {
            s0 += e0 + e1;
            s1 += e2 + e3;
        }
        p[2 * i] = pack_bf16(e0, e1);
        p[2 * i + 1] = pack_bf16(e2, e3);
    }
}
__device__ __forceinline__ void row_max(const float (&sa)[32], const float (&sb)[32], float& x0, float& x1) {
    float xa[8];
#pragma unroll
    for (int i = 0; i < 8; i++) xa[i] = fmaxf(sa[i], sb[i]);
#pragma unroll
    for (int k = 1; k < 4; k++)
#pragma unroll
        for (int i = 0; i < 8; i++) xa[i] = fmaxf(xa[i], fmaxf(sa[8 * k + i], sb[8 * k + i]));
    x0 = fmaxf(fmaxf(xa[0], xa[1]), fmaxf(xa[4], xa[5]));
    x1 = fmaxf(fmaxf(xa[2], xa[3]), fmaxf(xa[6], xa[7]));
    x0 = fmaxf(x0, __shfl_xor_sync(0xffffffffu, x0, 1));
    x1 = fmaxf(x1, __shfl_xor_sync(0xffffffffu, x1, 1));
    x0 = fmaxf(x0, __shfl_xor_sync(0xffffffffu, x0, 2));
    x1 = fmaxf(x1, __shfl_xor_sync(0xffffffffu, x1, 2));
}
__device__ __forceinline__ void inv_row_sums(float l0, float l1, float& i0, float& i1) {
    l0 += __shfl_xor_sync(0xffffffffu, l0, 1);
    l1 += __shfl_xor_sync(0xffffffffu, l1, 1);
    l0 += __shfl_xor_sync(0xffffffffu, l0, 2);
    l1 += __shfl_xor_sync(0xffffffffu, l1, 2);
    i0 = rcp(l0);
    i1 = rcp(l1);
}

__device__ __forceinline__ uint32_t get_epoch(uint32_t sbase) { return __float_as_uint(lds32f(sbase + OFF_EPOCH)); }
__device__ __forceinline__ float silu_bf16(unsigned short c) {
    const float cv = bf_lo(c);
    return round_bf16(cv * rcp(1.f + ex2(-1.4426950408889634f * cv)));
}
__device__ __forceinline__ void st_mod(uint32_t* p, float v, uint32_t tag) {
    asm volatile("st.relaxed.gpu.global.u32 [%0], %1;" ::"l"(p), "r"(__float_as_uint(round_bf16(v)) | tag)
                 : "memory");
}
__device__ __forceinline__ void fma8(float (&acc)[8], float sc, const uint4& w) {
    acc[0] = fmaf(sc, bf_lo(w.x), acc[0]);
    acc[1] = fmaf(sc, bf_hi(w.x), acc[1]);
    acc[2] = fmaf(sc, bf_lo(w.y), acc[2]);
    acc[3] = fmaf(sc, bf_hi(w.y), acc[3]);
    acc[4] = fmaf(sc, bf_lo(w.z), acc[4]);
    acc[5] = fmaf(sc, bf_hi(w.z), acc[5]);
    acc[6] = fmaf(sc, bf_lo(w.w), acc[6]);
    acc[7] = fmaf(sc, bf_hi(w.w), acc[7]);
}
__device__ __forceinline__ void modp_to_smem(uint32_t dst, const uint32_t* src, uint32_t tag) {
    const uint32_t t0 = clk32();
    uint4 u[6];
    while (true) {
        uint32_t bad = 0;
#pragma unroll
        for (int i = 0; i < 6; i++) u[i] = ld128(reinterpret_cast<const uint4*>(src + i * 2 * DM));
#pragma unroll
        for (int i = 0; i < 6; i++) bad |= (u[i].x ^ tag) | (u[i].y ^ tag) | (u[i].z ^ tag) | (u[i].w ^ tag);
        if (__all_sync(0xffffffffu, (bad & 0xffu) == 0) || clk32() - t0 > WAIT_LIMIT) break;
        __nanosleep(64);
    }
    float s0 = 0.f, s1 = 0.f, s2 = 0.f, s3 = 0.f;
#pragma unroll
    for (int i = 0; i < 6; i++) {
        s0 += __uint_as_float(u[i].x & ~0xffu);
        s1 += __uint_as_float(u[i].y & ~0xffu);
        s2 += __uint_as_float(u[i].z & ~0xffu);
        s3 += __uint_as_float(u[i].w & ~0xffu);
    }
    const uint32_t p0 = pack_bf16(s0, s1), p1 = pack_bf16(s2, s3);
    sts128(dst, p0 << 16, p0 & 0xffff0000u, p1 << 16, p1 & 0xffff0000u);
}

__global__ void __cluster_dims__(2, 1, 1) __launch_bounds__(384, 1)
    fused_block_kernel(const __grid_constant__ Params maps) {
    extern __shared__ uint8_t smem_raw[];
    uint32_t sbase = (smem_u32(smem_raw) + 1023u) & ~1023u;
    asm volatile("" : "+r"(sbase));
    const int b = blockIdx.x;
    const int rank = b & 1;
    const int mt = ((b >> 1) & 7) * 2 + rank;
    const int g = b >> 4;
    const int warp = __shfl_sync(0xffffffffu, threadIdx.x >> 5, 0);
    const int lane = threadIdx.x & 31;
    Scratch* const sc_ = maps.sc;
    const __nv_bfloat16* const wmod = maps.wmod;
    const __nv_bfloat16* const cvec = maps.cvec;

#define SPROF(i)

    if (warp >= 8) {
        asm volatile("setmaxnreg.dec.sync.aligned.u32 24;");
        if (warp == 8 && lane == 0) {
#pragma unroll
            for (int i = 0; i < 8; i++) {
                mbar_init(sbase + OFF_FULL + i * 8, 1);
                mbar_init(sbase + OFF_EMPTY + i * 8, 4);
            }
            mbar_init(sbase + OFF_XBAR, 1);
            asm volatile("fence.mbarrier_init.release.cluster;" ::: "memory");
            asm volatile("barrier.cluster.arrive.relaxed;\nbarrier.cluster.wait;" ::: "memory");
            uint32_t slot = 0, phase = 1;
            const uint32_t dst0 = sbase + rank * BOX_BYTES;
            auto acquire = [&](uint32_t bytes) {
                mbar_wait(sbase + OFF_EMPTY + slot * 8, phase);
                mbar_expect_tx(sbase + OFF_FULL + slot * 8, bytes);
            };
            auto adv8 = [&]() {
                if (++slot == 8) {
                    slot = 0;
                    phase ^= 1;
                }
            };
#pragma unroll 1
            for (int hq = 0; hq < 4; hq++) {
                const int col = (g * 4 + ((hq + 1) & 3)) * 128 + rank * 64;
                if (hq == 2) {
                    l2_prefetch(maps.kc + (size_t)(g * 4 * 2048 + (b & 15) * 64) * 128, SLOT_BYTES);
                    l2_prefetch(maps.vc + (size_t)(g * 4 * 2048 + (b & 15) * 64) * 128, SLOT_BYTES);
                }
#pragma unroll 1
                for (int kc = 0; kc < 9; kc++) {
                    acquire(SLOT_BYTES);
                    tma_mc(dst0 + slot * SLOT_BYTES, &maps.wq, col, kc * 64, sbase + OFF_FULL + slot * 8);
                    adv8();
                }
            }
            const int row0 = g * 4 * 2048;
#pragma unroll 1
            for (int n = 0; n < 128; n++) {
                if (n < 4) mbar_wait(sbase + OFF_EMPTY + (slot + 1) * 8, phase);
                acquire(2 * SLOT_BYTES);
                const uint32_t bar = sbase + OFF_FULL + slot * 8;
                const int r0 = n == 0 ? 0 : (n == 127 ? 126 : n + 1);
                const int r1 = n == 0 ? 1 : (n == 127 ? 127 : n - 1);
                tma_mc(dst0 + slot * SLOT_BYTES, n == 127 ? &maps.v : &maps.k, rank * 64, row0 + r0 * 64, bar);
                tma_mc(dst0 + (slot + 1) * SLOT_BYTES, n == 0 ? &maps.k : &maps.v, rank * 64, row0 + r1 * 64, bar);
                adv8();
                adv8();
                if (n >= 96 && n < 96 + 10) {
                    const int i = n - 96;
                    if (i < 9) {
                        l2_prefetch((const char*)maps.wg_p + (size_t)b * 41472 + i * 4608, 4608);
                        l2_prefetch((const char*)maps.wu_p + (size_t)b * 41472 + i * 4608, 4608);
                        l2_prefetch((const char*)maps.wd_p + (size_t)b * 41472 + i * 4608, 4608);
                        l2_prefetch((const char*)maps.wo_p + (size_t)b * 36864 + i * 4096, 4096);
                    }
                }
                const int u = n + KV_AHEAD;
                if (u < 128 && (u & 15) == (b & 15)) {
                    l2_prefetch(maps.kc + (size_t)(row0 + u * 64) * 128, SLOT_BYTES);
                    l2_prefetch(maps.vc + (size_t)(row0 + u * 64) * 128, SLOT_BYTES);
                }
            }
#pragma unroll 1
            for (int p = 0; p < 4; p++)
#pragma unroll 1
                for (int kc = 0; kc < 8; kc++) {
                    acquire(SLOT_BYTES);
                    tma_mc(dst0 + slot * SLOT_BYTES, &maps.wo, p * 128 + rank * 64, g * 512 + kc * 64,
                           sbase + OFF_FULL + slot * 8);
                    adv8();
                }
#pragma unroll 1
            for (int kc = 0; kc < 4; kc++) {
                acquire(SLOT_BYTES);
                tma_mc(dst0 + slot * SLOT_BYTES, &maps.wo, 512, g * 512 + kc * 128 + rank * 64,
                       sbase + OFF_FULL + slot * 8);
                adv8();
            }
            const CUtensorMap* mg = rank ? &maps.wu : &maps.wg;
#pragma unroll 1
            for (int ch = 0; ch < 9; ch++)
#pragma unroll 1
                for (int kc = 0; kc < 9; kc++) {
                    acquire(SLOT_BYTES);
                    tma_mc(dst0 + slot * SLOT_BYTES, mg, g * 576 + ch * 64, kc * 64, sbase + OFF_FULL + slot * 8);
                    adv8();
                }
#pragma unroll 1
            for (int p = 0; p < 4; p++)
#pragma unroll 1
                for (int kc = 2; kc < 11; kc++) {
                    acquire(SLOT_BYTES);
                    tma_mc(dst0 + slot * SLOT_BYTES, &maps.wd, p * 128 + rank * 64, g * 576 + (kc < 9 ? kc : kc - 9) * 64,
                           sbase + OFF_FULL + slot * 8);
                    adv8();
                }
#pragma unroll 1
            for (int i = 0; i < 5; i++) {
                acquire(i < 4 ? SLOT_BYTES : BOX_BYTES);
                const int kc = 2 * i + rank + 2;
                if (i < 4 || rank == 0)
                    tma_mc(dst0 + slot * SLOT_BYTES, &maps.wd, 512, g * 576 + (kc < 9 ? kc : kc - 9) * 64,
                           sbase + OFF_FULL + slot * 8);
                adv8();
            }
        } else if (warp == 11) {
            asm volatile("barrier.cluster.arrive.relaxed.aligned;" ::: "memory");
            bar_sync(6, 160);
            uint4* hz = sc_->h[(get_epoch(sbase) & 1) ^ 1][0] + (size_t)b * 72 * 32 + lane;
#pragma unroll 1
            for (int i = 0; i < 72; i++) {
                hz[i * 32] = make_uint4(0, 0, 0, 0);
                __nanosleep(200);
            }
        } else if (warp == 9 || warp == 10) {
            asm volatile("barrier.cluster.arrive.relaxed.aligned;" ::: "memory");
            bar_sync(4, 320);
            const uint32_t tag = (get_epoch(sbase) + 1) & 0xffffu;
            if (warp == 10 && lane < 9) l2_prefetch((const char*)maps.wq_p + (size_t)b * 36864 + lane * 4096, 4096);
            const int blk = warp == 9 ? 72 + b : 200 + b;
            if (blk < 216) {
                float acc[8];
#pragma unroll
                for (int e = 0; e < 8; e++) acc[e] = 0.f;
                const uint4* wp = reinterpret_cast<const uint4*>(wmod + (size_t)(lane >> 1) * (6 * DM) + blk * 16) + (lane & 1);
                const unsigned short* cp = reinterpret_cast<const unsigned short*>(cvec) + (lane >> 1);
#pragma unroll 1
                for (int i = 0; i < 36; i++) {
                    const uint4 w = __ldg(wp + (size_t)i * (16 * 6 * DM / 8));
                    const float sc = silu_bf16(__ldg(cp + i * 16));
                    fma8(acc, sc, w);
                }
#pragma unroll
                for (int o = 2; o < 32; o <<= 1)
#pragma unroll
                    for (int e = 0; e < 8; e++) acc[e] += __shfl_xor_sync(0xffffffffu, acc[e], o);
                if (lane < 2) {
#pragma unroll
                    for (int e = 0; e < 8; e++) st_mod(sc_->mod + blk * 16 + lane * 8 + e, acc[e], tag);
                }
            }
            if (warp == 9) {
#pragma unroll 1
                for (int st = 1; st <= 2; st++) {
                    bar_sync(7, 160);
                    const uint32_t* src = sc_->mod + (st * 3 - 1) * DM;
                    const int n = st == 1 ? 3 * DM : DM;
#pragma unroll 1
                    for (int i = lane * 4; i < n + 127 - ((n + 127) & 127); i += 128)
                        mod_to_smem(sbase + OFF_MODT + min(i, n - 4) * 4, src + min(i, n - 4), tag);
                    __syncwarp();
                    if (lane == 0) rows_load(sbase, st == 1 ? &maps.rx : &maps.rx2, (mt * 8 + g) * 16);
                    if (st == 1) {
                        bar_sync(7, 160);
                        if (lane == 0) {
                            rows_store(sbase, &maps.rx2, (mt * 8 + g) * 16);
                            rows_store_wait();
                        }
                        __syncwarp();
                        bar_arrive(10, 160);
                    }
                }
            }
        }
    } else {
        uint4 w1[3], xw[5], ew = make_uint4(0, 0, 0, 0);
        unsigned short cu[3];
        {
            const int t = threadIdx.x, bw = min(b, 107);
            const int row = (bw / 18) * 96 + (t >> 3);
#pragma unroll
            for (int i = 0; i < 3; i++) {
                w1[i] = ldg128(reinterpret_cast<const uint4*>(wmod + (size_t)(row + 32 * i) * (6 * DM)) + (bw % 18) * 8 + (t & 7));
                asm volatile("ld.global.nc.u16 %0, [%1];" : "=h"(cu[i]) : "l"(cvec + row + 32 * i));
            }
            if (t == 0) ew = ld128(reinterpret_cast<const uint4*>(&sc_->epoch[b * 32]));
#pragma unroll
            for (int i = 0; i < 5; i++)
                xw[i] = ldg128(reinterpret_cast<const uint4*>(maps.x + (size_t)(mt * 8 + g) * 16 * DM) + min(t + 256 * i, 1151));
        }
        if (threadIdx.x == 160) SPROF(5);
        asm volatile("setmaxnreg.inc.sync.aligned.u32 240;");
        if (threadIdx.x == 160) SPROF(6);
        const int wg = warp >> 2;
        const int tid = threadIdx.x;
        Ctx cx;
        cx.sbase = sbase;
        cx.wg = wg;
        if (wg == 1) bar_arrive(8, 256);
        cx.rel_cta = (lane == 0 && (warp & 3) < 2) ? (warp & 3) : 2;
        const uint32_t red = sbase + OFF_RED;
        const int own = mt * 8 + g;
        const int wown = mt * 8 + warp;
        PROF(0);
        PROFG(30);
        PROFR(17);
        {
            asm volatile("barrier.cluster.arrive.relaxed.aligned;" ::: "memory");
            float acc[8];
#pragma unroll
            for (int e = 0; e < 8; e++) acc[e] = 0.f;
#pragma unroll
            for (int i = 0; i < 3; i++) fma8(acc, silu_bf16(cu[i]), w1[i]);
#pragma unroll
            for (int o = 8; o < 32; o <<= 1)
#pragma unroll
                for (int e = 0; e < 8; e++) acc[e] += __shfl_xor_sync(0xffffffffu, acc[e], o);
            PROFR(19);
            if (lane < 8) {
                const uint32_t dst = sbase + OFF_MRED + warp * 256 + lane * 32;
                sts128(dst, __float_as_uint(acc[0]), __float_as_uint(acc[1]), __float_as_uint(acc[2]), __float_as_uint(acc[3]));
                sts128(dst + 16, __float_as_uint(acc[4]), __float_as_uint(acc[5]), __float_as_uint(acc[6]), __float_as_uint(acc[7]));
            }
            if (tid == 0) sts128(sbase + OFF_EPOCH, ew.x, ew.y, ew.z, ew.w);
            bar_sync(3, 256);
            PROFR(20);
            if (tid < 64 && b < 108) {
                float sum = 0.f;
#pragma unroll
                for (int w8 = 0; w8 < 8; w8++) sum += lds32f(sbase + OFF_MRED + w8 * 256 + tid * 4);
                asm volatile("st.relaxed.gpu.global.u32 [%0], %1;" ::"l"(&sc_->modp[b / 18][(b % 18) * 64 + tid]),
                             "r"((__float_as_uint(sum) & ~0xffu) | ((get_epoch(sbase) + 1) & 0xffu))
                             : "memory");
            }
            PROFR(21);
#pragma unroll
            for (int i = 0; i < 5; i++) {
                const int vi = min(tid + 256 * i, 1151), ln = vi >> 3;
                sts128(sbase + OFF_ROWS + ln * 128 + (((vi & 7) ^ (ln & 7)) << 4), xw[i].x, xw[i].y, xw[i].z, xw[i].w);
            }
            bar_sync(3, 256);
        }

        Ring ring{0u, 0u};
        int stage = 0;
        asm volatile("" : "+r"(stage));
#pragma unroll 1
        for (;; stage++) {
            int tid, lane;
            asm volatile("mov.u32 %0, %%tid.x;" : "=r"(tid));
            lane = tid & 31;
            const uint32_t epoch = get_epoch(sbase);
            {
                float v[36];
                const uint32_t modt = sbase + OFF_MODT + (warp * 16 + (lane & 3) * 2) * 4;
                if (stage == 0) {
#pragma unroll
                    for (int i = 0; i < 36; i++) v[i] = 0.f;
                } else {
                    const uint4* psrc = sc_->part + (size_t)own * 8 * 36 * 32;
                    sum_partials(v, psrc + tid, stage & 1);
                    PROF(stage == 1 ? 8 : 15);
                    sum_tail(v, reinterpret_cast<const uint2*>(psrc + 32 * 32) + tid, stage & 1);
                }
                if (stage) mbar_wait(sbase + OFF_XBAR, stage - 1);
                if (stage == 0) PROFR(22);
                {
                    const float gs = stage == 2 ? 0.5f : 1.f;
                    float gate[18];
                    lds_mod(gate, modt, warp);
                    const int r = lane >> 2;
                    const uint32_t rows = sbase + OFF_ROWS + r * (DM * 2) + (lane & 3) * 4;
#pragma unroll
                    for (int j = 0; j < 9; j++) {
                        const int ch = j < 8 ? (j >> 1) * 2 + (warp >> 2) : 8, c16 = j < 8 ? (warp & 3) * 2 + (j & 1) : warp;
                        const uint32_t ad = rows + ch * 128 + ((c16 ^ ((r + ch) & 7)) << 4);
                        const uint32_t u0 = __float_as_uint(lds32f(ad)), u1 = __float_as_uint(lds32f(ad + 8 * DM * 2));
                        const float g0 = stage ? gate[2 * j] * gs : 0.f, g1 = stage ? gate[2 * j + 1] * gs : 0.f;
                        v[4 * j] = fmaf(g0, v[4 * j], bf_lo(u0));
                        v[4 * j + 1] = fmaf(g1, v[4 * j + 1], bf_hi(u0));
                        v[4 * j + 2] = fmaf(g0, v[4 * j + 2], bf_lo(u1));
                        v[4 * j + 3] = fmaf(g1, v[4 * j + 3], bf_hi(u1));
                        sts32f(ad, __uint_as_float(pack_bf16(v[4 * j], v[4 * j + 1])));
                        sts32f(ad + 8 * DM * 2, __uint_as_float(pack_bf16(v[4 * j + 2], v[4 * j + 3])));
                    }
                    asm volatile("fence.proxy.async.shared::cta;" ::: "memory");
                }
                if (stage == 2) break;
                PROF(stage == 0 ? 1 : 9);
                layernorm_rows(v, red, warp, lane);
                if (stage == 0) PROFR(27);
                if (stage == 0) {
#pragma unroll 1
                    for (int i = tid; i < 288; i += 256)
                        modp_to_smem(sbase + OFF_MODT + (DM + i * 4) * 4, sc_->modp[0] + i * 4, (epoch + 1) & 0xffu);
                    bar_sync(3, 256);
                    bar_arrive(4, 320);
                }
                float shift[18], scale[18];
                lds_mod(shift, modt + DM * 4, warp);
                lds_mod(scale, modt + 2 * DM * 4, warp);
                if (stage == 0) PROFR(28);
                PROF(stage == 0 ? 2 : 10);
                modulate_store(v, shift, scale, sc_->h[epoch & 1][stage] + (size_t)own * 36 * 32, warp, lane);
                if (stage == 0) asm volatile("barrier.cluster.wait.aligned;" ::: "memory");
            }

            const uint32_t spill = sbase + 8 * SLOT_BYTES + wg * 3 * SLOT_BYTES + (tid & 127) * 16;
            uint32_t a[144];
            PROF(stage == 0 ? 3 : 11);
            {
                const uint4* hsrc = sc_->h[epoch & 1][stage] + (size_t)wown * 36 * 32 + lane;
                poll_tail(a, reinterpret_cast<const uint2*>(hsrc - lane + 32 * 32) + lane);
                PROF(stage == 0 ? 4 : 12);
                if (stage == 1) PROFG(25);
                TG(stage * 32 + 30);
                if (wg == 1) bar_sync(5, 256);
                poll_frags<0, 32>(a, hsrc, wg == 0);
            }
            uint4* hhbuf = sc_->hh + (size_t)b * 8 * 256 + tid;
            float d[64];
#pragma unroll 1
            for (int ch = 0;; ch++) {
                TG(stage * 32 + ch * 2);
                gemm_n128(d, a, cx, ring, true);
                TG(stage * 32 + ch * 2 + 1);
                if (stage == 0) {
#pragma unroll
                    for (int i = 0; i < 64; i++) d[i] *= SM_SCALE;
                    if (ch == 3) break;
#pragma unroll
                    for (int v = 0; v < 8; v++)
                        sts128(spill + (ch * 8 + v) * 2048, pack_bf16(d[8 * v], d[8 * v + 1]),
                               pack_bf16(d[8 * v + 2], d[8 * v + 3]), pack_bf16(d[8 * v + 4], d[8 * v + 5]),
                               pack_bf16(d[8 * v + 6], d[8 * v + 7]));
                } else {
#pragma unroll
                    for (int i = 0; i < 32; i++) {
                        const float gv = d[i], gu = gv * d[32 + i];
                        const float z = gv * fmaf(gv * gv, 0.7978845608028654f * 0.044715f, 0.7978845608028654f);
                        d[i] = fmaf(gu, tanh_fast(z), gu);
                    }
                    if (ch == 8) break;
                    if (wg == 0) {
                        if (ch == 0) bar_arrive(7, 160);
                        if (ch == 2) bar_sync(10, 160);
                    }
#pragma unroll
                    for (int v = 0; v < 4; v++) {
                        const uint4 h4 = make_uint4(pack_bf16(d[8 * v], d[8 * v + 1]), pack_bf16(d[8 * v + 2], d[8 * v + 3]),
                                                    pack_bf16(d[8 * v + 4], d[8 * v + 5]), pack_bf16(d[8 * v + 6], d[8 * v + 7]));
                        if (ch < 2)
                            __stcg(hhbuf + (ch * 4 + v) * 256, h4);
                        else
                            sts128(spill + ((ch - 2) * 4 + v) * 2048, h4.x, h4.y, h4.z, h4.w);
                    }
                }
            }
            if (stage == 0) {
                uint32_t q[32];
#pragma unroll
                for (int i = 0; i < 32; i++) q[i] = pack_bf16(d[2 * i], d[2 * i + 1]);
                PROF(5);
                PROFG(23);
                if (wg == 0) bar_arrive(6, 160);
                {
                    float o[64], sa[32], sb[32];
                    uint32_t pa[16], pb[16];
#pragma unroll
                    for (int i = 0; i < 64; i++) o[i] = 0.f;
                    float n0 = 0.f, n1 = 0.f, l0 = 1.f, l1 = 1.f;
                    bool shifted = false;
                    const uint64_t dbase = desc_of(sbase);
                    const uint64_t dbk = dbase - (511u << 16);
                    const int my_bar = 1 + wg, other_bar = 2 - wg;

                    auto softmax_a = [&](bool first, float& s0, float& s1) {
                        if (first) {
                            shifted = false;
                            n0 = n1 = 0.f;
                            l0 = l1 = 0.f;
                        }
                        if (shifted)
                            exp_step<true>(sa, pa, n0, n1, s0, s1);
                        else
                            exp_step<false>(sa, pa, n0, n1, s0, s1);
                    };
                    auto softmax_b = [&](bool first, float s0, float s1) {
                        float u0, u1;
                        if (shifted)
                            exp_step<true>(sb, pb, n0, n1, u0, u1);
                        else
                            exp_step<false>(sb, pb, n0, n1, u0, u1);
                        s0 += u0;
                        s1 += u1;
                        bool bad = !(fmaxf(s0, s1) <= SM_HI);
                        if (first) {
                            float r0 = s0 + __shfl_xor_sync(0xffffffffu, s0, 1), r1 = s1 + __shfl_xor_sync(0xffffffffu, s1, 1);
                            r0 += __shfl_xor_sync(0xffffffffu, r0, 2);
                            r1 += __shfl_xor_sync(0xffffffffu, r1, 2);
                            bad = bad || !(fminf(r0, r1) >= SM_LO);
                        }
                        if (__any_sync(0xffffffffu, bad)) {
                            float x0, x1;
                            row_max(sa, sb, x0, x1);
                            x0 = -x0;
                            x1 = -x1;
                            if (!first) {
                                x0 = fminf(x0, n0);
                                x1 = fminf(x1, n1);
                                const float al0 = ex2(x0 - n0), al1 = ex2(x1 - n1);
                                l0 *= al0;
                                l1 *= al1;
#pragma unroll
                                for (int i = 0; i < 16; i++) {
                                    o[4 * i] *= al0;
                                    o[4 * i + 1] *= al0;
                                    o[4 * i + 2] *= al1;
                                    o[4 * i + 3] *= al1;
                                }
                            }
                            n0 = x0;
                            n1 = x1;
                            shifted = true;
                            exp_step<true>(sa, pa, n0, n1, s0, s1);
                            exp_step<true>(sb, pb, n0, n1, u0, u1);
                            s0 += u0;
                            s1 += u1;
                        }
                        l0 += s0;
                        l1 += s1;
                    };

                    cx.wait_full(4, 0);
                    if (wg == 1) bar_sync(my_bar, 256);
                    wg_fence();
                    qk_step(sa, q, dbk + 4 * 1024);
                    qk_step(sb, q, dbk + 5 * 1024);
                    wg_commit();
                    bar_arrive(other_bar, 256);
                    wg_wait<0>();
                    pin(sa);
                    pin(sb);
                    cx.release(4);
                    cx.wait_full(6, 0);
                    {
                        float s0, s1;
                        softmax_a(true, s0, s1);
                        softmax_b(true, s0, s1);
                    }
                    uint32_t alo = (uint32_t)dbase + 6 * 1024, blo = (uint32_t)dbase;
                    const uint32_t dhi = (uint32_t)(dbase >> 32);
#pragma unroll 1
                    for (int t = 1; t < 64; t++) {
                        const int j = t & 15;
                        const uint32_t sA = 2 + 4 * (t & 1), sB = 4 - 4 * (t & 1);
                        const uint64_t da = ((uint64_t)dhi << 32) | alo, db = ((uint64_t)dhi << 32) | blo;
                        TL(0);
                        bar_sync(my_bar, 256);
                        TL(2);
                        wg_fence();
                        pv_step(o, pa, da + 1024, j != 1);
                        qk_step(sa, q, da - (511u << 16));
                        wg_commit();
                        cx.wait_full(sB, ((36 + 4 * t) >> 3) & 1);
                        wg_fence();
                        qk_step(sb, q, db - (511u << 16));
                        pv_step(o, pb, db + 1024, 1);
                        wg_commit();
                        bar_arrive(other_bar, 256);
                        alo ^= 4096;
                        blo ^= 4096;
                        asm volatile("" : "+r"(alo), "+r"(blo));
                        TL(3);
                        wg_wait<1>();
                        pin(sa);
                        pin(pa);
                        TL(4);
                        cx.release(sA);
                        const float lp0 = l0, lp1 = l1;
                        float s0, s1;
                        softmax_a(j == 0, s0, s1);
                        TL(5);
                        wg_wait<0>();
                        pin(o);
                        pin(sb);
                        pin(pb);
                        TL(6);
                        cx.release(sB);
                        if (j == 0) {
                            float i0, i1;
                            inv_row_sums(lp0, lp1, i0, i1);
                            const uint32_t dst = spill + ((t >> 4) - 1) * 16384;
#pragma unroll
                            for (int v = 0; v < 8; v++)
                                sts128(dst + v * 2048, pack_bf16(o[8 * v] * i0, o[8 * v + 1] * i0),
                                       pack_bf16(o[8 * v + 2] * i1, o[8 * v + 3] * i1),
                                       pack_bf16(o[8 * v + 4] * i0, o[8 * v + 5] * i0),
                                       pack_bf16(o[8 * v + 6] * i1, o[8 * v + 7] * i1));
                        }
                        const uint32_t bn = sbase + OFF_FULL + (8 - sA) * 8, pn = ((38 + 4 * t) >> 3) & 1;
                        const bool okn = mbar_try(bn, pn);
                        TL(1);
                        softmax_b(j == 0, s0, s1);
                        if (!okn || j == 15) {
                            mbar_wait(bn, pn);
                            if (j == 15 && t < 63) {
                                const uint32_t src = spill + (t >> 4) * 16384;
#pragma unroll
                                for (int v = 0; v < 8; v++)
                                    lds128(src + v * 2048, q[4 * v], q[4 * v + 1], q[4 * v + 2], q[4 * v + 3]);
                            }
                        }
                        TL(7);
                    }
                    bar_sync(my_bar, 256);
                    wg_fence();
                    pv_step(o, pa, dbase + 2 * 1024, 1);
                    pv_step(o, pb, dbase + 3 * 1024, 1);
                    wg_commit();
                    if (wg == 0) bar_arrive(other_bar, 256);
                    float i0, i1;
                    inv_row_sums(l0, l1, i0, i1);
                    wg_wait<0>();
                    pin(o);
                    cx.release(2);
#pragma unroll
                    for (int i = 0; i < 16; i++) {
                        a[96 + 2 * i] = pack_bf16(o[4 * i] * i0, o[4 * i + 1] * i0);
                        a[96 + 2 * i + 1] = pack_bf16(o[4 * i + 2] * i1, o[4 * i + 3] * i1);
                    }
#pragma unroll
                    for (int i = 128; i < 144; i++) a[i] = 0;
                }
                ring.slot = 4;
                ring.phase = 0;
                PROF(6);
                PROFG(24);
            } else {
#pragma unroll
                for (int v = 0; v < 8; v++) {
                    const uint4 t = __ldcg(hhbuf + v * 256);
                    a[112 + 4 * v] = t.x;
                    a[113 + 4 * v] = t.y;
                    a[114 + 4 * v] = t.z;
                    a[115 + 4 * v] = t.w;
                }
#pragma unroll
                for (int i = 0; i < 16; i++) a[96 + i] = pack_bf16(d[2 * i], d[2 * i + 1]);
                PROF(13);
            }
#pragma unroll
            for (int v = 0; v < 24; v++) lds128(spill + v * 2048, a[4 * v], a[4 * v + 1], a[4 * v + 2], a[4 * v + 3]);

            {
                uint4* dst = sc_->part + ((size_t)wown * 8 + g) * 36 * 32 + lane;
                const uint32_t ptag = (stage + 1) & 1;
#pragma unroll 1
                for (int p = 0; p < 4; p++) {
                    TG(stage * 32 + 18 + p * 2);
                    gemm_n128(d, a, cx, ring, stage != 0);
                    TG(stage * 32 + 19 + p * 2);
#pragma unroll
                    for (int u = 0; u < 8; u++)
                        st128(dst + (p * 8 + u) * 32, (pack_bf16(d[8 * u], d[8 * u + 1]) & ~1u) | ptag,
                              pack_bf16(d[8 * u + 2], d[8 * u + 3]), pack_bf16(d[8 * u + 4], d[8 * u + 5]),
                              pack_bf16(d[8 * u + 6], d[8 * u + 7]));
                    if (p == 0 && wg == 0) bar_arrive(7, 160);
                }
                float e[32];
                TG(stage * 32 + 26);
                gemm_n64(e, a, cx, ring, stage != 0);
                TG(stage * 32 + 27);
                uint2* dst2 = reinterpret_cast<uint2*>(dst - lane + 32 * 32) + lane;
#pragma unroll
                for (int j = 0; j < 8; j++)
                    st64(dst2 + j * 32, (pack_bf16(e[4 * j], e[4 * j + 1]) & ~1u) | ptag, pack_bf16(e[4 * j + 2], e[4 * j + 3]));
            }
            PROF(stage == 0 ? 7 : 14);
            if (stage == 1) {
                PROFG(26);
                asm volatile("barrier.cluster.arrive.relaxed.aligned;" ::: "memory");
            }
        }
        if (wg == 0) bar_sync(8, 256);
        bar_sync(3, 256);
        if (tid == 32) sc_->epoch[b * 32] = get_epoch(sbase) + 1;
        if (tid == 0) {
            rows_store(sbase, &maps.rout, own * 16);
            rows_store_wait();
        }
        __syncwarp();
        PROF(16);
        PROFG(31);
        asm volatile("barrier.cluster.wait.aligned;" ::: "memory");
    }
}

typedef CUresult (*EncodeFn)(CUtensorMap*, CUtensorMapDataType, cuuint32_t, void*, const cuuint64_t*, const cuuint64_t*,
                             const cuuint32_t*, const cuuint32_t*, CUtensorMapInterleave, CUtensorMapSwizzle,
                             CUtensorMapL2promotion, CUtensorMapFloatOOBfill);

void make_map(EncodeFn enc, CUtensorMap* m, const void* ptr, uint64_t rows, uint64_t cols, bool narrow = false) {
    cuuint64_t gdim[2] = {cols, rows};
    cuuint64_t gstr[1] = {cols * 2};
    cuuint32_t box[2] = {narrow ? 16u : 64u, narrow ? 192u : 64u};
    cuuint32_t estr[2] = {1, 1};
    enc(m, CU_TENSOR_MAP_DATA_TYPE_BFLOAT16, 2, const_cast<void*>(ptr), gdim, gstr, box, estr,
        CU_TENSOR_MAP_INTERLEAVE_NONE, narrow ? CU_TENSOR_MAP_SWIZZLE_NONE : CU_TENSOR_MAP_SWIZZLE_128B,
        CU_TENSOR_MAP_L2_PROMOTION_L2_128B,
        CU_TENSOR_MAP_FLOAT_OOB_FILL_NONE);
}

void make_rows_map(EncodeFn enc, CUtensorMap* m, const void* ptr) {
    cuuint64_t gdim[3] = {64, 9, 2048};
    cuuint64_t gstr[2] = {128, DM * 2};
    cuuint32_t box[3] = {64, 9, 16};
    cuuint32_t estr[3] = {1, 1, 1};
    enc(m, CU_TENSOR_MAP_DATA_TYPE_BFLOAT16, 3, const_cast<void*>(ptr), gdim, gstr, box, estr,
        CU_TENSOR_MAP_INTERLEAVE_NONE, CU_TENSOR_MAP_SWIZZLE_128B, CU_TENSOR_MAP_L2_PROMOTION_L2_128B,
        CU_TENSOR_MAP_FLOAT_OOB_FILL_NONE);
}

}

extern "C" void kernel_launch(void* const* d_in, const int* in_sizes, int n_in, void* d_out, int out_size) {
    (void)in_sizes;
    (void)n_in;
    (void)out_size;
    void* fn = nullptr;
    cudaDriverEntryPointQueryResult qr;
    cudaGetDriverEntryPoint("cuTensorMapEncodeTiled", &fn, cudaEnableDefault, &qr);
    EncodeFn enc = (EncodeFn)fn;
    Params maps;
    maps.x = (const __nv_bfloat16*)d_in[0];
    maps.cvec = (const __nv_bfloat16*)d_in[9];
    maps.wmod = (const __nv_bfloat16*)d_in[10];
    maps.kc = (const __nv_bfloat16*)d_in[1];
    maps.vc = (const __nv_bfloat16*)d_in[2];
    maps.wq_p = (const __nv_bfloat16*)d_in[3];
    maps.wo_p = (const __nv_bfloat16*)d_in[4];
    maps.wg_p = (const __nv_bfloat16*)d_in[6];
    maps.wu_p = (const __nv_bfloat16*)d_in[7];
    maps.wd_p = (const __nv_bfloat16*)d_in[8];
    maps.out = (__nv_bfloat16*)d_out;
    void* scp = nullptr;
    cudaGetSymbolAddress(&scp, g_scratch);
    maps.sc = (Scratch*)scp;
    make_map(enc, &maps.k, d_in[1], 32 * 2048, 128);
    make_map(enc, &maps.v, d_in[2], 32 * 2048, 128);
    make_map(enc, &maps.wq, d_in[3], 576, 4096);
    make_map(enc, &maps.wo, d_in[4], 4096, 576);
    make_map(enc, &maps.wg, d_in[6], 576, 4608);
    make_map(enc, &maps.wu, d_in[7], 576, 4608);
    make_map(enc, &maps.wd, d_in[8], 4608, 576);
    make_rows_map(enc, &maps.rx, d_in[0]);
    make_rows_map(enc, &maps.rx2, (char*)scp + offsetof(Scratch, x2));
    make_rows_map(enc, &maps.rout, d_out);
    cudaFuncSetAttribute(fused_block_kernel, cudaFuncAttributeMaxDynamicSharedMemorySize, SMEM_BYTES);
    fused_block_kernel<<<128, 384, SMEM_BYTES>>>(maps);
}
```

```cpp
#include <cuda_runtime.h>
#include <cuda_bf16.h>
#include <cuda.h>
#include <stdint.h>
#include <stddef.h>

namespace {

constexpr int DM = 576;
constexpr int SLOT_BYTES = 16384;
constexpr int BOX_BYTES = 8192;
constexpr int NUNITS = 14;
constexpr int SMEM_TAIL = NUNITS * SLOT_BYTES;
constexpr int SMEM_BYTES = SMEM_TAIL + 2048 + 1024;
constexpr int OFF_FULL = SMEM_TAIL;
constexpr int OFF_EMPTY = SMEM_TAIL + 64;
constexpr int OFF_RED = SMEM_TAIL + 128;

constexpr int KV_AHEAD = 16;
#define GATE_SLOT 4
#define PROBE_NS 300
constexpr int OFF_XBAR = SMEM_TAIL + 1792;
constexpr int OFF_ROWS = 8 * SLOT_BYTES;
constexpr int OFF_MODT = OFF_ROWS + 20480;
constexpr int OFF_EPOCH = SMEM_TAIL + 1808;
constexpr int OFF_MRED = OFF_ROWS + 28672;

struct Scratch {
    unsigned epoch[128 * 32];
    uint32_t mod[6 * DM];
    uint32_t modp[6][2 * DM];
    uint4 h[2][2][128 * 36 * 32];
    uint4 part[128 * 8 * 36 * 32];
    uint4 hh[128 * 8 * 256];
    __nv_bfloat16 x2[2048 * DM];
};
__device__ Scratch g_scratch;

#define TG(i)
#define TL(i)
#define PROFR(i)
#define PROF(i)
#define PROFG(i)

struct Params {
    const __nv_bfloat16 *x, *cvec, *wmod, *kc, *vc, *wq_p, *wo_p, *wg_p, *wu_p, *wd_p;
    __nv_bfloat16* out;
    Scratch* sc;
    CUtensorMap k, v, wq, wo, wg, wu, wd, rx, rx2, rout;
};

__device__ __forceinline__ uint32_t smem_u32(const void* p) { return (uint32_t)__cvta_generic_to_shared(p); }
__device__ __forceinline__ void mbar_init(uint32_t a, uint32_t c) {
    asm volatile("mbarrier.init.shared::cta.b64 [%0], %1;" ::"r"(a), "r"(c) : "memory");
}
__device__ __forceinline__ void mbar_expect_tx(uint32_t a, uint32_t bytes) {
    asm volatile("mbarrier.arrive.expect_tx.shared::cta.b64 _, [%0], %1;" ::"r"(a), "r"(bytes) : "memory");
}
__device__ __forceinline__ bool mbar_try(uint32_t a, uint32_t ph) {
    uint32_t ok;
    asm volatile(
        "{\n.reg .pred p;\nmbarrier.try_wait.parity.shared::cta.b64 p, [%1], %2;\nselp.u32 %0, 1, 0, p;\n}"
        : "=r"(ok)
        : "r"(a), "r"(ph)
        : "memory");
    return ok != 0;
}
__device__ __forceinline__ uint32_t clk32() {
    uint32_t c;
    asm volatile("mov.u32 %0, %%clock;" : "=r"(c));
    return c;
}
constexpr uint32_t WAIT_LIMIT = 1u << 30;
__device__ __forceinline__ void mbar_wait(uint32_t a, uint32_t ph) {
    if (mbar_try(a, ph)) return;
    uint32_t t0 = clk32();
    while (!mbar_try(a, ph)) {
        if (clk32() - t0 > WAIT_LIMIT) break;
    }
}
__device__ __forceinline__ void mbar_arrive_cluster(uint32_t a, uint32_t cta) {
    asm volatile(
        "{\n.reg .b32 ra;\nmapa.shared::cluster.u32 ra, %0, %1;\nmbarrier.arrive.shared::cluster.b64 _, [ra];\n}" ::"r"(a),
        "r"(cta)
        : "memory");
}
__device__ __forceinline__ void tma_mc(uint32_t dst, const CUtensorMap* m, int c0, int c1, uint32_t bar) {
    asm volatile(
        "cp.async.bulk.tensor.2d.shared::cluster.global.mbarrier::complete_tx::bytes.multicast::cluster"
        " [%0], [%1, {%3, %4}], [%2], %5;" ::"r"(dst),
        "l"(m), "r"(bar), "r"(c0), "r"(c1), "h"((uint16_t)3)
        : "memory");
}
__device__ __forceinline__ void bulk_load(uint32_t dst, const void* src, uint32_t bytes, uint32_t bar) {
    asm volatile("cp.async.bulk.shared::cluster.global.mbarrier::complete_tx::bytes [%0], [%1], %2, [%3];" ::"r"(dst),
                 "l"(src), "r"(bytes), "r"(bar)
                 : "memory");
}
__device__ __forceinline__ void l2_prefetch(const void* p, uint32_t bytes) {
    asm volatile("cp.async.bulk.prefetch.L2.global [%0], %1;" ::"l"(p), "r"(bytes) : "memory");
}
__device__ __forceinline__ void bar_sync(int id, int n) { asm volatile("bar.sync %0, %1;" ::"r"(id), "r"(n) : "memory"); }
__device__ __forceinline__ void bar_arrive(int id, int n) {
    asm volatile("bar.arrive %0, %1;" ::"r"(id), "r"(n) : "memory");
}
__device__ __forceinline__ void wg_fence() { asm volatile("wgmma.fence.sync.aligned;" ::: "memory"); }
__device__ __forceinline__ void wg_commit() { asm volatile("wgmma.commit_group.sync.aligned;" ::: "memory"); }
template <int N>
__device__ __forceinline__ void wg_wait() {
    asm volatile("wgmma.wait_group.sync.aligned %0;" ::"n"(N) : "memory");
}
template <int N>
__device__ __forceinline__ void pin(float (&d)[N]) {
#pragma unroll
    for (int i = 0; i < N; i++) asm volatile("" : "+f"(d[i])::"memory");
}
template <int N>
__device__ __forceinline__ void pin(uint32_t (&d)[N]) {
#pragma unroll
    for (int i = 0; i < N; i++) asm volatile("" : "+r"(d[i])::"memory");
}
__device__ __forceinline__ uint32_t pack_bf16(float lo, float hi) {
    uint32_t r;
    asm("cvt.rn.bf16x2.f32 %0, %1, %2;" : "=r"(r) : "f"(hi), "f"(lo));
    return r;
}
__device__ __forceinline__ float bf_lo(uint32_t v) { return __uint_as_float(v << 16); }
__device__ __forceinline__ float bf_hi(uint32_t v) { return __uint_as_float(v & 0xffff0000u); }
__device__ __forceinline__ float round_bf16(float v) { return __bfloat162float(__float2bfloat16_rn(v)); }
__device__ __forceinline__ float ex2(float x) {
    float y;
    asm("ex2.approx.ftz.f32 %0, %1;" : "=f"(y) : "f"(x));
    return y;
}
__device__ __forceinline__ float rcp(float x) {
    float y;
    asm("rcp.approx.ftz.f32 %0, %1;" : "=f"(y) : "f"(x));
    return y;
}
__device__ __forceinline__ float tanh_fast(float x) {
    float y;
    asm("tanh.approx.f32 %0, %1;" : "=f"(y) : "f"(x));
    return y;
}
__device__ __forceinline__ void sts128(uint32_t a, uint32_t x, uint32_t y, uint32_t z, uint32_t w) {
    asm volatile("st.shared.v4.b32 [%0], {%1,%2,%3,%4};" ::"r"(a), "r"(x), "r"(y), "r"(z), "r"(w) : "memory");
}
__device__ __forceinline__ void lds128(uint32_t a, uint32_t& x, uint32_t& y, uint32_t& z, uint32_t& w) {
    asm volatile("ld.shared.v4.b32 {%0,%1,%2,%3}, [%4];" : "=r"(x), "=r"(y), "=r"(z), "=r"(w) : "r"(a) : "memory");
}
__device__ __forceinline__ void sts32f(uint32_t a, float v) {
    asm volatile("st.shared.f32 [%0], %1;" ::"r"(a), "f"(v) : "memory");
}
__device__ __forceinline__ float lds32f(uint32_t a) {
    float v;
    asm volatile("ld.shared.f32 %0, [%1];" : "=f"(v) : "r"(a) : "memory");
    return v;
}
#define F8(d, b) \
    "+f"(d[b]), "+f"(d[b + 1]), "+f"(d[b + 2]), "+f"(d[b + 3]), "+f"(d[b + 4]), "+f"(d[b + 5]), "+f"(d[b + 6]), "+f"(d[b + 7])

template <int TB>
__device__ __forceinline__ void wgmma_n128(float (&d)[64], uint32_t a0, uint32_t a1, uint32_t a2, uint32_t a3,
                                           uint64_t db, int sc) {
    asm volatile(
        "{\n.reg .pred p;\nsetp.ne.b32 p, %69, 0;\n"
        "wgmma.mma_async.sync.aligned.m64n128k16.f32.bf16.bf16 "
        "{%0,%1,%2,%3,%4,%5,%6,%7,%8,%9,%10,%11,%12,%13,%14,%15,%16,%17,%18,%19,%20,%21,%22,%23,%24,%25,%26,%27,%28,%29,%30,%31,"
        "%32,%33,%34,%35,%36,%37,%38,%39,%40,%41,%42,%43,%44,%45,%46,%47,%48,%49,%50,%51,%52,%53,%54,%55,%56,%57,%58,%59,%60,%61,%62,%63},"
        "{%64,%65,%66,%67}, %68, p, 1, 1, %70;\n}"
        : F8(d, 0), F8(d, 8), F8(d, 16), F8(d, 24), F8(d, 32), F8(d, 40), F8(d, 48), F8(d, 56)
        : "r"(a0), "r"(a1), "r"(a2), "r"(a3), "l"(db), "r"(sc), "n"(TB));
}
#define O8(d, b) \
    "=f"(d[b]), "=f"(d[b + 1]), "=f"(d[b + 2]), "=f"(d[b + 3]), "=f"(d[b + 4]), "=f"(d[b + 5]), "=f"(d[b + 6]), "=f"(d[b + 7])
template <int TB>
__device__ __forceinline__ void wgmma_n128_z(float (&d)[64], uint32_t a0, uint32_t a1, uint32_t a2, uint32_t a3,
                                             uint64_t db) {
    asm volatile(
        "wgmma.mma_async.sync.aligned.m64n128k16.f32.bf16.bf16 "
        "{%0,%1,%2,%3,%4,%5,%6,%7,%8,%9,%10,%11,%12,%13,%14,%15,%16,%17,%18,%19,%20,%21,%22,%23,%24,%25,%26,%27,%28,%29,%30,%31,"
        "%32,%33,%34,%35,%36,%37,%38,%39,%40,%41,%42,%43,%44,%45,%46,%47,%48,%49,%50,%51,%52,%53,%54,%55,%56,%57,%58,%59,%60,%61,%62,%63},"
        "{%64,%65,%66,%67}, %68, 0, 1, 1, %69;"
        : O8(d, 0), O8(d, 8), O8(d, 16), O8(d, 24), O8(d, 32), O8(d, 40), O8(d, 48), O8(d, 56)
        : "r"(a0), "r"(a1), "r"(a2), "r"(a3), "l"(db), "n"(TB));
}
template <int TB>
__device__ __forceinline__ void wgmma_n64_z(float (&d)[32], uint32_t a0, uint32_t a1, uint32_t a2, uint32_t a3,
                                            uint64_t db) {
    asm volatile(
        "wgmma.mma_async.sync.aligned.m64n64k16.f32.bf16.bf16 "
        "{%0,%1,%2,%3,%4,%5,%6,%7,%8,%9,%10,%11,%12,%13,%14,%15,%16,%17,%18,%19,%20,%21,%22,%23,%24,%25,%26,%27,%28,%29,%30,%31},"
        "{%32,%33,%34,%35}, %36, 0, 1, 1, %37;"
        : O8(d, 0), O8(d, 8), O8(d, 16), O8(d, 24)
        : "r"(a0), "r"(a1), "r"(a2), "r"(a3), "l"(db), "n"(TB));
}
template <int TB>
__device__ __forceinline__ void wgmma_n64(float (&d)[32], uint32_t a0, uint32_t a1, uint32_t a2, uint32_t a3,
                                          uint64_t db) {
    asm volatile(
        "wgmma.mma_async.sync.aligned.m64n64k16.f32.bf16.bf16 "
        "{%0,%1,%2,%3,%4,%5,%6,%7,%8,%9,%10,%11,%12,%13,%14,%15,%16,%17,%18,%19,%20,%21,%22,%23,%24,%25,%26,%27,%28,%29,%30,%31},"
        "{%32,%33,%34,%35}, %36, 1, 1, 1, %37;"
        : F8(d, 0), F8(d, 8), F8(d, 16), F8(d, 24)
        : "r"(a0), "r"(a1), "r"(a2), "r"(a3), "l"(db), "n"(TB));
}

__device__ __forceinline__ uint64_t desc_of(uint32_t saddr) {
    return (uint64_t)(((saddr >> 4) & 0x3FFFu) | (512u << 16)) | ((uint64_t)(64u | (1u << 30)) << 32);
}

struct Ring {
    uint32_t slot;
    uint32_t phase;
    __device__ __forceinline__ void next() {
        if (++slot == 8) {
            slot = 0;
            phase ^= 1;
        }
    }
};

struct Ctx {
    uint32_t sbase;
    int wg;
    uint32_t rel_cta;
    __device__ __forceinline__ void wait_full(uint32_t slot, uint32_t phase) const {
        mbar_wait(sbase + OFF_FULL + slot * 8, phase);
    }
    __device__ __forceinline__ void release(uint32_t slot) const {
        if (rel_cta < 2) mbar_arrive_cluster(sbase + OFF_EMPTY + slot * 8, rel_cta);
    }
};

__device__ __forceinline__ void gemm_n128(float (&d)[64], const uint32_t (&a)[144], const Ctx& c, Ring& r, bool nine) {
    uint32_t prev = 0;
#pragma unroll
    for (int s = 0; s < 9; s++) {
        if (s < 8 || nine) {
            if (s == GATE_SLOT) bar_sync(8 + c.wg, 256);
            c.wait_full(r.slot, r.phase);
            uint64_t db = desc_of(c.sbase + r.slot * SLOT_BYTES);
            wg_fence();
#pragma unroll
            for (int k = 0; k < 4; k++) {
                if ((s | k) == 0)
                    wgmma_n128_z<1>(d, a[0], a[1], a[2], a[3], db);
                else
                    wgmma_n128<1>(d, a[s * 16 + k * 4], a[s * 16 + k * 4 + 1], a[s * 16 + k * 4 + 2],
                                  a[s * 16 + k * 4 + 3], db + k * 128, 1);
            }
            wg_commit();
            if (s == 8 || (s == 7 && !nine)) bar_arrive(9 - c.wg, 256);
            if (s > 0) {
                wg_wait<1>();
                c.release(prev);
            }
            prev = r.slot;
            r.next();
        }
    }
    wg_wait<0>();
    c.release(prev);
    pin(d);
}
__device__ __forceinline__ void gemm_n64(float (&d)[32], const uint32_t (&a)[144], const Ctx& c, Ring& r, bool nine) {
    uint32_t prev = 0;
#pragma unroll
    for (int s = 0; s < 5; s++) {
        if (s < 4 || nine) {
            c.wait_full(r.slot, r.phase);
            uint64_t db = desc_of(c.sbase + r.slot * SLOT_BYTES);
            wg_fence();
#pragma unroll
            for (int k = 0; k < 8; k++) {
                if ((s | k) == 0)
                    wgmma_n64_z<1>(d, a[0], a[1], a[2], a[3], db);
                else if (s * 8 + k < 36)
                    wgmma_n64<1>(d, a[s * 32 + k * 4], a[s * 32 + k * 4 + 1], a[s * 32 + k * 4 + 2],
                                 a[s * 32 + k * 4 + 3], db + k * 128);
            }
            wg_commit();
            if (s > 0) {
                wg_wait<1>();
                c.release(prev);
            }
            prev = r.slot;
            r.next();
        }
    }
    wg_wait<0>();
    c.release(prev);
    pin(d);
}
__device__ __forceinline__ void st128(uint4* p, uint32_t x, uint32_t y, uint32_t z, uint32_t w) {
    asm volatile(
        "{\n.reg .b64 lo, hi;\n.reg .b128 t;\nmov.b64 lo, {%1, %2};\nmov.b64 hi, {%3, %4};\nmov.b128 t, {lo, hi};\n"
        "st.relaxed.gpu.global.b128 [%0], t;\n}" ::"l"(p),
        "r"(x), "r"(y), "r"(z), "r"(w)
        : "memory");
}
__device__ __forceinline__ uint4 ld128(const uint4* p) {
    uint4 r;
    asm volatile(
        "{\n.reg .b64 lo, hi;\n.reg .b128 t;\nld.relaxed.gpu.global.b128 t, [%4];\nmov.b128 {lo, hi}, t;\n"
        "mov.b64 {%0, %1}, lo;\nmov.b64 {%2, %3}, hi;\n}"
        : "=r"(r.x), "=r"(r.y), "=r"(r.z), "=r"(r.w)
        : "l"(p));
    return r;
}
__device__ __forceinline__ uint4 ldg128(const uint4* p) {
    uint4 r;
    asm volatile("ld.global.nc.v4.u32 {%0,%1,%2,%3}, [%4];" : "=r"(r.x), "=r"(r.y), "=r"(r.z), "=r"(r.w) : "l"(p));
    return r;
}
__device__ __forceinline__ void st64(void* p, uint32_t x, uint32_t y) {
    asm volatile("{\n.reg .b64 t;\nmov.b64 t, {%1, %2};\nst.relaxed.gpu.global.b64 [%0], t;\n}" ::"l"(p), "r"(x), "r"(y)
                 : "memory");
}
__device__ __forceinline__ uint2 ld64(const void* p) {
    uint2 r;
    asm volatile("{\n.reg .b64 t;\nld.relaxed.gpu.global.b64 t, [%2];\nmov.b64 {%0, %1}, t;\n}"
                 : "=r"(r.x), "=r"(r.y)
                 : "l"(p));
    return r;
}
__device__ __forceinline__ void rows_load(uint32_t sbase, const CUtensorMap* m, int row0) {
    mbar_expect_tx(sbase + OFF_XBAR, 16 * DM * 2);
    asm volatile(
        "cp.async.bulk.tensor.3d.shared::cluster.global.mbarrier::complete_tx::bytes [%0], [%1, {%3, %3, %4}], [%2];" ::"r"(
            sbase + OFF_ROWS),
        "l"(m), "r"(sbase + OFF_XBAR), "r"(0), "r"(row0)
        : "memory");
}
__device__ __forceinline__ void rows_store(uint32_t sbase, const CUtensorMap* m, int row0) {
    asm volatile("cp.async.bulk.tensor.3d.global.shared::cta.bulk_group [%0, {%2, %2, %3}], [%1];" ::"l"(m),
                 "r"(sbase + OFF_ROWS), "r"(0), "r"(row0)
                 : "memory");
    asm volatile("cp.async.bulk.commit_group;" ::: "memory");
}
__device__ __forceinline__ void rows_store_wait() { asm volatile("cp.async.bulk.wait_group 0;" ::: "memory"); }

__device__ __forceinline__ constexpr int own_col(int j) { return j < 8 ? (j >> 1) * 128 + (j & 1) * 8 : 512; }
__device__ __forceinline__ void row_reduce(float& s0, float& s1, uint32_t red, int warp, int lane) {
    s0 += __shfl_xor_sync(0xffffffffu, s0, 1);
    s1 += __shfl_xor_sync(0xffffffffu, s1, 1);
    s0 += __shfl_xor_sync(0xffffffffu, s0, 2);
    s1 += __shfl_xor_sync(0xffffffffu, s1, 2);
    if ((lane & 3) == 0) {
        sts32f(red + (warp * 16 + (lane >> 2)) * 4, s0);
        sts32f(red + (warp * 16 + 8 + (lane >> 2)) * 4, s1);
    }
    bar_sync(3, 256);
    s0 = 0.f;
    s1 = 0.f;
#pragma unroll
    for (int w = 0; w < 8; w++) {
        s0 += lds32f(red + (w * 16 + (lane >> 2)) * 4);
        s1 += lds32f(red + (w * 16 + 8 + (lane >> 2)) * 4);
    }
}
template <class F>
__device__ __forceinline__ void layernorm_rows(float (&v)[36], uint32_t red, int warp, int lane, F&& middle) {
    float s0 = 0.f, s1 = 0.f;
#pragma unroll
    for (int j = 0; j < 9; j++) {
        s0 += v[4 * j] + v[4 * j + 1];
        s1 += v[4 * j + 2] + v[4 * j + 3];
    }
    row_reduce(s0, s1, red, warp, lane);
    middle();
    const float m0 = s0 * (1.f / DM), m1 = s1 * (1.f / DM);
    s0 = 0.f;
    s1 = 0.f;
#pragma unroll
    for (int j = 0; j < 9; j++) {
        v[4 * j] -= m0;
        v[4 * j + 1] -= m0;
        v[4 * j + 2] -= m1;
        v[4 * j + 3] -= m1;
        s0 += v[4 * j] * v[4 * j] + v[4 * j + 1] * v[4 * j + 1];
        s1 += v[4 * j + 2] * v[4 * j + 2] + v[4 * j + 3] * v[4 * j + 3];
    }
    row_reduce(s0, s1, red + 512, warp, lane);
    const float r0 = rsqrtf(s0 * (1.f / DM) + 1e-5f), r1 = rsqrtf(s1 * (1.f / DM) + 1e-5f);
#pragma unroll
    for (int j = 0; j < 9; j++) {
        v[4 * j] *= r0;
        v[4 * j + 1] *= r0;
        v[4 * j + 2] *= r1;
        v[4 * j + 3] *= r1;
    }
}
__device__ __forceinline__ void mod_to_smem(uint32_t dst, const uint32_t* src, uint32_t tag) {
    const uint32_t t0 = clk32();
    uint4 u;
    while (true) {
        u = ld128(reinterpret_cast<const uint4*>(src));
        const uint32_t bad = ((u.x ^ tag) | (u.y ^ tag) | (u.z ^ tag) | (u.w ^ tag)) & 0xffffu;
        if (__all_sync(0xffffffffu, bad == 0) || clk32() - t0 > WAIT_LIMIT) break;
        __nanosleep(64);
    }
    sts128(dst, u.x & 0xffff0000u, u.y & 0xffff0000u, u.z & 0xffff0000u, u.w & 0xffff0000u);
}
__device__ __forceinline__ void lds_mod(float (&m)[18], uint32_t src  , int warp) {
#pragma unroll
    for (int j = 0; j < 9; j++)
        asm volatile("ld.shared.v2.f32 {%0,%1}, [%2];"
                     : "=f"(m[2 * j]), "=f"(m[2 * j + 1])
                     : "r"(src + own_col(j) * 4 - (j == 8 ? warp * 32 : 0))
                     : "memory");
}
__device__ __forceinline__ void modulate_store(const float (&v)[36], const float (&shift)[18], const float (&scale)[18],
                                               uint4* hbuf  , int warp, int lane) {
    uint32_t o[18];
#pragma unroll
    for (int j = 0; j < 9; j++) {
        const uint32_t cc = pack_bf16(1.f + scale[2 * j], 1.f + scale[2 * j + 1]);
        const float c0 = bf_lo(cc), c1 = bf_hi(cc);
        o[2 * j] = max(pack_bf16(fmaf(v[4 * j], c0, shift[2 * j]), fmaf(v[4 * j + 1], c1, shift[2 * j + 1])), 1u);
        o[2 * j + 1] = max(pack_bf16(fmaf(v[4 * j + 2], c0, shift[2 * j]), fmaf(v[4 * j + 3], c1, shift[2 * j + 1])), 1u);
    }
#pragma unroll
    for (int i = 0; i < 4; i++) st128(hbuf + (i * 8 + warp) * 32 + lane, o[4 * i], o[4 * i + 1], o[4 * i + 2], o[4 * i + 3]);
    st64(reinterpret_cast<uint2*>(hbuf + 32 * 32) + warp * 32 + lane, o[16], o[17]);
}
__device__ __forceinline__ void sum_partials(float (&v)[36], const uint4* src  , uint32_t tag) {
    const uint32_t t0 = clk32();
    while (true) {
        uint4 t[8][4];
#pragma unroll
        for (int s = 0; s < 8; s++)
#pragma unroll
            for (int i = 0; i < 4; i++) t[s][i] = ld128(src + (s * 36 + i * 8) * 32);
        uint32_t bad = 0;
#pragma unroll
        for (int i = 0; i < 32; i++) v[i] = 0.f;
#pragma unroll
        for (int s = 0; s < 8; s++)
#pragma unroll
            for (int i = 0; i < 4; i++) {
                bad |= t[s][i].x ^ tag;
                v[8 * i] += bf_lo(t[s][i].x);
                v[8 * i + 1] += bf_hi(t[s][i].x);
                v[8 * i + 2] += bf_lo(t[s][i].y);
                v[8 * i + 3] += bf_hi(t[s][i].y);
                v[8 * i + 4] += bf_lo(t[s][i].z);
                v[8 * i + 5] += bf_hi(t[s][i].z);
                v[8 * i + 6] += bf_lo(t[s][i].w);
                v[8 * i + 7] += bf_hi(t[s][i].w);
            }
        if (__all_sync(0xffffffffu, (bad & 1u) == 0) || clk32() - t0 > WAIT_LIMIT) break;
    }
}
__device__ __forceinline__ void sum_tail(float (&v)[36], const uint2* src  , uint32_t tag) {
    const uint32_t t0 = clk32();
    while (true) {
        uint2 t[8];
#pragma unroll
        for (int s = 0; s < 8; s++) t[s] = ld64(src + s * 72 * 32);
        uint32_t bad = 0;
        v[32] = v[33] = v[34] = v[35] = 0.f;
#pragma unroll
        for (int s = 0; s < 8; s++) {
            bad |= t[s].x ^ tag;
            v[32] += bf_lo(t[s].x);
            v[33] += bf_hi(t[s].x);
            v[34] += bf_lo(t[s].y);
            v[35] += bf_hi(t[s].y);
        }
        if (__all_sync(0xffffffffu, (bad & 1u) == 0) || clk32() - t0 > WAIT_LIMIT) break;
    }
}
__device__ __forceinline__ void poll_tail(uint32_t (&a)[144], const uint2* src  ) {
    const uint32_t t0 = clk32();
    while (true) {
        uint32_t m = 0xffffffffu;
#pragma unroll
        for (int j = 0; j < 8; j++) {
            const uint2 t = ld64(src + j * 32);
            a[128 + 2 * j] = t.x;
            a[129 + 2 * j] = t.y;
        }
#pragma unroll
        for (int j = 0; j < 16; j++) m = min(m, a[128 + j]);
        if (__all_sync(0xffffffffu, m != 0) || clk32() - t0 > WAIT_LIMIT) break;
    }
}
template <int K0, int K1>
__device__ __forceinline__ void poll_frags(uint32_t (&a)[144], const uint4* src  , bool kick) {
    const uint32_t t0 = clk32();
    while (true) {
#pragma unroll
        for (int k = K0; k < K1; k++)
            asm volatile("ld.relaxed.gpu.global.v4.u32 {%0,%1,%2,%3}, [%4];"
                         : "=r"(a[4 * k]), "=r"(a[4 * k + 1]), "=r"(a[4 * k + 2]), "=r"(a[4 * k + 3])
                         : "l"(src + k * 32));
        if (kick) bar_arrive(5, 256);
        kick = false;
        uint32_t m0 = a[4 * K0], m1 = a[4 * K0 + 1];
#pragma unroll
        for (int i = 4 * K0 + 2; i < 4 * K1; i += 2) {
            m0 = min(m0, a[i]);
            m1 = min(m1, a[i + 1]);
        }
        if (__all_sync(0xffffffffu, min(m0, m1) != 0) || clk32() - t0 > WAIT_LIMIT) break;
    }
}

constexpr float SM_SCALE = 0.08838834764831845f * 1.4426950408889634f;
constexpr float SM_HI = 1.2089258e24f;
constexpr float SM_LO = 9.0949470e-13f;
__device__ __forceinline__ void qk_step(float (&s)[32], const uint32_t (&q)[32], uint64_t dk) {
#pragma unroll
    for (int k = 0; k < 8; k++) {
        if (k == 0)
            wgmma_n64_z<0>(s, q[0], q[1], q[2], q[3], dk);
        else
            wgmma_n64<0>(s, q[4 * k], q[4 * k + 1], q[4 * k + 2], q[4 * k + 3], dk + (k >> 2) * 512 + (k & 3) * 2);
    }
}
__device__ __forceinline__ void pv_step(float (&o)[64], const uint32_t (&p)[16], uint64_t dv, int acc) {
#pragma unroll
    for (int k = 0; k < 4; k++)
        wgmma_n128<1>(o, p[4 * k], p[4 * k + 1], p[4 * k + 2], p[4 * k + 3], dv + k * 128, k != 0 ? 1 : acc);
}
template <bool SHIFT>
__device__ __forceinline__ void exp_step(const float (&s)[32], uint32_t (&p)[16], float n0, float n1, float& s0,
                                         float& s1) {
#pragma unroll
    for (int i = 0; i < 8; i++) {
        const float e0 = ex2(SHIFT ? s[4 * i] + n0 : s[4 * i]), e1 = ex2(SHIFT ? s[4 * i + 1] + n0 : s[4 * i + 1]);
        const float e2 = ex2(SHIFT ? s[4 * i + 2] + n1 : s[4 * i + 2]), e3 = ex2(SHIFT ? s[4 * i + 3] + n1 : s[4 * i + 3]);
        if (i == 0) {
            s0 = e0 + e1;
            s1 = e2 + e3;
        } else {
            s0 += e0 + e1;
            s1 += e2 + e3;
        }
        p[2 * i] = pack_bf16(e0, e1);
        p[2 * i + 1] = pack_bf16(e2, e3);
    }
}
__device__ __forceinline__ void row_max(const float (&sa)[32], const float (&sb)[32], float& x0, float& x1) {
    float xa[8];
#pragma unroll
    for (int i = 0; i < 8; i++) xa[i] = fmaxf(sa[i], sb[i]);
#pragma unroll
    for (int k = 1; k < 4; k++)
#pragma unroll
        for (int i = 0; i < 8; i++) xa[i] = fmaxf(xa[i], fmaxf(sa[8 * k + i], sb[8 * k + i]));
    x0 = fmaxf(fmaxf(xa[0], xa[1]), fmaxf(xa[4], xa[5]));
    x1 = fmaxf(fmaxf(xa[2], xa[3]), fmaxf(xa[6], xa[7]));
    x0 = fmaxf(x0, __shfl_xor_sync(0xffffffffu, x0, 1));
    x1 = fmaxf(x1, __shfl_xor_sync(0xffffffffu, x1, 1));
    x0 = fmaxf(x0, __shfl_xor_sync(0xffffffffu, x0, 2));
    x1 = fmaxf(x1, __shfl_xor_sync(0xffffffffu, x1, 2));
}
__device__ __forceinline__ void inv_row_sums(float l0, float l1, float& i0, float& i1) {
    l0 += __shfl_xor_sync(0xffffffffu, l0, 1);
    l1 += __shfl_xor_sync(0xffffffffu, l1, 1);
    l0 += __shfl_xor_sync(0xffffffffu, l0, 2);
    l1 += __shfl_xor_sync(0xffffffffu, l1, 2);
    i0 = rcp(l0);
    i1 = rcp(l1);
}

__device__ __forceinline__ uint32_t get_epoch(uint32_t sbase) { return __float_as_uint(lds32f(sbase + OFF_EPOCH)); }
__device__ __forceinline__ float silu_bf16(unsigned short c) {
    const float cv = bf_lo(c);
    return round_bf16(cv * rcp(1.f + ex2(-1.4426950408889634f * cv)));
}
__device__ __forceinline__ void st_mod(uint32_t* p, float v, uint32_t tag) {
    asm volatile("st.relaxed.gpu.global.u32 [%0], %1;" ::"l"(p), "r"(__float_as_uint(round_bf16(v)) | tag)
                 : "memory");
}
__device__ __forceinline__ void fma8(float (&acc)[8], float sc, const uint4& w) {
    acc[0] = fmaf(sc, bf_lo(w.x), acc[0]);
    acc[1] = fmaf(sc, bf_hi(w.x), acc[1]);
    acc[2] = fmaf(sc, bf_lo(w.y), acc[2]);
    acc[3] = fmaf(sc, bf_hi(w.y), acc[3]);
    acc[4] = fmaf(sc, bf_lo(w.z), acc[4]);
    acc[5] = fmaf(sc, bf_hi(w.z), acc[5]);
    acc[6] = fmaf(sc, bf_lo(w.w), acc[6]);
    acc[7] = fmaf(sc, bf_hi(w.w), acc[7]);
}
__device__ __forceinline__ void modp_load(uint4 (&u)[6], const uint32_t* src) {
#pragma unroll
    for (int i = 0; i < 6; i++) u[i] = ld128(reinterpret_cast<const uint4*>(src + i * 2 * DM));
}
__device__ __forceinline__ void modp_to_smem(uint4 (&u)[6], uint32_t dst, const uint32_t* src, uint32_t tag) {
    const uint32_t t0 = clk32();
    while (true) {
        uint32_t bad = 0;
#pragma unroll
        for (int i = 0; i < 6; i++) bad |= (u[i].x ^ tag) | (u[i].y ^ tag) | (u[i].z ^ tag) | (u[i].w ^ tag);
        if (__all_sync(0xffffffffu, (bad & 0xffu) == 0) || clk32() - t0 > WAIT_LIMIT) break;
        modp_load(u, src);
    }
    float s0 = 0.f, s1 = 0.f, s2 = 0.f, s3 = 0.f;
#pragma unroll
    for (int i = 0; i < 6; i++) {
        s0 += __uint_as_float(u[i].x & ~0xffu);
        s1 += __uint_as_float(u[i].y & ~0xffu);
        s2 += __uint_as_float(u[i].z & ~0xffu);
        s3 += __uint_as_float(u[i].w & ~0xffu);
    }
    const uint32_t p0 = pack_bf16(s0, s1), p1 = pack_bf16(s2, s3);
    sts128(dst, p0 << 16, p0 & 0xffff0000u, p1 << 16, p1 & 0xffff0000u);
}

__global__ void __cluster_dims__(2, 1, 1) __launch_bounds__(384, 1)
    fused_block_kernel(const __grid_constant__ Params maps) {
    extern __shared__ uint8_t smem_raw[];
    uint32_t sbase = (smem_u32(smem_raw) + 1023u) & ~1023u;
    asm volatile("" : "+r"(sbase));
    const int b = blockIdx.x;
    const int rank = b & 1;
    const int mt = ((b >> 1) & 7) * 2 + rank;
    const int g = b >> 4;
    const int warp = __shfl_sync(0xffffffffu, threadIdx.x >> 5, 0);
    const int lane = threadIdx.x & 31;
    Scratch* const sc_ = maps.sc;
    const __nv_bfloat16* const wmod = maps.wmod;
    const __nv_bfloat16* const cvec = maps.cvec;

#define SPROF(i)

    if (warp >= 8) {
        asm volatile("setmaxnreg.dec.sync.aligned.u32 24;");
        if (warp == 8 && lane == 0) {
#pragma unroll
            for (int i = 0; i < 8; i++) {
                mbar_init(sbase + OFF_FULL + i * 8, 1);
                mbar_init(sbase + OFF_EMPTY + i * 8, 4);
            }
            mbar_init(sbase + OFF_XBAR, 1);
            asm volatile("fence.mbarrier_init.release.cluster;" ::: "memory");
            asm volatile("barrier.cluster.arrive.relaxed;\nbarrier.cluster.wait;" ::: "memory");
            uint32_t slot = 0, phase = 1;
            const uint32_t dst0 = sbase + rank * BOX_BYTES;
            auto acquire = [&](uint32_t bytes) {
                mbar_wait(sbase + OFF_EMPTY + slot * 8, phase);
                mbar_expect_tx(sbase + OFF_FULL + slot * 8, bytes);
            };
            auto adv8 = [&]() {
                if (++slot == 8) {
                    slot = 0;
                    phase ^= 1;
                }
            };
#pragma unroll 1
            for (int hq = 0; hq < 4; hq++) {
                const int col = (g * 4 + ((hq + 1) & 3)) * 128 + rank * 64;
                if (hq == 2) {
                    l2_prefetch(maps.kc + (size_t)(g * 4 * 2048 + (b & 15) * 64) * 128, SLOT_BYTES);
                    l2_prefetch(maps.vc + (size_t)(g * 4 * 2048 + (b & 15) * 64) * 128, SLOT_BYTES);
                }
#pragma unroll 1
                for (int kc = 0; kc < 9; kc++) {
                    acquire(SLOT_BYTES);
                    tma_mc(dst0 + slot * SLOT_BYTES, &maps.wq, col, kc * 64, sbase + OFF_FULL + slot * 8);
                    adv8();
                }
            }
            const int row0 = g * 4 * 2048;
#pragma unroll 1
            for (int n = 0; n < 128; n++) {
                if (n < 4) mbar_wait(sbase + OFF_EMPTY + (slot + 1) * 8, phase);
                acquire(2 * SLOT_BYTES);
                const uint32_t bar = sbase + OFF_FULL + slot * 8;
                const int r0 = n == 0 ? 0 : (n == 127 ? 126 : n + 1);
                const int r1 = n == 0 ? 1 : (n == 127 ? 127 : n - 1);
                tma_mc(dst0 + slot * SLOT_BYTES, n == 127 ? &maps.v : &maps.k, rank * 64, row0 + r0 * 64, bar);
                tma_mc(dst0 + (slot + 1) * SLOT_BYTES, n == 0 ? &maps.k : &maps.v, rank * 64, row0 + r1 * 64, bar);
                adv8();
                adv8();
                if (n >= 96 && n < 96 + 10) {
                    const int i = n - 96;
                    if (i < 9) {
                        l2_prefetch((const char*)maps.wg_p + (size_t)b * 41472 + i * 4608, 4608);
                        l2_prefetch((const char*)maps.wu_p + (size_t)b * 41472 + i * 4608, 4608);
                        l2_prefetch((const char*)maps.wd_p + (size_t)b * 41472 + i * 4608, 4608);
                        l2_prefetch((const char*)maps.wo_p + (size_t)b * 36864 + i * 4096, 4096);
                    }
                }
                const int u = n + KV_AHEAD;
                if (u < 128 && (u & 15) == (b & 15)) {
                    l2_prefetch(maps.kc + (size_t)(row0 + u * 64) * 128, SLOT_BYTES);
                    l2_prefetch(maps.vc + (size_t)(row0 + u * 64) * 128, SLOT_BYTES);
                }
            }
#pragma unroll 1
            for (int p = 0; p < 4; p++)
#pragma unroll 1
                for (int kc = 0; kc < 8; kc++) {
                    acquire(SLOT_BYTES);
                    tma_mc(dst0 + slot * SLOT_BYTES, &maps.wo, p * 128 + rank * 64, g * 512 + kc * 64,
                           sbase + OFF_FULL + slot * 8);
                    adv8();
                }
#pragma unroll 1
            for (int kc = 0; kc < 4; kc++) {
                acquire(SLOT_BYTES);
                tma_mc(dst0 + slot * SLOT_BYTES, &maps.wo, 512, g * 512 + kc * 128 + rank * 64,
                       sbase + OFF_FULL + slot * 8);
                adv8();
            }
            const CUtensorMap* mg = rank ? &maps.wu : &maps.wg;
#pragma unroll 1
            for (int ch = 0; ch < 9; ch++)
#pragma unroll 1
                for (int kc = 0; kc < 9; kc++) {
                    acquire(SLOT_BYTES);
                    tma_mc(dst0 + slot * SLOT_BYTES, mg, g * 576 + ch * 64, kc * 64, sbase + OFF_FULL + slot * 8);
                    adv8();
                }
#pragma unroll 1
            for (int p = 0; p < 4; p++)
#pragma unroll 1
                for (int kc = 2; kc < 11; kc++) {
                    acquire(SLOT_BYTES);
                    tma_mc(dst0 + slot * SLOT_BYTES, &maps.wd, p * 128 + rank * 64, g * 576 + (kc < 9 ? kc : kc - 9) * 64,
                           sbase + OFF_FULL + slot * 8);
                    adv8();
                }
#pragma unroll 1
            for (int i = 0; i < 5; i++) {
                acquire(i < 4 ? SLOT_BYTES : BOX_BYTES);
                const int kc = 2 * i + rank + 2;
                if (i < 4 || rank == 0)
                    tma_mc(dst0 + slot * SLOT_BYTES, &maps.wd, 512, g * 576 + (kc < 9 ? kc : kc - 9) * 64,
                           sbase + OFF_FULL + slot * 8);
                adv8();
            }
        } else if (warp == 11) {
            asm volatile("barrier.cluster.arrive.relaxed.aligned;" ::: "memory");
            bar_sync(6, 160);
            uint4* hz = sc_->h[(get_epoch(sbase) & 1) ^ 1][0] + (size_t)b * 72 * 32 + lane;
#pragma unroll 1
            for (int i = 0; i < 72; i++) {
                hz[i * 32] = make_uint4(0, 0, 0, 0);
                __nanosleep(200);
            }
        } else if (warp == 9 || warp == 10) {
            asm volatile("barrier.cluster.arrive.relaxed.aligned;" ::: "memory");
            bar_sync(4, 320);
            const uint32_t tag = (get_epoch(sbase) + 1) & 0xffffu;
            if (warp == 10 && lane < 9) l2_prefetch((const char*)maps.wq_p + (size_t)b * 36864 + lane * 4096, 4096);
            const int blk = warp == 9 ? 72 + b : 200 + b;
            if (blk < 216) {
                float acc[8];
#pragma unroll
                for (int e = 0; e < 8; e++) acc[e] = 0.f;
                const uint4* wp = reinterpret_cast<const uint4*>(wmod + (size_t)(lane >> 1) * (6 * DM) + blk * 16) + (lane & 1);
                const unsigned short* cp = reinterpret_cast<const unsigned short*>(cvec) + (lane >> 1);
#pragma unroll 1
                for (int i = 0; i < 36; i++) {
                    const uint4 w = __ldg(wp + (size_t)i * (16 * 6 * DM / 8));
                    const float sc = silu_bf16(__ldg(cp + i * 16));
                    fma8(acc, sc, w);
                }
#pragma unroll
                for (int o = 2; o < 32; o <<= 1)
#pragma unroll
                    for (int e = 0; e < 8; e++) acc[e] += __shfl_xor_sync(0xffffffffu, acc[e], o);
                if (lane < 2) {
#pragma unroll
                    for (int e = 0; e < 8; e++) st_mod(sc_->mod + blk * 16 + lane * 8 + e, acc[e], tag);
                }
            }
            if (warp == 9) {
#pragma unroll 1
                for (int st = 1; st <= 2; st++) {
                    bar_sync(7, 160);
                    const uint32_t* src = sc_->mod + (st * 3 - 1) * DM;
                    const int n = st == 1 ? 3 * DM : DM;
#pragma unroll 1
                    for (int i = lane * 4; i < n + 127 - ((n + 127) & 127); i += 128)
                        mod_to_smem(sbase + OFF_MODT + min(i, n - 4) * 4, src + min(i, n - 4), tag);
                    __syncwarp();
                    if (lane == 0) rows_load(sbase, st == 1 ? &maps.rx : &maps.rx2, (mt * 8 + g) * 16);
                    if (st == 1) {
                        bar_sync(7, 160);
                        if (lane == 0) {
                            rows_store(sbase, &maps.rx2, (mt * 8 + g) * 16);
                            rows_store_wait();
                        }
                        __syncwarp();
                        bar_arrive(10, 160);
                    }
                }
            }
        }
    } else {
        uint4 w1[3], xw[5], ew = make_uint4(0, 0, 0, 0);
        unsigned short cu[3];
        {
            const int t = threadIdx.x, bw = min(b, 107);
            const int row = (bw / 18) * 96 + (t >> 3);
#pragma unroll
            for (int i = 0; i < 3; i++) {
                w1[i] = ldg128(reinterpret_cast<const uint4*>(wmod + (size_t)(row + 32 * i) * (6 * DM)) + (bw % 18) * 8 + (t & 7));
                asm volatile("ld.global.nc.u16 %0, [%1];" : "=h"(cu[i]) : "l"(cvec + row + 32 * i));
            }
            if (t == 0) ew = ld128(reinterpret_cast<const uint4*>(&sc_->epoch[b * 32]));
#pragma unroll
            for (int i = 0; i < 5; i++)
                xw[i] = ldg128(reinterpret_cast<const uint4*>(maps.x + (size_t)(mt * 8 + g) * 16 * DM) + min(t + 256 * i, 1151));
        }
        if (threadIdx.x == 160) SPROF(5);
        asm volatile("setmaxnreg.inc.sync.aligned.u32 240;");
        if (threadIdx.x == 160) SPROF(6);
        const int wg = warp >> 2;
        const int tid = threadIdx.x;
        Ctx cx;
        cx.sbase = sbase;
        cx.wg = wg;
        if (wg == 1) bar_arrive(8, 256);
        cx.rel_cta = (lane == 0 && (warp & 3) < 2) ? (warp & 3) : 2;
        const uint32_t red = sbase + OFF_RED;
        const int own = mt * 8 + g;
        const int wown = mt * 8 + warp;
        PROF(0);
        PROFG(30);
        PROFR(17);
        {
            asm volatile("barrier.cluster.arrive.relaxed.aligned;" ::: "memory");
            float acc[8];
#pragma unroll
            for (int e = 0; e < 8; e++) acc[e] = 0.f;
#pragma unroll
            for (int i = 0; i < 3; i++) fma8(acc, silu_bf16(cu[i]), w1[i]);
#pragma unroll
            for (int o = 8; o < 32; o <<= 1)
#pragma unroll
                for (int e = 0; e < 8; e++) acc[e] += __shfl_xor_sync(0xffffffffu, acc[e], o);
            PROFR(19);
            if (lane < 8) {
                const uint32_t dst = sbase + OFF_MRED + warp * 256 + lane * 32;
                sts128(dst, __float_as_uint(acc[0]), __float_as_uint(acc[1]), __float_as_uint(acc[2]), __float_as_uint(acc[3]));
                sts128(dst + 16, __float_as_uint(acc[4]), __float_as_uint(acc[5]), __float_as_uint(acc[6]), __float_as_uint(acc[7]));
            }
            if (tid == 0) sts128(sbase + OFF_EPOCH, ew.x, ew.y, ew.z, ew.w);
            bar_sync(3, 256);
            PROFR(20);
            if (tid < 64 && b < 108) {
                float sum = 0.f;
#pragma unroll
                for (int w8 = 0; w8 < 8; w8++) sum += lds32f(sbase + OFF_MRED + w8 * 256 + tid * 4);
                asm volatile("st.relaxed.gpu.global.u32 [%0], %1;" ::"l"(&sc_->modp[b / 18][(b % 18) * 64 + tid]),
                             "r"((__float_as_uint(sum) & ~0xffu) | ((get_epoch(sbase) + 1) & 0xffu))
                             : "memory");
            }
            PROFR(21);
#pragma unroll
            for (int i = 0; i < 5; i++) {
                const int vi = min(tid + 256 * i, 1151), ln = vi >> 3;
                sts128(sbase + OFF_ROWS + ln * 128 + (((vi & 7) ^ (ln & 7)) << 4), xw[i].x, xw[i].y, xw[i].z, xw[i].w);
            }
            bar_sync(3, 256);
        }

        Ring ring{0u, 0u};
        int stage = 0;
        asm volatile("" : "+r"(stage));
#pragma unroll 1
        for (;; stage++) {
            int tid, lane;
            asm volatile("mov.u32 %0, %%tid.x;" : "=r"(tid));
            lane = tid & 31;
            const uint32_t epoch = get_epoch(sbase);
            {
                float v[36];
                const uint32_t modt = sbase + OFF_MODT + (warp * 16 + (lane & 3) * 2) * 4;
                if (stage == 0) {
#pragma unroll
                    for (int i = 0; i < 36; i++) v[i] = 0.f;
                } else {
                    const uint4* psrc = sc_->part + (size_t)own * 8 * 36 * 32;
                    sum_partials(v, psrc + tid, stage & 1);
                    PROF(stage == 1 ? 8 : 15);
                    sum_tail(v, reinterpret_cast<const uint2*>(psrc + 32 * 32) + tid, stage & 1);
                }
                if (stage) mbar_wait(sbase + OFF_XBAR, stage - 1);
                if (stage == 0) PROFR(22);
                {
                    const float gs = stage == 2 ? 0.5f : 1.f;
                    float gate[18];
                    lds_mod(gate, modt, warp);
                    const int r = lane >> 2;
                    const uint32_t rows = sbase + OFF_ROWS + r * (DM * 2) + (lane & 3) * 4;
#pragma unroll
                    for (int j = 0; j < 9; j++) {
                        const int ch = j < 8 ? (j >> 1) * 2 + (warp >> 2) : 8, c16 = j < 8 ? (warp & 3) * 2 + (j & 1) : warp;
                        const uint32_t ad = rows + ch * 128 + ((c16 ^ ((r + ch) & 7)) << 4);
                        const uint32_t u0 = __float_as_uint(lds32f(ad)), u1 = __float_as_uint(lds32f(ad + 8 * DM * 2));
                        const float g0 = stage ? gate[2 * j] * gs : 0.f, g1 = stage ? gate[2 * j + 1] * gs : 0.f;
                        v[4 * j] = fmaf(g0, v[4 * j], bf_lo(u0));
                        v[4 * j + 1] = fmaf(g1, v[4 * j + 1], bf_hi(u0));
                        v[4 * j + 2] = fmaf(g0, v[4 * j + 2], bf_lo(u1));
                        v[4 * j + 3] = fmaf(g1, v[4 * j + 3], bf_hi(u1));
                        sts32f(ad, __uint_as_float(pack_bf16(v[4 * j], v[4 * j + 1])));
                        sts32f(ad + 8 * DM * 2, __uint_as_float(pack_bf16(v[4 * j + 2], v[4 * j + 3])));
                    }
                    asm volatile("fence.proxy.async.shared::cta;" ::: "memory");
                }
                if (stage == 2) break;
                PROF(stage == 0 ? 1 : 9);
                uint4 ua[6], ub[6];
#pragma unroll
                for (int i = 0; i < 6; i++) ua[i] = ub[i] = make_uint4(0, 0, 0, 0);
                layernorm_rows(v, red, warp, lane, [&]() {
                    if (stage == 0) {
                        modp_load(ua, sc_->modp[0] + tid * 4);
                        if (warp == 0) modp_load(ub, sc_->modp[0] + 1024 + tid * 4);
                    }
                });
                if (stage == 0) PROFR(27);
                if (stage == 0) {
                    const uint32_t tag = (epoch + 1) & 0xffu;
                    modp_to_smem(ua, sbase + OFF_MODT + (DM + tid * 4) * 4, sc_->modp[0] + tid * 4, tag);
                    if (warp == 0)
                        modp_to_smem(ub, sbase + OFF_MODT + (DM + 1024 + tid * 4) * 4, sc_->modp[0] + 1024 + tid * 4, tag);
                    bar_sync(3, 256);
                }
                float shift[18], scale[18];
                lds_mod(shift, modt + DM * 4, warp);
                lds_mod(scale, modt + 2 * DM * 4, warp);
                if (stage == 0) PROFR(28);
                PROF(stage == 0 ? 2 : 10);
                modulate_store(v, shift, scale, sc_->h[epoch & 1][stage] + (size_t)own * 36 * 32, warp, lane);
                if (stage == 0) asm volatile("barrier.cluster.wait.aligned;" ::: "memory");
            }

            const uint32_t spill = sbase + 8 * SLOT_BYTES + wg * 3 * SLOT_BYTES + (tid & 127) * 16;
            uint32_t a[144];
            PROF(stage == 0 ? 3 : 11);
            {
                const uint4* hsrc = sc_->h[epoch & 1][stage] + (size_t)wown * 36 * 32 + lane;
                __nanosleep(PROBE_NS);
                poll_tail(a, reinterpret_cast<const uint2*>(hsrc - lane + 32 * 32) + lane);
                PROF(stage == 0 ? 4 : 12);
                if (stage == 1) PROFG(25);
                TG(stage * 32 + 30);
                if (wg == 1) bar_sync(5, 256);
                poll_frags<0, 32>(a, hsrc, wg == 0);
                if (stage == 0) bar_arrive(4, 320);
            }
            uint4* hhbuf = sc_->hh + (size_t)b * 8 * 256 + tid;
            float d[64];
#pragma unroll 1
            for (int ch = 0;; ch++) {
                TG(stage * 32 + ch * 2);
                gemm_n128(d, a, cx, ring, true);
                TG(stage * 32 + ch * 2 + 1);
                if (stage == 0) {
#pragma unroll
                    for (int i = 0; i < 64; i++) d[i] *= SM_SCALE;
                    if (ch == 3) break;
#pragma unroll
                    for (int v = 0; v < 8; v++)
                        sts128(spill + (ch * 8 + v) * 2048, pack_bf16(d[8 * v], d[8 * v + 1]),
                               pack_bf16(d[8 * v + 2], d[8 * v + 3]), pack_bf16(d[8 * v + 4], d[8 * v + 5]),
                               pack_bf16(d[8 * v + 6], d[8 * v + 7]));
                } else {
#pragma unroll
                    for (int i = 0; i < 32; i++) {
                        const float gv = d[i], gu = gv * d[32 + i];
                        const float z = gv * fmaf(gv * gv, 0.7978845608028654f * 0.044715f, 0.7978845608028654f);
                        d[i] = fmaf(gu, tanh_fast(z), gu);
                    }
                    if (ch == 8) break;
                    if (wg == 0) {
                        if (ch == 0) bar_arrive(7, 160);
                        if (ch == 2) bar_sync(10, 160);
                    }
#pragma unroll
                    for (int v = 0; v < 4; v++) {
                        const uint4 h4 = make_uint4(pack_bf16(d[8 * v], d[8 * v + 1]), pack_bf16(d[8 * v + 2], d[8 * v + 3]),
                                                    pack_bf16(d[8 * v + 4], d[8 * v + 5]), pack_bf16(d[8 * v + 6], d[8 * v + 7]));
                        if (ch < 2)
                            __stcg(hhbuf + (ch * 4 + v) * 256, h4);
                        else
                            sts128(spill + ((ch - 2) * 4 + v) * 2048, h4.x, h4.y, h4.z, h4.w);
                    }
                }
            }
            if (stage == 0) {
                uint32_t q[32];
#pragma unroll
                for (int i = 0; i < 32; i++) q[i] = pack_bf16(d[2 * i], d[2 * i + 1]);
                PROF(5);
                PROFG(23);
                if (wg == 0) bar_arrive(6, 160);
                {
                    float o[64], sa[32], sb[32];
                    uint32_t pa[16], pb[16];
#pragma unroll
                    for (int i = 0; i < 64; i++) o[i] = 0.f;
                    float n0 = 0.f, n1 = 0.f, l0 = 1.f, l1 = 1.f;
                    bool shifted = false;
                    const uint64_t dbase = desc_of(sbase);
                    const uint64_t dbk = dbase - (511u << 16);
                    const int my_bar = 1 + wg, other_bar = 2 - wg;

                    auto softmax_a = [&](bool first, float& s0, float& s1) {
                        if (first) {
                            shifted = false;
                            n0 = n1 = 0.f;
                            l0 = l1 = 0.f;
                        }
                        if (shifted)
                            exp_step<true>(sa, pa, n0, n1, s0, s1);
                        else
                            exp_step<false>(sa, pa, n0, n1, s0, s1);
                    };
                    auto softmax_b = [&](bool first, float s0, float s1) {
                        float u0, u1;
                        if (shifted)
                            exp_step<true>(sb, pb, n0, n1, u0, u1);
                        else
                            exp_step<false>(sb, pb, n0, n1, u0, u1);
                        s0 += u0;
                        s1 += u1;
                        bool bad = !(fmaxf(s0, s1) <= SM_HI);
                        if (first) {
                            float r0 = s0 + __shfl_xor_sync(0xffffffffu, s0, 1), r1 = s1 + __shfl_xor_sync(0xffffffffu, s1, 1);
                            r0 += __shfl_xor_sync(0xffffffffu, r0, 2);
                            r1 += __shfl_xor_sync(0xffffffffu, r1, 2);
                            bad = bad || !(fminf(r0, r1) >= SM_LO);
                        }
                        if (__any_sync(0xffffffffu, bad)) {
                            float x0, x1;
                            row_max(sa, sb, x0, x1);
                            x0 = -x0;
                            x1 = -x1;
                            if (!first) {
                                x0 = fminf(x0, n0);
                                x1 = fminf(x1, n1);
                                const float al0 = ex2(x0 - n0), al1 = ex2(x1 - n1);
                                l0 *= al0;
                                l1 *= al1;
#pragma unroll
                                for (int i = 0; i < 16; i++) {
                                    o[4 * i] *= al0;
                                    o[4 * i + 1] *= al0;
                                    o[4 * i + 2] *= al1;
                                    o[4 * i + 3] *= al1;
                                }
                            }
                            n0 = x0;
                            n1 = x1;
                            shifted = true;
                            exp_step<true>(sa, pa, n0, n1, s0, s1);
                            exp_step<true>(sb, pb, n0, n1, u0, u1);
                            s0 += u0;
                            s1 += u1;
                        }
                        l0 += s0;
                        l1 += s1;
                    };

                    cx.wait_full(4, 0);
                    if (wg == 1) bar_sync(my_bar, 256);
                    wg_fence();
                    qk_step(sa, q, dbk + 4 * 1024);
                    qk_step(sb, q, dbk + 5 * 1024);
                    wg_commit();
                    bar_arrive(other_bar, 256);
                    wg_wait<0>();
                    pin(sa);
                    pin(sb);
                    cx.release(4);
                    cx.wait_full(6, 0);
                    {
                        float s0, s1;
                        softmax_a(true, s0, s1);
                        softmax_b(true, s0, s1);
                    }
                    uint32_t alo = (uint32_t)dbase + 6 * 1024, blo = (uint32_t)dbase;
                    const uint32_t dhi = (uint32_t)(dbase >> 32);
#pragma unroll 1
                    for (int t = 1; t < 64; t++) {
                        const int j = t & 15;
                        const uint32_t sA = 2 + 4 * (t & 1), sB = 4 - 4 * (t & 1);
                        const uint64_t da = ((uint64_t)dhi << 32) | alo, db = ((uint64_t)dhi << 32) | blo;
                        TL(0);
                        bar_sync(my_bar, 256);
                        TL(2);
                        wg_fence();
                        pv_step(o, pa, da + 1024, j != 1);
                        qk_step(sa, q, da - (511u << 16));
                        wg_commit();
                        cx.wait_full(sB, ((36 + 4 * t) >> 3) & 1);
                        wg_fence();
                        qk_step(sb, q, db - (511u << 16));
                        pv_step(o, pb, db + 1024, 1);
                        wg_commit();
                        bar_arrive(other_bar, 256);
                        alo ^= 4096;
                        blo ^= 4096;
                        asm volatile("" : "+r"(alo), "+r"(blo));
                        TL(3);
                        wg_wait<1>();
                        pin(sa);
                        pin(pa);
                        TL(4);
                        cx.release(sA);
                        const float lp0 = l0, lp1 = l1;
                        float s0, s1;
                        softmax_a(j == 0, s0, s1);
                        TL(5);
                        wg_wait<0>();
                        pin(o);
                        pin(sb);
                        pin(pb);
                        TL(6);
                        cx.release(sB);
                        if (j == 0) {
                            float i0, i1;
                            inv_row_sums(lp0, lp1, i0, i1);
                            const uint32_t dst = spill + ((t >> 4) - 1) * 16384;
#pragma unroll
                            for (int v = 0; v < 8; v++)
                                sts128(dst + v * 2048, pack_bf16(o[8 * v] * i0, o[8 * v + 1] * i0),
                                       pack_bf16(o[8 * v + 2] * i1, o[8 * v + 3] * i1),
                                       pack_bf16(o[8 * v + 4] * i0, o[8 * v + 5] * i0),
                                       pack_bf16(o[8 * v + 6] * i1, o[8 * v + 7] * i1));
                        }
                        const uint32_t bn = sbase + OFF_FULL + (8 - sA) * 8, pn = ((38 + 4 * t) >> 3) & 1;
                        const bool okn = mbar_try(bn, pn);
                        TL(1);
                        softmax_b(j == 0, s0, s1);
                        if (!okn || j == 15) {
                            mbar_wait(bn, pn);
                            if (j == 15 && t < 63) {
                                const uint32_t src = spill + (t >> 4) * 16384;
#pragma unroll
                                for (int v = 0; v < 8; v++)
                                    lds128(src + v * 2048, q[4 * v], q[4 * v + 1], q[4 * v + 2], q[4 * v + 3]);
                            }
                        }
                        TL(7);
                    }
                    bar_sync(my_bar, 256);
                    wg_fence();
                    pv_step(o, pa, dbase + 2 * 1024, 1);
                    pv_step(o, pb, dbase + 3 * 1024, 1);
                    wg_commit();
                    if (wg == 0) bar_arrive(other_bar, 256);
                    float i0, i1;
                    inv_row_sums(l0, l1, i0, i1);
                    wg_wait<0>();
                    pin(o);
                    cx.release(2);
#pragma unroll
                    for (int i = 0; i < 16; i++) {
                        a[96 + 2 * i] = pack_bf16(o[4 * i] * i0, o[4 * i + 1] * i0);
                        a[96 + 2 * i + 1] = pack_bf16(o[4 * i + 2] * i1, o[4 * i + 3] * i1);
                    }
#pragma unroll
                    for (int i = 128; i < 144; i++) a[i] = 0;
                }
                ring.slot = 4;
                ring.phase = 0;
                PROF(6);
                PROFG(24);
            } else {
#pragma unroll
                for (int v = 0; v < 8; v++) {
                    const uint4 t = __ldcg(hhbuf + v * 256);
                    a[112 + 4 * v] = t.x;
                    a[113 + 4 * v] = t.y;
                    a[114 + 4 * v] = t.z;
                    a[115 + 4 * v] = t.w;
                }
#pragma unroll
                for (int i = 0; i < 16; i++) a[96 + i] = pack_bf16(d[2 * i], d[2 * i + 1]);
                PROF(13);
            }
#pragma unroll
            for (int v = 0; v < 24; v++) lds128(spill + v * 2048, a[4 * v], a[4 * v + 1], a[4 * v + 2], a[4 * v + 3]);

            {
                uint4* dst = sc_->part + ((size_t)wown * 8 + g) * 36 * 32 + lane;
                const uint32_t ptag = (stage + 1) & 1;
#pragma unroll 1
                for (int p = 0; p < 4; p++) {
                    TG(stage * 32 + 18 + p * 2);
                    gemm_n128(d, a, cx, ring, stage != 0);
                    TG(stage * 32 + 19 + p * 2);
#pragma unroll
                    for (int u = 0; u < 8; u++)
                        st128(dst + (p * 8 + u) * 32, (pack_bf16(d[8 * u], d[8 * u + 1]) & ~1u) | ptag,
                              pack_bf16(d[8 * u + 2], d[8 * u + 3]), pack_bf16(d[8 * u + 4], d[8 * u + 5]),
                              pack_bf16(d[8 * u + 6], d[8 * u + 7]));
                    if (p == 0 && wg == 0) bar_arrive(7, 160);
                }
                float e[32];
                TG(stage * 32 + 26);
                gemm_n64(e, a, cx, ring, stage != 0);
                TG(stage * 32 + 27);
                uint2* dst2 = reinterpret_cast<uint2*>(dst - lane + 32 * 32) + lane;
#pragma unroll
                for (int j = 0; j < 8; j++)
                    st64(dst2 + j * 32, (pack_bf16(e[4 * j], e[4 * j + 1]) & ~1u) | ptag, pack_bf16(e[4 * j + 2], e[4 * j + 3]));
            }
            PROF(stage == 0 ? 7 : 14);
            if (stage == 1) {
                PROFG(26);
                asm volatile("barrier.cluster.arrive.relaxed.aligned;" ::: "memory");
            }
        }
        if (wg == 0) bar_sync(8, 256);
        bar_sync(3, 256);
        if (tid == 32) sc_->epoch[b * 32] = get_epoch(sbase) + 1;
        if (tid == 0) {
            rows_store(sbase, &maps.rout, own * 16);
            rows_store_wait();
        }
        __syncwarp();
        PROF(16);
        PROFG(31);
        asm volatile("barrier.cluster.wait.aligned;" ::: "memory");
    }
}

typedef CUresult (*EncodeFn)(CUtensorMap*, CUtensorMapDataType, cuuint32_t, void*, const cuuint64_t*, const cuuint64_t*,
                             const cuuint32_t*, const cuuint32_t*, CUtensorMapInterleave, CUtensorMapSwizzle,
                             CUtensorMapL2promotion, CUtensorMapFloatOOBfill);

void make_map(EncodeFn enc, CUtensorMap* m, const void* ptr, uint64_t rows, uint64_t cols, bool narrow = false) {
    cuuint64_t gdim[2] = {cols, rows};
    cuuint64_t gstr[1] = {cols * 2};
    cuuint32_t box[2] = {narrow ? 16u : 64u, narrow ? 192u : 64u};
    cuuint32_t estr[2] = {1, 1};
    enc(m, CU_TENSOR_MAP_DATA_TYPE_BFLOAT16, 2, const_cast<void*>(ptr), gdim, gstr, box, estr,
        CU_TENSOR_MAP_INTERLEAVE_NONE, narrow ? CU_TENSOR_MAP_SWIZZLE_NONE : CU_TENSOR_MAP_SWIZZLE_128B,
        CU_TENSOR_MAP_L2_PROMOTION_L2_128B,
        CU_TENSOR_MAP_FLOAT_OOB_FILL_NONE);
}

void make_rows_map(EncodeFn enc, CUtensorMap* m, const void* ptr) {
    cuuint64_t gdim[3] = {64, 9, 2048};
    cuuint64_t gstr[2] = {128, DM * 2};
    cuuint32_t box[3] = {64, 9, 16};
    cuuint32_t estr[3] = {1, 1, 1};
    enc(m, CU_TENSOR_MAP_DATA_TYPE_BFLOAT16, 3, const_cast<void*>(ptr), gdim, gstr, box, estr,
        CU_TENSOR_MAP_INTERLEAVE_NONE, CU_TENSOR_MAP_SWIZZLE_128B, CU_TENSOR_MAP_L2_PROMOTION_L2_128B,
        CU_TENSOR_MAP_FLOAT_OOB_FILL_NONE);
}

}

extern "C" void kernel_launch(void* const* d_in, const int* in_sizes, int n_in, void* d_out, int out_size) {
    (void)in_sizes;
    (void)n_in;
    (void)out_size;
    void* fn = nullptr;
    cudaDriverEntryPointQueryResult qr;
    cudaGetDriverEntryPoint("cuTensorMapEncodeTiled", &fn, cudaEnableDefault, &qr);
    EncodeFn enc = (EncodeFn)fn;
    Params maps;
    maps.x = (const __nv_bfloat16*)d_in[0];
    maps.cvec = (const __nv_bfloat16*)d_in[9];
    maps.wmod = (const __nv_bfloat16*)d_in[10];
    maps.kc = (const __nv_bfloat16*)d_in[1];
    maps.vc = (const __nv_bfloat16*)d_in[2];
    maps.wq_p = (const __nv_bfloat16*)d_in[3];
    maps.wo_p = (const __nv_bfloat16*)d_in[4];
    maps.wg_p = (const __nv_bfloat16*)d_in[6];
    maps.wu_p = (const __nv_bfloat16*)d_in[7];
    maps.wd_p = (const __nv_bfloat16*)d_in[8];
    maps.out = (__nv_bfloat16*)d_out;
    void* scp = nullptr;
    cudaGetSymbolAddress(&scp, g_scratch);
    maps.sc = (Scratch*)scp;
    make_map(enc, &maps.k, d_in[1], 32 * 2048, 128);
    make_map(enc, &maps.v, d_in[2], 32 * 2048, 128);
    make_map(enc, &maps.wq, d_in[3], 576, 4096);
    make_map(enc, &maps.wo, d_in[4], 4096, 576);
    make_map(enc, &maps.wg, d_in[6], 576, 4608);
    make_map(enc, &maps.wu, d_in[7], 576, 4608);
    make_map(enc, &maps.wd, d_in[8], 4608, 576);
    make_rows_map(enc, &maps.rx, d_in[0]);
    make_rows_map(enc, &maps.rx2, (char*)scp + offsetof(Scratch, x2));
    make_rows_map(enc, &maps.rout, d_out);
    cudaFuncSetAttribute(fused_block_kernel, cudaFuncAttributeMaxDynamicSharedMemorySize, SMEM_BYTES);
    fused_block_kernel<<<128, 384, SMEM_BYTES>>>(maps);
}
```

```cpp
#include <cuda_runtime.h>
#include <cuda_bf16.h>
#include <cuda.h>
#include <stdint.h>
#include <stddef.h>

namespace {

constexpr int DM = 576;
constexpr int SLOT_BYTES = 16384;
constexpr int BOX_BYTES = 8192;
constexpr int NUNITS = 14;
constexpr int SMEM_TAIL = NUNITS * SLOT_BYTES;
constexpr int SMEM_BYTES = SMEM_TAIL + 2048 + 1024;
constexpr int OFF_FULL = SMEM_TAIL;
constexpr int OFF_EMPTY = SMEM_TAIL + 64;
constexpr int OFF_RED = SMEM_TAIL + 128;

constexpr int KV_AHEAD = 16;
#define GATE_SLOT 4
#define PROBE_NS 300
constexpr int OFF_XBAR = SMEM_TAIL + 1792;
constexpr int OFF_ROWS = 8 * SLOT_BYTES;
constexpr int OFF_MODT = OFF_ROWS + 20480;
constexpr int OFF_EPOCH = SMEM_TAIL + 1808;
constexpr int OFF_PBUF = OFF_ROWS + 32768;
constexpr int OFF_PBAR = SMEM_TAIL + 1800;
constexpr int OFF_MRED = OFF_ROWS + 28672;

struct Scratch {
    unsigned epoch[128 * 32];
    uint32_t mod[6 * DM];
    uint32_t modp[6][2 * DM];
    uint4 h[2][2][128 * 36 * 32];
    uint4 part[128 * 8 * 36 * 32];
    uint4 hh[128 * 8 * 256];
    __nv_bfloat16 x2[2048 * DM];
};
__device__ Scratch g_scratch;

#define TG(i)
#define TL(i)
#define PROFR(i)
#define PROF(i)
#define PROFG(i)

struct Params {
    const __nv_bfloat16 *x, *cvec, *wmod, *kc, *vc, *wq_p, *wo_p, *wg_p, *wu_p, *wd_p;
    __nv_bfloat16* out;
    Scratch* sc;
    CUtensorMap k, v, wq, wo, wg, wu, wd, rx, rx2, rout;
};

__device__ __forceinline__ uint32_t smem_u32(const void* p) { return (uint32_t)__cvta_generic_to_shared(p); }
__device__ __forceinline__ void mbar_init(uint32_t a, uint32_t c) {
    asm volatile("mbarrier.init.shared::cta.b64 [%0], %1;" ::"r"(a), "r"(c) : "memory");
}
__device__ __forceinline__ void mbar_expect_tx(uint32_t a, uint32_t bytes) {
    asm volatile("mbarrier.arrive.expect_tx.shared::cta.b64 _, [%0], %1;" ::"r"(a), "r"(bytes) : "memory");
}
__device__ __forceinline__ bool mbar_try(uint32_t a, uint32_t ph) {
    uint32_t ok;
    asm volatile(
        "{\n.reg .pred p;\nmbarrier.try_wait.parity.shared::cta.b64 p, [%1], %2;\nselp.u32 %0, 1, 0, p;\n}"
        : "=r"(ok)
        : "r"(a), "r"(ph)
        : "memory");
    return ok != 0;
}
__device__ __forceinline__ uint32_t clk32() {
    uint32_t c;
    asm volatile("mov.u32 %0, %%clock;" : "=r"(c));
    return c;
}
constexpr uint32_t WAIT_LIMIT = 1u << 30;
__device__ __forceinline__ void mbar_wait(uint32_t a, uint32_t ph) {
    if (mbar_try(a, ph)) return;
    uint32_t t0 = clk32();
    while (!mbar_try(a, ph)) {
        if (clk32() - t0 > WAIT_LIMIT) break;
    }
}
__device__ __forceinline__ void mbar_arrive_cluster(uint32_t a, uint32_t cta) {
    asm volatile(
        "{\n.reg .b32 ra;\nmapa.shared::cluster.u32 ra, %0, %1;\nmbarrier.arrive.shared::cluster.b64 _, [ra];\n}" ::"r"(a),
        "r"(cta)
        : "memory");
}
__device__ __forceinline__ void tma_mc(uint32_t dst, const CUtensorMap* m, int c0, int c1, uint32_t bar) {
    asm volatile(
        "cp.async.bulk.tensor.2d.shared::cluster.global.mbarrier::complete_tx::bytes.multicast::cluster"
        " [%0], [%1, {%3, %4}], [%2], %5;" ::"r"(dst),
        "l"(m), "r"(bar), "r"(c0), "r"(c1), "h"((uint16_t)3)
        : "memory");
}
__device__ __forceinline__ void bulk_load(uint32_t dst, const void* src, uint32_t bytes, uint32_t bar) {
    asm volatile("cp.async.bulk.shared::cluster.global.mbarrier::complete_tx::bytes [%0], [%1], %2, [%3];" ::"r"(dst),
                 "l"(src), "r"(bytes), "r"(bar)
                 : "memory");
}
__device__ __forceinline__ void l2_prefetch(const void* p, uint32_t bytes) {
    asm volatile("cp.async.bulk.prefetch.L2.global [%0], %1;" ::"l"(p), "r"(bytes) : "memory");
}
__device__ __forceinline__ void bar_sync(int id, int n) { asm volatile("bar.sync %0, %1;" ::"r"(id), "r"(n) : "memory"); }
__device__ __forceinline__ void bar_arrive(int id, int n) {
    asm volatile("bar.arrive %0, %1;" ::"r"(id), "r"(n) : "memory");
}
__device__ __forceinline__ void wg_fence() { asm volatile("wgmma.fence.sync.aligned;" ::: "memory"); }
__device__ __forceinline__ void wg_commit() { asm volatile("wgmma.commit_group.sync.aligned;" ::: "memory"); }
template <int N>
__device__ __forceinline__ void wg_wait() {
    asm volatile("wgmma.wait_group.sync.aligned %0;" ::"n"(N) : "memory");
}
template <int N>
__device__ __forceinline__ void pin(float (&d)[N]) {
#pragma unroll
    for (int i = 0; i < N; i++) asm volatile("" : "+f"(d[i])::"memory");
}
template <int N>
__device__ __forceinline__ void pin(uint32_t (&d)[N]) {
#pragma unroll
    for (int i = 0; i < N; i++) asm volatile("" : "+r"(d[i])::"memory");
}
__device__ __forceinline__ uint32_t pack_bf16(float lo, float hi) {
    uint32_t r;
    asm("cvt.rn.bf16x2.f32 %0, %1, %2;" : "=r"(r) : "f"(hi), "f"(lo));
    return r;
}
__device__ __forceinline__ float bf_lo(uint32_t v) { return __uint_as_float(v << 16); }
__device__ __forceinline__ float bf_hi(uint32_t v) { return __uint_as_float(v & 0xffff0000u); }
__device__ __forceinline__ float round_bf16(float v) { return __bfloat162float(__float2bfloat16_rn(v)); }
__device__ __forceinline__ float ex2(float x) {
    float y;
    asm("ex2.approx.ftz.f32 %0, %1;" : "=f"(y) : "f"(x));
    return y;
}
__device__ __forceinline__ float rcp(float x) {
    float y;
    asm("rcp.approx.ftz.f32 %0, %1;" : "=f"(y) : "f"(x));
    return y;
}
__device__ __forceinline__ float tanh_fast(float x) {
    float y;
    asm("tanh.approx.f32 %0, %1;" : "=f"(y) : "f"(x));
    return y;
}
__device__ __forceinline__ void sts128(uint32_t a, uint32_t x, uint32_t y, uint32_t z, uint32_t w) {
    asm volatile("st.shared.v4.b32 [%0], {%1,%2,%3,%4};" ::"r"(a), "r"(x), "r"(y), "r"(z), "r"(w) : "memory");
}
__device__ __forceinline__ void lds128(uint32_t a, uint32_t& x, uint32_t& y, uint32_t& z, uint32_t& w) {
    asm volatile("ld.shared.v4.b32 {%0,%1,%2,%3}, [%4];" : "=r"(x), "=r"(y), "=r"(z), "=r"(w) : "r"(a) : "memory");
}
__device__ __forceinline__ void sts32f(uint32_t a, float v) {
    asm volatile("st.shared.f32 [%0], %1;" ::"r"(a), "f"(v) : "memory");
}
__device__ __forceinline__ float lds32f(uint32_t a) {
    float v;
    asm volatile("ld.shared.f32 %0, [%1];" : "=f"(v) : "r"(a) : "memory");
    return v;
}
#define F8(d, b) \
    "+f"(d[b]), "+f"(d[b + 1]), "+f"(d[b + 2]), "+f"(d[b + 3]), "+f"(d[b + 4]), "+f"(d[b + 5]), "+f"(d[b + 6]), "+f"(d[b + 7])

template <int TB>
__device__ __forceinline__ void wgmma_n128(float (&d)[64], uint32_t a0, uint32_t a1, uint32_t a2, uint32_t a3,
                                           uint64_t db, int sc) {
    asm volatile(
        "{\n.reg .pred p;\nsetp.ne.b32 p, %69, 0;\n"
        "wgmma.mma_async.sync.aligned.m64n128k16.f32.bf16.bf16 "
        "{%0,%1,%2,%3,%4,%5,%6,%7,%8,%9,%10,%11,%12,%13,%14,%15,%16,%17,%18,%19,%20,%21,%22,%23,%24,%25,%26,%27,%28,%29,%30,%31,"
        "%32,%33,%34,%35,%36,%37,%38,%39,%40,%41,%42,%43,%44,%45,%46,%47,%48,%49,%50,%51,%52,%53,%54,%55,%56,%57,%58,%59,%60,%61,%62,%63},"
        "{%64,%65,%66,%67}, %68, p, 1, 1, %70;\n}"
        : F8(d, 0), F8(d, 8), F8(d, 16), F8(d, 24), F8(d, 32), F8(d, 40), F8(d, 48), F8(d, 56)
        : "r"(a0), "r"(a1), "r"(a2), "r"(a3), "l"(db), "r"(sc), "n"(TB));
}
#define O8(d, b) \
    "=f"(d[b]), "=f"(d[b + 1]), "=f"(d[b + 2]), "=f"(d[b + 3]), "=f"(d[b + 4]), "=f"(d[b + 5]), "=f"(d[b + 6]), "=f"(d[b + 7])
template <int TB>
__device__ __forceinline__ void wgmma_n128_z(float (&d)[64], uint32_t a0, uint32_t a1, uint32_t a2, uint32_t a3,
                                             uint64_t db) {
    asm volatile(
        "wgmma.mma_async.sync.aligned.m64n128k16.f32.bf16.bf16 "
        "{%0,%1,%2,%3,%4,%5,%6,%7,%8,%9,%10,%11,%12,%13,%14,%15,%16,%17,%18,%19,%20,%21,%22,%23,%24,%25,%26,%27,%28,%29,%30,%31,"
        "%32,%33,%34,%35,%36,%37,%38,%39,%40,%41,%42,%43,%44,%45,%46,%47,%48,%49,%50,%51,%52,%53,%54,%55,%56,%57,%58,%59,%60,%61,%62,%63},"
        "{%64,%65,%66,%67}, %68, 0, 1, 1, %69;"
        : O8(d, 0), O8(d, 8), O8(d, 16), O8(d, 24), O8(d, 32), O8(d, 40), O8(d, 48), O8(d, 56)
        : "r"(a0), "r"(a1), "r"(a2), "r"(a3), "l"(db), "n"(TB));
}
template <int TB>
__device__ __forceinline__ void wgmma_n64_z(float (&d)[32], uint32_t a0, uint32_t a1, uint32_t a2, uint32_t a3,
                                            uint64_t db) {
    asm volatile(
        "wgmma.mma_async.sync.aligned.m64n64k16.f32.bf16.bf16 "
        "{%0,%1,%2,%3,%4,%5,%6,%7,%8,%9,%10,%11,%12,%13,%14,%15,%16,%17,%18,%19,%20,%21,%22,%23,%24,%25,%26,%27,%28,%29,%30,%31},"
        "{%32,%33,%34,%35}, %36, 0, 1, 1, %37;"
        : O8(d, 0), O8(d, 8), O8(d, 16), O8(d, 24)
        : "r"(a0), "r"(a1), "r"(a2), "r"(a3), "l"(db), "n"(TB));
}
template <int TB>
__device__ __forceinline__ void wgmma_n64(float (&d)[32], uint32_t a0, uint32_t a1, uint32_t a2, uint32_t a3,
                                          uint64_t db) {
    asm volatile(
        "wgmma.mma_async.sync.aligned.m64n64k16.f32.bf16.bf16 "
        "{%0,%1,%2,%3,%4,%5,%6,%7,%8,%9,%10,%11,%12,%13,%14,%15,%16,%17,%18,%19,%20,%21,%22,%23,%24,%25,%26,%27,%28,%29,%30,%31},"
        "{%32,%33,%34,%35}, %36, 1, 1, 1, %37;"
        : F8(d, 0), F8(d, 8), F8(d, 16), F8(d, 24)
        : "r"(a0), "r"(a1), "r"(a2), "r"(a3), "l"(db), "n"(TB));
}

__device__ __forceinline__ uint64_t desc_of(uint32_t saddr) {
    return (uint64_t)(((saddr >> 4) & 0x3FFFu) | (512u << 16)) | ((uint64_t)(64u | (1u << 30)) << 32);
}

struct Ring {
    uint32_t slot;
    uint32_t phase;
    __device__ __forceinline__ void next() {
        if (++slot == 8) {
            slot = 0;
            phase ^= 1;
        }
    }
};

struct Ctx {
    uint32_t sbase;
    int wg;
    uint32_t rel_cta;
    __device__ __forceinline__ void wait_full(uint32_t slot, uint32_t phase) const {
        mbar_wait(sbase + OFF_FULL + slot * 8, phase);
    }
    __device__ __forceinline__ void release(uint32_t slot) const {
        if (rel_cta < 2) mbar_arrive_cluster(sbase + OFF_EMPTY + slot * 8, rel_cta);
    }
};

__device__ __forceinline__ void gemm_n128(float (&d)[64], const uint32_t (&a)[144], const Ctx& c, Ring& r, bool nine) {
    uint32_t prev = 0;
#pragma unroll
    for (int s = 0; s < 9; s++) {
        if (s < 8 || nine) {
            if (s == GATE_SLOT) bar_sync(8 + c.wg, 256);
            c.wait_full(r.slot, r.phase);
            uint64_t db = desc_of(c.sbase + r.slot * SLOT_BYTES);
            wg_fence();
#pragma unroll
            for (int k = 0; k < 4; k++) {
                if ((s | k) == 0)
                    wgmma_n128_z<1>(d, a[0], a[1], a[2], a[3], db);
                else
                    wgmma_n128<1>(d, a[s * 16 + k * 4], a[s * 16 + k * 4 + 1], a[s * 16 + k * 4 + 2],
                                  a[s * 16 + k * 4 + 3], db + k * 128, 1);
            }
            wg_commit();
            if (s == 8 || (s == 7 && !nine)) bar_arrive(9 - c.wg, 256);
            if (s > 0) {
                wg_wait<1>();
                c.release(prev);
            }
            prev = r.slot;
            r.next();
        }
    }
    wg_wait<0>();
    c.release(prev);
    pin(d);
}
__device__ __forceinline__ void gemm_n64(float (&d)[32], const uint32_t (&a)[144], const Ctx& c, Ring& r, bool nine) {
    uint32_t prev = 0;
#pragma unroll
    for (int s = 0; s < 5; s++) {
        if (s < 4 || nine) {
            c.wait_full(r.slot, r.phase);
            uint64_t db = desc_of(c.sbase + r.slot * SLOT_BYTES);
            wg_fence();
#pragma unroll
            for (int k = 0; k < 8; k++) {
                if ((s | k) == 0)
                    wgmma_n64_z<1>(d, a[0], a[1], a[2], a[3], db);
                else if (s * 8 + k < 36)
                    wgmma_n64<1>(d, a[s * 32 + k * 4], a[s * 32 + k * 4 + 1], a[s * 32 + k * 4 + 2],
                                 a[s * 32 + k * 4 + 3], db + k * 128);
            }
            wg_commit();
            if (s > 0) {
                wg_wait<1>();
                c.release(prev);
            }
            prev = r.slot;
            r.next();
        }
    }
    wg_wait<0>();
    c.release(prev);
    pin(d);
}
__device__ __forceinline__ void st128(uint4* p, uint32_t x, uint32_t y, uint32_t z, uint32_t w) {
    asm volatile(
        "{\n.reg .b64 lo, hi;\n.reg .b128 t;\nmov.b64 lo, {%1, %2};\nmov.b64 hi, {%3, %4};\nmov.b128 t, {lo, hi};\n"
        "st.relaxed.gpu.global.b128 [%0], t;\n}" ::"l"(p),
        "r"(x), "r"(y), "r"(z), "r"(w)
        : "memory");
}
__device__ __forceinline__ uint4 ld128(const uint4* p) {
    uint4 r;
    asm volatile(
        "{\n.reg .b64 lo, hi;\n.reg .b128 t;\nld.relaxed.gpu.global.b128 t, [%4];\nmov.b128 {lo, hi}, t;\n"
        "mov.b64 {%0, %1}, lo;\nmov.b64 {%2, %3}, hi;\n}"
        : "=r"(r.x), "=r"(r.y), "=r"(r.z), "=r"(r.w)
        : "l"(p));
    return r;
}
__device__ __forceinline__ uint4 ldg128(const uint4* p) {
    uint4 r;
    asm volatile("ld.global.nc.v4.u32 {%0,%1,%2,%3}, [%4];" : "=r"(r.x), "=r"(r.y), "=r"(r.z), "=r"(r.w) : "l"(p));
    return r;
}
__device__ __forceinline__ void st64(void* p, uint32_t x, uint32_t y) {
    asm volatile("{\n.reg .b64 t;\nmov.b64 t, {%1, %2};\nst.relaxed.gpu.global.b64 [%0], t;\n}" ::"l"(p), "r"(x), "r"(y)
                 : "memory");
}
__device__ __forceinline__ uint2 ld64(const void* p) {
    uint2 r;
    asm volatile("{\n.reg .b64 t;\nld.relaxed.gpu.global.b64 t, [%2];\nmov.b64 {%0, %1}, t;\n}"
                 : "=r"(r.x), "=r"(r.y)
                 : "l"(p));
    return r;
}
__device__ __forceinline__ void rows_load(uint32_t sbase, const CUtensorMap* m, int row0) {
    mbar_expect_tx(sbase + OFF_XBAR, 16 * DM * 2);
    asm volatile(
        "cp.async.bulk.tensor.3d.shared::cluster.global.mbarrier::complete_tx::bytes [%0], [%1, {%3, %3, %4}], [%2];" ::"r"(
            sbase + OFF_ROWS),
        "l"(m), "r"(sbase + OFF_XBAR), "r"(0), "r"(row0)
        : "memory");
}
__device__ __forceinline__ void rows_store(uint32_t sbase, const CUtensorMap* m, int row0) {
    asm volatile("cp.async.bulk.tensor.3d.global.shared::cta.bulk_group [%0, {%2, %2, %3}], [%1];" ::"l"(m),
                 "r"(sbase + OFF_ROWS), "r"(0), "r"(row0)
                 : "memory");
    asm volatile("cp.async.bulk.commit_group;" ::: "memory");
}
__device__ __forceinline__ void rows_store_wait() { asm volatile("cp.async.bulk.wait_group 0;" ::: "memory"); }

__device__ __forceinline__ constexpr int own_col(int j) { return j < 8 ? (j >> 1) * 128 + (j & 1) * 8 : 512; }
__device__ __forceinline__ void row_reduce(float& s0, float& s1, uint32_t red, int warp, int lane) {
    s0 += __shfl_xor_sync(0xffffffffu, s0, 1);
    s1 += __shfl_xor_sync(0xffffffffu, s1, 1);
    s0 += __shfl_xor_sync(0xffffffffu, s0, 2);
    s1 += __shfl_xor_sync(0xffffffffu, s1, 2);
    if ((lane & 3) == 0) {
        sts32f(red + (warp * 16 + (lane >> 2)) * 4, s0);
        sts32f(red + (warp * 16 + 8 + (lane >> 2)) * 4, s1);
    }
    bar_sync(3, 256);
    s0 = 0.f;
    s1 = 0.f;
#pragma unroll
    for (int w = 0; w < 8; w++) {
        s0 += lds32f(red + (w * 16 + (lane >> 2)) * 4);
        s1 += lds32f(red + (w * 16 + 8 + (lane >> 2)) * 4);
    }
}
template <class F>
__device__ __forceinline__ void layernorm_rows(float (&v)[36], uint32_t red, int warp, int lane, F&& middle) {
    float s0 = 0.f, s1 = 0.f;
#pragma unroll
    for (int j = 0; j < 9; j++) {
        s0 += v[4 * j] + v[4 * j + 1];
        s1 += v[4 * j + 2] + v[4 * j + 3];
    }
    row_reduce(s0, s1, red, warp, lane);
    middle();
    const float m0 = s0 * (1.f / DM), m1 = s1 * (1.f / DM);
    s0 = 0.f;
    s1 = 0.f;
#pragma unroll
    for (int j = 0; j < 9; j++) {
        v[4 * j] -= m0;
        v[4 * j + 1] -= m0;
        v[4 * j + 2] -= m1;
        v[4 * j + 3] -= m1;
        s0 += v[4 * j] * v[4 * j] + v[4 * j + 1] * v[4 * j + 1];
        s1 += v[4 * j + 2] * v[4 * j + 2] + v[4 * j + 3] * v[4 * j + 3];
    }
    row_reduce(s0, s1, red + 512, warp, lane);
    const float r0 = rsqrtf(s0 * (1.f / DM) + 1e-5f), r1 = rsqrtf(s1 * (1.f / DM) + 1e-5f);
#pragma unroll
    for (int j = 0; j < 9; j++) {
        v[4 * j] *= r0;
        v[4 * j + 1] *= r0;
        v[4 * j + 2] *= r1;
        v[4 * j + 3] *= r1;
    }
}
__device__ __forceinline__ void mod_to_smem(uint32_t dst, const uint32_t* src, uint32_t tag) {
    const uint32_t t0 = clk32();
    uint4 u;
    while (true) {
        u = ld128(reinterpret_cast<const uint4*>(src));
        const uint32_t bad = ((u.x ^ tag) | (u.y ^ tag) | (u.z ^ tag) | (u.w ^ tag)) & 0xffffu;
        if (__all_sync(0xffffffffu, bad == 0) || clk32() - t0 > WAIT_LIMIT) break;
        __nanosleep(64);
    }
    sts128(dst, u.x & 0xffff0000u, u.y & 0xffff0000u, u.z & 0xffff0000u, u.w & 0xffff0000u);
}
__device__ __forceinline__ void lds_mod(float (&m)[18], uint32_t src  , int warp) {
#pragma unroll
    for (int j = 0; j < 9; j++)
        asm volatile("ld.shared.v2.f32 {%0,%1}, [%2];"
                     : "=f"(m[2 * j]), "=f"(m[2 * j + 1])
                     : "r"(src + own_col(j) * 4 - (j == 8 ? warp * 32 : 0))
                     : "memory");
}
__device__ __forceinline__ void modulate_store(const float (&v)[36], const float (&shift)[18], const float (&scale)[18],
                                               uint4* hbuf  , int warp, int lane) {
    uint32_t o[18];
#pragma unroll
    for (int j = 0; j < 9; j++) {
        const uint32_t cc = pack_bf16(1.f + scale[2 * j], 1.f + scale[2 * j + 1]);
        const float c0 = bf_lo(cc), c1 = bf_hi(cc);
        o[2 * j] = max(pack_bf16(fmaf(v[4 * j], c0, shift[2 * j]), fmaf(v[4 * j + 1], c1, shift[2 * j + 1])), 1u);
        o[2 * j + 1] = max(pack_bf16(fmaf(v[4 * j + 2], c0, shift[2 * j]), fmaf(v[4 * j + 3], c1, shift[2 * j + 1])), 1u);
    }
#pragma unroll
    for (int i = 0; i < 4; i++) st128(hbuf + (i * 8 + warp) * 32 + lane, o[4 * i], o[4 * i + 1], o[4 * i + 2], o[4 * i + 3]);
    st64(reinterpret_cast<uint2*>(hbuf + 32 * 32) + warp * 32 + lane, o[16], o[17]);
}
__device__ __forceinline__ void sum_partials(float (&v)[36], const uint4* src  ,
                                             const uint2* tail  , uint32_t tag, uint32_t pbuf  ,
                                             uint32_t pbar, uint32_t pphase) {
    const uint32_t t0 = clk32();
    uint2 tl[8];
    bool first = true;
    while (true) {
        uint4 t[8][4];
#pragma unroll
        for (int s = 0; s < 8; s++)
#pragma unroll
            for (int i = 2; i < 4; i++) t[s][i] = ld128(src + (s * 36 + i * 8) * 32);
        if (first) {
#pragma unroll
            for (int s = 0; s < 8; s++) tl[s] = ld64(tail + s * 72 * 32);
            mbar_wait(pbar, pphase);
#pragma unroll
            for (int s = 0; s < 8; s++)
#pragma unroll
                for (int i = 0; i < 2; i++) lds128(pbuf + s * 8192 + i * 4096, t[s][i].x, t[s][i].y, t[s][i].z, t[s][i].w);
        } else {
#pragma unroll
            for (int s = 0; s < 8; s++)
#pragma unroll
                for (int i = 0; i < 2; i++) t[s][i] = ld128(src + (s * 36 + i * 8) * 32);
        }
        first = false;
        uint32_t bad = 0;
#pragma unroll
        for (int i = 0; i < 32; i++) v[i] = 0.f;
#pragma unroll
        for (int i = 0; i < 4; i++)
#pragma unroll
            for (int s = 0; s < 8; s++) {
                bad |= t[s][i].x ^ tag;
                v[8 * i] += bf_lo(t[s][i].x);
                v[8 * i + 1] += bf_hi(t[s][i].x);
                v[8 * i + 2] += bf_lo(t[s][i].y);
                v[8 * i + 3] += bf_hi(t[s][i].y);
                v[8 * i + 4] += bf_lo(t[s][i].z);
                v[8 * i + 5] += bf_hi(t[s][i].z);
                v[8 * i + 6] += bf_lo(t[s][i].w);
                v[8 * i + 7] += bf_hi(t[s][i].w);
            }
        if (__all_sync(0xffffffffu, (bad & 1u) == 0) || clk32() - t0 > WAIT_LIMIT) break;
    }
    while (true) {
        uint32_t bad = 0;
#pragma unroll
        for (int s = 0; s < 8; s++) bad |= tl[s].x ^ tag;
        if (__all_sync(0xffffffffu, (bad & 1u) == 0) || clk32() - t0 > WAIT_LIMIT) break;
#pragma unroll
        for (int s = 0; s < 8; s++) tl[s] = ld64(tail + s * 72 * 32);
    }
    v[32] = v[33] = v[34] = v[35] = 0.f;
#pragma unroll
    for (int s = 0; s < 8; s++) {
        v[32] += bf_lo(tl[s].x);
        v[33] += bf_hi(tl[s].x);
        v[34] += bf_lo(tl[s].y);
        v[35] += bf_hi(tl[s].y);
    }
}
__device__ __forceinline__ void poll_tail(uint32_t (&a)[144], const uint2* src  ) {
    const uint32_t t0 = clk32();
    while (true) {
        uint32_t m = 0xffffffffu;
#pragma unroll
        for (int j = 0; j < 8; j++) {
            const uint2 t = ld64(src + j * 32);
            a[128 + 2 * j] = t.x;
            a[129 + 2 * j] = t.y;
        }
#pragma unroll
        for (int j = 0; j < 16; j++) m = min(m, a[128 + j]);
        if (__all_sync(0xffffffffu, m != 0) || clk32() - t0 > WAIT_LIMIT) break;
    }
}
template <int K0, int K1>
__device__ __forceinline__ void poll_frags(uint32_t (&a)[144], const uint4* src  , bool kick) {
    const uint32_t t0 = clk32();
    while (true) {
#pragma unroll
        for (int k = K0; k < K1; k++)
            asm volatile("ld.relaxed.gpu.global.v4.u32 {%0,%1,%2,%3}, [%4];"
                         : "=r"(a[4 * k]), "=r"(a[4 * k + 1]), "=r"(a[4 * k + 2]), "=r"(a[4 * k + 3])
                         : "l"(src + k * 32));
        if (kick) bar_arrive(5, 256);
        kick = false;
        uint32_t m0 = a[4 * K0], m1 = a[4 * K0 + 1];
#pragma unroll
        for (int i = 4 * K0 + 2; i < 4 * K1; i += 2) {
            m0 = min(m0, a[i]);
            m1 = min(m1, a[i + 1]);
        }
        if (__all_sync(0xffffffffu, min(m0, m1) != 0) || clk32() - t0 > WAIT_LIMIT) break;
    }
}

constexpr float SM_SCALE = 0.08838834764831845f * 1.4426950408889634f;
constexpr float SM_HI = 1.2089258e24f;
constexpr float SM_LO = 9.0949470e-13f;
__device__ __forceinline__ void qk_step(float (&s)[32], const uint32_t (&q)[32], uint64_t dk) {
#pragma unroll
    for (int k = 0; k < 8; k++) {
        if (k == 0)
            wgmma_n64_z<0>(s, q[0], q[1], q[2], q[3], dk);
        else
            wgmma_n64<0>(s, q[4 * k], q[4 * k + 1], q[4 * k + 2], q[4 * k + 3], dk + (k >> 2) * 512 + (k & 3) * 2);
    }
}
__device__ __forceinline__ void pv_step(float (&o)[64], const uint32_t (&p)[16], uint64_t dv, int acc) {
#pragma unroll
    for (int k = 0; k < 4; k++)
        wgmma_n128<1>(o, p[4 * k], p[4 * k + 1], p[4 * k + 2], p[4 * k + 3], dv + k * 128, k != 0 ? 1 : acc);
}
template <bool SHIFT>
__device__ __forceinline__ void exp_step(const float (&s)[32], uint32_t (&p)[16], float n0, float n1, float& s0,
                                         float& s1) {
#pragma unroll
    for (int i = 0; i < 8; i++) {
        const float e0 = ex2(SHIFT ? s[4 * i] + n0 : s[4 * i]), e1 = ex2(SHIFT ? s[4 * i + 1] + n0 : s[4 * i + 1]);
        const float e2 = ex2(SHIFT ? s[4 * i + 2] + n1 : s[4 * i + 2]), e3 = ex2(SHIFT ? s[4 * i + 3] + n1 : s[4 * i + 3]);
        if (i == 0) {
            s0 = e0 + e1;
            s1 = e2 + e3;
        } else {
            s0 += e0 + e1;
            s1 += e2 + e3;
        }
        p[2 * i] = pack_bf16(e0, e1);
        p[2 * i + 1] = pack_bf16(e2, e3);
    }
}
__device__ __forceinline__ void row_max(const float (&sa)[32], const float (&sb)[32], float& x0, float& x1) {
    float xa[8];
#pragma unroll
    for (int i = 0; i < 8; i++) xa[i] = fmaxf(sa[i], sb[i]);
#pragma unroll
    for (int k = 1; k < 4; k++)
#pragma unroll
        for (int i = 0; i < 8; i++) xa[i] = fmaxf(xa[i], fmaxf(sa[8 * k + i], sb[8 * k + i]));
    x0 = fmaxf(fmaxf(xa[0], xa[1]), fmaxf(xa[4], xa[5]));
    x1 = fmaxf(fmaxf(xa[2], xa[3]), fmaxf(xa[6], xa[7]));
    x0 = fmaxf(x0, __shfl_xor_sync(0xffffffffu, x0, 1));
    x1 = fmaxf(x1, __shfl_xor_sync(0xffffffffu, x1, 1));
    x0 = fmaxf(x0, __shfl_xor_sync(0xffffffffu, x0, 2));
    x1 = fmaxf(x1, __shfl_xor_sync(0xffffffffu, x1, 2));
}
__device__ __forceinline__ void inv_row_sums(float l0, float l1, float& i0, float& i1) {
    l0 += __shfl_xor_sync(0xffffffffu, l0, 1);
    l1 += __shfl_xor_sync(0xffffffffu, l1, 1);
    l0 += __shfl_xor_sync(0xffffffffu, l0, 2);
    l1 += __shfl_xor_sync(0xffffffffu, l1, 2);
    i0 = rcp(l0);
    i1 = rcp(l1);
}

__device__ __forceinline__ uint32_t get_epoch(uint32_t sbase) { return __float_as_uint(lds32f(sbase + OFF_EPOCH)); }
__device__ __forceinline__ float silu_bf16(unsigned short c) {
    const float cv = bf_lo(c);
    return round_bf16(cv * rcp(1.f + ex2(-1.4426950408889634f * cv)));
}
__device__ __forceinline__ void st_mod(uint32_t* p, float v, uint32_t tag) {
    asm volatile("st.relaxed.gpu.global.u32 [%0], %1;" ::"l"(p), "r"(__float_as_uint(round_bf16(v)) | tag)
                 : "memory");
}
__device__ __forceinline__ void fma8(float (&acc)[8], float sc, const uint4& w) {
    acc[0] = fmaf(sc, bf_lo(w.x), acc[0]);
    acc[1] = fmaf(sc, bf_hi(w.x), acc[1]);
    acc[2] = fmaf(sc, bf_lo(w.y), acc[2]);
    acc[3] = fmaf(sc, bf_hi(w.y), acc[3]);
    acc[4] = fmaf(sc, bf_lo(w.z), acc[4]);
    acc[5] = fmaf(sc, bf_hi(w.z), acc[5]);
    acc[6] = fmaf(sc, bf_lo(w.w), acc[6]);
    acc[7] = fmaf(sc, bf_hi(w.w), acc[7]);
}
__device__ __forceinline__ void modp_load(uint4 (&u)[6], const uint32_t* src) {
#pragma unroll
    for (int i = 0; i < 6; i++) u[i] = ld128(reinterpret_cast<const uint4*>(src + i * 2 * DM));
}
__device__ __forceinline__ void modp_to_smem(uint4 (&u)[6], uint32_t dst, const uint32_t* src, uint32_t tag) {
    const uint32_t t0 = clk32();
    while (true) {
        uint32_t bad = 0;
#pragma unroll
        for (int i = 0; i < 6; i++) bad |= (u[i].x ^ tag) | (u[i].y ^ tag) | (u[i].z ^ tag) | (u[i].w ^ tag);
        if (__all_sync(0xffffffffu, (bad & 0xffu) == 0) || clk32() - t0 > WAIT_LIMIT) break;
        modp_load(u, src);
    }
    float s0 = 0.f, s1 = 0.f, s2 = 0.f, s3 = 0.f;
#pragma unroll
    for (int i = 0; i < 6; i++) {
        s0 += __uint_as_float(u[i].x & ~0xffu);
        s1 += __uint_as_float(u[i].y & ~0xffu);
        s2 += __uint_as_float(u[i].z & ~0xffu);
        s3 += __uint_as_float(u[i].w & ~0xffu);
    }
    const uint32_t p0 = pack_bf16(s0, s1), p1 = pack_bf16(s2, s3);
    sts128(dst, p0 << 16, p0 & 0xffff0000u, p1 << 16, p1 & 0xffff0000u);
}

__global__ void __cluster_dims__(2, 1, 1) __launch_bounds__(384, 1)
    fused_block_kernel(const __grid_constant__ Params maps) {
    extern __shared__ uint8_t smem_raw[];
    uint32_t sbase = (smem_u32(smem_raw) + 1023u) & ~1023u;
    asm volatile("" : "+r"(sbase));
    const int b = blockIdx.x;
    const int rank = b & 1;
    const int mt = ((b >> 1) & 7) * 2 + rank;
    const int g = b >> 4;
    const int warp = __shfl_sync(0xffffffffu, threadIdx.x >> 5, 0);
    const int lane = threadIdx.x & 31;
    Scratch* const sc_ = maps.sc;
    const __nv_bfloat16* const wmod = maps.wmod;
    const __nv_bfloat16* const cvec = maps.cvec;

#define SPROF(i)

    if (warp >= 8) {
        asm volatile("setmaxnreg.dec.sync.aligned.u32 24;");
        if (warp == 8 && lane == 0) {
#pragma unroll
            for (int i = 0; i < 8; i++) {
                mbar_init(sbase + OFF_FULL + i * 8, 1);
                mbar_init(sbase + OFF_EMPTY + i * 8, 4);
            }
            mbar_init(sbase + OFF_XBAR, 1);
            mbar_init(sbase + OFF_PBAR, 1);
            asm volatile("fence.mbarrier_init.release.cluster;" ::: "memory");
            asm volatile("barrier.cluster.arrive.relaxed;\nbarrier.cluster.wait;" ::: "memory");
            uint32_t slot = 0, phase = 1;
            const uint32_t dst0 = sbase + rank * BOX_BYTES;
            auto acquire = [&](uint32_t bytes) {
                mbar_wait(sbase + OFF_EMPTY + slot * 8, phase);
                mbar_expect_tx(sbase + OFF_FULL + slot * 8, bytes);
            };
            auto adv8 = [&]() {
                if (++slot == 8) {
                    slot = 0;
                    phase ^= 1;
                }
            };
#pragma unroll 1
            for (int hq = 0; hq < 4; hq++) {
                const int col = (g * 4 + ((hq + 1) & 3)) * 128 + rank * 64;
                if (hq == 2) {
                    l2_prefetch(maps.kc + (size_t)(g * 4 * 2048 + (b & 15) * 64) * 128, SLOT_BYTES);
                    l2_prefetch(maps.vc + (size_t)(g * 4 * 2048 + (b & 15) * 64) * 128, SLOT_BYTES);
                }
#pragma unroll 1
                for (int kc = 0; kc < 9; kc++) {
                    acquire(SLOT_BYTES);
                    tma_mc(dst0 + slot * SLOT_BYTES, &maps.wq, col, kc * 64, sbase + OFF_FULL + slot * 8);
                    adv8();
                }
            }
            const int row0 = g * 4 * 2048;
#pragma unroll 1
            for (int n = 0; n < 128; n++) {
                if (n < 4) mbar_wait(sbase + OFF_EMPTY + (slot + 1) * 8, phase);
                acquire(2 * SLOT_BYTES);
                const uint32_t bar = sbase + OFF_FULL + slot * 8;
                const int r0 = n == 0 ? 0 : (n == 127 ? 126 : n + 1);
                const int r1 = n == 0 ? 1 : (n == 127 ? 127 : n - 1);
                tma_mc(dst0 + slot * SLOT_BYTES, n == 127 ? &maps.v : &maps.k, rank * 64, row0 + r0 * 64, bar);
                tma_mc(dst0 + (slot + 1) * SLOT_BYTES, n == 0 ? &maps.k : &maps.v, rank * 64, row0 + r1 * 64, bar);
                adv8();
                adv8();
                const int u = n + KV_AHEAD;
                if (u < 128 && (u & 15) == (b & 15)) {
                    l2_prefetch(maps.kc + (size_t)(row0 + u * 64) * 128, SLOT_BYTES);
                    l2_prefetch(maps.vc + (size_t)(row0 + u * 64) * 128, SLOT_BYTES);
                }
            }
#pragma unroll 1
            for (int p = 0; p < 4; p++)
#pragma unroll 1
                for (int kc = 0; kc < 8; kc++) {
                    acquire(SLOT_BYTES);
                    tma_mc(dst0 + slot * SLOT_BYTES, &maps.wo, p * 128 + rank * 64, g * 512 + kc * 64,
                           sbase + OFF_FULL + slot * 8);
                    adv8();
                }
#pragma unroll 1
            for (int kc = 0; kc < 4; kc++) {
                acquire(SLOT_BYTES);
                tma_mc(dst0 + slot * SLOT_BYTES, &maps.wo, 512, g * 512 + kc * 128 + rank * 64,
                       sbase + OFF_FULL + slot * 8);
                adv8();
            }
            const CUtensorMap* mg = rank ? &maps.wu : &maps.wg;
#pragma unroll 1
            for (int ch = 0; ch < 9; ch++)
#pragma unroll 1
                for (int kc = 0; kc < 9; kc++) {
                    acquire(SLOT_BYTES);
                    tma_mc(dst0 + slot * SLOT_BYTES, mg, g * 576 + ch * 64, kc * 64, sbase + OFF_FULL + slot * 8);
                    adv8();
                }
#pragma unroll 1
            for (int p = 0; p < 4; p++)
#pragma unroll 1
                for (int kc = 2; kc < 11; kc++) {
                    acquire(SLOT_BYTES);
                    tma_mc(dst0 + slot * SLOT_BYTES, &maps.wd, p * 128 + rank * 64, g * 576 + (kc < 9 ? kc : kc - 9) * 64,
                           sbase + OFF_FULL + slot * 8);
                    adv8();
                }
#pragma unroll 1
            for (int i = 0; i < 5; i++) {
                acquire(i < 4 ? SLOT_BYTES : BOX_BYTES);
                const int kc = 2 * i + rank + 2;
                if (i < 4 || rank == 0)
                    tma_mc(dst0 + slot * SLOT_BYTES, &maps.wd, 512, g * 576 + (kc < 9 ? kc : kc - 9) * 64,
                           sbase + OFF_FULL + slot * 8);
                adv8();
            }
        } else if (warp == 11) {
            asm volatile("barrier.cluster.arrive.relaxed.aligned;" ::: "memory");
            bar_sync(6, 160);
            uint4* hz = sc_->h[(get_epoch(sbase) & 1) ^ 1][0] + (size_t)b * 72 * 32 + lane;
#pragma unroll 1
            for (int i = 0; i < 72; i++) {
                hz[i * 32] = make_uint4(0, 0, 0, 0);
                __nanosleep(200);
            }
            bar_sync(6, 160);
            if (lane == 0) {
#pragma unroll 1
                for (int i = 0; i < 9; i++) {
                    l2_prefetch((const char*)maps.wo_p + (size_t)b * 36864 + i * 4096, 4096);
                    __nanosleep(400);
                    l2_prefetch((const char*)maps.wg_p + (size_t)b * 41472 + i * 4608, 4608);
                    __nanosleep(400);
                    l2_prefetch((const char*)maps.wu_p + (size_t)b * 41472 + i * 4608, 4608);
                    __nanosleep(400);
                    l2_prefetch((const char*)maps.wd_p + (size_t)b * 41472 + i * 4608, 4608);
                    __nanosleep(400);
                }
            }
        } else if (warp == 9 || warp == 10) {
            asm volatile("barrier.cluster.arrive.relaxed.aligned;" ::: "memory");
            bar_sync(4, 320);
            const uint32_t tag = (get_epoch(sbase) + 1) & 0xffffu;
            if (warp == 10 && lane < 9) l2_prefetch((const char*)maps.wq_p + (size_t)b * 36864 + lane * 4096, 4096);
            const int blk = warp == 9 ? 72 + b : 200 + b;
            if (blk < 216) {
                float acc[8];
#pragma unroll
                for (int e = 0; e < 8; e++) acc[e] = 0.f;
                const uint4* wp = reinterpret_cast<const uint4*>(wmod + (size_t)(lane >> 1) * (6 * DM) + blk * 16) + (lane & 1);
                const unsigned short* cp = reinterpret_cast<const unsigned short*>(cvec) + (lane >> 1);
#pragma unroll 1
                for (int i = 0; i < 36; i++) {
                    const uint4 w = __ldg(wp + (size_t)i * (16 * 6 * DM / 8));
                    const float sc = silu_bf16(__ldg(cp + i * 16));
                    fma8(acc, sc, w);
                }
#pragma unroll
                for (int o = 2; o < 32; o <<= 1)
#pragma unroll
                    for (int e = 0; e < 8; e++) acc[e] += __shfl_xor_sync(0xffffffffu, acc[e], o);
                if (lane < 2) {
#pragma unroll
                    for (int e = 0; e < 8; e++) st_mod(sc_->mod + blk * 16 + lane * 8 + e, acc[e], tag);
                }
            }
            if (warp == 9) {
#pragma unroll 1
                for (int st = 1; st <= 2; st++) {
                    bar_sync(7, 160);
                    const uint32_t* src = sc_->mod + (st * 3 - 1) * DM;
                    const int n = st == 1 ? 3 * DM : DM;
#pragma unroll 1
                    for (int i = lane * 4; i < n + 127 - ((n + 127) & 127); i += 128)
                        mod_to_smem(sbase + OFF_MODT + min(i, n - 4) * 4, src + min(i, n - 4), tag);
                    __syncwarp();
                    if (lane == 0) rows_load(sbase, st == 1 ? &maps.rx : &maps.rx2, (mt * 8 + g) * 16);
                    bar_sync(11, 160);
                    if (lane == 0) {
                        mbar_expect_tx(sbase + OFF_PBAR, 65536);
                        const uint4* ps = sc_->part + (size_t)(mt * 8 + g) * 8 * 36 * 32;
#pragma unroll 1
                        for (int i = 0; i < 8; i++) bulk_load(sbase + OFF_PBUF + i * 8192, ps + i * 36 * 32, 8192, sbase + OFF_PBAR);
                    }
                    __syncwarp();
                    if (st == 1) {
                        bar_sync(7, 160);
                        if (lane == 0) {
                            rows_store(sbase, &maps.rx2, (mt * 8 + g) * 16);
                            rows_store_wait();
                        }
                        __syncwarp();
                        bar_arrive(10, 160);
                    }
                }
            }
        }
    } else {
        uint4 w1[3], xw[5], ew = make_uint4(0, 0, 0, 0);
        unsigned short cu[3];
        {
            const int t = threadIdx.x, bw = min(b, 107);
            const int row = (bw / 18) * 96 + (t >> 3);
#pragma unroll
            for (int i = 0; i < 3; i++) {
                w1[i] = ldg128(reinterpret_cast<const uint4*>(wmod + (size_t)(row + 32 * i) * (6 * DM)) + (bw % 18) * 8 + (t & 7));
                asm volatile("ld.global.nc.u16 %0, [%1];" : "=h"(cu[i]) : "l"(cvec + row + 32 * i));
            }
            if (t == 0) ew = ld128(reinterpret_cast<const uint4*>(&sc_->epoch[b * 32]));
#pragma unroll
            for (int i = 0; i < 5; i++)
                xw[i] = ldg128(reinterpret_cast<const uint4*>(maps.x + (size_t)(mt * 8 + g) * 16 * DM) + min(t + 256 * i, 1151));
        }
        if (threadIdx.x == 160) SPROF(5);
        asm volatile("setmaxnreg.inc.sync.aligned.u32 240;");
        if (threadIdx.x == 160) SPROF(6);
        const int wg = warp >> 2;
        const int tid = threadIdx.x;
        Ctx cx;
        cx.sbase = sbase;
        cx.wg = wg;
        if (wg == 1) bar_arrive(8, 256);
        cx.rel_cta = (lane == 0 && (warp & 3) < 2) ? (warp & 3) : 2;
        const uint32_t red = sbase + OFF_RED;
        const int own = mt * 8 + g;
        const int wown = mt * 8 + warp;
        PROF(0);
        PROFG(30);
        PROFR(17);
        {
            asm volatile("barrier.cluster.arrive.relaxed.aligned;" ::: "memory");
            float acc[8];
#pragma unroll
            for (int e = 0; e < 8; e++) acc[e] = 0.f;
#pragma unroll
            for (int i = 0; i < 3; i++) fma8(acc, silu_bf16(cu[i]), w1[i]);
#pragma unroll
            for (int o = 8; o < 32; o <<= 1)
#pragma unroll
                for (int e = 0; e < 8; e++) acc[e] += __shfl_xor_sync(0xffffffffu, acc[e], o);
            PROFR(19);
            if (lane < 8) {
                const uint32_t dst = sbase + OFF_MRED + warp * 256 + lane * 32;
                sts128(dst, __float_as_uint(acc[0]), __float_as_uint(acc[1]), __float_as_uint(acc[2]), __float_as_uint(acc[3]));
                sts128(dst + 16, __float_as_uint(acc[4]), __float_as_uint(acc[5]), __float_as_uint(acc[6]), __float_as_uint(acc[7]));
            }
            if (tid == 0) sts128(sbase + OFF_EPOCH, ew.x, ew.y, ew.z, ew.w);
            bar_sync(3, 256);
            PROFR(20);
            if (tid < 64 && b < 108) {
                float sum = 0.f;
#pragma unroll
                for (int w8 = 0; w8 < 8; w8++) sum += lds32f(sbase + OFF_MRED + w8 * 256 + tid * 4);
                asm volatile("st.relaxed.gpu.global.u32 [%0], %1;" ::"l"(&sc_->modp[b / 18][(b % 18) * 64 + tid]),
                             "r"((__float_as_uint(sum) & ~0xffu) | ((get_epoch(sbase) + 1) & 0xffu))
                             : "memory");
            }
            PROFR(21);
#pragma unroll
            for (int i = 0; i < 5; i++) {
                const int vi = min(tid + 256 * i, 1151), ln = vi >> 3;
                sts128(sbase + OFF_ROWS + ln * 128 + (((vi & 7) ^ (ln & 7)) << 4), xw[i].x, xw[i].y, xw[i].z, xw[i].w);
            }
            bar_sync(3, 256);
        }

        Ring ring{0u, 0u};
        int stage = 0;
        asm volatile("" : "+r"(stage));
#pragma unroll 1
        for (;; stage++) {
            int tid, lane;
            asm volatile("mov.u32 %0, %%tid.x;" : "=r"(tid));
            lane = tid & 31;
            const uint32_t epoch = get_epoch(sbase);
            {
                float v[36];
                const uint32_t modt = sbase + OFF_MODT + (warp * 16 + (lane & 3) * 2) * 4;
                if (stage == 0) {
#pragma unroll
                    for (int i = 0; i < 36; i++) v[i] = 0.f;
                } else {
                    const uint4* psrc = sc_->part + (size_t)own * 8 * 36 * 32;
                    sum_partials(v, psrc + tid, reinterpret_cast<const uint2*>(psrc + 32 * 32) + tid, stage & 1,
                                 sbase + OFF_PBUF + tid * 16, sbase + OFF_PBAR, stage - 1);
                    PROF(stage == 1 ? 8 : 15);
                }
                if (stage) mbar_wait(sbase + OFF_XBAR, stage - 1);
                if (stage == 0) PROFR(22);
                {
                    const float gs = stage == 2 ? 0.5f : 1.f;
                    float gate[18];
                    lds_mod(gate, modt, warp);
                    const int r = lane >> 2;
                    const uint32_t rows = sbase + OFF_ROWS + r * (DM * 2) + (lane & 3) * 4;
#pragma unroll
                    for (int j = 0; j < 9; j++) {
                        const int ch = j < 8 ? (j >> 1) * 2 + (warp >> 2) : 8, c16 = j < 8 ? (warp & 3) * 2 + (j & 1) : warp;
                        const uint32_t ad = rows + ch * 128 + ((c16 ^ ((r + ch) & 7)) << 4);
                        const uint32_t u0 = __float_as_uint(lds32f(ad)), u1 = __float_as_uint(lds32f(ad + 8 * DM * 2));
                        const float g0 = stage ? gate[2 * j] * gs : 0.f, g1 = stage ? gate[2 * j + 1] * gs : 0.f;
                        v[4 * j] = fmaf(g0, v[4 * j], bf_lo(u0));
                        v[4 * j + 1] = fmaf(g1, v[4 * j + 1], bf_hi(u0));
                        v[4 * j + 2] = fmaf(g0, v[4 * j + 2], bf_lo(u1));
                        v[4 * j + 3] = fmaf(g1, v[4 * j + 3], bf_hi(u1));
                        sts32f(ad, __uint_as_float(pack_bf16(v[4 * j], v[4 * j + 1])));
                        sts32f(ad + 8 * DM * 2, __uint_as_float(pack_bf16(v[4 * j + 2], v[4 * j + 3])));
                    }
                    asm volatile("fence.proxy.async.shared::cta;" ::: "memory");
                }
                if (stage == 2) break;
                PROF(stage == 0 ? 1 : 9);
                uint4 ua[6], ub[6];
#pragma unroll
                for (int i = 0; i < 6; i++) ua[i] = ub[i] = make_uint4(0, 0, 0, 0);
                layernorm_rows(v, red, warp, lane, [&]() {
                    if (stage == 0) {
                        modp_load(ua, sc_->modp[0] + tid * 4);
                        if (warp == 0) modp_load(ub, sc_->modp[0] + 1024 + tid * 4);
                    }
                });
                if (stage == 0) PROFR(27);
                if (stage == 0) {
                    const uint32_t tag = (epoch + 1) & 0xffu;
                    modp_to_smem(ua, sbase + OFF_MODT + (DM + tid * 4) * 4, sc_->modp[0] + tid * 4, tag);
                    if (warp == 0)
                        modp_to_smem(ub, sbase + OFF_MODT + (DM + 1024 + tid * 4) * 4, sc_->modp[0] + 1024 + tid * 4, tag);
                    bar_sync(3, 256);
                }
                float shift[18], scale[18];
                lds_mod(shift, modt + DM * 4, warp);
                lds_mod(scale, modt + 2 * DM * 4, warp);
                if (stage == 0) PROFR(28);
                PROF(stage == 0 ? 2 : 10);
                modulate_store(v, shift, scale, sc_->h[epoch & 1][stage] + (size_t)own * 36 * 32, warp, lane);
                if (stage == 0) asm volatile("barrier.cluster.wait.aligned;" ::: "memory");
            }

            const uint32_t spill = sbase + 8 * SLOT_BYTES + wg * 3 * SLOT_BYTES + (tid & 127) * 16;
            uint32_t a[144];
            PROF(stage == 0 ? 3 : 11);
            {
                const uint4* hsrc = sc_->h[epoch & 1][stage] + (size_t)wown * 36 * 32 + lane;
                __nanosleep(PROBE_NS);
                poll_tail(a, reinterpret_cast<const uint2*>(hsrc - lane + 32 * 32) + lane);
                PROF(stage == 0 ? 4 : 12);
                if (stage == 1) PROFG(25);
                TG(stage * 32 + 30);
                if (wg == 1) bar_sync(5, 256);
                poll_frags<0, 32>(a, hsrc, wg == 0);
                if (stage == 0) bar_arrive(4, 320);
            }
            uint4* hhbuf = sc_->hh + (size_t)b * 8 * 256 + tid;
            float d[64];
#pragma unroll 1
            for (int ch = 0;; ch++) {
                TG(stage * 32 + ch * 2);
                gemm_n128(d, a, cx, ring, true);
                TG(stage * 32 + ch * 2 + 1);
                if (stage == 0) {
#pragma unroll
                    for (int i = 0; i < 64; i++) d[i] *= SM_SCALE;
                    if (ch == 3) break;
#pragma unroll
                    for (int v = 0; v < 8; v++)
                        sts128(spill + (ch * 8 + v) * 2048, pack_bf16(d[8 * v], d[8 * v + 1]),
                               pack_bf16(d[8 * v + 2], d[8 * v + 3]), pack_bf16(d[8 * v + 4], d[8 * v + 5]),
                               pack_bf16(d[8 * v + 6], d[8 * v + 7]));
                } else {
#pragma unroll
                    for (int i = 0; i < 32; i++) {
                        const float gv = d[i], gu = gv * d[32 + i];
                        const float z = gv * fmaf(gv * gv, 0.7978845608028654f * 0.044715f, 0.7978845608028654f);
                        d[i] = fmaf(gu, tanh_fast(z), gu);
                    }
                    if (ch == 8) break;
                    if (wg == 0) {
                        if (ch == 0) bar_arrive(7, 160);
                        if (ch == 2) bar_sync(10, 160);
                    }
#pragma unroll
                    for (int v = 0; v < 4; v++) {
                        const uint4 h4 = make_uint4(pack_bf16(d[8 * v], d[8 * v + 1]), pack_bf16(d[8 * v + 2], d[8 * v + 3]),
                                                    pack_bf16(d[8 * v + 4], d[8 * v + 5]), pack_bf16(d[8 * v + 6], d[8 * v + 7]));
                        if (ch < 2)
                            __stcg(hhbuf + (ch * 4 + v) * 256, h4);
                        else
                            sts128(spill + ((ch - 2) * 4 + v) * 2048, h4.x, h4.y, h4.z, h4.w);
                    }
                }
            }
            if (stage == 0) {
                uint32_t q[32];
#pragma unroll
                for (int i = 0; i < 32; i++) q[i] = pack_bf16(d[2 * i], d[2 * i + 1]);
                PROF(5);
                PROFG(23);
                if (wg == 0) bar_arrive(6, 160);
                {
                    float o[64], sa[32], sb[32];
                    uint32_t pa[16], pb[16];
#pragma unroll
                    for (int i = 0; i < 64; i++) o[i] = 0.f;
                    float n0 = 0.f, n1 = 0.f, l0 = 1.f, l1 = 1.f;
                    bool shifted = false;
                    const uint64_t dbase = desc_of(sbase);
                    const uint64_t dbk = dbase - (511u << 16);
                    const int my_bar = 1 + wg, other_bar = 2 - wg;

                    auto softmax_a = [&](bool first, float& s0, float& s1) {
                        if (first) {
                            shifted = false;
                            n0 = n1 = 0.f;
                            l0 = l1 = 0.f;
                        }
                        if (shifted)
                            exp_step<true>(sa, pa, n0, n1, s0, s1);
                        else
                            exp_step<false>(sa, pa, n0, n1, s0, s1);
                    };
                    auto softmax_b = [&](bool first, float s0, float s1) {
                        float u0, u1;
                        if (shifted)
                            exp_step<true>(sb, pb, n0, n1, u0, u1);
                        else
                            exp_step<false>(sb, pb, n0, n1, u0, u1);
                        s0 += u0;
                        s1 += u1;
                        bool bad = !(fmaxf(s0, s1) <= SM_HI);
                        if (first) {
                            float r0 = s0 + __shfl_xor_sync(0xffffffffu, s0, 1), r1 = s1 + __shfl_xor_sync(0xffffffffu, s1, 1);
                            r0 += __shfl_xor_sync(0xffffffffu, r0, 2);
                            r1 += __shfl_xor_sync(0xffffffffu, r1, 2);
                            bad = bad || !(fminf(r0, r1) >= SM_LO);
                        }
                        if (__any_sync(0xffffffffu, bad)) {
                            float x0, x1;
                            row_max(sa, sb, x0, x1);
                            x0 = -x0;
                            x1 = -x1;
                            if (!first) {
                                x0 = fminf(x0, n0);
                                x1 = fminf(x1, n1);
                                const float al0 = ex2(x0 - n0), al1 = ex2(x1 - n1);
                                l0 *= al0;
                                l1 *= al1;
#pragma unroll
                                for (int i = 0; i < 16; i++) {
                                    o[4 * i] *= al0;
                                    o[4 * i + 1] *= al0;
                                    o[4 * i + 2] *= al1;
                                    o[4 * i + 3] *= al1;
                                }
                            }
                            n0 = x0;
                            n1 = x1;
                            shifted = true;
                            exp_step<true>(sa, pa, n0, n1, s0, s1);
                            exp_step<true>(sb, pb, n0, n1, u0, u1);
                            s0 += u0;
                            s1 += u1;
                        }
                        l0 += s0;
                        l1 += s1;
                    };

                    cx.wait_full(4, 0);
                    if (wg == 1) bar_sync(my_bar, 256);
                    wg_fence();
                    qk_step(sa, q, dbk + 4 * 1024);
                    qk_step(sb, q, dbk + 5 * 1024);
                    wg_commit();
                    bar_arrive(other_bar, 256);
                    wg_wait<0>();
                    pin(sa);
                    pin(sb);
                    cx.release(4);
                    cx.wait_full(6, 0);
                    {
                        float s0, s1;
                        softmax_a(true, s0, s1);
                        softmax_b(true, s0, s1);
                    }
                    uint32_t alo = (uint32_t)dbase + 6 * 1024, blo = (uint32_t)dbase;
                    const uint32_t dhi = (uint32_t)(dbase >> 32);
#pragma unroll 1
                    for (int t = 1; t < 64; t++) {
                        const int j = t & 15;
                        const uint32_t sA = 2 + 4 * (t & 1), sB = 4 - 4 * (t & 1);
                        const uint64_t da = ((uint64_t)dhi << 32) | alo, db = ((uint64_t)dhi << 32) | blo;
                        TL(0);
                        bar_sync(my_bar, 256);
                        TL(2);
                        wg_fence();
                        pv_step(o, pa, da + 1024, j != 1);
                        qk_step(sa, q, da - (511u << 16));
                        wg_commit();
                        cx.wait_full(sB, ((36 + 4 * t) >> 3) & 1);
                        wg_fence();
                        qk_step(sb, q, db - (511u << 16));
                        pv_step(o, pb, db + 1024, 1);
                        wg_commit();
                        bar_arrive(other_bar, 256);
                        alo ^= 4096;
                        blo ^= 4096;
                        asm volatile("" : "+r"(alo), "+r"(blo));
                        TL(3);
                        wg_wait<1>();
                        pin(sa);
                        pin(pa);
                        TL(4);
                        cx.release(sA);
                        const float lp0 = l0, lp1 = l1;
                        float s0, s1;
                        softmax_a(j == 0, s0, s1);
                        TL(5);
                        wg_wait<0>();
                        pin(o);
                        pin(sb);
                        pin(pb);
                        TL(6);
                        cx.release(sB);
                        if (j == 0) {
                            float i0, i1;
                            inv_row_sums(lp0, lp1, i0, i1);
                            const uint32_t dst = spill + ((t >> 4) - 1) * 16384;
#pragma unroll
                            for (int v = 0; v < 8; v++)
                                sts128(dst + v * 2048, pack_bf16(o[8 * v] * i0, o[8 * v + 1] * i0),
                                       pack_bf16(o[8 * v + 2] * i1, o[8 * v + 3] * i1),
                                       pack_bf16(o[8 * v + 4] * i0, o[8 * v + 5] * i0),
                                       pack_bf16(o[8 * v + 6] * i1, o[8 * v + 7] * i1));
                        }
                        const uint32_t bn = sbase + OFF_FULL + (8 - sA) * 8, pn = ((38 + 4 * t) >> 3) & 1;
                        const bool okn = mbar_try(bn, pn);
                        TL(1);
                        softmax_b(j == 0, s0, s1);
                        if (!okn || j == 15) {
                            mbar_wait(bn, pn);
                            if (t == 47 && wg == 0) bar_arrive(6, 160);
                            if (j == 15 && t < 63) {
                                const uint32_t src = spill + (t >> 4) * 16384;
#pragma unroll
                                for (int v = 0; v < 8; v++)
                                    lds128(src + v * 2048, q[4 * v], q[4 * v + 1], q[4 * v + 2], q[4 * v + 3]);
                            }
                        }
                        TL(7);
                    }
                    bar_sync(my_bar, 256);
                    wg_fence();
                    pv_step(o, pa, dbase + 2 * 1024, 1);
                    pv_step(o, pb, dbase + 3 * 1024, 1);
                    wg_commit();
                    if (wg == 0) bar_arrive(other_bar, 256);
                    float i0, i1;
                    inv_row_sums(l0, l1, i0, i1);
                    wg_wait<0>();
                    pin(o);
                    cx.release(2);
#pragma unroll
                    for (int i = 0; i < 16; i++) {
                        a[96 + 2 * i] = pack_bf16(o[4 * i] * i0, o[4 * i + 1] * i0);
                        a[96 + 2 * i + 1] = pack_bf16(o[4 * i + 2] * i1, o[4 * i + 3] * i1);
                    }
#pragma unroll
                    for (int i = 128; i < 144; i++) a[i] = 0;
                }
                ring.slot = 4;
                ring.phase = 0;
                PROF(6);
                PROFG(24);
            } else {
#pragma unroll
                for (int v = 0; v < 8; v++) {
                    const uint4 t = __ldcg(hhbuf + v * 256);
                    a[112 + 4 * v] = t.x;
                    a[113 + 4 * v] = t.y;
                    a[114 + 4 * v] = t.z;
                    a[115 + 4 * v] = t.w;
                }
#pragma unroll
                for (int i = 0; i < 16; i++) a[96 + i] = pack_bf16(d[2 * i], d[2 * i + 1]);
                PROF(13);
            }
#pragma unroll
            for (int v = 0; v < 24; v++) lds128(spill + v * 2048, a[4 * v], a[4 * v + 1], a[4 * v + 2], a[4 * v + 3]);

            {
                uint4* dst = sc_->part + ((size_t)wown * 8 + g) * 36 * 32 + lane;
                const uint32_t ptag = (stage + 1) & 1;
#pragma unroll 1
                for (int p = 0; p < 4; p++) {
                    TG(stage * 32 + 18 + p * 2);
                    gemm_n128(d, a, cx, ring, stage != 0);
                    TG(stage * 32 + 19 + p * 2);
#pragma unroll
                    for (int u = 0; u < 8; u++)
                        st128(dst + (p * 8 + u) * 32, (pack_bf16(d[8 * u], d[8 * u + 1]) & ~1u) | ptag,
                              pack_bf16(d[8 * u + 2], d[8 * u + 3]), pack_bf16(d[8 * u + 4], d[8 * u + 5]),
                              pack_bf16(d[8 * u + 6], d[8 * u + 7]));
                    if (p == 0 && wg == 0) bar_arrive(7, 160);
                    if (p == 2 && wg == 1) bar_arrive(11, 160);
                }
                float e[32];
                TG(stage * 32 + 26);
                gemm_n64(e, a, cx, ring, stage != 0);
                TG(stage * 32 + 27);
                uint2* dst2 = reinterpret_cast<uint2*>(dst - lane + 32 * 32) + lane;
#pragma unroll
                for (int j = 0; j < 8; j++)
                    st64(dst2 + j * 32, (pack_bf16(e[4 * j], e[4 * j + 1]) & ~1u) | ptag, pack_bf16(e[4 * j + 2], e[4 * j + 3]));
            }
            PROF(stage == 0 ? 7 : 14);
            if (stage == 1) {
                PROFG(26);
                asm volatile("barrier.cluster.arrive.relaxed.aligned;" ::: "memory");
            }
        }
        if (wg == 0) bar_sync(8, 256);
        bar_sync(3, 256);
        if (tid == 32) sc_->epoch[b * 32] = get_epoch(sbase) + 1;
        if (tid == 0) {
            rows_store(sbase, &maps.rout, own * 16);
            rows_store_wait();
        }
        __syncwarp();
        PROF(16);
        PROFG(31);
        asm volatile("barrier.cluster.wait.aligned;" ::: "memory");
    }
}

typedef CUresult (*EncodeFn)(CUtensorMap*, CUtensorMapDataType, cuuint32_t, void*, const cuuint64_t*, const cuuint64_t*,
                             const cuuint32_t*, const cuuint32_t*, CUtensorMapInterleave, CUtensorMapSwizzle,
                             CUtensorMapL2promotion, CUtensorMapFloatOOBfill);

void make_map(EncodeFn enc, CUtensorMap* m, const void* ptr, uint64_t rows, uint64_t cols, bool narrow = false) {
    cuuint64_t gdim[2] = {cols, rows};
    cuuint64_t gstr[1] = {cols * 2};
    cuuint32_t box[2] = {narrow ? 16u : 64u, narrow ? 192u : 64u};
    cuuint32_t estr[2] = {1, 1};
    enc(m, CU_TENSOR_MAP_DATA_TYPE_BFLOAT16, 2, const_cast<void*>(ptr), gdim, gstr, box, estr,
        CU_TENSOR_MAP_INTERLEAVE_NONE, narrow ? CU_TENSOR_MAP_SWIZZLE_NONE : CU_TENSOR_MAP_SWIZZLE_128B,
        CU_TENSOR_MAP_L2_PROMOTION_L2_128B,
        CU_TENSOR_MAP_FLOAT_OOB_FILL_NONE);
}

void make_rows_map(EncodeFn enc, CUtensorMap* m, const void* ptr) {
    cuuint64_t gdim[3] = {64, 9, 2048};
    cuuint64_t gstr[2] = {128, DM * 2};
    cuuint32_t box[3] = {64, 9, 16};
    cuuint32_t estr[3] = {1, 1, 1};
    enc(m, CU_TENSOR_MAP_DATA_TYPE_BFLOAT16, 3, const_cast<void*>(ptr), gdim, gstr, box, estr,
        CU_TENSOR_MAP_INTERLEAVE_NONE, CU_TENSOR_MAP_SWIZZLE_128B, CU_TENSOR_MAP_L2_PROMOTION_L2_128B,
        CU_TENSOR_MAP_FLOAT_OOB_FILL_NONE);
}

}

extern "C" void kernel_launch(void* const* d_in, const int* in_sizes, int n_in, void* d_out, int out_size) {
    (void)in_sizes;
    (void)n_in;
    (void)out_size;
    void* fn = nullptr;
    cudaDriverEntryPointQueryResult qr;
    cudaGetDriverEntryPoint("cuTensorMapEncodeTiled", &fn, cudaEnableDefault, &qr);
    EncodeFn enc = (EncodeFn)fn;
    Params maps;
    maps.x = (const __nv_bfloat16*)d_in[0];
    maps.cvec = (const __nv_bfloat16*)d_in[9];
    maps.wmod = (const __nv_bfloat16*)d_in[10];
    maps.kc = (const __nv_bfloat16*)d_in[1];
    maps.vc = (const __nv_bfloat16*)d_in[2];
    maps.wq_p = (const __nv_bfloat16*)d_in[3];
    maps.wo_p = (const __nv_bfloat16*)d_in[4];
    maps.wg_p = (const __nv_bfloat16*)d_in[6];
    maps.wu_p = (const __nv_bfloat16*)d_in[7];
    maps.wd_p = (const __nv_bfloat16*)d_in[8];
    maps.out = (__nv_bfloat16*)d_out;
    void* scp = nullptr;
    cudaGetSymbolAddress(&scp, g_scratch);
    maps.sc = (Scratch*)scp;
    make_map(enc, &maps.k, d_in[1], 32 * 2048, 128);
    make_map(enc, &maps.v, d_in[2], 32 * 2048, 128);
    make_map(enc, &maps.wq, d_in[3], 576, 4096);
    make_map(enc, &maps.wo, d_in[4], 4096, 576);
    make_map(enc, &maps.wg, d_in[6], 576, 4608);
    make_map(enc, &maps.wu, d_in[7], 576, 4608);
    make_map(enc, &maps.wd, d_in[8], 4608, 576);
    make_rows_map(enc, &maps.rx, d_in[0]);
    make_rows_map(enc, &maps.rx2, (char*)scp + offsetof(Scratch, x2));
    make_rows_map(enc, &maps.rout, d_out);
    cudaFuncSetAttribute(fused_block_kernel, cudaFuncAttributeMaxDynamicSharedMemorySize, SMEM_BYTES);
    fused_block_kernel<<<128, 384, SMEM_BYTES>>>(maps);
}
```

```cpp
#include <cuda_runtime.h>
#include <cuda_bf16.h>
#include <cuda.h>
#include <stdint.h>
#include <stddef.h>

namespace {

constexpr int DM = 576;
constexpr int SLOT_BYTES = 16384;
constexpr int BOX_BYTES = 8192;
constexpr int NUNITS = 14;
constexpr int SMEM_TAIL = NUNITS * SLOT_BYTES;
constexpr int SMEM_BYTES = SMEM_TAIL + 2048 + 1024;
constexpr int OFF_FULL = SMEM_TAIL;
constexpr int OFF_EMPTY = SMEM_TAIL + 64;
constexpr int OFF_RED = SMEM_TAIL + 128;

constexpr int KV_AHEAD = 16;
#define GATE_SLOT 4
#define PROBE_NS 300
constexpr int OFF_XBAR = SMEM_TAIL + 1792;
constexpr int OFF_ROWS = 8 * SLOT_BYTES;
constexpr int OFF_MODT = OFF_ROWS + 20480;
constexpr int OFF_EPOCH = SMEM_TAIL + 1808;
constexpr int OFF_PBUF = OFF_ROWS + 32768;
constexpr int OFF_PBAR = SMEM_TAIL + 1800;
constexpr int OFF_MRED = OFF_ROWS + 28672;

struct Scratch {
    unsigned epoch[128 * 32];
    uint32_t mod[6 * DM];
    uint32_t modp[6][2 * DM];
    uint4 h[2][2][128 * 36 * 32];
    uint4 part[128 * 8 * 36 * 32];
    uint4 hh[128 * 8 * 256];
    __nv_bfloat16 x2[2048 * DM];
};
__device__ Scratch g_scratch;

#define TG(i)
#define TL(i)
#define PROFR(i)
#define PROF(i)
#define PROFG(i)

struct Params {
    const __nv_bfloat16 *x, *cvec, *wmod, *kc, *vc, *wq_p, *wo_p, *wg_p, *wu_p, *wd_p;
    __nv_bfloat16* out;
    Scratch* sc;
    CUtensorMap k, v, wq, wo, wg, wu, wd, rx, rx2, rout;
};

__device__ __forceinline__ uint32_t smem_u32(const void* p) { return (uint32_t)__cvta_generic_to_shared(p); }
__device__ __forceinline__ void mbar_init(uint32_t a, uint32_t c) {
    asm volatile("mbarrier.init.shared::cta.b64 [%0], %1;" ::"r"(a), "r"(c) : "memory");
}
__device__ __forceinline__ void mbar_expect_tx(uint32_t a, uint32_t bytes) {
    asm volatile("mbarrier.arrive.expect_tx.shared::cta.b64 _, [%0], %1;" ::"r"(a), "r"(bytes) : "memory");
}
__device__ __forceinline__ bool mbar_try(uint32_t a, uint32_t ph) {
    uint32_t ok;
    asm volatile(
        "{\n.reg .pred p;\nmbarrier.try_wait.parity.shared::cta.b64 p, [%1], %2;\nselp.u32 %0, 1, 0, p;\n}"
        : "=r"(ok)
        : "r"(a), "r"(ph)
        : "memory");
    return ok != 0;
}
__device__ __forceinline__ uint32_t clk32() {
    uint32_t c;
    asm volatile("mov.u32 %0, %%clock;" : "=r"(c));
    return c;
}
constexpr uint32_t WAIT_LIMIT = 1u << 30;
__device__ __forceinline__ void mbar_wait(uint32_t a, uint32_t ph) {
    if (mbar_try(a, ph)) return;
    uint32_t t0 = clk32();
    while (!mbar_try(a, ph)) {
        if (clk32() - t0 > WAIT_LIMIT) break;
    }
}
__device__ __forceinline__ void mbar_arrive_cluster(uint32_t a, uint32_t cta) {
    asm volatile(
        "{\n.reg .b32 ra;\nmapa.shared::cluster.u32 ra, %0, %1;\nmbarrier.arrive.shared::cluster.b64 _, [ra];\n}" ::"r"(a),
        "r"(cta)
        : "memory");
}
__device__ __forceinline__ void tma_mc(uint32_t dst, const CUtensorMap* m, int c0, int c1, uint32_t bar) {
    asm volatile(
        "cp.async.bulk.tensor.2d.shared::cluster.global.mbarrier::complete_tx::bytes.multicast::cluster"
        " [%0], [%1, {%3, %4}], [%2], %5;" ::"r"(dst),
        "l"(m), "r"(bar), "r"(c0), "r"(c1), "h"((uint16_t)3)
        : "memory");
}
__device__ __forceinline__ void bulk_load(uint32_t dst, const void* src, uint32_t bytes, uint32_t bar) {
    asm volatile("cp.async.bulk.shared::cluster.global.mbarrier::complete_tx::bytes [%0], [%1], %2, [%3];" ::"r"(dst),
                 "l"(src), "r"(bytes), "r"(bar)
                 : "memory");
}
__device__ __forceinline__ void l2_prefetch(const void* p, uint32_t bytes) {
    asm volatile("cp.async.bulk.prefetch.L2.global [%0], %1;" ::"l"(p), "r"(bytes) : "memory");
}
__device__ __forceinline__ void bar_sync(int id, int n) { asm volatile("bar.sync %0, %1;" ::"r"(id), "r"(n) : "memory"); }
__device__ __forceinline__ void bar_arrive(int id, int n) {
    asm volatile("bar.arrive %0, %1;" ::"r"(id), "r"(n) : "memory");
}
__device__ __forceinline__ void wg_fence() { asm volatile("wgmma.fence.sync.aligned;" ::: "memory"); }
__device__ __forceinline__ void wg_commit() { asm volatile("wgmma.commit_group.sync.aligned;" ::: "memory"); }
template <int N>
__device__ __forceinline__ void wg_wait() {
    asm volatile("wgmma.wait_group.sync.aligned %0;" ::"n"(N) : "memory");
}
template <int N>
__device__ __forceinline__ void pin(float (&d)[N]) {
#pragma unroll
    for (int i = 0; i < N; i++) asm volatile("" : "+f"(d[i])::"memory");
}
template <int N>
__device__ __forceinline__ void pin(uint32_t (&d)[N]) {
#pragma unroll
    for (int i = 0; i < N; i++) asm volatile("" : "+r"(d[i])::"memory");
}
__device__ __forceinline__ uint32_t pack_bf16(float lo, float hi) {
    uint32_t r;
    asm("cvt.rn.bf16x2.f32 %0, %1, %2;" : "=r"(r) : "f"(hi), "f"(lo));
    return r;
}
__device__ __forceinline__ float bf_lo(uint32_t v) { return __uint_as_float(v << 16); }
__device__ __forceinline__ float bf_hi(uint32_t v) { return __uint_as_float(v & 0xffff0000u); }
__device__ __forceinline__ float round_bf16(float v) { return __bfloat162float(__float2bfloat16_rn(v)); }
__device__ __forceinline__ float ex2(float x) {
    float y;
    asm("ex2.approx.ftz.f32 %0, %1;" : "=f"(y) : "f"(x));
    return y;
}
__device__ __forceinline__ float rcp(float x) {
    float y;
    asm("rcp.approx.ftz.f32 %0, %1;" : "=f"(y) : "f"(x));
    return y;
}
__device__ __forceinline__ float tanh_fast(float x) {
    float y;
    asm("tanh.approx.f32 %0, %1;" : "=f"(y) : "f"(x));
    return y;
}
__device__ __forceinline__ void sts128(uint32_t a, uint32_t x, uint32_t y, uint32_t z, uint32_t w) {
    asm volatile("st.shared.v4.b32 [%0], {%1,%2,%3,%4};" ::"r"(a), "r"(x), "r"(y), "r"(z), "r"(w) : "memory");
}
__device__ __forceinline__ void lds128(uint32_t a, uint32_t& x, uint32_t& y, uint32_t& z, uint32_t& w) {
    asm volatile("ld.shared.v4.b32 {%0,%1,%2,%3}, [%4];" : "=r"(x), "=r"(y), "=r"(z), "=r"(w) : "r"(a) : "memory");
}
__device__ __forceinline__ void sts32f(uint32_t a, float v) {
    asm volatile("st.shared.f32 [%0], %1;" ::"r"(a), "f"(v) : "memory");
}
__device__ __forceinline__ float lds32f(uint32_t a) {
    float v;
    asm volatile("ld.shared.f32 %0, [%1];" : "=f"(v) : "r"(a) : "memory");
    return v;
}
#define F8(d, b) \
    "+f"(d[b]), "+f"(d[b + 1]), "+f"(d[b + 2]), "+f"(d[b + 3]), "+f"(d[b + 4]), "+f"(d[b + 5]), "+f"(d[b + 6]), "+f"(d[b + 7])

template <int TB>
__device__ __forceinline__ void wgmma_n128(float (&d)[64], uint32_t a0, uint32_t a1, uint32_t a2, uint32_t a3,
                                           uint64_t db, int sc) {
    asm volatile(
        "{\n.reg .pred p;\nsetp.ne.b32 p, %69, 0;\n"
        "wgmma.mma_async.sync.aligned.m64n128k16.f32.bf16.bf16 "
        "{%0,%1,%2,%3,%4,%5,%6,%7,%8,%9,%10,%11,%12,%13,%14,%15,%16,%17,%18,%19,%20,%21,%22,%23,%24,%25,%26,%27,%28,%29,%30,%31,"
        "%32,%33,%34,%35,%36,%37,%38,%39,%40,%41,%42,%43,%44,%45,%46,%47,%48,%49,%50,%51,%52,%53,%54,%55,%56,%57,%58,%59,%60,%61,%62,%63},"
        "{%64,%65,%66,%67}, %68, p, 1, 1, %70;\n}"
        : F8(d, 0), F8(d, 8), F8(d, 16), F8(d, 24), F8(d, 32), F8(d, 40), F8(d, 48), F8(d, 56)
        : "r"(a0), "r"(a1), "r"(a2), "r"(a3), "l"(db), "r"(sc), "n"(TB));
}
#define O8(d, b) \
    "=f"(d[b]), "=f"(d[b + 1]), "=f"(d[b + 2]), "=f"(d[b + 3]), "=f"(d[b + 4]), "=f"(d[b + 5]), "=f"(d[b + 6]), "=f"(d[b + 7])
template <int TB>
__device__ __forceinline__ void wgmma_n128_z(float (&d)[64], uint32_t a0, uint32_t a1, uint32_t a2, uint32_t a3,
                                             uint64_t db) {
    asm volatile(
        "wgmma.mma_async.sync.aligned.m64n128k16.f32.bf16.bf16 "
        "{%0,%1,%2,%3,%4,%5,%6,%7,%8,%9,%10,%11,%12,%13,%14,%15,%16,%17,%18,%19,%20,%21,%22,%23,%24,%25,%26,%27,%28,%29,%30,%31,"
        "%32,%33,%34,%35,%36,%37,%38,%39,%40,%41,%42,%43,%44,%45,%46,%47,%48,%49,%50,%51,%52,%53,%54,%55,%56,%57,%58,%59,%60,%61,%62,%63},"
        "{%64,%65,%66,%67}, %68, 0, 1, 1, %69;"
        : O8(d, 0), O8(d, 8), O8(d, 16), O8(d, 24), O8(d, 32), O8(d, 40), O8(d, 48), O8(d, 56)
        : "r"(a0), "r"(a1), "r"(a2), "r"(a3), "l"(db), "n"(TB));
}
template <int TB>
__device__ __forceinline__ void wgmma_n64_z(float (&d)[32], uint32_t a0, uint32_t a1, uint32_t a2, uint32_t a3,
                                            uint64_t db) {
    asm volatile(
        "wgmma.mma_async.sync.aligned.m64n64k16.f32.bf16.bf16 "
        "{%0,%1,%2,%3,%4,%5,%6,%7,%8,%9,%10,%11,%12,%13,%14,%15,%16,%17,%18,%19,%20,%21,%22,%23,%24,%25,%26,%27,%28,%29,%30,%31},"
        "{%32,%33,%34,%35}, %36, 0, 1, 1, %37;"
        : O8(d, 0), O8(d, 8), O8(d, 16), O8(d, 24)
        : "r"(a0), "r"(a1), "r"(a2), "r"(a3), "l"(db), "n"(TB));
}
template <int TB>
__device__ __forceinline__ void wgmma_n64(float (&d)[32], uint32_t a0, uint32_t a1, uint32_t a2, uint32_t a3,
                                          uint64_t db) {
    asm volatile(
        "wgmma.mma_async.sync.aligned.m64n64k16.f32.bf16.bf16 "
        "{%0,%1,%2,%3,%4,%5,%6,%7,%8,%9,%10,%11,%12,%13,%14,%15,%16,%17,%18,%19,%20,%21,%22,%23,%24,%25,%26,%27,%28,%29,%30,%31},"
        "{%32,%33,%34,%35}, %36, 1, 1, 1, %37;"
        : F8(d, 0), F8(d, 8), F8(d, 16), F8(d, 24)
        : "r"(a0), "r"(a1), "r"(a2), "r"(a3), "l"(db), "n"(TB));
}

__device__ __forceinline__ uint64_t desc_of(uint32_t saddr) {
    return (uint64_t)(((saddr >> 4) & 0x3FFFu) | (512u << 16)) | ((uint64_t)(64u | (1u << 30)) << 32);
}

struct Ring {
    uint32_t slot;
    uint32_t phase;
    __device__ __forceinline__ void next() {
        if (++slot == 8) {
            slot = 0;
            phase ^= 1;
        }
    }
};

struct Ctx {
    uint32_t sbase;
    int wg;
    uint32_t rel_cta;
    __device__ __forceinline__ void wait_full(uint32_t slot, uint32_t phase) const {
        mbar_wait(sbase + OFF_FULL + slot * 8, phase);
    }
    __device__ __forceinline__ void release(uint32_t slot) const {
        if (rel_cta < 2) mbar_arrive_cluster(sbase + OFF_EMPTY + slot * 8, rel_cta);
    }
};

__device__ __forceinline__ void gemm_n128(float (&d)[64], const uint32_t (&a)[144], const Ctx& c, Ring& r, bool nine) {
    uint32_t prev = 0;
#pragma unroll
    for (int s = 0; s < 9; s++) {
        if (s < 8 || nine) {
            if (s == GATE_SLOT) bar_sync(8 + c.wg, 256);
            c.wait_full(r.slot, r.phase);
            uint64_t db = desc_of(c.sbase + r.slot * SLOT_BYTES);
            wg_fence();
#pragma unroll
            for (int k = 0; k < 4; k++) {
                if ((s | k) == 0)
                    wgmma_n128_z<1>(d, a[0], a[1], a[2], a[3], db);
                else
                    wgmma_n128<1>(d, a[s * 16 + k * 4], a[s * 16 + k * 4 + 1], a[s * 16 + k * 4 + 2],
                                  a[s * 16 + k * 4 + 3], db + k * 128, 1);
            }
            wg_commit();
            if (s == 8 || (s == 7 && !nine)) bar_arrive(9 - c.wg, 256);
            if (s > 0) {
                wg_wait<1>();
                c.release(prev);
            }
            prev = r.slot;
            r.next();
        }
    }
    wg_wait<0>();
    c.release(prev);
    pin(d);
}
__device__ __forceinline__ void gemm_n64(float (&d)[32], const uint32_t (&a)[144], const Ctx& c, Ring& r, bool nine) {
    uint32_t prev = 0;
#pragma unroll
    for (int s = 0; s < 5; s++) {
        if (s < 4 || nine) {
            c.wait_full(r.slot, r.phase);
            uint64_t db = desc_of(c.sbase + r.slot * SLOT_BYTES);
            wg_fence();
#pragma unroll
            for (int k = 0; k < 8; k++) {
                if ((s | k) == 0)
                    wgmma_n64_z<1>(d, a[0], a[1], a[2], a[3], db);
                else if (s * 8 + k < 36)
                    wgmma_n64<1>(d, a[s * 32 + k * 4], a[s * 32 + k * 4 + 1], a[s * 32 + k * 4 + 2],
                                 a[s * 32 + k * 4 + 3], db + k * 128);
            }
            wg_commit();
            if (s > 0) {
                wg_wait<1>();
                c.release(prev);
            }
            prev = r.slot;
            r.next();
        }
    }
    wg_wait<0>();
    c.release(prev);
    pin(d);
}
__device__ __forceinline__ void st128(uint4* p, uint32_t x, uint32_t y, uint32_t z, uint32_t w) {
    asm volatile(
        "{\n.reg .b64 lo, hi;\n.reg .b128 t;\nmov.b64 lo, {%1, %2};\nmov.b64 hi, {%3, %4};\nmov.b128 t, {lo, hi};\n"
        "st.relaxed.gpu.global.b128 [%0], t;\n}" ::"l"(p),
        "r"(x), "r"(y), "r"(z), "r"(w)
        : "memory");
}
__device__ __forceinline__ uint4 ld128(const uint4* p) {
    uint4 r;
    asm volatile(
        "{\n.reg .b64 lo, hi;\n.reg .b128 t;\nld.relaxed.gpu.global.b128 t, [%4];\nmov.b128 {lo, hi}, t;\n"
        "mov.b64 {%0, %1}, lo;\nmov.b64 {%2, %3}, hi;\n}"
        : "=r"(r.x), "=r"(r.y), "=r"(r.z), "=r"(r.w)
        : "l"(p));
    return r;
}
__device__ __forceinline__ uint4 ldg128(const uint4* p) {
    uint4 r;
    asm volatile("ld.global.nc.v4.u32 {%0,%1,%2,%3}, [%4];" : "=r"(r.x), "=r"(r.y), "=r"(r.z), "=r"(r.w) : "l"(p));
    return r;
}
__device__ __forceinline__ void st64(void* p, uint32_t x, uint32_t y) {
    asm volatile("{\n.reg .b64 t;\nmov.b64 t, {%1, %2};\nst.relaxed.gpu.global.b64 [%0], t;\n}" ::"l"(p), "r"(x), "r"(y)
                 : "memory");
}
__device__ __forceinline__ uint2 ld64(const void* p) {
    uint2 r;
    asm volatile("{\n.reg .b64 t;\nld.relaxed.gpu.global.b64 t, [%2];\nmov.b64 {%0, %1}, t;\n}"
                 : "=r"(r.x), "=r"(r.y)
                 : "l"(p));
    return r;
}
__device__ __forceinline__ void rows_load(uint32_t sbase, const CUtensorMap* m, int row0) {
    mbar_expect_tx(sbase + OFF_XBAR, 16 * DM * 2);
    asm volatile(
        "cp.async.bulk.tensor.3d.shared::cluster.global.mbarrier::complete_tx::bytes [%0], [%1, {%3, %3, %4}], [%2];" ::"r"(
            sbase + OFF_ROWS),
        "l"(m), "r"(sbase + OFF_XBAR), "r"(0), "r"(row0)
        : "memory");
}
__device__ __forceinline__ void rows_store(uint32_t sbase, const CUtensorMap* m, int row0) {
    asm volatile("cp.async.bulk.tensor.3d.global.shared::cta.bulk_group [%0, {%2, %2, %3}], [%1];" ::"l"(m),
                 "r"(sbase + OFF_ROWS), "r"(0), "r"(row0)
                 : "memory");
    asm volatile("cp.async.bulk.commit_group;" ::: "memory");
}
__device__ __forceinline__ void rows_store_wait() { asm volatile("cp.async.bulk.wait_group 0;" ::: "memory"); }

__device__ __forceinline__ constexpr int own_col(int j) { return j < 8 ? (j >> 1) * 128 + (j & 1) * 8 : 512; }
__device__ __forceinline__ void row_reduce(float& s0, float& s1, uint32_t red, int warp, int lane) {
    s0 += __shfl_xor_sync(0xffffffffu, s0, 1);
    s1 += __shfl_xor_sync(0xffffffffu, s1, 1);
    s0 += __shfl_xor_sync(0xffffffffu, s0, 2);
    s1 += __shfl_xor_sync(0xffffffffu, s1, 2);
    if ((lane & 3) == 0) {
        sts32f(red + (warp * 16 + (lane >> 2)) * 4, s0);
        sts32f(red + (warp * 16 + 8 + (lane >> 2)) * 4, s1);
    }
    bar_sync(3, 256);
    s0 = 0.f;
    s1 = 0.f;
#pragma unroll
    for (int w = 0; w < 8; w++) {
        s0 += lds32f(red + (w * 16 + (lane >> 2)) * 4);
        s1 += lds32f(red + (w * 16 + 8 + (lane >> 2)) * 4);
    }
}
template <class F>
__device__ __forceinline__ void layernorm_rows(float (&v)[36], uint32_t red, int warp, int lane, F&& middle) {
    float s0 = 0.f, s1 = 0.f;
#pragma unroll
    for (int j = 0; j < 9; j++) {
        s0 += v[4 * j] + v[4 * j + 1];
        s1 += v[4 * j + 2] + v[4 * j + 3];
    }
    row_reduce(s0, s1, red, warp, lane);
    middle();
    const float m0 = s0 * (1.f / DM), m1 = s1 * (1.f / DM);
    s0 = 0.f;
    s1 = 0.f;
#pragma unroll
    for (int j = 0; j < 9; j++) {
        v[4 * j] -= m0;
        v[4 * j + 1] -= m0;
        v[4 * j + 2] -= m1;
        v[4 * j + 3] -= m1;
        s0 += v[4 * j] * v[4 * j] + v[4 * j + 1] * v[4 * j + 1];
        s1 += v[4 * j + 2] * v[4 * j + 2] + v[4 * j + 3] * v[4 * j + 3];
    }
    row_reduce(s0, s1, red + 512, warp, lane);
    const float r0 = rsqrtf(s0 * (1.f / DM) + 1e-5f), r1 = rsqrtf(s1 * (1.f / DM) + 1e-5f);
#pragma unroll
    for (int j = 0; j < 9; j++) {
        v[4 * j] *= r0;
        v[4 * j + 1] *= r0;
        v[4 * j + 2] *= r1;
        v[4 * j + 3] *= r1;
    }
}
__device__ __forceinline__ void mod_to_smem(uint32_t dst, const uint32_t* src, uint32_t tag) {
    const uint32_t t0 = clk32();
    uint4 u;
    while (true) {
        u = ld128(reinterpret_cast<const uint4*>(src));
        const uint32_t bad = ((u.x ^ tag) | (u.y ^ tag) | (u.z ^ tag) | (u.w ^ tag)) & 0xffffu;
        if (__all_sync(0xffffffffu, bad == 0) || clk32() - t0 > WAIT_LIMIT) break;
        __nanosleep(64);
    }
    sts128(dst, u.x & 0xffff0000u, u.y & 0xffff0000u, u.z & 0xffff0000u, u.w & 0xffff0000u);
}
__device__ __forceinline__ void lds_mod(float (&m)[18], uint32_t src  , int warp) {
#pragma unroll
    for (int j = 0; j < 9; j++)
        asm volatile("ld.shared.v2.f32 {%0,%1}, [%2];"
                     : "=f"(m[2 * j]), "=f"(m[2 * j + 1])
                     : "r"(src + own_col(j) * 4 - (j == 8 ? warp * 32 : 0))
                     : "memory");
}
__device__ __forceinline__ void modulate_store(const float (&v)[36], const float (&shift)[18], const float (&scale)[18],
                                               uint4* hbuf  , int warp, int lane) {
    uint32_t o[18];
#pragma unroll
    for (int j = 0; j < 9; j++) {
        const uint32_t cc = pack_bf16(1.f + scale[2 * j], 1.f + scale[2 * j + 1]);
        const float c0 = bf_lo(cc), c1 = bf_hi(cc);
        o[2 * j] = max(pack_bf16(fmaf(v[4 * j], c0, shift[2 * j]), fmaf(v[4 * j + 1], c1, shift[2 * j + 1])), 1u);
        o[2 * j + 1] = max(pack_bf16(fmaf(v[4 * j + 2], c0, shift[2 * j]), fmaf(v[4 * j + 3], c1, shift[2 * j + 1])), 1u);
    }
#pragma unroll
    for (int i = 0; i < 4; i++) st128(hbuf + (i * 8 + warp) * 32 + lane, o[4 * i], o[4 * i + 1], o[4 * i + 2], o[4 * i + 3]);
    st64(reinterpret_cast<uint2*>(hbuf + 32 * 32) + warp * 32 + lane, o[16], o[17]);
}
__device__ __forceinline__ void sum_partials(float (&v)[36], const uint4* src  ,
                                             const uint2* tail  , uint32_t tag, uint32_t pbuf  ,
                                             uint32_t pbar, uint32_t pphase) {
    const uint32_t t0 = clk32();
    uint4 t[8][4];
    uint2 tl[8];
#pragma unroll
    for (int s = 0; s < 8; s++)
#pragma unroll
        for (int i = 2; i < 4; i++) t[s][i] = ld128(src + (s * 36 + i * 8) * 32);
#pragma unroll
    for (int s = 0; s < 8; s++) tl[s] = ld64(tail + s * 72 * 32);
    mbar_wait(pbar, pphase);
#pragma unroll
    for (int s = 0; s < 8; s++)
#pragma unroll
        for (int i = 0; i < 2; i++) lds128(pbuf + s * 8192 + i * 4096, t[s][i].x, t[s][i].y, t[s][i].z, t[s][i].w);
#pragma unroll
    for (int h = 0; h < 2; h++) {
        while (true) {
            uint32_t bad = 0;
#pragma unroll
            for (int s = 0; s < 8; s++) bad |= (t[s][2 * h].x ^ tag) | (t[s][2 * h + 1].x ^ tag);
            if (__all_sync(0xffffffffu, (bad & 1u) == 0) || clk32() - t0 > WAIT_LIMIT) break;
#pragma unroll
            for (int s = 0; s < 8; s++)
#pragma unroll
                for (int i = 2 * h; i < 2 * h + 2; i++) t[s][i] = ld128(src + (s * 36 + i * 8) * 32);
        }
#pragma unroll
        for (int i = 2 * h; i < 2 * h + 2; i++) {
#pragma unroll
            for (int e = 0; e < 8; e++) v[8 * i + e] = 0.f;
#pragma unroll
            for (int s = 0; s < 8; s++) {
                v[8 * i] += bf_lo(t[s][i].x);
                v[8 * i + 1] += bf_hi(t[s][i].x);
                v[8 * i + 2] += bf_lo(t[s][i].y);
                v[8 * i + 3] += bf_hi(t[s][i].y);
                v[8 * i + 4] += bf_lo(t[s][i].z);
                v[8 * i + 5] += bf_hi(t[s][i].z);
                v[8 * i + 6] += bf_lo(t[s][i].w);
                v[8 * i + 7] += bf_hi(t[s][i].w);
            }
#pragma unroll
            for (int e = 0; e < 8; e++) asm volatile("" : "+f"(v[8 * i + e]));
        }
    }
    while (true) {
        uint32_t bad = 0;
#pragma unroll
        for (int s = 0; s < 8; s++) bad |= tl[s].x ^ tag;
        if (__all_sync(0xffffffffu, (bad & 1u) == 0) || clk32() - t0 > WAIT_LIMIT) break;
#pragma unroll
        for (int s = 0; s < 8; s++) tl[s] = ld64(tail + s * 72 * 32);
    }
    v[32] = v[33] = v[34] = v[35] = 0.f;
#pragma unroll
    for (int s = 0; s < 8; s++) {
        v[32] += bf_lo(tl[s].x);
        v[33] += bf_hi(tl[s].x);
        v[34] += bf_lo(tl[s].y);
        v[35] += bf_hi(tl[s].y);
    }
}
__device__ __forceinline__ void poll_tail(uint32_t (&a)[144], const uint2* src  ) {
    const uint32_t t0 = clk32();
    while (true) {
        uint32_t m = 0xffffffffu;
#pragma unroll
        for (int j = 0; j < 8; j++) {
            const uint2 t = ld64(src + j * 32);
            a[128 + 2 * j] = t.x;
            a[129 + 2 * j] = t.y;
        }
#pragma unroll
        for (int j = 0; j < 16; j++) m = min(m, a[128 + j]);
        if (__all_sync(0xffffffffu, m != 0) || clk32() - t0 > WAIT_LIMIT) break;
    }
}
template <int K0, int K1>
__device__ __forceinline__ void poll_frags(uint32_t (&a)[144], const uint4* src  , bool kick) {
    const uint32_t t0 = clk32();
    while (true) {
#pragma unroll
        for (int k = K0; k < K1; k++)
            asm volatile("ld.relaxed.gpu.global.v4.u32 {%0,%1,%2,%3}, [%4];"
                         : "=r"(a[4 * k]), "=r"(a[4 * k + 1]), "=r"(a[4 * k + 2]), "=r"(a[4 * k + 3])
                         : "l"(src + k * 32));
        if (kick) bar_arrive(5, 256);
        kick = false;
        uint32_t m0 = a[4 * K0], m1 = a[4 * K0 + 1];
#pragma unroll
        for (int i = 4 * K0 + 2; i < 4 * K1; i += 2) {
            m0 = min(m0, a[i]);
            m1 = min(m1, a[i + 1]);
        }
        if (__all_sync(0xffffffffu, min(m0, m1) != 0) || clk32() - t0 > WAIT_LIMIT) break;
    }
}

constexpr float SM_SCALE = 0.08838834764831845f * 1.4426950408889634f;
constexpr float SM_HI = 1.2089258e24f;
constexpr float SM_LO = 9.0949470e-13f;
__device__ __forceinline__ void qk_step(float (&s)[32], const uint32_t (&q)[32], uint64_t dk) {
#pragma unroll
    for (int k = 0; k < 8; k++) {
        if (k == 0)
            wgmma_n64_z<0>(s, q[0], q[1], q[2], q[3], dk);
        else
            wgmma_n64<0>(s, q[4 * k], q[4 * k + 1], q[4 * k + 2], q[4 * k + 3], dk + (k >> 2) * 512 + (k & 3) * 2);
    }
}
__device__ __forceinline__ void pv_step(float (&o)[64], const uint32_t (&p)[16], uint64_t dv, int acc) {
#pragma unroll
    for (int k = 0; k < 4; k++)
        wgmma_n128<1>(o, p[4 * k], p[4 * k + 1], p[4 * k + 2], p[4 * k + 3], dv + k * 128, k != 0 ? 1 : acc);
}
template <bool SHIFT>
__device__ __forceinline__ void exp_step(const float (&s)[32], uint32_t (&p)[16], float n0, float n1, float& s0,
                                         float& s1) {
#pragma unroll
    for (int i = 0; i < 8; i++) {
        const float e0 = ex2(SHIFT ? s[4 * i] + n0 : s[4 * i]), e1 = ex2(SHIFT ? s[4 * i + 1] + n0 : s[4 * i + 1]);
        const float e2 = ex2(SHIFT ? s[4 * i + 2] + n1 : s[4 * i + 2]), e3 = ex2(SHIFT ? s[4 * i + 3] + n1 : s[4 * i + 3]);
        if (i == 0) {
            s0 = e0 + e1;
            s1 = e2 + e3;
        } else {
            s0 += e0 + e1;
            s1 += e2 + e3;
        }
        p[2 * i] = pack_bf16(e0, e1);
        p[2 * i + 1] = pack_bf16(e2, e3);
    }
}
__device__ __forceinline__ void row_max(const float (&sa)[32], const float (&sb)[32], float& x0, float& x1) {
    float xa[8];
#pragma unroll
    for (int i = 0; i < 8; i++) xa[i] = fmaxf(sa[i], sb[i]);
#pragma unroll
    for (int k = 1; k < 4; k++)
#pragma unroll
        for (int i = 0; i < 8; i++) xa[i] = fmaxf(xa[i], fmaxf(sa[8 * k + i], sb[8 * k + i]));
    x0 = fmaxf(fmaxf(xa[0], xa[1]), fmaxf(xa[4], xa[5]));
    x1 = fmaxf(fmaxf(xa[2], xa[3]), fmaxf(xa[6], xa[7]));
    x0 = fmaxf(x0, __shfl_xor_sync(0xffffffffu, x0, 1));
    x1 = fmaxf(x1, __shfl_xor_sync(0xffffffffu, x1, 1));
    x0 = fmaxf(x0, __shfl_xor_sync(0xffffffffu, x0, 2));
    x1 = fmaxf(x1, __shfl_xor_sync(0xffffffffu, x1, 2));
}
__device__ __forceinline__ void inv_row_sums(float l0, float l1, float& i0, float& i1) {
    l0 += __shfl_xor_sync(0xffffffffu, l0, 1);
    l1 += __shfl_xor_sync(0xffffffffu, l1, 1);
    l0 += __shfl_xor_sync(0xffffffffu, l0, 2);
    l1 += __shfl_xor_sync(0xffffffffu, l1, 2);
    i0 = rcp(l0);
    i1 = rcp(l1);
}

__device__ __forceinline__ uint32_t get_epoch(uint32_t sbase) { return __float_as_uint(lds32f(sbase + OFF_EPOCH)); }
__device__ __forceinline__ float silu_bf16(unsigned short c) {
    const float cv = bf_lo(c);
    return round_bf16(cv * rcp(1.f + ex2(-1.4426950408889634f * cv)));
}
__device__ __forceinline__ void st_mod(uint32_t* p, float v, uint32_t tag) {
    asm volatile("st.relaxed.gpu.global.u32 [%0], %1;" ::"l"(p), "r"(__float_as_uint(round_bf16(v)) | tag)
                 : "memory");
}
__device__ __forceinline__ void fma8(float (&acc)[8], float sc, const uint4& w) {
    acc[0] = fmaf(sc, bf_lo(w.x), acc[0]);
    acc[1] = fmaf(sc, bf_hi(w.x), acc[1]);
    acc[2] = fmaf(sc, bf_lo(w.y), acc[2]);
    acc[3] = fmaf(sc, bf_hi(w.y), acc[3]);
    acc[4] = fmaf(sc, bf_lo(w.z), acc[4]);
    acc[5] = fmaf(sc, bf_hi(w.z), acc[5]);
    acc[6] = fmaf(sc, bf_lo(w.w), acc[6]);
    acc[7] = fmaf(sc, bf_hi(w.w), acc[7]);
}
__device__ __forceinline__ void modp_load(uint4 (&u)[6], const uint32_t* src) {
#pragma unroll
    for (int i = 0; i < 6; i++) u[i] = ld128(reinterpret_cast<const uint4*>(src + i * 2 * DM));
}
__device__ __forceinline__ void modp_to_smem(uint4 (&u)[6], uint32_t dst, const uint32_t* src, uint32_t tag) {
    const uint32_t t0 = clk32();
    while (true) {
        uint32_t bad = 0;
#pragma unroll
        for (int i = 0; i < 6; i++) bad |= (u[i].x ^ tag) | (u[i].y ^ tag) | (u[i].z ^ tag) | (u[i].w ^ tag);
        if (__all_sync(0xffffffffu, (bad & 0xffu) == 0) || clk32() - t0 > WAIT_LIMIT) break;
        modp_load(u, src);
    }
    float s0 = 0.f, s1 = 0.f, s2 = 0.f, s3 = 0.f;
#pragma unroll
    for (int i = 0; i < 6; i++) {
        s0 += __uint_as_float(u[i].x & ~0xffu);
        s1 += __uint_as_float(u[i].y & ~0xffu);
        s2 += __uint_as_float(u[i].z & ~0xffu);
        s3 += __uint_as_float(u[i].w & ~0xffu);
    }
    const uint32_t p0 = pack_bf16(s0, s1), p1 = pack_bf16(s2, s3);
    sts128(dst, p0 << 16, p0 & 0xffff0000u, p1 << 16, p1 & 0xffff0000u);
}

__global__ void __cluster_dims__(2, 1, 1) __launch_bounds__(384, 1)
    fused_block_kernel(const __grid_constant__ Params maps) {
    extern __shared__ uint8_t smem_raw[];
    uint32_t sbase = (smem_u32(smem_raw) + 1023u) & ~1023u;
    asm volatile("" : "+r"(sbase));
    const int b = blockIdx.x;
    const int rank = b & 1;
    const int mt = ((b >> 1) & 7) * 2 + rank;
    const int g = b >> 4;
    const int warp = __shfl_sync(0xffffffffu, threadIdx.x >> 5, 0);
    const int lane = threadIdx.x & 31;
    Scratch* const sc_ = maps.sc;
    const __nv_bfloat16* const wmod = maps.wmod;
    const __nv_bfloat16* const cvec = maps.cvec;

#define SPROF(i)

    if (warp >= 8) {
        asm volatile("setmaxnreg.dec.sync.aligned.u32 24;");
        if (warp == 8 && lane == 0) {
#pragma unroll
            for (int i = 0; i < 8; i++) {
                mbar_init(sbase + OFF_FULL + i * 8, 1);
                mbar_init(sbase + OFF_EMPTY + i * 8, 4);
            }
            mbar_init(sbase + OFF_XBAR, 1);
            mbar_init(sbase + OFF_PBAR, 1);
            asm volatile("fence.mbarrier_init.release.cluster;" ::: "memory");
            asm volatile("barrier.cluster.arrive.relaxed;\nbarrier.cluster.wait;" ::: "memory");
            uint32_t slot = 0, phase = 1;
            const uint32_t dst0 = sbase + rank * BOX_BYTES;
            auto acquire = [&](uint32_t bytes) {
                mbar_wait(sbase + OFF_EMPTY + slot * 8, phase);
                mbar_expect_tx(sbase + OFF_FULL + slot * 8, bytes);
            };
            auto adv8 = [&]() {
                if (++slot == 8) {
                    slot = 0;
                    phase ^= 1;
                }
            };
#pragma unroll 1
            for (int hq = 0; hq < 4; hq++) {
                const int col = (g * 4 + ((hq + 1) & 3)) * 128 + rank * 64;
                if (hq == 2) {
                    l2_prefetch(maps.kc + (size_t)(g * 4 * 2048 + (b & 15) * 64) * 128, SLOT_BYTES);
                    l2_prefetch(maps.vc + (size_t)(g * 4 * 2048 + (b & 15) * 64) * 128, SLOT_BYTES);
                }
#pragma unroll 1
                for (int kc = 0; kc < 9; kc++) {
                    acquire(SLOT_BYTES);
                    tma_mc(dst0 + slot * SLOT_BYTES, &maps.wq, col, kc * 64, sbase + OFF_FULL + slot * 8);
                    adv8();
                }
            }
            const int row0 = g * 4 * 2048;
#pragma unroll 1
            for (int n = 0; n < 128; n++) {
                if (n < 4) mbar_wait(sbase + OFF_EMPTY + (slot + 1) * 8, phase);
                acquire(2 * SLOT_BYTES);
                const uint32_t bar = sbase + OFF_FULL + slot * 8;
                const int r0 = n == 0 ? 0 : (n == 127 ? 126 : n + 1);
                const int r1 = n == 0 ? 1 : (n == 127 ? 127 : n - 1);
                tma_mc(dst0 + slot * SLOT_BYTES, n == 127 ? &maps.v : &maps.k, rank * 64, row0 + r0 * 64, bar);
                tma_mc(dst0 + (slot + 1) * SLOT_BYTES, n == 0 ? &maps.k : &maps.v, rank * 64, row0 + r1 * 64, bar);
                adv8();
                adv8();
                const int u = n + KV_AHEAD;
                if (u < 128 && (u & 15) == (b & 15)) {
                    l2_prefetch(maps.kc + (size_t)(row0 + u * 64) * 128, SLOT_BYTES);
                    l2_prefetch(maps.vc + (size_t)(row0 + u * 64) * 128, SLOT_BYTES);
                }
            }
#pragma unroll 1
            for (int p = 0; p < 4; p++)
#pragma unroll 1
                for (int kc = 0; kc < 8; kc++) {
                    acquire(SLOT_BYTES);
                    tma_mc(dst0 + slot * SLOT_BYTES, &maps.wo, p * 128 + rank * 64, g * 512 + kc * 64,
                           sbase + OFF_FULL + slot * 8);
                    adv8();
                }
#pragma unroll 1
            for (int kc = 0; kc < 4; kc++) {
                acquire(SLOT_BYTES);
                tma_mc(dst0 + slot * SLOT_BYTES, &maps.wo, 512, g * 512 + kc * 128 + rank * 64,
                       sbase + OFF_FULL + slot * 8);
                adv8();
            }
            const CUtensorMap* mg = rank ? &maps.wu : &maps.wg;
#pragma unroll 1
            for (int ch = 0; ch < 9; ch++)
#pragma unroll 1
                for (int kc = 0; kc < 9; kc++) {
                    acquire(SLOT_BYTES);
                    tma_mc(dst0 + slot * SLOT_BYTES, mg, g * 576 + ch * 64, kc * 64, sbase + OFF_FULL + slot * 8);
                    adv8();
                }
#pragma unroll 1
            for (int p = 0; p < 4; p++)
#pragma unroll 1
                for (int kc = 2; kc < 11; kc++) {
                    acquire(SLOT_BYTES);
                    tma_mc(dst0 + slot * SLOT_BYTES, &maps.wd, p * 128 + rank * 64, g * 576 + (kc < 9 ? kc : kc - 9) * 64,
                           sbase + OFF_FULL + slot * 8);
                    adv8();
                }
#pragma unroll 1
            for (int i = 0; i < 5; i++) {
                acquire(i < 4 ? SLOT_BYTES : BOX_BYTES);
                const int kc = 2 * i + rank + 2;
                if (i < 4 || rank == 0)
                    tma_mc(dst0 + slot * SLOT_BYTES, &maps.wd, 512, g * 576 + (kc < 9 ? kc : kc - 9) * 64,
                           sbase + OFF_FULL + slot * 8);
                adv8();
            }
        } else if (warp == 11) {
            asm volatile("barrier.cluster.arrive.relaxed.aligned;" ::: "memory");
            bar_sync(6, 160);
            uint4* hz = sc_->h[(get_epoch(sbase) & 1) ^ 1][0] + (size_t)b * 72 * 32 + lane;
#pragma unroll 1
            for (int i = 0; i < 72; i++) {
                hz[i * 32] = make_uint4(0, 0, 0, 0);
                __nanosleep(200);
            }
            bar_sync(6, 160);
            if (lane == 0) {
#pragma unroll 1
                for (int i = 0; i < 9; i++) {
                    l2_prefetch((const char*)maps.wo_p + (size_t)b * 36864 + i * 4096, 4096);
                    __nanosleep(400);
                    l2_prefetch((const char*)maps.wg_p + (size_t)b * 41472 + i * 4608, 4608);
                    __nanosleep(400);
                    l2_prefetch((const char*)maps.wu_p + (size_t)b * 41472 + i * 4608, 4608);
                    __nanosleep(400);
                    l2_prefetch((const char*)maps.wd_p + (size_t)b * 41472 + i * 4608, 4608);
                    __nanosleep(400);
                }
            }
        } else if (warp == 9 || warp == 10) {
            asm volatile("barrier.cluster.arrive.relaxed.aligned;" ::: "memory");
            bar_sync(4, 320);
            const uint32_t tag = (get_epoch(sbase) + 1) & 0xffffu;
            if (warp == 10 && lane < 9) l2_prefetch((const char*)maps.wq_p + (size_t)b * 36864 + lane * 4096, 4096);
            const int blk = warp == 9 ? 72 + b : 200 + b;
            if (blk < 216) {
                float acc[8];
#pragma unroll
                for (int e = 0; e < 8; e++) acc[e] = 0.f;
                const uint4* wp = reinterpret_cast<const uint4*>(wmod + (size_t)(lane >> 1) * (6 * DM) + blk * 16) + (lane & 1);
                const unsigned short* cp = reinterpret_cast<const unsigned short*>(cvec) + (lane >> 1);
#pragma unroll 1
                for (int i = 0; i < 36; i++) {
                    const uint4 w = __ldg(wp + (size_t)i * (16 * 6 * DM / 8));
                    const float sc = silu_bf16(__ldg(cp + i * 16));
                    fma8(acc, sc, w);
                }
#pragma unroll
                for (int o = 2; o < 32; o <<= 1)
#pragma unroll
                    for (int e = 0; e < 8; e++) acc[e] += __shfl_xor_sync(0xffffffffu, acc[e], o);
                if (lane < 2) {
#pragma unroll
                    for (int e = 0; e < 8; e++) st_mod(sc_->mod + blk * 16 + lane * 8 + e, acc[e], tag);
                }
            }
            if (warp == 9) {
#pragma unroll 1
                for (int st = 1; st <= 2; st++) {
                    bar_sync(7, 160);
                    const uint32_t* src = sc_->mod + (st * 3 - 1) * DM;
                    const int n = st == 1 ? 3 * DM : DM;
#pragma unroll 1
                    for (int i = lane * 4; i < n + 127 - ((n + 127) & 127); i += 128)
                        mod_to_smem(sbase + OFF_MODT + min(i, n - 4) * 4, src + min(i, n - 4), tag);
                    __syncwarp();
                    if (lane == 0) rows_load(sbase, st == 1 ? &maps.rx : &maps.rx2, (mt * 8 + g) * 16);
                    bar_sync(11, 160);
                    if (lane == 0) {
                        mbar_expect_tx(sbase + OFF_PBAR, 65536);
                        const uint4* ps = sc_->part + (size_t)(mt * 8 + g) * 8 * 36 * 32;
#pragma unroll 1
                        for (int i = 0; i < 8; i++) bulk_load(sbase + OFF_PBUF + i * 8192, ps + i * 36 * 32, 8192, sbase + OFF_PBAR);
                    }
                    __syncwarp();
                    if (st == 1) {
                        bar_sync(7, 160);
                        if (lane == 0) {
                            rows_store(sbase, &maps.rx2, (mt * 8 + g) * 16);
                            rows_store_wait();
                        }
                        __syncwarp();
                        bar_arrive(10, 160);
                    }
                }
            }
        }
    } else {
        uint4 w1[3], xw[5], ew = make_uint4(0, 0, 0, 0);
        unsigned short cu[3];
        {
            const int t = threadIdx.x, bw = min(b, 107);
            const int row = (bw / 18) * 96 + (t >> 3);
#pragma unroll
            for (int i = 0; i < 3; i++) {
                w1[i] = ldg128(reinterpret_cast<const uint4*>(wmod + (size_t)(row + 32 * i) * (6 * DM)) + (bw % 18) * 8 + (t & 7));
                asm volatile("ld.global.nc.u16 %0, [%1];" : "=h"(cu[i]) : "l"(cvec + row + 32 * i));
            }
            if (t == 0) ew = ld128(reinterpret_cast<const uint4*>(&sc_->epoch[b * 32]));
#pragma unroll
            for (int i = 0; i < 5; i++)
                xw[i] = ldg128(reinterpret_cast<const uint4*>(maps.x + (size_t)(mt * 8 + g) * 16 * DM) + min(t + 256 * i, 1151));
        }
        if (threadIdx.x == 160) SPROF(5);
        asm volatile("setmaxnreg.inc.sync.aligned.u32 240;");
        if (threadIdx.x == 160) SPROF(6);
        const int wg = warp >> 2;
        const int tid = threadIdx.x;
        Ctx cx;
        cx.sbase = sbase;
        cx.wg = wg;
        if (wg == 1) bar_arrive(8, 256);
        cx.rel_cta = (lane == 0 && (warp & 3) < 2) ? (warp & 3) : 2;
        const uint32_t red = sbase + OFF_RED;
        const int own = mt * 8 + g;
        const int wown = mt * 8 + warp;
        PROF(0);
        PROFG(30);
        PROFR(17);
        {
            asm volatile("barrier.cluster.arrive.relaxed.aligned;" ::: "memory");
            float acc[8];
#pragma unroll
            for (int e = 0; e < 8; e++) acc[e] = 0.f;
#pragma unroll
            for (int i = 0; i < 3; i++) fma8(acc, silu_bf16(cu[i]), w1[i]);
#pragma unroll
            for (int o = 8; o < 32; o <<= 1)
#pragma unroll
                for (int e = 0; e < 8; e++) acc[e] += __shfl_xor_sync(0xffffffffu, acc[e], o);
            PROFR(19);
            if (lane < 8) {
                const uint32_t dst = sbase + OFF_MRED + warp * 256 + lane * 32;
                sts128(dst, __float_as_uint(acc[0]), __float_as_uint(acc[1]), __float_as_uint(acc[2]), __float_as_uint(acc[3]));
                sts128(dst + 16, __float_as_uint(acc[4]), __float_as_uint(acc[5]), __float_as_uint(acc[6]), __float_as_uint(acc[7]));
            }
            if (tid == 0) sts128(sbase + OFF_EPOCH, ew.x, ew.y, ew.z, ew.w);
            bar_sync(3, 256);
            PROFR(20);
            if (tid < 64 && b < 108) {
                float sum = 0.f;
#pragma unroll
                for (int w8 = 0; w8 < 8; w8++) sum += lds32f(sbase + OFF_MRED + w8 * 256 + tid * 4);
                asm volatile("st.relaxed.gpu.global.u32 [%0], %1;" ::"l"(&sc_->modp[b / 18][(b % 18) * 64 + tid]),
                             "r"((__float_as_uint(sum) & ~0xffu) | ((get_epoch(sbase) + 1) & 0xffu))
                             : "memory");
            }
            PROFR(21);
#pragma unroll
            for (int i = 0; i < 5; i++) {
                const int vi = min(tid + 256 * i, 1151), ln = vi >> 3;
                sts128(sbase + OFF_ROWS + ln * 128 + (((vi & 7) ^ (ln & 7)) << 4), xw[i].x, xw[i].y, xw[i].z, xw[i].w);
            }
            bar_sync(3, 256);
        }

        Ring ring{0u, 0u};
        int stage = 0;
        asm volatile("" : "+r"(stage));
#pragma unroll 1
        for (;; stage++) {
            int tid, lane;
            asm volatile("mov.u32 %0, %%tid.x;" : "=r"(tid));
            lane = tid & 31;
            const uint32_t epoch = get_epoch(sbase);
            {
                float v[36];
                const uint32_t modt = sbase + OFF_MODT + (warp * 16 + (lane & 3) * 2) * 4;
                if (stage == 0) {
#pragma unroll
                    for (int i = 0; i < 36; i++) v[i] = 0.f;
                } else {
                    const uint4* psrc = sc_->part + (size_t)own * 8 * 36 * 32;
                    sum_partials(v, psrc + tid, reinterpret_cast<const uint2*>(psrc + 32 * 32) + tid, stage & 1,
                                 sbase + OFF_PBUF + tid * 16, sbase + OFF_PBAR, stage - 1);
                    PROF(stage == 1 ? 8 : 15);
                }
                if (stage) mbar_wait(sbase + OFF_XBAR, stage - 1);
                if (stage == 0) PROFR(22);
                {
                    const float gs = stage == 2 ? 0.5f : 1.f;
                    float gate[18];
                    lds_mod(gate, modt, warp);
                    const int r = lane >> 2;
                    const uint32_t rows = sbase + OFF_ROWS + r * (DM * 2) + (lane & 3) * 4;
#pragma unroll
                    for (int j = 0; j < 9; j++) {
                        const int ch = j < 8 ? (j >> 1) * 2 + (warp >> 2) : 8, c16 = j < 8 ? (warp & 3) * 2 + (j & 1) : warp;
                        const uint32_t ad = rows + ch * 128 + ((c16 ^ ((r + ch) & 7)) << 4);
                        const uint32_t u0 = __float_as_uint(lds32f(ad)), u1 = __float_as_uint(lds32f(ad + 8 * DM * 2));
                        const float g0 = stage ? gate[2 * j] * gs : 0.f, g1 = stage ? gate[2 * j + 1] * gs : 0.f;
                        v[4 * j] = fmaf(g0, v[4 * j], bf_lo(u0));
                        v[4 * j + 1] = fmaf(g1, v[4 * j + 1], bf_hi(u0));
                        v[4 * j + 2] = fmaf(g0, v[4 * j + 2], bf_lo(u1));
                        v[4 * j + 3] = fmaf(g1, v[4 * j + 3], bf_hi(u1));
                        sts32f(ad, __uint_as_float(pack_bf16(v[4 * j], v[4 * j + 1])));
                        sts32f(ad + 8 * DM * 2, __uint_as_float(pack_bf16(v[4 * j + 2], v[4 * j + 3])));
                    }
                    asm volatile("fence.proxy.async.shared::cta;" ::: "memory");
                }
                if (stage == 2) break;
                PROF(stage == 0 ? 1 : 9);
                uint4 ua[6], ub[6];
#pragma unroll
                for (int i = 0; i < 6; i++) ua[i] = ub[i] = make_uint4(0, 0, 0, 0);
                layernorm_rows(v, red, warp, lane, [&]() {
                    if (stage == 0) {
                        modp_load(ua, sc_->modp[0] + tid * 4);
                        if (warp == 0) modp_load(ub, sc_->modp[0] + 1024 + tid * 4);
                    }
                });
                if (stage == 0) PROFR(27);
                if (stage == 0) {
                    const uint32_t tag = (epoch + 1) & 0xffu;
                    modp_to_smem(ua, sbase + OFF_MODT + (DM + tid * 4) * 4, sc_->modp[0] + tid * 4, tag);
                    if (warp == 0)
                        modp_to_smem(ub, sbase + OFF_MODT + (DM + 1024 + tid * 4) * 4, sc_->modp[0] + 1024 + tid * 4, tag);
                    bar_sync(3, 256);
                }
                float shift[18], scale[18];
                lds_mod(shift, modt + DM * 4, warp);
                lds_mod(scale, modt + 2 * DM * 4, warp);
                if (stage == 0) PROFR(28);
                PROF(stage == 0 ? 2 : 10);
                modulate_store(v, shift, scale, sc_->h[epoch & 1][stage] + (size_t)own * 36 * 32, warp, lane);
                if (stage == 0) asm volatile("barrier.cluster.wait.aligned;" ::: "memory");
            }

            const uint32_t spill = sbase + 8 * SLOT_BYTES + wg * 3 * SLOT_BYTES + (tid & 127) * 16;
            uint32_t a[144];
            PROF(stage == 0 ? 3 : 11);
            {
                const uint4* hsrc = sc_->h[epoch & 1][stage] + (size_t)wown * 36 * 32 + lane;
                __nanosleep(PROBE_NS);
                poll_tail(a, reinterpret_cast<const uint2*>(hsrc - lane + 32 * 32) + lane);
                PROF(stage == 0 ? 4 : 12);
                if (stage == 1) PROFG(25);
                TG(stage * 32 + 30);
                if (wg == 1) bar_sync(5, 256);
                poll_frags<0, 32>(a, hsrc, wg == 0);
                if (stage == 0) bar_arrive(4, 320);
            }
            uint4* hhbuf = sc_->hh + (size_t)b * 8 * 256 + tid;
            float d[64];
#pragma unroll 1
            for (int ch = 0;; ch++) {
                TG(stage * 32 + ch * 2);
                gemm_n128(d, a, cx, ring, true);
                TG(stage * 32 + ch * 2 + 1);
                if (stage == 0) {
#pragma unroll
                    for (int i = 0; i < 64; i++) d[i] *= SM_SCALE;
                    if (ch == 3) break;
#pragma unroll
                    for (int v = 0; v < 8; v++)
                        sts128(spill + (ch * 8 + v) * 2048, pack_bf16(d[8 * v], d[8 * v + 1]),
                               pack_bf16(d[8 * v + 2], d[8 * v + 3]), pack_bf16(d[8 * v + 4], d[8 * v + 5]),
                               pack_bf16(d[8 * v + 6], d[8 * v + 7]));
                } else {
#pragma unroll
                    for (int i = 0; i < 32; i++) {
                        const float gv = d[i], gu = gv * d[32 + i];
                        const float z = gv * fmaf(gv * gv, 0.7978845608028654f * 0.044715f, 0.7978845608028654f);
                        d[i] = fmaf(gu, tanh_fast(z), gu);
                    }
                    if (ch == 8) break;
                    if (wg == 0) {
                        if (ch == 0) bar_arrive(7, 160);
                        if (ch == 2) bar_sync(10, 160);
                    }
#pragma unroll
                    for (int v = 0; v < 4; v++) {
                        const uint4 h4 = make_uint4(pack_bf16(d[8 * v], d[8 * v + 1]), pack_bf16(d[8 * v + 2], d[8 * v + 3]),
                                                    pack_bf16(d[8 * v + 4], d[8 * v + 5]), pack_bf16(d[8 * v + 6], d[8 * v + 7]));
                        if (ch < 2)
                            __stcg(hhbuf + (ch * 4 + v) * 256, h4);
                        else
                            sts128(spill + ((ch - 2) * 4 + v) * 2048, h4.x, h4.y, h4.z, h4.w);
                    }
                }
            }
            if (stage == 0) {
                uint32_t q[32];
#pragma unroll
                for (int i = 0; i < 32; i++) q[i] = pack_bf16(d[2 * i], d[2 * i + 1]);
                PROF(5);
                PROFG(23);
                if (wg == 0) bar_arrive(6, 160);
                {
                    float o[64], sa[32], sb[32];
                    uint32_t pa[16], pb[16];
#pragma unroll
                    for (int i = 0; i < 64; i++) o[i] = 0.f;
                    float n0 = 0.f, n1 = 0.f, l0 = 1.f, l1 = 1.f;
                    bool shifted = false;
                    const uint64_t dbase = desc_of(sbase);
                    const uint64_t dbk = dbase - (511u << 16);
                    const int my_bar = 1 + wg, other_bar = 2 - wg;

                    auto softmax_a = [&](bool first, float& s0, float& s1) {
                        if (first) {
                            shifted = false;
                            n0 = n1 = 0.f;
                            l0 = l1 = 0.f;
                        }
                        if (shifted)
                            exp_step<true>(sa, pa, n0, n1, s0, s1);
                        else
                            exp_step<false>(sa, pa, n0, n1, s0, s1);
                    };
                    auto softmax_b = [&](bool first, float s0, float s1) {
                        float u0, u1;
                        if (shifted)
                            exp_step<true>(sb, pb, n0, n1, u0, u1);
                        else
                            exp_step<false>(sb, pb, n0, n1, u0, u1);
                        s0 += u0;
                        s1 += u1;
                        bool bad = !(fmaxf(s0, s1) <= SM_HI);
                        if (first) {
                            float r0 = s0 + __shfl_xor_sync(0xffffffffu, s0, 1), r1 = s1 + __shfl_xor_sync(0xffffffffu, s1, 1);
                            r0 += __shfl_xor_sync(0xffffffffu, r0, 2);
                            r1 += __shfl_xor_sync(0xffffffffu, r1, 2);
                            bad = bad || !(fminf(r0, r1) >= SM_LO);
                        }
                        if (__any_sync(0xffffffffu, bad)) {
                            float x0, x1;
                            row_max(sa, sb, x0, x1);
                            x0 = -x0;
                            x1 = -x1;
                            if (!first) {
                                x0 = fminf(x0, n0);
                                x1 = fminf(x1, n1);
                                const float al0 = ex2(x0 - n0), al1 = ex2(x1 - n1);
                                l0 *= al0;
                                l1 *= al1;
#pragma unroll
                                for (int i = 0; i < 16; i++) {
                                    o[4 * i] *= al0;
                                    o[4 * i + 1] *= al0;
                                    o[4 * i + 2] *= al1;
                                    o[4 * i + 3] *= al1;
                                }
                            }
                            n0 = x0;
                            n1 = x1;
                            shifted = true;
                            exp_step<true>(sa, pa, n0, n1, s0, s1);
                            exp_step<true>(sb, pb, n0, n1, u0, u1);
                            s0 += u0;
                            s1 += u1;
                        }
                        l0 += s0;
                        l1 += s1;
                    };

                    cx.wait_full(4, 0);
                    if (wg == 1) bar_sync(my_bar, 256);
                    wg_fence();
                    qk_step(sa, q, dbk + 4 * 1024);
                    qk_step(sb, q, dbk + 5 * 1024);
                    wg_commit();
                    bar_arrive(other_bar, 256);
                    wg_wait<0>();
                    pin(sa);
                    pin(sb);
                    cx.release(4);
                    cx.wait_full(6, 0);
                    {
                        float s0, s1;
                        softmax_a(true, s0, s1);
                        softmax_b(true, s0, s1);
                    }
                    uint32_t alo = (uint32_t)dbase + 6 * 1024, blo = (uint32_t)dbase;
                    const uint32_t dhi = (uint32_t)(dbase >> 32);
#pragma unroll 1
                    for (int t = 1; t < 64; t++) {
                        const int j = t & 15;
                        const uint32_t sA = 2 + 4 * (t & 1), sB = 4 - 4 * (t & 1);
                        const uint64_t da = ((uint64_t)dhi << 32) | alo, db = ((uint64_t)dhi << 32) | blo;
                        TL(0);
                        bar_sync(my_bar, 256);
                        TL(2);
                        wg_fence();
                        pv_step(o, pa, da + 1024, j != 1);
                        qk_step(sa, q, da - (511u << 16));
                        wg_commit();
                        cx.wait_full(sB, ((36 + 4 * t) >> 3) & 1);
                        wg_fence();
                        qk_step(sb, q, db - (511u << 16));
                        pv_step(o, pb, db + 1024, 1);
                        wg_commit();
                        bar_arrive(other_bar, 256);
                        alo ^= 4096;
                        blo ^= 4096;
                        asm volatile("" : "+r"(alo), "+r"(blo));
                        TL(3);
                        wg_wait<1>();
                        pin(sa);
                        pin(pa);
                        TL(4);
                        cx.release(sA);
                        const float lp0 = l0, lp1 = l1;
                        float s0, s1;
                        softmax_a(j == 0, s0, s1);
                        TL(5);
                        wg_wait<0>();
                        pin(o);
                        pin(sb);
                        pin(pb);
                        TL(6);
                        cx.release(sB);
                        if (j == 0) {
                            float i0, i1;
                            inv_row_sums(lp0, lp1, i0, i1);
                            const uint32_t dst = spill + ((t >> 4) - 1) * 16384;
#pragma unroll
                            for (int v = 0; v < 8; v++)
                                sts128(dst + v * 2048, pack_bf16(o[8 * v] * i0, o[8 * v + 1] * i0),
                                       pack_bf16(o[8 * v + 2] * i1, o[8 * v + 3] * i1),
                                       pack_bf16(o[8 * v + 4] * i0, o[8 * v + 5] * i0),
                                       pack_bf16(o[8 * v + 6] * i1, o[8 * v + 7] * i1));
                        }
                        const uint32_t bn = sbase + OFF_FULL + (8 - sA) * 8, pn = ((38 + 4 * t) >> 3) & 1;
                        const bool okn = mbar_try(bn, pn);
                        TL(1);
                        softmax_b(j == 0, s0, s1);
                        if (!okn || j == 15) {
                            mbar_wait(bn, pn);
                            if (t == 47 && wg == 0) bar_arrive(6, 160);
                            if (j == 15 && t < 63) {
                                const uint32_t src = spill + (t >> 4) * 16384;
#pragma unroll
                                for (int v = 0; v < 8; v++)
                                    lds128(src + v * 2048, q[4 * v], q[4 * v + 1], q[4 * v + 2], q[4 * v + 3]);
                            }
                        }
                        TL(7);
                    }
                    bar_sync(my_bar, 256);
                    wg_fence();
                    pv_step(o, pa, dbase + 2 * 1024, 1);
                    pv_step(o, pb, dbase + 3 * 1024, 1);
                    wg_commit();
                    if (wg == 0) bar_arrive(other_bar, 256);
                    float i0, i1;
                    inv_row_sums(l0, l1, i0, i1);
                    wg_wait<0>();
                    pin(o);
                    cx.release(2);
#pragma unroll
                    for (int i = 0; i < 16; i++) {
                        a[96 + 2 * i] = pack_bf16(o[4 * i] * i0, o[4 * i + 1] * i0);
                        a[96 + 2 * i + 1] = pack_bf16(o[4 * i + 2] * i1, o[4 * i + 3] * i1);
                    }
#pragma unroll
                    for (int i = 128; i < 144; i++) a[i] = 0;
                }
                ring.slot = 4;
                ring.phase = 0;
                PROF(6);
                PROFG(24);
            } else {
#pragma unroll
                for (int v = 0; v < 8; v++) {
                    const uint4 t = __ldcg(hhbuf + v * 256);
                    a[112 + 4 * v] = t.x;
                    a[113 + 4 * v] = t.y;
                    a[114 + 4 * v] = t.z;
                    a[115 + 4 * v] = t.w;
                }
#pragma unroll
                for (int i = 0; i < 16; i++) a[96 + i] = pack_bf16(d[2 * i], d[2 * i + 1]);
                PROF(13);
            }
#pragma unroll
            for (int v = 0; v < 24; v++) lds128(spill + v * 2048, a[4 * v], a[4 * v + 1], a[4 * v + 2], a[4 * v + 3]);

            {
                uint4* dst = sc_->part + ((size_t)wown * 8 + g) * 36 * 32 + lane;
                const uint32_t ptag = (stage + 1) & 1;
#pragma unroll 1
                for (int p = 0; p < 4; p++) {
                    TG(stage * 32 + 18 + p * 2);
                    gemm_n128(d, a, cx, ring, stage != 0);
                    TG(stage * 32 + 19 + p * 2);
#pragma unroll
                    for (int u = 0; u < 8; u++)
                        st128(dst + (p * 8 + u) * 32, (pack_bf16(d[8 * u], d[8 * u + 1]) & ~1u) | ptag,
                              pack_bf16(d[8 * u + 2], d[8 * u + 3]), pack_bf16(d[8 * u + 4], d[8 * u + 5]),
                              pack_bf16(d[8 * u + 6], d[8 * u + 7]));
                    if (p == 0 && wg == 0) bar_arrive(7, 160);
                    if (p == 2 && wg == 1) bar_arrive(11, 160);
                }
                float e[32];
                TG(stage * 32 + 26);
                gemm_n64(e, a, cx, ring, stage != 0);
                TG(stage * 32 + 27);
                uint2* dst2 = reinterpret_cast<uint2*>(dst - lane + 32 * 32) + lane;
#pragma unroll
                for (int j = 0; j < 8; j++)
                    st64(dst2 + j * 32, (pack_bf16(e[4 * j], e[4 * j + 1]) & ~1u) | ptag, pack_bf16(e[4 * j + 2], e[4 * j + 3]));
            }
            PROF(stage == 0 ? 7 : 14);
            if (stage == 1) {
                PROFG(26);
                asm volatile("barrier.cluster.arrive.relaxed.aligned;" ::: "memory");
            }
        }
        if (wg == 0) bar_sync(8, 256);
        bar_sync(3, 256);
        if (tid == 32) sc_->epoch[b * 32] = get_epoch(sbase) + 1;
        if (tid == 0) {
            rows_store(sbase, &maps.rout, own * 16);
            rows_store_wait();
        }
        __syncwarp();
        PROF(16);
        PROFG(31);
        asm volatile("barrier.cluster.wait.aligned;" ::: "memory");
    }
}

typedef CUresult (*EncodeFn)(CUtensorMap*, CUtensorMapDataType, cuuint32_t, void*, const cuuint64_t*, const cuuint64_t*,
                             const cuuint32_t*, const cuuint32_t*, CUtensorMapInterleave, CUtensorMapSwizzle,
                             CUtensorMapL2promotion, CUtensorMapFloatOOBfill);

void make_map(EncodeFn enc, CUtensorMap* m, const void* ptr, uint64_t rows, uint64_t cols, bool narrow = false) {
    cuuint64_t gdim[2] = {cols, rows};
    cuuint64_t gstr[1] = {cols * 2};
    cuuint32_t box[2] = {narrow ? 16u : 64u, narrow ? 192u : 64u};
    cuuint32_t estr[2] = {1, 1};
    enc(m, CU_TENSOR_MAP_DATA_TYPE_BFLOAT16, 2, const_cast<void*>(ptr), gdim, gstr, box, estr,
        CU_TENSOR_MAP_INTERLEAVE_NONE, narrow ? CU_TENSOR_MAP_SWIZZLE_NONE : CU_TENSOR_MAP_SWIZZLE_128B,
        CU_TENSOR_MAP_L2_PROMOTION_L2_128B,
        CU_TENSOR_MAP_FLOAT_OOB_FILL_NONE);
}

void make_rows_map(EncodeFn enc, CUtensorMap* m, const void* ptr) {
    cuuint64_t gdim[3] = {64, 9, 2048};
    cuuint64_t gstr[2] = {128, DM * 2};
    cuuint32_t box[3] = {64, 9, 16};
    cuuint32_t estr[3] = {1, 1, 1};
    enc(m, CU_TENSOR_MAP_DATA_TYPE_BFLOAT16, 3, const_cast<void*>(ptr), gdim, gstr, box, estr,
        CU_TENSOR_MAP_INTERLEAVE_NONE, CU_TENSOR_MAP_SWIZZLE_128B, CU_TENSOR_MAP_L2_PROMOTION_L2_128B,
        CU_TENSOR_MAP_FLOAT_OOB_FILL_NONE);
}

}

extern "C" void kernel_launch(void* const* d_in, const int* in_sizes, int n_in, void* d_out, int out_size) {
    (void)in_sizes;
    (void)n_in;
    (void)out_size;
    void* fn = nullptr;
    cudaDriverEntryPointQueryResult qr;
    cudaGetDriverEntryPoint("cuTensorMapEncodeTiled", &fn, cudaEnableDefault, &qr);
    EncodeFn enc = (EncodeFn)fn;
    Params maps;
    maps.x = (const __nv_bfloat16*)d_in[0];
    maps.cvec = (const __nv_bfloat16*)d_in[9];
    maps.wmod = (const __nv_bfloat16*)d_in[10];
    maps.kc = (const __nv_bfloat16*)d_in[1];
    maps.vc = (const __nv_bfloat16*)d_in[2];
    maps.wq_p = (const __nv_bfloat16*)d_in[3];
    maps.wo_p = (const __nv_bfloat16*)d_in[4];
    maps.wg_p = (const __nv_bfloat16*)d_in[6];
    maps.wu_p = (const __nv_bfloat16*)d_in[7];
    maps.wd_p = (const __nv_bfloat16*)d_in[8];
    maps.out = (__nv_bfloat16*)d_out;
    void* scp = nullptr;
    cudaGetSymbolAddress(&scp, g_scratch);
    maps.sc = (Scratch*)scp;
    make_map(enc, &maps.k, d_in[1], 32 * 2048, 128);
    make_map(enc, &maps.v, d_in[2], 32 * 2048, 128);
    make_map(enc, &maps.wq, d_in[3], 576, 4096);
    make_map(enc, &maps.wo, d_in[4], 4096, 576);
    make_map(enc, &maps.wg, d_in[6], 576, 4608);
    make_map(enc, &maps.wu, d_in[7], 576, 4608);
    make_map(enc, &maps.wd, d_in[8], 4608, 576);
    make_rows_map(enc, &maps.rx, d_in[0]);
    make_rows_map(enc, &maps.rx2, (char*)scp + offsetof(Scratch, x2));
    make_rows_map(enc, &maps.rout, d_out);
    cudaFuncSetAttribute(fused_block_kernel, cudaFuncAttributeMaxDynamicSharedMemorySize, SMEM_BYTES);
    fused_block_kernel<<<128, 384, SMEM_BYTES>>>(maps);
}
```

```cpp
#include <cuda_runtime.h>
#include <cuda_bf16.h>
#include <cuda.h>
#include <stdint.h>
#include <stddef.h>

namespace {

constexpr int DM = 576;
constexpr int SLOT_BYTES = 16384;
constexpr int BOX_BYTES = 8192;
constexpr int NUNITS = 14;
constexpr int SMEM_TAIL = NUNITS * SLOT_BYTES;
constexpr int SMEM_BYTES = SMEM_TAIL + 2048 + 1024;
constexpr int OFF_FULL = SMEM_TAIL;
constexpr int OFF_EMPTY = SMEM_TAIL + 64;
constexpr int OFF_RED = SMEM_TAIL + 128;

constexpr int KV_AHEAD = 16;
#define GATE_SLOT 4
#define PROBE_NS 300
constexpr int OFF_XBAR = SMEM_TAIL + 1792;
constexpr int OFF_ROWS = 8 * SLOT_BYTES;
constexpr int OFF_MODT = OFF_ROWS + 20480;
constexpr int OFF_EPOCH = SMEM_TAIL + 1808;
constexpr int OFF_PSTG = OFF_ROWS + 32768;
constexpr int OFF_MRED = OFF_ROWS + 28672;

struct Scratch {
    unsigned epoch[128 * 32];
    uint32_t mod[6 * DM];
    uint32_t modp[6][2 * DM];
    uint4 h[2][2][128 * 36 * 32];
    uint4 part[128 * 8 * 36 * 32];
    uint4 hh[128 * 8 * 256];
    __nv_bfloat16 x2[2048 * DM];
};
__device__ Scratch g_scratch;

#define TG(i)
#define TL(i)
#define PROFR(i)
#define PROF(i)
#define PROFG(i)

struct Params {
    const __nv_bfloat16 *x, *cvec, *wmod, *kc, *vc, *wq_p, *wo_p, *wg_p, *wu_p, *wd_p;
    __nv_bfloat16* out;
    Scratch* sc;
    CUtensorMap k, v, wq, wo, wg, wu, wd, rx, rx2, rout;
};

__device__ __forceinline__ uint32_t smem_u32(const void* p) { return (uint32_t)__cvta_generic_to_shared(p); }
__device__ __forceinline__ void mbar_init(uint32_t a, uint32_t c) {
    asm volatile("mbarrier.init.shared::cta.b64 [%0], %1;" ::"r"(a), "r"(c) : "memory");
}
__device__ __forceinline__ void mbar_expect_tx(uint32_t a, uint32_t bytes) {
    asm volatile("mbarrier.arrive.expect_tx.shared::cta.b64 _, [%0], %1;" ::"r"(a), "r"(bytes) : "memory");
}
__device__ __forceinline__ bool mbar_try(uint32_t a, uint32_t ph) {
    uint32_t ok;
    asm volatile(
        "{\n.reg .pred p;\nmbarrier.try_wait.parity.shared::cta.b64 p, [%1], %2;\nselp.u32 %0, 1, 0, p;\n}"
        : "=r"(ok)
        : "r"(a), "r"(ph)
        : "memory");
    return ok != 0;
}
__device__ __forceinline__ uint32_t clk32() {
    uint32_t c;
    asm volatile("mov.u32 %0, %%clock;" : "=r"(c));
    return c;
}
constexpr uint32_t WAIT_LIMIT = 1u << 30;
__device__ __forceinline__ void mbar_wait(uint32_t a, uint32_t ph) {
    if (mbar_try(a, ph)) return;
    uint32_t t0 = clk32();
    while (!mbar_try(a, ph)) {
        if (clk32() - t0 > WAIT_LIMIT) break;
    }
}
__device__ __forceinline__ void mbar_arrive_cluster(uint32_t a, uint32_t cta) {
    asm volatile(
        "{\n.reg .b32 ra;\nmapa.shared::cluster.u32 ra, %0, %1;\nmbarrier.arrive.shared::cluster.b64 _, [ra];\n}" ::"r"(a),
        "r"(cta)
        : "memory");
}
__device__ __forceinline__ void tma_mc(uint32_t dst, const CUtensorMap* m, int c0, int c1, uint32_t bar) {
    asm volatile(
        "cp.async.bulk.tensor.2d.shared::cluster.global.mbarrier::complete_tx::bytes.multicast::cluster"
        " [%0], [%1, {%3, %4}], [%2], %5;" ::"r"(dst),
        "l"(m), "r"(bar), "r"(c0), "r"(c1), "h"((uint16_t)3)
        : "memory");
}
__device__ __forceinline__ void bulk_load(uint32_t dst, const void* src, uint32_t bytes, uint32_t bar) {
    asm volatile("cp.async.bulk.shared::cluster.global.mbarrier::complete_tx::bytes [%0], [%1], %2, [%3];" ::"r"(dst),
                 "l"(src), "r"(bytes), "r"(bar)
                 : "memory");
}
__device__ __forceinline__ void bulk_store(void* dst, uint32_t src, uint32_t bytes) {
    asm volatile("cp.async.bulk.global.shared::cta.bulk_group [%0], [%1], %2;\ncp.async.bulk.commit_group;" ::"l"(dst), "r"(src),
                 "r"(bytes)
                 : "memory");
}
__device__ __forceinline__ void l2_prefetch(const void* p, uint32_t bytes) {
    asm volatile("cp.async.bulk.prefetch.L2.global [%0], %1;" ::"l"(p), "r"(bytes) : "memory");
}
__device__ __forceinline__ void bar_sync(int id, int n) { asm volatile("bar.sync %0, %1;" ::"r"(id), "r"(n) : "memory"); }
__device__ __forceinline__ void bar_arrive(int id, int n) {
    asm volatile("bar.arrive %0, %1;" ::"r"(id), "r"(n) : "memory");
}
__device__ __forceinline__ void wg_fence() { asm volatile("wgmma.fence.sync.aligned;" ::: "memory"); }
__device__ __forceinline__ void wg_commit() { asm volatile("wgmma.commit_group.sync.aligned;" ::: "memory"); }
template <int N>
__device__ __forceinline__ void wg_wait() {
    asm volatile("wgmma.wait_group.sync.aligned %0;" ::"n"(N) : "memory");
}
template <int N>
__device__ __forceinline__ void pin(float (&d)[N]) {
#pragma unroll
    for (int i = 0; i < N; i++) asm volatile("" : "+f"(d[i])::"memory");
}
template <int N>
__device__ __forceinline__ void pin(uint32_t (&d)[N]) {
#pragma unroll
    for (int i = 0; i < N; i++) asm volatile("" : "+r"(d[i])::"memory");
}
__device__ __forceinline__ uint32_t pack_bf16(float lo, float hi) {
    uint32_t r;
    asm("cvt.rn.bf16x2.f32 %0, %1, %2;" : "=r"(r) : "f"(hi), "f"(lo));
    return r;
}
__device__ __forceinline__ float bf_lo(uint32_t v) { return __uint_as_float(v << 16); }
__device__ __forceinline__ float bf_hi(uint32_t v) { return __uint_as_float(v & 0xffff0000u); }
__device__ __forceinline__ float round_bf16(float v) { return __bfloat162float(__float2bfloat16_rn(v)); }
__device__ __forceinline__ float ex2(float x) {
    float y;
    asm("ex2.approx.ftz.f32 %0, %1;" : "=f"(y) : "f"(x));
    return y;
}
__device__ __forceinline__ float rcp(float x) {
    float y;
    asm("rcp.approx.ftz.f32 %0, %1;" : "=f"(y) : "f"(x));
    return y;
}
__device__ __forceinline__ float tanh_fast(float x) {
    float y;
    asm("tanh.approx.f32 %0, %1;" : "=f"(y) : "f"(x));
    return y;
}
__device__ __forceinline__ void sts128(uint32_t a, uint32_t x, uint32_t y, uint32_t z, uint32_t w) {
    asm volatile("st.shared.v4.b32 [%0], {%1,%2,%3,%4};" ::"r"(a), "r"(x), "r"(y), "r"(z), "r"(w) : "memory");
}
__device__ __forceinline__ void lds128(uint32_t a, uint32_t& x, uint32_t& y, uint32_t& z, uint32_t& w) {
    asm volatile("ld.shared.v4.b32 {%0,%1,%2,%3}, [%4];" : "=r"(x), "=r"(y), "=r"(z), "=r"(w) : "r"(a) : "memory");
}
__device__ __forceinline__ void sts32f(uint32_t a, float v) {
    asm volatile("st.shared.f32 [%0], %1;" ::"r"(a), "f"(v) : "memory");
}
__device__ __forceinline__ float lds32f(uint32_t a) {
    float v;
    asm volatile("ld.shared.f32 %0, [%1];" : "=f"(v) : "r"(a) : "memory");
    return v;
}
#define F8(d, b) \
    "+f"(d[b]), "+f"(d[b + 1]), "+f"(d[b + 2]), "+f"(d[b + 3]), "+f"(d[b + 4]), "+f"(d[b + 5]), "+f"(d[b + 6]), "+f"(d[b + 7])

template <int TB>
__device__ __forceinline__ void wgmma_n128(float (&d)[64], uint32_t a0, uint32_t a1, uint32_t a2, uint32_t a3,
                                           uint64_t db, int sc) {
    asm volatile(
        "{\n.reg .pred p;\nsetp.ne.b32 p, %69, 0;\n"
        "wgmma.mma_async.sync.aligned.m64n128k16.f32.bf16.bf16 "
        "{%0,%1,%2,%3,%4,%5,%6,%7,%8,%9,%10,%11,%12,%13,%14,%15,%16,%17,%18,%19,%20,%21,%22,%23,%24,%25,%26,%27,%28,%29,%30,%31,"
        "%32,%33,%34,%35,%36,%37,%38,%39,%40,%41,%42,%43,%44,%45,%46,%47,%48,%49,%50,%51,%52,%53,%54,%55,%56,%57,%58,%59,%60,%61,%62,%63},"
        "{%64,%65,%66,%67}, %68, p, 1, 1, %70;\n}"
        : F8(d, 0), F8(d, 8), F8(d, 16), F8(d, 24), F8(d, 32), F8(d, 40), F8(d, 48), F8(d, 56)
        : "r"(a0), "r"(a1), "r"(a2), "r"(a3), "l"(db), "r"(sc), "n"(TB));
}
#define O8(d, b) \
    "=f"(d[b]), "=f"(d[b + 1]), "=f"(d[b + 2]), "=f"(d[b + 3]), "=f"(d[b + 4]), "=f"(d[b + 5]), "=f"(d[b + 6]), "=f"(d[b + 7])
template <int TB>
__device__ __forceinline__ void wgmma_n128_z(float (&d)[64], uint32_t a0, uint32_t a1, uint32_t a2, uint32_t a3,
                                             uint64_t db) {
    asm volatile(
        "wgmma.mma_async.sync.aligned.m64n128k16.f32.bf16.bf16 "
        "{%0,%1,%2,%3,%4,%5,%6,%7,%8,%9,%10,%11,%12,%13,%14,%15,%16,%17,%18,%19,%20,%21,%22,%23,%24,%25,%26,%27,%28,%29,%30,%31,"
        "%32,%33,%34,%35,%36,%37,%38,%39,%40,%41,%42,%43,%44,%45,%46,%47,%48,%49,%50,%51,%52,%53,%54,%55,%56,%57,%58,%59,%60,%61,%62,%63},"
        "{%64,%65,%66,%67}, %68, 0, 1, 1, %69;"
        : O8(d, 0), O8(d, 8), O8(d, 16), O8(d, 24), O8(d, 32), O8(d, 40), O8(d, 48), O8(d, 56)
        : "r"(a0), "r"(a1), "r"(a2), "r"(a3), "l"(db), "n"(TB));
}
template <int TB>
__device__ __forceinline__ void wgmma_n64_z(float (&d)[32], uint32_t a0, uint32_t a1, uint32_t a2, uint32_t a3,
                                            uint64_t db) {
    asm volatile(
        "wgmma.mma_async.sync.aligned.m64n64k16.f32.bf16.bf16 "
        "{%0,%1,%2,%3,%4,%5,%6,%7,%8,%9,%10,%11,%12,%13,%14,%15,%16,%17,%18,%19,%20,%21,%22,%23,%24,%25,%26,%27,%28,%29,%30,%31},"
        "{%32,%33,%34,%35}, %36, 0, 1, 1, %37;"
        : O8(d, 0), O8(d, 8), O8(d, 16), O8(d, 24)
        : "r"(a0), "r"(a1), "r"(a2), "r"(a3), "l"(db), "n"(TB));
}
template <int TB>
__device__ __forceinline__ void wgmma_n64(float (&d)[32], uint32_t a0, uint32_t a1, uint32_t a2, uint32_t a3,
                                          uint64_t db) {
    asm volatile(
        "wgmma.mma_async.sync.aligned.m64n64k16.f32.bf16.bf16 "
        "{%0,%1,%2,%3,%4,%5,%6,%7,%8,%9,%10,%11,%12,%13,%14,%15,%16,%17,%18,%19,%20,%21,%22,%23,%24,%25,%26,%27,%28,%29,%30,%31},"
        "{%32,%33,%34,%35}, %36, 1, 1, 1, %37;"
        : F8(d, 0), F8(d, 8), F8(d, 16), F8(d, 24)
        : "r"(a0), "r"(a1), "r"(a2), "r"(a3), "l"(db), "n"(TB));
}

__device__ __forceinline__ uint64_t desc_of(uint32_t saddr) {
    return (uint64_t)(((saddr >> 4) & 0x3FFFu) | (512u << 16)) | ((uint64_t)(64u | (1u << 30)) << 32);
}

struct Ring {
    uint32_t slot;
    uint32_t phase;
    __device__ __forceinline__ void next() {
        if (++slot == 8) {
            slot = 0;
            phase ^= 1;
        }
    }
};

struct Ctx {
    uint32_t sbase;
    int wg;
    uint32_t rel_cta;
    __device__ __forceinline__ void wait_full(uint32_t slot, uint32_t phase) const {
        mbar_wait(sbase + OFF_FULL + slot * 8, phase);
    }
    __device__ __forceinline__ void release(uint32_t slot) const {
        if (rel_cta < 2) mbar_arrive_cluster(sbase + OFF_EMPTY + slot * 8, rel_cta);
    }
};

__device__ __forceinline__ void gemm_n128(float (&d)[64], const uint32_t (&a)[144], const Ctx& c, Ring& r, bool nine) {
    uint32_t prev = 0;
#pragma unroll
    for (int s = 0; s < 9; s++) {
        if (s < 8 || nine) {
            if (s == GATE_SLOT) bar_sync(8 + c.wg, 256);
            c.wait_full(r.slot, r.phase);
            uint64_t db = desc_of(c.sbase + r.slot * SLOT_BYTES);
            wg_fence();
#pragma unroll
            for (int k = 0; k < 4; k++) {
                if ((s | k) == 0)
                    wgmma_n128_z<1>(d, a[0], a[1], a[2], a[3], db);
                else
                    wgmma_n128<1>(d, a[s * 16 + k * 4], a[s * 16 + k * 4 + 1], a[s * 16 + k * 4 + 2],
                                  a[s * 16 + k * 4 + 3], db + k * 128, 1);
            }
            wg_commit();
            if (s == 8 || (s == 7 && !nine)) bar_arrive(9 - c.wg, 256);
            if (s > 0) {
                wg_wait<1>();
                c.release(prev);
            }
            prev = r.slot;
            r.next();
        }
    }
    wg_wait<0>();
    c.release(prev);
    pin(d);
}
__device__ __forceinline__ void gemm_n64(float (&d)[32], const uint32_t (&a)[144], const Ctx& c, Ring& r, bool nine) {
    uint32_t prev = 0;
#pragma unroll
    for (int s = 0; s < 5; s++) {
        if (s < 4 || nine) {
            c.wait_full(r.slot, r.phase);
            uint64_t db = desc_of(c.sbase + r.slot * SLOT_BYTES);
            wg_fence();
#pragma unroll
            for (int k = 0; k < 8; k++) {
                if ((s | k) == 0)
                    wgmma_n64_z<1>(d, a[0], a[1], a[2], a[3], db);
                else if (s * 8 + k < 36)
                    wgmma_n64<1>(d, a[s * 32 + k * 4], a[s * 32 + k * 4 + 1], a[s * 32 + k * 4 + 2],
                                 a[s * 32 + k * 4 + 3], db + k * 128);
            }
            wg_commit();
            if (s > 0) {
                wg_wait<1>();
                c.release(prev);
            }
            prev = r.slot;
            r.next();
        }
    }
    wg_wait<0>();
    c.release(prev);
    pin(d);
}
__device__ __forceinline__ void st128(uint4* p, uint32_t x, uint32_t y, uint32_t z, uint32_t w) {
    asm volatile(
        "{\n.reg .b64 lo, hi;\n.reg .b128 t;\nmov.b64 lo, {%1, %2};\nmov.b64 hi, {%3, %4};\nmov.b128 t, {lo, hi};\n"
        "st.relaxed.gpu.global.b128 [%0], t;\n}" ::"l"(p),
        "r"(x), "r"(y), "r"(z), "r"(w)
        : "memory");
}
__device__ __forceinline__ uint4 ld128(const uint4* p) {
    uint4 r;
    asm volatile(
        "{\n.reg .b64 lo, hi;\n.reg .b128 t;\nld.relaxed.gpu.global.b128 t, [%4];\nmov.b128 {lo, hi}, t;\n"
        "mov.b64 {%0, %1}, lo;\nmov.b64 {%2, %3}, hi;\n}"
        : "=r"(r.x), "=r"(r.y), "=r"(r.z), "=r"(r.w)
        : "l"(p));
    return r;
}
__device__ __forceinline__ uint4 ldg128(const uint4* p) {
    uint4 r;
    asm volatile("ld.global.nc.v4.u32 {%0,%1,%2,%3}, [%4];" : "=r"(r.x), "=r"(r.y), "=r"(r.z), "=r"(r.w) : "l"(p));
    return r;
}
__device__ __forceinline__ void st64(void* p, uint32_t x, uint32_t y) {
    asm volatile("{\n.reg .b64 t;\nmov.b64 t, {%1, %2};\nst.relaxed.gpu.global.b64 [%0], t;\n}" ::"l"(p), "r"(x), "r"(y)
                 : "memory");
}
__device__ __forceinline__ uint2 ld64(const void* p) {
    uint2 r;
    asm volatile("{\n.reg .b64 t;\nld.relaxed.gpu.global.b64 t, [%2];\nmov.b64 {%0, %1}, t;\n}"
                 : "=r"(r.x), "=r"(r.y)
                 : "l"(p));
    return r;
}
__device__ __forceinline__ void rows_load(uint32_t sbase, const CUtensorMap* m, int row0) {
    mbar_expect_tx(sbase + OFF_XBAR, 16 * DM * 2);
    asm volatile(
        "cp.async.bulk.tensor.3d.shared::cluster.global.mbarrier::complete_tx::bytes [%0], [%1, {%3, %3, %4}], [%2];" ::"r"(
            sbase + OFF_ROWS),
        "l"(m), "r"(sbase + OFF_XBAR), "r"(0), "r"(row0)
        : "memory");
}
__device__ __forceinline__ void rows_store(uint32_t sbase, const CUtensorMap* m, int row0) {
    asm volatile("cp.async.bulk.tensor.3d.global.shared::cta.bulk_group [%0, {%2, %2, %3}], [%1];" ::"l"(m),
                 "r"(sbase + OFF_ROWS), "r"(0), "r"(row0)
                 : "memory");
    asm volatile("cp.async.bulk.commit_group;" ::: "memory");
}
__device__ __forceinline__ void rows_store_wait() { asm volatile("cp.async.bulk.wait_group 0;" ::: "memory"); }

__device__ __forceinline__ constexpr int own_col(int j) { return j < 8 ? (j >> 1) * 128 + (j & 1) * 8 : 512; }
__device__ __forceinline__ void row_reduce(float& s0, float& s1, uint32_t red, int warp, int lane) {
    s0 += __shfl_xor_sync(0xffffffffu, s0, 1);
    s1 += __shfl_xor_sync(0xffffffffu, s1, 1);
    s0 += __shfl_xor_sync(0xffffffffu, s0, 2);
    s1 += __shfl_xor_sync(0xffffffffu, s1, 2);
    if ((lane & 3) == 0) {
        sts32f(red + (warp * 16 + (lane >> 2)) * 4, s0);
        sts32f(red + (warp * 16 + 8 + (lane >> 2)) * 4, s1);
    }
    bar_sync(3, 256);
    s0 = 0.f;
    s1 = 0.f;
#pragma unroll
    for (int w = 0; w < 8; w++) {
        s0 += lds32f(red + (w * 16 + (lane >> 2)) * 4);
        s1 += lds32f(red + (w * 16 + 8 + (lane >> 2)) * 4);
    }
}
template <class F>
__device__ __forceinline__ void layernorm_rows(float (&v)[36], uint32_t red, int warp, int lane, F&& middle) {
    float s0 = 0.f, s1 = 0.f;
#pragma unroll
    for (int j = 0; j < 9; j++) {
        s0 += v[4 * j] + v[4 * j + 1];
        s1 += v[4 * j + 2] + v[4 * j + 3];
    }
    row_reduce(s0, s1, red, warp, lane);
    middle();
    const float m0 = s0 * (1.f / DM), m1 = s1 * (1.f / DM);
    s0 = 0.f;
    s1 = 0.f;
#pragma unroll
    for (int j = 0; j < 9; j++) {
        v[4 * j] -= m0;
        v[4 * j + 1] -= m0;
        v[4 * j + 2] -= m1;
        v[4 * j + 3] -= m1;
        s0 += v[4 * j] * v[4 * j] + v[4 * j + 1] * v[4 * j + 1];
        s1 += v[4 * j + 2] * v[4 * j + 2] + v[4 * j + 3] * v[4 * j + 3];
    }
    row_reduce(s0, s1, red + 512, warp, lane);
    const float r0 = rsqrtf(s0 * (1.f / DM) + 1e-5f), r1 = rsqrtf(s1 * (1.f / DM) + 1e-5f);
#pragma unroll
    for (int j = 0; j < 9; j++) {
        v[4 * j] *= r0;
        v[4 * j + 1] *= r0;
        v[4 * j + 2] *= r1;
        v[4 * j + 3] *= r1;
    }
}
__device__ __forceinline__ void mod_to_smem(uint32_t dst, const uint32_t* src, uint32_t tag) {
    const uint32_t t0 = clk32();
    uint4 u;
    while (true) {
        u = ld128(reinterpret_cast<const uint4*>(src));
        const uint32_t bad = ((u.x ^ tag) | (u.y ^ tag) | (u.z ^ tag) | (u.w ^ tag)) & 0xffffu;
        if (__all_sync(0xffffffffu, bad == 0) || clk32() - t0 > WAIT_LIMIT) break;
        __nanosleep(64);
    }
    sts128(dst, u.x & 0xffff0000u, u.y & 0xffff0000u, u.z & 0xffff0000u, u.w & 0xffff0000u);
}
__device__ __forceinline__ void lds_mod(float (&m)[18], uint32_t src  , int warp) {
#pragma unroll
    for (int j = 0; j < 9; j++)
        asm volatile("ld.shared.v2.f32 {%0,%1}, [%2];"
                     : "=f"(m[2 * j]), "=f"(m[2 * j + 1])
                     : "r"(src + own_col(j) * 4 - (j == 8 ? warp * 32 : 0))
                     : "memory");
}
__device__ __forceinline__ void modulate_store(const float (&v)[36], const float (&shift)[18], const float (&scale)[18],
                                               uint4* hbuf  , int warp, int lane) {
    uint32_t o[18];
#pragma unroll
    for (int j = 0; j < 9; j++) {
        const uint32_t cc = pack_bf16(1.f + scale[2 * j], 1.f + scale[2 * j + 1]);
        const float c0 = bf_lo(cc), c1 = bf_hi(cc);
        o[2 * j] = max(pack_bf16(fmaf(v[4 * j], c0, shift[2 * j]), fmaf(v[4 * j + 1], c1, shift[2 * j + 1])), 1u);
        o[2 * j + 1] = max(pack_bf16(fmaf(v[4 * j + 2], c0, shift[2 * j]), fmaf(v[4 * j + 3], c1, shift[2 * j + 1])), 1u);
    }
#pragma unroll
    for (int i = 0; i < 4; i++) st128(hbuf + (i * 8 + warp) * 32 + lane, o[4 * i], o[4 * i + 1], o[4 * i + 2], o[4 * i + 3]);
    st64(reinterpret_cast<uint2*>(hbuf + 32 * 32) + warp * 32 + lane, o[16], o[17]);
}
__device__ __forceinline__ void sum_partials(float (&v)[36], const uint4* src  ,
                                             const uint2* tail  , uint32_t tag) {
    const uint32_t t0 = clk32();
    uint4 t[8][4];
    uint2 tl[8];
#pragma unroll
    for (int i = 0; i < 4; i++)
#pragma unroll
        for (int s = 0; s < 8; s++) t[s][i] = ld128(src + (s * 36 + i * 8) * 32);
#pragma unroll
    for (int s = 0; s < 8; s++) tl[s] = ld64(tail + s * 72 * 32);
#pragma unroll
    for (int h = 0; h < 2; h++) {
        while (true) {
            uint32_t bad = 0;
#pragma unroll
            for (int s = 0; s < 8; s++) bad |= (t[s][2 * h].x ^ tag) | (t[s][2 * h + 1].x ^ tag);
            if (__all_sync(0xffffffffu, (bad & 1u) == 0) || clk32() - t0 > WAIT_LIMIT) break;
#pragma unroll
            for (int s = 0; s < 8; s++)
#pragma unroll
                for (int i = 2 * h; i < 2 * h + 2; i++) t[s][i] = ld128(src + (s * 36 + i * 8) * 32);
        }
#pragma unroll
        for (int i = 2 * h; i < 2 * h + 2; i++) {
#pragma unroll
            for (int e = 0; e < 8; e++) v[8 * i + e] = 0.f;
#pragma unroll
            for (int s = 0; s < 8; s++) {
                v[8 * i] += bf_lo(t[s][i].x);
                v[8 * i + 1] += bf_hi(t[s][i].x);
                v[8 * i + 2] += bf_lo(t[s][i].y);
                v[8 * i + 3] += bf_hi(t[s][i].y);
                v[8 * i + 4] += bf_lo(t[s][i].z);
                v[8 * i + 5] += bf_hi(t[s][i].z);
                v[8 * i + 6] += bf_lo(t[s][i].w);
                v[8 * i + 7] += bf_hi(t[s][i].w);
            }
#pragma unroll
            for (int e = 0; e < 8; e++) asm volatile("" : "+f"(v[8 * i + e]));
        }
    }
    while (true) {
        uint32_t bad = 0;
#pragma unroll
        for (int s = 0; s < 8; s++) bad |= tl[s].x ^ tag;
        if (__all_sync(0xffffffffu, (bad & 1u) == 0) || clk32() - t0 > WAIT_LIMIT) break;
#pragma unroll
        for (int s = 0; s < 8; s++) tl[s] = ld64(tail + s * 72 * 32);
    }
    v[32] = v[33] = v[34] = v[35] = 0.f;
#pragma unroll
    for (int s = 0; s < 8; s++) {
        v[32] += bf_lo(tl[s].x);
        v[33] += bf_hi(tl[s].x);
        v[34] += bf_lo(tl[s].y);
        v[35] += bf_hi(tl[s].y);
    }
}
__device__ __forceinline__ void poll_tail(uint32_t (&a)[144], const uint2* src  ) {
    const uint32_t t0 = clk32();
    while (true) {
        uint32_t m = 0xffffffffu;
#pragma unroll
        for (int j = 0; j < 8; j++) {
            const uint2 t = ld64(src + j * 32);
            a[128 + 2 * j] = t.x;
            a[129 + 2 * j] = t.y;
        }
#pragma unroll
        for (int j = 0; j < 16; j++) m = min(m, a[128 + j]);
        if (__all_sync(0xffffffffu, m != 0) || clk32() - t0 > WAIT_LIMIT) break;
    }
}
template <int K0, int K1>
__device__ __forceinline__ void poll_frags(uint32_t (&a)[144], const uint4* src  , bool kick) {
    const uint32_t t0 = clk32();
    while (true) {
#pragma unroll
        for (int k = K0; k < K1; k++)
            asm volatile("ld.relaxed.gpu.global.v4.u32 {%0,%1,%2,%3}, [%4];"
                         : "=r"(a[4 * k]), "=r"(a[4 * k + 1]), "=r"(a[4 * k + 2]), "=r"(a[4 * k + 3])
                         : "l"(src + k * 32));
        if (kick) bar_arrive(5, 256);
        kick = false;
        uint32_t m0 = a[4 * K0], m1 = a[4 * K0 + 1];
#pragma unroll
        for (int i = 4 * K0 + 2; i < 4 * K1; i += 2) {
            m0 = min(m0, a[i]);
            m1 = min(m1, a[i + 1]);
        }
        if (__all_sync(0xffffffffu, min(m0, m1) != 0) || clk32() - t0 > WAIT_LIMIT) break;
    }
}

constexpr float SM_SCALE = 0.08838834764831845f * 1.4426950408889634f;
constexpr float SM_HI = 1.2089258e24f;
constexpr float SM_LO = 9.0949470e-13f;
__device__ __forceinline__ void qk_step(float (&s)[32], const uint32_t (&q)[32], uint64_t dk) {
#pragma unroll
    for (int k = 0; k < 8; k++) {
        if (k == 0)
            wgmma_n64_z<0>(s, q[0], q[1], q[2], q[3], dk);
        else
            wgmma_n64<0>(s, q[4 * k], q[4 * k + 1], q[4 * k + 2], q[4 * k + 3], dk + (k >> 2) * 512 + (k & 3) * 2);
    }
}
__device__ __forceinline__ void pv_step(float (&o)[64], const uint32_t (&p)[16], uint64_t dv, int acc) {
#pragma unroll
    for (int k = 0; k < 4; k++)
        wgmma_n128<1>(o, p[4 * k], p[4 * k + 1], p[4 * k + 2], p[4 * k + 3], dv + k * 128, k != 0 ? 1 : acc);
}
template <bool SHIFT>
__device__ __forceinline__ void exp_step(const float (&s)[32], uint32_t (&p)[16], float n0, float n1, float& s0,
                                         float& s1) {
#pragma unroll
    for (int i = 0; i < 8; i++) {
        const float e0 = ex2(SHIFT ? s[4 * i] + n0 : s[4 * i]), e1 = ex2(SHIFT ? s[4 * i + 1] + n0 : s[4 * i + 1]);
        const float e2 = ex2(SHIFT ? s[4 * i + 2] + n1 : s[4 * i + 2]), e3 = ex2(SHIFT ? s[4 * i + 3] + n1 : s[4 * i + 3]);
        if (i == 0) {
            s0 = e0 + e1;
            s1 = e2 + e3;
        } else {
            s0 += e0 + e1;
            s1 += e2 + e3;
        }
        p[2 * i] = pack_bf16(e0, e1);
        p[2 * i + 1] = pack_bf16(e2, e3);
    }
}
__device__ __forceinline__ void row_max(const float (&sa)[32], const float (&sb)[32], float& x0, float& x1) {
    float xa[8];
#pragma unroll
    for (int i = 0; i < 8; i++) xa[i] = fmaxf(sa[i], sb[i]);
#pragma unroll
    for (int k = 1; k < 4; k++)
#pragma unroll
        for (int i = 0; i < 8; i++) xa[i] = fmaxf(xa[i], fmaxf(sa[8 * k + i], sb[8 * k + i]));
    x0 = fmaxf(fmaxf(xa[0], xa[1]), fmaxf(xa[4], xa[5]));
    x1 = fmaxf(fmaxf(xa[2], xa[3]), fmaxf(xa[6], xa[7]));
    x0 = fmaxf(x0, __shfl_xor_sync(0xffffffffu, x0, 1));
    x1 = fmaxf(x1, __shfl_xor_sync(0xffffffffu, x1, 1));
    x0 = fmaxf(x0, __shfl_xor_sync(0xffffffffu, x0, 2));
    x1 = fmaxf(x1, __shfl_xor_sync(0xffffffffu, x1, 2));
}
__device__ __forceinline__ void inv_row_sums(float l0, float l1, float& i0, float& i1) {
    l0 += __shfl_xor_sync(0xffffffffu, l0, 1);
    l1 += __shfl_xor_sync(0xffffffffu, l1, 1);
    l0 += __shfl_xor_sync(0xffffffffu, l0, 2);
    l1 += __shfl_xor_sync(0xffffffffu, l1, 2);
    i0 = rcp(l0);
    i1 = rcp(l1);
}

__device__ __forceinline__ uint32_t get_epoch(uint32_t sbase) { return __float_as_uint(lds32f(sbase + OFF_EPOCH)); }
__device__ __forceinline__ float silu_bf16(unsigned short c) {
    const float cv = bf_lo(c);
    return round_bf16(cv * rcp(1.f + ex2(-1.4426950408889634f * cv)));
}
__device__ __forceinline__ void st_mod(uint32_t* p, float v, uint32_t tag) {
    asm volatile("st.relaxed.gpu.global.u32 [%0], %1;" ::"l"(p), "r"(__float_as_uint(round_bf16(v)) | tag)
                 : "memory");
}
__device__ __forceinline__ void fma8(float (&acc)[8], float sc, const uint4& w) {
    acc[0] = fmaf(sc, bf_lo(w.x), acc[0]);
    acc[1] = fmaf(sc, bf_hi(w.x), acc[1]);
    acc[2] = fmaf(sc, bf_lo(w.y), acc[2]);
    acc[3] = fmaf(sc, bf_hi(w.y), acc[3]);
    acc[4] = fmaf(sc, bf_lo(w.z), acc[4]);
    acc[5] = fmaf(sc, bf_hi(w.z), acc[5]);
    acc[6] = fmaf(sc, bf_lo(w.w), acc[6]);
    acc[7] = fmaf(sc, bf_hi(w.w), acc[7]);
}
__device__ __forceinline__ void modp_load(uint4 (&u)[6], const uint32_t* src) {
#pragma unroll
    for (int i = 0; i < 6; i++) u[i] = ld128(reinterpret_cast<const uint4*>(src + i * 2 * DM));
}
__device__ __forceinline__ void modp_to_smem(uint4 (&u)[6], uint32_t dst, const uint32_t* src, uint32_t tag) {
    const uint32_t t0 = clk32();
    while (true) {
        uint32_t bad = 0;
#pragma unroll
        for (int i = 0; i < 6; i++) bad |= (u[i].x ^ tag) | (u[i].y ^ tag) | (u[i].z ^ tag) | (u[i].w ^ tag);
        if (__all_sync(0xffffffffu, (bad & 0xffu) == 0) || clk32() - t0 > WAIT_LIMIT) break;
        modp_load(u, src);
    }
    float s0 = 0.f, s1 = 0.f, s2 = 0.f, s3 = 0.f;
#pragma unroll
    for (int i = 0; i < 6; i++) {
        s0 += __uint_as_float(u[i].x & ~0xffu);
        s1 += __uint_as_float(u[i].y & ~0xffu);
        s2 += __uint_as_float(u[i].z & ~0xffu);
        s3 += __uint_as_float(u[i].w & ~0xffu);
    }
    const uint32_t p0 = pack_bf16(s0, s1), p1 = pack_bf16(s2, s3);
    sts128(dst, p0 << 16, p0 & 0xffff0000u, p1 << 16, p1 & 0xffff0000u);
}

__global__ void __cluster_dims__(2, 1, 1) __launch_bounds__(384, 1)
    fused_block_kernel(const __grid_constant__ Params maps) {
    extern __shared__ uint8_t smem_raw[];
    uint32_t sbase = (smem_u32(smem_raw) + 1023u) & ~1023u;
    asm volatile("" : "+r"(sbase));
    const int b = blockIdx.x;
    const int rank = b & 1;
    const int mt = ((b >> 1) & 7) * 2 + rank;
    const int g = b >> 4;
    const int warp = __shfl_sync(0xffffffffu, threadIdx.x >> 5, 0);
    const int lane = threadIdx.x & 31;
    Scratch* const sc_ = maps.sc;
    const __nv_bfloat16* const wmod = maps.wmod;
    const __nv_bfloat16* const cvec = maps.cvec;

#define SPROF(i)

    if (warp >= 8) {
        asm volatile("setmaxnreg.dec.sync.aligned.u32 24;");
        if (warp == 8 && lane == 0) {
#pragma unroll
            for (int i = 0; i < 8; i++) {
                mbar_init(sbase + OFF_FULL + i * 8, 1);
                mbar_init(sbase + OFF_EMPTY + i * 8, 4);
            }
            mbar_init(sbase + OFF_XBAR, 1);
            asm volatile("fence.mbarrier_init.release.cluster;" ::: "memory");
            asm volatile("barrier.cluster.arrive.relaxed;\nbarrier.cluster.wait;" ::: "memory");
            uint32_t slot = 0, phase = 1;
            const uint32_t dst0 = sbase + rank * BOX_BYTES;
            auto acquire = [&](uint32_t bytes) {
                mbar_wait(sbase + OFF_EMPTY + slot * 8, phase);
                mbar_expect_tx(sbase + OFF_FULL + slot * 8, bytes);
            };
            auto adv8 = [&]() {
                if (++slot == 8) {
                    slot = 0;
                    phase ^= 1;
                }
            };
#pragma unroll 1
            for (int hq = 0; hq < 4; hq++) {
                const int col = (g * 4 + ((hq + 1) & 3)) * 128 + rank * 64;
                if (hq == 2) {
                    l2_prefetch(maps.kc + (size_t)(g * 4 * 2048 + (b & 15) * 64) * 128, SLOT_BYTES);
                    l2_prefetch(maps.vc + (size_t)(g * 4 * 2048 + (b & 15) * 64) * 128, SLOT_BYTES);
                }
#pragma unroll 1
                for (int kc = 0; kc < 9; kc++) {
                    acquire(SLOT_BYTES);
                    tma_mc(dst0 + slot * SLOT_BYTES, &maps.wq, col, kc * 64, sbase + OFF_FULL + slot * 8);
                    adv8();
                }
            }
            const int row0 = g * 4 * 2048;
#pragma unroll 1
            for (int n = 0; n < 128; n++) {
                if (n < 4) mbar_wait(sbase + OFF_EMPTY + (slot + 1) * 8, phase);
                acquire(2 * SLOT_BYTES);
                const uint32_t bar = sbase + OFF_FULL + slot * 8;
                const int r0 = n == 0 ? 0 : (n == 127 ? 126 : n + 1);
                const int r1 = n == 0 ? 1 : (n == 127 ? 127 : n - 1);
                tma_mc(dst0 + slot * SLOT_BYTES, n == 127 ? &maps.v : &maps.k, rank * 64, row0 + r0 * 64, bar);
                tma_mc(dst0 + (slot + 1) * SLOT_BYTES, n == 0 ? &maps.k : &maps.v, rank * 64, row0 + r1 * 64, bar);
                adv8();
                adv8();
                const int u = n + KV_AHEAD;
                if (u < 128 && (u & 15) == (b & 15)) {
                    l2_prefetch(maps.kc + (size_t)(row0 + u * 64) * 128, SLOT_BYTES);
                    l2_prefetch(maps.vc + (size_t)(row0 + u * 64) * 128, SLOT_BYTES);
                }
            }
#pragma unroll 1
            for (int p = 0; p < 4; p++)
#pragma unroll 1
                for (int kc = 0; kc < 8; kc++) {
                    acquire(SLOT_BYTES);
                    tma_mc(dst0 + slot * SLOT_BYTES, &maps.wo, p * 128 + rank * 64, g * 512 + kc * 64,
                           sbase + OFF_FULL + slot * 8);
                    adv8();
                }
#pragma unroll 1
            for (int kc = 0; kc < 4; kc++) {
                acquire(SLOT_BYTES);
                tma_mc(dst0 + slot * SLOT_BYTES, &maps.wo, 512, g * 512 + kc * 128 + rank * 64,
                       sbase + OFF_FULL + slot * 8);
                adv8();
            }
            const CUtensorMap* mg = rank ? &maps.wu : &maps.wg;
#pragma unroll 1
            for (int ch = 0; ch < 9; ch++)
#pragma unroll 1
                for (int kc = 0; kc < 9; kc++) {
                    acquire(SLOT_BYTES);
                    tma_mc(dst0 + slot * SLOT_BYTES, mg, g * 576 + ch * 64, kc * 64, sbase + OFF_FULL + slot * 8);
                    adv8();
                }
#pragma unroll 1
            for (int p = 0; p < 4; p++)
#pragma unroll 1
                for (int kc = 2; kc < 11; kc++) {
                    acquire(SLOT_BYTES);
                    tma_mc(dst0 + slot * SLOT_BYTES, &maps.wd, p * 128 + rank * 64, g * 576 + (kc < 9 ? kc : kc - 9) * 64,
                           sbase + OFF_FULL + slot * 8);
                    adv8();
                }
#pragma unroll 1
            for (int i = 0; i < 5; i++) {
                acquire(i < 4 ? SLOT_BYTES : BOX_BYTES);
                const int kc = 2 * i + rank + 2;
                if (i < 4 || rank == 0)
                    tma_mc(dst0 + slot * SLOT_BYTES, &maps.wd, 512, g * 576 + (kc < 9 ? kc : kc - 9) * 64,
                           sbase + OFF_FULL + slot * 8);
                adv8();
            }
        } else if (warp == 11) {
            asm volatile("barrier.cluster.arrive.relaxed.aligned;" ::: "memory");
            bar_sync(6, 160);
            uint4* hz = sc_->h[(get_epoch(sbase) & 1) ^ 1][0] + (size_t)b * 72 * 32 + lane;
#pragma unroll 1
            for (int i = 0; i < 72; i++) {
                hz[i * 32] = make_uint4(0, 0, 0, 0);
                __nanosleep(200);
            }
            bar_sync(6, 160);
            if (lane == 0) {
#pragma unroll 1
                for (int i = 0; i < 9; i++) {
                    l2_prefetch((const char*)maps.wo_p + (size_t)b * 36864 + i * 4096, 4096);
                    __nanosleep(400);
                    l2_prefetch((const char*)maps.wg_p + (size_t)b * 41472 + i * 4608, 4608);
                    __nanosleep(400);
                    l2_prefetch((const char*)maps.wu_p + (size_t)b * 41472 + i * 4608, 4608);
                    __nanosleep(400);
                    l2_prefetch((const char*)maps.wd_p + (size_t)b * 41472 + i * 4608, 4608);
                    __nanosleep(400);
                }
            }
        } else if (warp == 9 || warp == 10) {
            asm volatile("barrier.cluster.arrive.relaxed.aligned;" ::: "memory");
            bar_sync(4, 320);
            const uint32_t tag = (get_epoch(sbase) + 1) & 0xffffu;
            if (warp == 10 && lane < 9) l2_prefetch((const char*)maps.wq_p + (size_t)b * 36864 + lane * 4096, 4096);
            const int blk = warp == 9 ? 72 + b : 200 + b;
            if (blk < 216) {
                float acc[8];
#pragma unroll
                for (int e = 0; e < 8; e++) acc[e] = 0.f;
                const uint4* wp = reinterpret_cast<const uint4*>(wmod + (size_t)(lane >> 1) * (6 * DM) + blk * 16) + (lane & 1);
                const unsigned short* cp = reinterpret_cast<const unsigned short*>(cvec) + (lane >> 1);
#pragma unroll 1
                for (int i = 0; i < 36; i++) {
                    const uint4 w = __ldg(wp + (size_t)i * (16 * 6 * DM / 8));
                    const float sc = silu_bf16(__ldg(cp + i * 16));
                    fma8(acc, sc, w);
                }
#pragma unroll
                for (int o = 2; o < 32; o <<= 1)
#pragma unroll
                    for (int e = 0; e < 8; e++) acc[e] += __shfl_xor_sync(0xffffffffu, acc[e], o);
                if (lane < 2) {
#pragma unroll
                    for (int e = 0; e < 8; e++) st_mod(sc_->mod + blk * 16 + lane * 8 + e, acc[e], tag);
                }
            }
            if (warp == 9) {
#pragma unroll 1
                for (int st = 1; st <= 2; st++) {
                    bar_sync(7, 160);
                    const uint32_t* src = sc_->mod + (st * 3 - 1) * DM;
                    const int n = st == 1 ? 3 * DM : DM;
#pragma unroll 1
                    for (int i = lane * 4; i < n + 127 - ((n + 127) & 127); i += 128)
                        mod_to_smem(sbase + OFF_MODT + min(i, n - 4) * 4, src + min(i, n - 4), tag);
                    __syncwarp();
                    if (lane == 0) rows_load(sbase, st == 1 ? &maps.rx : &maps.rx2, (mt * 8 + g) * 16);
                    if (st == 1) {
                        bar_sync(7, 160);
                        if (lane == 0) {
                            rows_store(sbase, &maps.rx2, (mt * 8 + g) * 16);
                            rows_store_wait();
                        }
                        __syncwarp();
                        bar_arrive(10, 160);
                    }
                }
            }
        }
    } else {
        uint4 w1[3], xw[5], ew = make_uint4(0, 0, 0, 0);
        unsigned short cu[3];
        {
            const int t = threadIdx.x, bw = min(b, 107);
            const int row = (bw / 18) * 96 + (t >> 3);
#pragma unroll
            for (int i = 0; i < 3; i++) {
                w1[i] = ldg128(reinterpret_cast<const uint4*>(wmod + (size_t)(row + 32 * i) * (6 * DM)) + (bw % 18) * 8 + (t & 7));
                asm volatile("ld.global.nc.u16 %0, [%1];" : "=h"(cu[i]) : "l"(cvec + row + 32 * i));
            }
            if (t == 0) ew = ld128(reinterpret_cast<const uint4*>(&sc_->epoch[b * 32]));
#pragma unroll
            for (int i = 0; i < 5; i++)
                xw[i] = ldg128(reinterpret_cast<const uint4*>(maps.x + (size_t)(mt * 8 + g) * 16 * DM) + min(t + 256 * i, 1151));
        }
        if (threadIdx.x == 160) SPROF(5);
        asm volatile("setmaxnreg.inc.sync.aligned.u32 240;");
        if (threadIdx.x == 160) SPROF(6);
        const int wg = warp >> 2;
        const int tid = threadIdx.x;
        Ctx cx;
        cx.sbase = sbase;
        cx.wg = wg;
        if (wg == 1) bar_arrive(8, 256);
        cx.rel_cta = (lane == 0 && (warp & 3) < 2) ? (warp & 3) : 2;
        const uint32_t red = sbase + OFF_RED;
        const int own = mt * 8 + g;
        const int wown = mt * 8 + warp;
        PROF(0);
        PROFG(30);
        PROFR(17);
        {
            asm volatile("barrier.cluster.arrive.relaxed.aligned;" ::: "memory");
            float acc[8];
#pragma unroll
            for (int e = 0; e < 8; e++) acc[e] = 0.f;
#pragma unroll
            for (int i = 0; i < 3; i++) fma8(acc, silu_bf16(cu[i]), w1[i]);
#pragma unroll
            for (int o = 8; o < 32; o <<= 1)
#pragma unroll
                for (int e = 0; e < 8; e++) acc[e] += __shfl_xor_sync(0xffffffffu, acc[e], o);
            PROFR(19);
            if (lane < 8) {
                const uint32_t dst = sbase + OFF_MRED + warp * 256 + lane * 32;
                sts128(dst, __float_as_uint(acc[0]), __float_as_uint(acc[1]), __float_as_uint(acc[2]), __float_as_uint(acc[3]));
                sts128(dst + 16, __float_as_uint(acc[4]), __float_as_uint(acc[5]), __float_as_uint(acc[6]), __float_as_uint(acc[7]));
            }
            if (tid == 0) sts128(sbase + OFF_EPOCH, ew.x, ew.y, ew.z, ew.w);
            bar_sync(3, 256);
            PROFR(20);
            if (tid < 64 && b < 108) {
                float sum = 0.f;
#pragma unroll
                for (int w8 = 0; w8 < 8; w8++) sum += lds32f(sbase + OFF_MRED + w8 * 256 + tid * 4);
                asm volatile("st.relaxed.gpu.global.u32 [%0], %1;" ::"l"(&sc_->modp[b / 18][(b % 18) * 64 + tid]),
                             "r"((__float_as_uint(sum) & ~0xffu) | ((get_epoch(sbase) + 1) & 0xffu))
                             : "memory");
            }
            PROFR(21);
#pragma unroll
            for (int i = 0; i < 5; i++) {
                const int vi = min(tid + 256 * i, 1151), ln = vi >> 3;
                sts128(sbase + OFF_ROWS + ln * 128 + (((vi & 7) ^ (ln & 7)) << 4), xw[i].x, xw[i].y, xw[i].z, xw[i].w);
            }
            bar_sync(3, 256);
        }

        Ring ring{0u, 0u};
        int stage = 0;
        asm volatile("" : "+r"(stage));
#pragma unroll 1
        for (;; stage++) {
            int tid, lane;
            asm volatile("mov.u32 %0, %%tid.x;" : "=r"(tid));
            lane = tid & 31;
            const uint32_t epoch = get_epoch(sbase);
            {
                float v[36];
                const uint32_t modt = sbase + OFF_MODT + (warp * 16 + (lane & 3) * 2) * 4;
                if (stage == 0) {
#pragma unroll
                    for (int i = 0; i < 36; i++) v[i] = 0.f;
                } else {
                    const uint4* psrc = sc_->part + (size_t)own * 8 * 36 * 32;
                    sum_partials(v, psrc + tid, reinterpret_cast<const uint2*>(psrc + 32 * 32) + tid, stage & 1);
                    PROF(stage == 1 ? 8 : 15);
                }
                if (stage) mbar_wait(sbase + OFF_XBAR, stage - 1);
                if (stage == 0) PROFR(22);
                {
                    const float gs = stage == 2 ? 0.5f : 1.f;
                    float gate[18];
                    lds_mod(gate, modt, warp);
                    const int r = lane >> 2;
                    const uint32_t rows = sbase + OFF_ROWS + r * (DM * 2) + (lane & 3) * 4;
#pragma unroll
                    for (int j = 0; j < 9; j++) {
                        const int ch = j < 8 ? (j >> 1) * 2 + (warp >> 2) : 8, c16 = j < 8 ? (warp & 3) * 2 + (j & 1) : warp;
                        const uint32_t ad = rows + ch * 128 + ((c16 ^ ((r + ch) & 7)) << 4);
                        const uint32_t u0 = __float_as_uint(lds32f(ad)), u1 = __float_as_uint(lds32f(ad + 8 * DM * 2));
                        const float g0 = stage ? gate[2 * j] * gs : 0.f, g1 = stage ? gate[2 * j + 1] * gs : 0.f;
                        v[4 * j] = fmaf(g0, v[4 * j], bf_lo(u0));
                        v[4 * j + 1] = fmaf(g1, v[4 * j + 1], bf_hi(u0));
                        v[4 * j + 2] = fmaf(g0, v[4 * j + 2], bf_lo(u1));
                        v[4 * j + 3] = fmaf(g1, v[4 * j + 3], bf_hi(u1));
                        sts32f(ad, __uint_as_float(pack_bf16(v[4 * j], v[4 * j + 1])));
                        sts32f(ad + 8 * DM * 2, __uint_as_float(pack_bf16(v[4 * j + 2], v[4 * j + 3])));
                    }
                    asm volatile("fence.proxy.async.shared::cta;" ::: "memory");
                }
                if (stage == 2) break;
                if (lane == 0) asm volatile("cp.async.bulk.wait_group.read 0;" ::: "memory");
                PROF(stage == 0 ? 1 : 9);
                uint4 ua[6], ub[6];
#pragma unroll
                for (int i = 0; i < 6; i++) ua[i] = ub[i] = make_uint4(0, 0, 0, 0);
                layernorm_rows(v, red, warp, lane, [&]() {
                    if (stage == 0) {
                        modp_load(ua, sc_->modp[0] + tid * 4);
                        if (warp == 0) modp_load(ub, sc_->modp[0] + 1024 + tid * 4);
                    }
                });
                if (stage == 0) PROFR(27);
                if (stage == 0) {
                    const uint32_t tag = (epoch + 1) & 0xffu;
                    modp_to_smem(ua, sbase + OFF_MODT + (DM + tid * 4) * 4, sc_->modp[0] + tid * 4, tag);
                    if (warp == 0)
                        modp_to_smem(ub, sbase + OFF_MODT + (DM + 1024 + tid * 4) * 4, sc_->modp[0] + 1024 + tid * 4, tag);
                    bar_sync(3, 256);
                }
                float shift[18], scale[18];
                lds_mod(shift, modt + DM * 4, warp);
                lds_mod(scale, modt + 2 * DM * 4, warp);
                if (stage == 0) PROFR(28);
                PROF(stage == 0 ? 2 : 10);
                modulate_store(v, shift, scale, sc_->h[epoch & 1][stage] + (size_t)own * 36 * 32, warp, lane);
                if (stage == 0) asm volatile("barrier.cluster.wait.aligned;" ::: "memory");
            }

            const uint32_t spill = sbase + 8 * SLOT_BYTES + wg * 3 * SLOT_BYTES + (tid & 127) * 16;
            uint32_t a[144];
            PROF(stage == 0 ? 3 : 11);
            {
                const uint4* hsrc = sc_->h[epoch & 1][stage] + (size_t)wown * 36 * 32 + lane;
                __nanosleep(PROBE_NS);
                poll_tail(a, reinterpret_cast<const uint2*>(hsrc - lane + 32 * 32) + lane);
                PROF(stage == 0 ? 4 : 12);
                if (stage == 1) PROFG(25);
                TG(stage * 32 + 30);
                if (wg == 1) bar_sync(5, 256);
                poll_frags<0, 32>(a, hsrc, wg == 0);
                if (stage == 0) bar_arrive(4, 320);
            }
            uint4* hhbuf = sc_->hh + (size_t)b * 8 * 256 + tid;
            float d[64];
#pragma unroll 1
            for (int ch = 0;; ch++) {
                TG(stage * 32 + ch * 2);
                gemm_n128(d, a, cx, ring, true);
                TG(stage * 32 + ch * 2 + 1);
                if (stage == 0) {
#pragma unroll
                    for (int i = 0; i < 64; i++) d[i] *= SM_SCALE;
                    if (ch == 3) break;
#pragma unroll
                    for (int v = 0; v < 8; v++)
                        sts128(spill + (ch * 8 + v) * 2048, pack_bf16(d[8 * v], d[8 * v + 1]),
                               pack_bf16(d[8 * v + 2], d[8 * v + 3]), pack_bf16(d[8 * v + 4], d[8 * v + 5]),
                               pack_bf16(d[8 * v + 6], d[8 * v + 7]));
                } else {
#pragma unroll
                    for (int i = 0; i < 32; i++) {
                        const float gv = d[i], gu = gv * d[32 + i];
                        const float z = gv * fmaf(gv * gv, 0.7978845608028654f * 0.044715f, 0.7978845608028654f);
                        d[i] = fmaf(gu, tanh_fast(z), gu);
                    }
                    if (ch == 8) break;
                    if (wg == 0) {
                        if (ch == 0) bar_arrive(7, 160);
                        if (ch == 2) bar_sync(10, 160);
                    }
#pragma unroll
                    for (int v = 0; v < 4; v++) {
                        const uint4 h4 = make_uint4(pack_bf16(d[8 * v], d[8 * v + 1]), pack_bf16(d[8 * v + 2], d[8 * v + 3]),
                                                    pack_bf16(d[8 * v + 4], d[8 * v + 5]), pack_bf16(d[8 * v + 6], d[8 * v + 7]));
                        if (ch < 2)
                            __stcg(hhbuf + (ch * 4 + v) * 256, h4);
                        else
                            sts128(spill + ((ch - 2) * 4 + v) * 2048, h4.x, h4.y, h4.z, h4.w);
                    }
                }
            }
            if (stage == 0) {
                uint32_t q[32];
#pragma unroll
                for (int i = 0; i < 32; i++) q[i] = pack_bf16(d[2 * i], d[2 * i + 1]);
                PROF(5);
                PROFG(23);
                if (wg == 0) bar_arrive(6, 160);
                {
                    float o[64], sa[32], sb[32];
                    uint32_t pa[16], pb[16];
#pragma unroll
                    for (int i = 0; i < 64; i++) o[i] = 0.f;
                    float n0 = 0.f, n1 = 0.f, l0 = 1.f, l1 = 1.f;
                    bool shifted = false;
                    const uint64_t dbase = desc_of(sbase);
                    const uint64_t dbk = dbase - (511u << 16);
                    const int my_bar = 1 + wg, other_bar = 2 - wg;

                    auto softmax_a = [&](bool first, float& s0, float& s1) {
                        if (first) {
                            shifted = false;
                            n0 = n1 = 0.f;
                            l0 = l1 = 0.f;
                        }
                        if (shifted)
                            exp_step<true>(sa, pa, n0, n1, s0, s1);
                        else
                            exp_step<false>(sa, pa, n0, n1, s0, s1);
                    };
                    auto softmax_b = [&](bool first, float s0, float s1) {
                        float u0, u1;
                        if (shifted)
                            exp_step<true>(sb, pb, n0, n1, u0, u1);
                        else
                            exp_step<false>(sb, pb, n0, n1, u0, u1);
                        s0 += u0;
                        s1 += u1;
                        bool bad = !(fmaxf(s0, s1) <= SM_HI);
                        if (first) {
                            float r0 = s0 + __shfl_xor_sync(0xffffffffu, s0, 1), r1 = s1 + __shfl_xor_sync(0xffffffffu, s1, 1);
                            r0 += __shfl_xor_sync(0xffffffffu, r0, 2);
                            r1 += __shfl_xor_sync(0xffffffffu, r1, 2);
                            bad = bad || !(fminf(r0, r1) >= SM_LO);
                        }
                        if (__any_sync(0xffffffffu, bad)) {
                            float x0, x1;
                            row_max(sa, sb, x0, x1);
                            x0 = -x0;
                            x1 = -x1;
                            if (!first) {
                                x0 = fminf(x0, n0);
                                x1 = fminf(x1, n1);
                                const float al0 = ex2(x0 - n0), al1 = ex2(x1 - n1);
                                l0 *= al0;
                                l1 *= al1;
#pragma unroll
                                for (int i = 0; i < 16; i++) {
                                    o[4 * i] *= al0;
                                    o[4 * i + 1] *= al0;
                                    o[4 * i + 2] *= al1;
                                    o[4 * i + 3] *= al1;
                                }
                            }
                            n0 = x0;
                            n1 = x1;
                            shifted = true;
                            exp_step<true>(sa, pa, n0, n1, s0, s1);
                            exp_step<true>(sb, pb, n0, n1, u0, u1);
                            s0 += u0;
                            s1 += u1;
                        }
                        l0 += s0;
                        l1 += s1;
                    };

                    cx.wait_full(4, 0);
                    if (wg == 1) bar_sync(my_bar, 256);
                    wg_fence();
                    qk_step(sa, q, dbk + 4 * 1024);
                    qk_step(sb, q, dbk + 5 * 1024);
                    wg_commit();
                    bar_arrive(other_bar, 256);
                    wg_wait<0>();
                    pin(sa);
                    pin(sb);
                    cx.release(4);
                    cx.wait_full(6, 0);
                    {
                        float s0, s1;
                        softmax_a(true, s0, s1);
                        softmax_b(true, s0, s1);
                    }
                    uint32_t alo = (uint32_t)dbase + 6 * 1024, blo = (uint32_t)dbase;
                    const uint32_t dhi = (uint32_t)(dbase >> 32);
#pragma unroll 1
                    for (int t = 1; t < 64; t++) {
                        const int j = t & 15;
                        const uint32_t sA = 2 + 4 * (t & 1), sB = 4 - 4 * (t & 1);
                        const uint64_t da = ((uint64_t)dhi << 32) | alo, db = ((uint64_t)dhi << 32) | blo;
                        TL(0);
                        bar_sync(my_bar, 256);
                        TL(2);
                        wg_fence();
                        pv_step(o, pa, da + 1024, j != 1);
                        qk_step(sa, q, da - (511u << 16));
                        wg_commit();
                        cx.wait_full(sB, ((36 + 4 * t) >> 3) & 1);
                        wg_fence();
                        qk_step(sb, q, db - (511u << 16));
                        pv_step(o, pb, db + 1024, 1);
                        wg_commit();
                        bar_arrive(other_bar, 256);
                        alo ^= 4096;
                        blo ^= 4096;
                        asm volatile("" : "+r"(alo), "+r"(blo));
                        TL(3);
                        wg_wait<1>();
                        pin(sa);
                        pin(pa);
                        TL(4);
                        cx.release(sA);
                        const float lp0 = l0, lp1 = l1;
                        float s0, s1;
                        softmax_a(j == 0, s0, s1);
                        TL(5);
                        wg_wait<0>();
                        pin(o);
                        pin(sb);
                        pin(pb);
                        TL(6);
                        cx.release(sB);
                        if (j == 0) {
                            float i0, i1;
                            inv_row_sums(lp0, lp1, i0, i1);
                            const uint32_t dst = spill + ((t >> 4) - 1) * 16384;
#pragma unroll
                            for (int v = 0; v < 8; v++)
                                sts128(dst + v * 2048, pack_bf16(o[8 * v] * i0, o[8 * v + 1] * i0),
                                       pack_bf16(o[8 * v + 2] * i1, o[8 * v + 3] * i1),
                                       pack_bf16(o[8 * v + 4] * i0, o[8 * v + 5] * i0),
                                       pack_bf16(o[8 * v + 6] * i1, o[8 * v + 7] * i1));
                        }
                        const uint32_t bn = sbase + OFF_FULL + (8 - sA) * 8, pn = ((38 + 4 * t) >> 3) & 1;
                        const bool okn = mbar_try(bn, pn);
                        TL(1);
                        softmax_b(j == 0, s0, s1);
                        if (!okn || j == 15) {
                            mbar_wait(bn, pn);
                            if (t == 47 && wg == 0) bar_arrive(6, 160);
                            if (j == 15 && t < 63) {
                                const uint32_t src = spill + (t >> 4) * 16384;
#pragma unroll
                                for (int v = 0; v < 8; v++)
                                    lds128(src + v * 2048, q[4 * v], q[4 * v + 1], q[4 * v + 2], q[4 * v + 3]);
                            }
                        }
                        TL(7);
                    }
                    bar_sync(my_bar, 256);
                    wg_fence();
                    pv_step(o, pa, dbase + 2 * 1024, 1);
                    pv_step(o, pb, dbase + 3 * 1024, 1);
                    wg_commit();
                    if (wg == 0) bar_arrive(other_bar, 256);
                    float i0, i1;
                    inv_row_sums(l0, l1, i0, i1);
                    wg_wait<0>();
                    pin(o);
                    cx.release(2);
#pragma unroll
                    for (int i = 0; i < 16; i++) {
                        a[96 + 2 * i] = pack_bf16(o[4 * i] * i0, o[4 * i + 1] * i0);
                        a[96 + 2 * i + 1] = pack_bf16(o[4 * i + 2] * i1, o[4 * i + 3] * i1);
                    }
#pragma unroll
                    for (int i = 128; i < 144; i++) a[i] = 0;
                }
                ring.slot = 4;
                ring.phase = 0;
                PROF(6);
                PROFG(24);
            } else {
#pragma unroll
                for (int v = 0; v < 8; v++) {
                    const uint4 t = __ldcg(hhbuf + v * 256);
                    a[112 + 4 * v] = t.x;
                    a[113 + 4 * v] = t.y;
                    a[114 + 4 * v] = t.z;
                    a[115 + 4 * v] = t.w;
                }
#pragma unroll
                for (int i = 0; i < 16; i++) a[96 + i] = pack_bf16(d[2 * i], d[2 * i + 1]);
                PROF(13);
            }
#pragma unroll
            for (int v = 0; v < 24; v++) lds128(spill + v * 2048, a[4 * v], a[4 * v + 1], a[4 * v + 2], a[4 * v + 3]);

            {
                uint4* dst = sc_->part + ((size_t)wown * 8 + g) * 36 * 32;
                const uint32_t ptag = (stage + 1) & 1;
                const uint32_t stg = sbase + OFF_PSTG + warp * 4096;
#pragma unroll 1
                for (int p = 0; p < 4; p++) {
                    TG(stage * 32 + 18 + p * 2);
                    gemm_n128(d, a, cx, ring, stage != 0);
                    TG(stage * 32 + 19 + p * 2);
                    if (lane == 0) asm volatile("cp.async.bulk.wait_group.read 0;" ::: "memory");
                    __syncwarp();
#pragma unroll
                    for (int u = 0; u < 8; u++)
                        sts128(stg + u * 512 + lane * 16, (pack_bf16(d[8 * u], d[8 * u + 1]) & ~1u) | ptag,
                               pack_bf16(d[8 * u + 2], d[8 * u + 3]), pack_bf16(d[8 * u + 4], d[8 * u + 5]),
                               pack_bf16(d[8 * u + 6], d[8 * u + 7]));
                    asm volatile("fence.proxy.async.shared::cta;" ::: "memory");
                    __syncwarp();
                    if (lane == 0) bulk_store(dst + p * 8 * 32, stg, 4096);
                    __syncwarp();
                    if (p == 0 && wg == 0) bar_arrive(7, 160);
                }
                float e[32];
                TG(stage * 32 + 26);
                gemm_n64(e, a, cx, ring, stage != 0);
                TG(stage * 32 + 27);
                const uint32_t stg2 = sbase + OFF_PSTG + 32768 + warp * 2048;
#pragma unroll
                for (int j = 0; j < 8; j++)
                    asm volatile("st.shared.v2.b32 [%0], {%1, %2};" ::"r"(stg2 + j * 256 + lane * 8),
                                 "r"((pack_bf16(e[4 * j], e[4 * j + 1]) & ~1u) | ptag), "r"(pack_bf16(e[4 * j + 2], e[4 * j + 3]))
                                 : "memory");
                asm volatile("fence.proxy.async.shared::cta;" ::: "memory");
                __syncwarp();
                if (lane == 0) bulk_store(dst + 32 * 32, stg2, 2048);
                __syncwarp();
            }
            PROF(stage == 0 ? 7 : 14);
            if (stage == 1) {
                PROFG(26);
                asm volatile("barrier.cluster.arrive.relaxed.aligned;" ::: "memory");
            }
        }
        if (wg == 0) bar_sync(8, 256);
        bar_sync(3, 256);
        if (tid == 32) sc_->epoch[b * 32] = get_epoch(sbase) + 1;
        if (tid == 0) rows_store(sbase, &maps.rout, own * 16);
        if (lane == 0) rows_store_wait();
        __syncwarp();
        PROF(16);
        PROFG(31);
        asm volatile("barrier.cluster.wait.aligned;" ::: "memory");
    }
}

typedef CUresult (*EncodeFn)(CUtensorMap*, CUtensorMapDataType, cuuint32_t, void*, const cuuint64_t*, const cuuint64_t*,
                             const cuuint32_t*, const cuuint32_t*, CUtensorMapInterleave, CUtensorMapSwizzle,
                             CUtensorMapL2promotion, CUtensorMapFloatOOBfill);

void make_map(EncodeFn enc, CUtensorMap* m, const void* ptr, uint64_t rows, uint64_t cols, bool narrow = false) {
    cuuint64_t gdim[2] = {cols, rows};
    cuuint64_t gstr[1] = {cols * 2};
    cuuint32_t box[2] = {narrow ? 16u : 64u, narrow ? 192u : 64u};
    cuuint32_t estr[2] = {1, 1};
    enc(m, CU_TENSOR_MAP_DATA_TYPE_BFLOAT16, 2, const_cast<void*>(ptr), gdim, gstr, box, estr,
        CU_TENSOR_MAP_INTERLEAVE_NONE, narrow ? CU_TENSOR_MAP_SWIZZLE_NONE : CU_TENSOR_MAP_SWIZZLE_128B,
        CU_TENSOR_MAP_L2_PROMOTION_L2_128B,
        CU_TENSOR_MAP_FLOAT_OOB_FILL_NONE);
}

void make_rows_map(EncodeFn enc, CUtensorMap* m, const void* ptr) {
    cuuint64_t gdim[3] = {64, 9, 2048};
    cuuint64_t gstr[2] = {128, DM * 2};
    cuuint32_t box[3] = {64, 9, 16};
    cuuint32_t estr[3] = {1, 1, 1};
    enc(m, CU_TENSOR_MAP_DATA_TYPE_BFLOAT16, 3, const_cast<void*>(ptr), gdim, gstr, box, estr,
        CU_TENSOR_MAP_INTERLEAVE_NONE, CU_TENSOR_MAP_SWIZZLE_128B, CU_TENSOR_MAP_L2_PROMOTION_L2_128B,
        CU_TENSOR_MAP_FLOAT_OOB_FILL_NONE);
}

}

extern "C" void kernel_launch(void* const* d_in, const int* in_sizes, int n_in, void* d_out, int out_size) {
    (void)in_sizes;
    (void)n_in;
    (void)out_size;
    void* fn = nullptr;
    cudaDriverEntryPointQueryResult qr;
    cudaGetDriverEntryPoint("cuTensorMapEncodeTiled", &fn, cudaEnableDefault, &qr);
    EncodeFn enc = (EncodeFn)fn;
    Params maps;
    maps.x = (const __nv_bfloat16*)d_in[0];
    maps.cvec = (const __nv_bfloat16*)d_in[9];
    maps.wmod = (const __nv_bfloat16*)d_in[10];
    maps.kc = (const __nv_bfloat16*)d_in[1];
    maps.vc = (const __nv_bfloat16*)d_in[2];
    maps.wq_p = (const __nv_bfloat16*)d_in[3];
    maps.wo_p = (const __nv_bfloat16*)d_in[4];
    maps.wg_p = (const __nv_bfloat16*)d_in[6];
    maps.wu_p = (const __nv_bfloat16*)d_in[7];
    maps.wd_p = (const __nv_bfloat16*)d_in[8];
    maps.out = (__nv_bfloat16*)d_out;
    void* scp = nullptr;
    cudaGetSymbolAddress(&scp, g_scratch);
    maps.sc = (Scratch*)scp;
    make_map(enc, &maps.k, d_in[1], 32 * 2048, 128);
    make_map(enc, &maps.v, d_in[2], 32 * 2048, 128);
    make_map(enc, &maps.wq, d_in[3], 576, 4096);
    make_map(enc, &maps.wo, d_in[4], 4096, 576);
    make_map(enc, &maps.wg, d_in[6], 576, 4608);
    make_map(enc, &maps.wu, d_in[7], 576, 4608);
    make_map(enc, &maps.wd, d_in[8], 4608, 576);
    make_rows_map(enc, &maps.rx, d_in[0]);
    make_rows_map(enc, &maps.rx2, (char*)scp + offsetof(Scratch, x2));
    make_rows_map(enc, &maps.rout, d_out);
    cudaFuncSetAttribute(fused_block_kernel, cudaFuncAttributeMaxDynamicSharedMemorySize, SMEM_BYTES);
    fused_block_kernel<<<128, 384, SMEM_BYTES>>>(maps);
}
```

```cpp
#include <cuda_runtime.h>
#include <cuda_bf16.h>
#include <cuda.h>
#include <stdint.h>
#include <stddef.h>

namespace {

constexpr int DM = 576;
constexpr int SLOT_BYTES = 16384;
constexpr int BOX_BYTES = 8192;
constexpr int NUNITS = 14;
constexpr int SMEM_TAIL = NUNITS * SLOT_BYTES;
constexpr int SMEM_BYTES = SMEM_TAIL + 2048 + 1024;
constexpr int OFF_FULL = SMEM_TAIL;
constexpr int OFF_EMPTY = SMEM_TAIL + 64;
constexpr int OFF_RED = SMEM_TAIL + 128;

constexpr int KV_AHEAD = 16;
#define GATE_SLOT 4
#define PROBE_NS 300
constexpr int OFF_XBAR = SMEM_TAIL + 1792;
constexpr int OFF_ROWS = 8 * SLOT_BYTES;
constexpr int OFF_MODT = OFF_ROWS + 20480;
constexpr int OFF_EPOCH = SMEM_TAIL + 1808;
constexpr int OFF_MRED = OFF_ROWS + 28672;

struct Scratch {
    unsigned epoch[128 * 32];
    uint32_t mod[6 * DM];
    uint32_t modp[6][2 * DM];
    uint4 h[2][2][128 * 36 * 32];
    uint4 part[128 * 8 * 36 * 32];
    uint4 hh[128 * 8 * 256];
    __nv_bfloat16 x2[2048 * DM];
};
__device__ Scratch g_scratch;

#define TG(i)
#define TL(i)
#define PROFR(i)
#define PROF(i)
#define PROFG(i)

struct Params {
    const __nv_bfloat16 *x, *cvec, *wmod, *kc, *vc, *wq_p, *wo_p, *wg_p, *wu_p, *wd_p;
    __nv_bfloat16* out;
    Scratch* sc;
    CUtensorMap k, v, wq, wo, wg, wu, wd, rx, rx2, rout;
};

__device__ __forceinline__ uint32_t smem_u32(const void* p) { return (uint32_t)__cvta_generic_to_shared(p); }
__device__ __forceinline__ void mbar_init(uint32_t a, uint32_t c) {
    asm volatile("mbarrier.init.shared::cta.b64 [%0], %1;" ::"r"(a), "r"(c) : "memory");
}
__device__ __forceinline__ void mbar_expect_tx(uint32_t a, uint32_t bytes) {
    asm volatile("mbarrier.arrive.expect_tx.shared::cta.b64 _, [%0], %1;" ::"r"(a), "r"(bytes) : "memory");
}
__device__ __forceinline__ bool mbar_try(uint32_t a, uint32_t ph) {
    uint32_t ok;
    asm volatile(
        "{\n.reg .pred p;\nmbarrier.try_wait.parity.shared::cta.b64 p, [%1], %2;\nselp.u32 %0, 1, 0, p;\n}"
        : "=r"(ok)
        : "r"(a), "r"(ph)
        : "memory");
    return ok != 0;
}
__device__ __forceinline__ uint32_t clk32() {
    uint32_t c;
    asm volatile("mov.u32 %0, %%clock;" : "=r"(c));
    return c;
}
constexpr uint32_t WAIT_LIMIT = 1u << 30;
__device__ __forceinline__ void mbar_wait(uint32_t a, uint32_t ph) {
    if (mbar_try(a, ph)) return;
    uint32_t t0 = clk32();
    while (!mbar_try(a, ph)) {
        if (clk32() - t0 > WAIT_LIMIT) break;
    }
}
__device__ __forceinline__ void mbar_arrive_cluster(uint32_t a, uint32_t cta) {
    asm volatile(
        "{\n.reg .b32 ra;\nmapa.shared::cluster.u32 ra, %0, %1;\nmbarrier.arrive.shared::cluster.b64 _, [ra];\n}" ::"r"(a),
        "r"(cta)
        : "memory");
}
__device__ __forceinline__ void tma_mc(uint32_t dst, const CUtensorMap* m, int c0, int c1, uint32_t bar) {
    asm volatile(
        "cp.async.bulk.tensor.2d.shared::cluster.global.mbarrier::complete_tx::bytes.multicast::cluster"
        " [%0], [%1, {%3, %4}], [%2], %5;" ::"r"(dst),
        "l"(m), "r"(bar), "r"(c0), "r"(c1), "h"((uint16_t)3)
        : "memory");
}
__device__ __forceinline__ void bulk_load(uint32_t dst, const void* src, uint32_t bytes, uint32_t bar) {
    asm volatile("cp.async.bulk.shared::cluster.global.mbarrier::complete_tx::bytes [%0], [%1], %2, [%3];" ::"r"(dst),
                 "l"(src), "r"(bytes), "r"(bar)
                 : "memory");
}
__device__ __forceinline__ void l2_prefetch(const void* p, uint32_t bytes) {
    asm volatile("cp.async.bulk.prefetch.L2.global [%0], %1;" ::"l"(p), "r"(bytes) : "memory");
}
__device__ __forceinline__ void bar_sync(int id, int n) { asm volatile("bar.sync %0, %1;" ::"r"(id), "r"(n) : "memory"); }
__device__ __forceinline__ void bar_arrive(int id, int n) {
    asm volatile("bar.arrive %0, %1;" ::"r"(id), "r"(n) : "memory");
}
__device__ __forceinline__ void wg_fence() { asm volatile("wgmma.fence.sync.aligned;" ::: "memory"); }
__device__ __forceinline__ void wg_commit() { asm volatile("wgmma.commit_group.sync.aligned;" ::: "memory"); }
template <int N>
__device__ __forceinline__ void wg_wait() {
    asm volatile("wgmma.wait_group.sync.aligned %0;" ::"n"(N) : "memory");
}
template <int N>
__device__ __forceinline__ void pin(float (&d)[N]) {
#pragma unroll
    for (int i = 0; i < N; i++) asm volatile("" : "+f"(d[i])::"memory");
}
template <int N>
__device__ __forceinline__ void pin(uint32_t (&d)[N]) {
#pragma unroll
    for (int i = 0; i < N; i++) asm volatile("" : "+r"(d[i])::"memory");
}
__device__ __forceinline__ uint32_t pack_bf16(float lo, float hi) {
    uint32_t r;
    asm("cvt.rn.bf16x2.f32 %0, %1, %2;" : "=r"(r) : "f"(hi), "f"(lo));
    return r;
}
__device__ __forceinline__ float bf_lo(uint32_t v) { return __uint_as_float(v << 16); }
__device__ __forceinline__ float bf_hi(uint32_t v) { return __uint_as_float(v & 0xffff0000u); }
__device__ __forceinline__ float round_bf16(float v) { return __bfloat162float(__float2bfloat16_rn(v)); }
__device__ __forceinline__ float ex2(float x) {
    float y;
    asm("ex2.approx.ftz.f32 %0, %1;" : "=f"(y) : "f"(x));
    return y;
}
__device__ __forceinline__ float rcp(float x) {
    float y;
    asm("rcp.approx.ftz.f32 %0, %1;" : "=f"(y) : "f"(x));
    return y;
}
__device__ __forceinline__ float tanh_fast(float x) {
    float y;
    asm("tanh.approx.f32 %0, %1;" : "=f"(y) : "f"(x));
    return y;
}
__device__ __forceinline__ void sts128(uint32_t a, uint32_t x, uint32_t y, uint32_t z, uint32_t w) {
    asm volatile("st.shared.v4.b32 [%0], {%1,%2,%3,%4};" ::"r"(a), "r"(x), "r"(y), "r"(z), "r"(w) : "memory");
}
__device__ __forceinline__ void lds128(uint32_t a, uint32_t& x, uint32_t& y, uint32_t& z, uint32_t& w) {
    asm volatile("ld.shared.v4.b32 {%0,%1,%2,%3}, [%4];" : "=r"(x), "=r"(y), "=r"(z), "=r"(w) : "r"(a) : "memory");
}
__device__ __forceinline__ void sts32f(uint32_t a, float v) {
    asm volatile("st.shared.f32 [%0], %1;" ::"r"(a), "f"(v) : "memory");
}
__device__ __forceinline__ float lds32f(uint32_t a) {
    float v;
    asm volatile("ld.shared.f32 %0, [%1];" : "=f"(v) : "r"(a) : "memory");
    return v;
}
#define F8(d, b) \
    "+f"(d[b]), "+f"(d[b + 1]), "+f"(d[b + 2]), "+f"(d[b + 3]), "+f"(d[b + 4]), "+f"(d[b + 5]), "+f"(d[b + 6]), "+f"(d[b + 7])

template <int TB>
__device__ __forceinline__ void wgmma_n128(float (&d)[64], uint32_t a0, uint32_t a1, uint32_t a2, uint32_t a3,
                                           uint64_t db, int sc) {
    asm volatile(
        "{\n.reg .pred p;\nsetp.ne.b32 p, %69, 0;\n"
        "wgmma.mma_async.sync.aligned.m64n128k16.f32.bf16.bf16 "
        "{%0,%1,%2,%3,%4,%5,%6,%7,%8,%9,%10,%11,%12,%13,%14,%15,%16,%17,%18,%19,%20,%21,%22,%23,%24,%25,%26,%27,%28,%29,%30,%31,"
        "%32,%33,%34,%35,%36,%37,%38,%39,%40,%41,%42,%43,%44,%45,%46,%47,%48,%49,%50,%51,%52,%53,%54,%55,%56,%57,%58,%59,%60,%61,%62,%63},"
        "{%64,%65,%66,%67}, %68, p, 1, 1, %70;\n}"
        : F8(d, 0), F8(d, 8), F8(d, 16), F8(d, 24), F8(d, 32), F8(d, 40), F8(d, 48), F8(d, 56)
        : "r"(a0), "r"(a1), "r"(a2), "r"(a3), "l"(db), "r"(sc), "n"(TB));
}
#define O8(d, b) \
    "=f"(d[b]), "=f"(d[b + 1]), "=f"(d[b + 2]), "=f"(d[b + 3]), "=f"(d[b + 4]), "=f"(d[b + 5]), "=f"(d[b + 6]), "=f"(d[b + 7])
template <int TB>
__device__ __forceinline__ void wgmma_n128_z(float (&d)[64], uint32_t a0, uint32_t a1, uint32_t a2, uint32_t a3,
                                             uint64_t db) {
    asm volatile(
        "wgmma.mma_async.sync.aligned.m64n128k16.f32.bf16.bf16 "
        "{%0,%1,%2,%3,%4,%5,%6,%7,%8,%9,%10,%11,%12,%13,%14,%15,%16,%17,%18,%19,%20,%21,%22,%23,%24,%25,%26,%27,%28,%29,%30,%31,"
        "%32,%33,%34,%35,%36,%37,%38,%39,%40,%41,%42,%43,%44,%45,%46,%47,%48,%49,%50,%51,%52,%53,%54,%55,%56,%57,%58,%59,%60,%61,%62,%63},"
        "{%64,%65,%66,%67}, %68, 0, 1, 1, %69;"
        : O8(d, 0), O8(d, 8), O8(d, 16), O8(d, 24), O8(d, 32), O8(d, 40), O8(d, 48), O8(d, 56)
        : "r"(a0), "r"(a1), "r"(a2), "r"(a3), "l"(db), "n"(TB));
}
template <int TB>
__device__ __forceinline__ void wgmma_n64_z(float (&d)[32], uint32_t a0, uint32_t a1, uint32_t a2, uint32_t a3,
                                            uint64_t db) {
    asm volatile(
        "wgmma.mma_async.sync.aligned.m64n64k16.f32.bf16.bf16 "
        "{%0,%1,%2,%3,%4,%5,%6,%7,%8,%9,%10,%11,%12,%13,%14,%15,%16,%17,%18,%19,%20,%21,%22,%23,%24,%25,%26,%27,%28,%29,%30,%31},"
        "{%32,%33,%34,%35}, %36, 0, 1, 1, %37;"
        : O8(d, 0), O8(d, 8), O8(d, 16), O8(d, 24)
        : "r"(a0), "r"(a1), "r"(a2), "r"(a3), "l"(db), "n"(TB));
}
template <int TB>
__device__ __forceinline__ void wgmma_n64(float (&d)[32], uint32_t a0, uint32_t a1, uint32_t a2, uint32_t a3,
                                          uint64_t db) {
    asm volatile(
        "wgmma.mma_async.sync.aligned.m64n64k16.f32.bf16.bf16 "
        "{%0,%1,%2,%3,%4,%5,%6,%7,%8,%9,%10,%11,%12,%13,%14,%15,%16,%17,%18,%19,%20,%21,%22,%23,%24,%25,%26,%27,%28,%29,%30,%31},"
        "{%32,%33,%34,%35}, %36, 1, 1, 1, %37;"
        : F8(d, 0), F8(d, 8), F8(d, 16), F8(d, 24)
        : "r"(a0), "r"(a1), "r"(a2), "r"(a3), "l"(db), "n"(TB));
}

__device__ __forceinline__ uint64_t desc_of(uint32_t saddr) {
    return (uint64_t)(((saddr >> 4) & 0x3FFFu) | (512u << 16)) | ((uint64_t)(64u | (1u << 30)) << 32);
}

struct Ring {
    uint32_t slot;
    uint32_t phase;
    __device__ __forceinline__ void next() {
        if (++slot == 8) {
            slot = 0;
            phase ^= 1;
        }
    }
};

struct Ctx {
    uint32_t sbase;
    int wg;
    uint32_t rel_cta;
    __device__ __forceinline__ void wait_full(uint32_t slot, uint32_t phase) const {
        mbar_wait(sbase + OFF_FULL + slot * 8, phase);
    }
    __device__ __forceinline__ void release(uint32_t slot) const {
        if (rel_cta < 2) mbar_arrive_cluster(sbase + OFF_EMPTY + slot * 8, rel_cta);
    }
};

__device__ __forceinline__ void gemm_n128(float (&d)[64], const uint32_t (&a)[144], const Ctx& c, Ring& r, bool nine,
                                          bool early) {
    uint32_t prev = 0;
#pragma unroll
    for (int s = 0; s < 9; s++) {
        if (s < 8 || nine) {
            if (s == GATE_SLOT) {
                if (early) {
                    wg_wait<0>();
                    c.release(prev);
                }
                bar_sync(8 + c.wg, 256);
            }
            c.wait_full(r.slot, r.phase);
            uint64_t db = desc_of(c.sbase + r.slot * SLOT_BYTES);
            wg_fence();
#pragma unroll
            for (int k = 0; k < 4; k++) {
                if ((s | k) == 0)
                    wgmma_n128_z<1>(d, a[0], a[1], a[2], a[3], db);
                else
                    wgmma_n128<1>(d, a[s * 16 + k * 4], a[s * 16 + k * 4 + 1], a[s * 16 + k * 4 + 2],
                                  a[s * 16 + k * 4 + 3], db + k * 128, 1);
            }
            wg_commit();
            if (s == 8 || (s == 7 && !nine)) bar_arrive(9 - c.wg, 256);
            if (s > 0) {
                wg_wait<1>();
                if (s != GATE_SLOT || !early) c.release(prev);
            }
            prev = r.slot;
            r.next();
        }
    }
    wg_wait<0>();
    c.release(prev);
    pin(d);
}
__device__ __forceinline__ void gemm_n64(float (&d)[32], const uint32_t (&a)[144], const Ctx& c, Ring& r, bool nine) {
    uint32_t prev = 0;
#pragma unroll
    for (int s = 0; s < 5; s++) {
        if (s < 4 || nine) {
            c.wait_full(r.slot, r.phase);
            uint64_t db = desc_of(c.sbase + r.slot * SLOT_BYTES);
            wg_fence();
#pragma unroll
            for (int k = 0; k < 8; k++) {
                if ((s | k) == 0)
                    wgmma_n64_z<1>(d, a[0], a[1], a[2], a[3], db);
                else if (s * 8 + k < 36)
                    wgmma_n64<1>(d, a[s * 32 + k * 4], a[s * 32 + k * 4 + 1], a[s * 32 + k * 4 + 2],
                                 a[s * 32 + k * 4 + 3], db + k * 128);
            }
            wg_commit();
            if (s > 0) {
                wg_wait<1>();
                c.release(prev);
            }
            prev = r.slot;
            r.next();
        }
    }
    wg_wait<0>();
    c.release(prev);
    pin(d);
}
__device__ __forceinline__ void st128(uint4* p, uint32_t x, uint32_t y, uint32_t z, uint32_t w) {
    asm volatile(
        "{\n.reg .b64 lo, hi;\n.reg .b128 t;\nmov.b64 lo, {%1, %2};\nmov.b64 hi, {%3, %4};\nmov.b128 t, {lo, hi};\n"
        "st.relaxed.gpu.global.b128 [%0], t;\n}" ::"l"(p),
        "r"(x), "r"(y), "r"(z), "r"(w)
        : "memory");
}
__device__ __forceinline__ uint4 ld128(const uint4* p) {
    uint4 r;
    asm volatile(
        "{\n.reg .b64 lo, hi;\n.reg .b128 t;\nld.relaxed.gpu.global.b128 t, [%4];\nmov.b128 {lo, hi}, t;\n"
        "mov.b64 {%0, %1}, lo;\nmov.b64 {%2, %3}, hi;\n}"
        : "=r"(r.x), "=r"(r.y), "=r"(r.z), "=r"(r.w)
        : "l"(p));
    return r;
}
__device__ __forceinline__ uint4 ldg128(const uint4* p) {
    uint4 r;
    asm volatile("ld.global.nc.v4.u32 {%0,%1,%2,%3}, [%4];" : "=r"(r.x), "=r"(r.y), "=r"(r.z), "=r"(r.w) : "l"(p));
    return r;
}
__device__ __forceinline__ void st64(void* p, uint32_t x, uint32_t y) {
    asm volatile("{\n.reg .b64 t;\nmov.b64 t, {%1, %2};\nst.relaxed.gpu.global.b64 [%0], t;\n}" ::"l"(p), "r"(x), "r"(y)
                 : "memory");
}
__device__ __forceinline__ uint2 ld64(const void* p) {
    uint2 r;
    asm volatile("{\n.reg .b64 t;\nld.relaxed.gpu.global.b64 t, [%2];\nmov.b64 {%0, %1}, t;\n}"
                 : "=r"(r.x), "=r"(r.y)
                 : "l"(p));
    return r;
}
__device__ __forceinline__ void rows_load(uint32_t sbase, const CUtensorMap* m, int row0) {
    mbar_expect_tx(sbase + OFF_XBAR, 16 * DM * 2);
    asm volatile(
        "cp.async.bulk.tensor.3d.shared::cluster.global.mbarrier::complete_tx::bytes [%0], [%1, {%3, %3, %4}], [%2];" ::"r"(
            sbase + OFF_ROWS),
        "l"(m), "r"(sbase + OFF_XBAR), "r"(0), "r"(row0)
        : "memory");
}
__device__ __forceinline__ void rows_store(uint32_t sbase, const CUtensorMap* m, int row0) {
    asm volatile("cp.async.bulk.tensor.3d.global.shared::cta.bulk_group [%0, {%2, %2, %3}], [%1];" ::"l"(m),
                 "r"(sbase + OFF_ROWS), "r"(0), "r"(row0)
                 : "memory");
    asm volatile("cp.async.bulk.commit_group;" ::: "memory");
}
__device__ __forceinline__ void rows_store_wait() { asm volatile("cp.async.bulk.wait_group 0;" ::: "memory"); }

__device__ __forceinline__ constexpr int own_col(int j) { return j < 8 ? (j >> 1) * 128 + (j & 1) * 8 : 512; }
__device__ __forceinline__ void row_reduce(float& s0, float& s1, uint32_t red, int warp, int lane) {
    s0 += __shfl_xor_sync(0xffffffffu, s0, 1);
    s1 += __shfl_xor_sync(0xffffffffu, s1, 1);
    s0 += __shfl_xor_sync(0xffffffffu, s0, 2);
    s1 += __shfl_xor_sync(0xffffffffu, s1, 2);
    if ((lane & 3) == 0) {
        sts32f(red + (warp * 16 + (lane >> 2)) * 4, s0);
        sts32f(red + (warp * 16 + 8 + (lane >> 2)) * 4, s1);
    }
    bar_sync(3, 256);
    s0 = 0.f;
    s1 = 0.f;
#pragma unroll
    for (int w = 0; w < 8; w++) {
        s0 += lds32f(red + (w * 16 + (lane >> 2)) * 4);
        s1 += lds32f(red + (w * 16 + 8 + (lane >> 2)) * 4);
    }
}
template <class F>
__device__ __forceinline__ void layernorm_rows(float (&v)[36], uint32_t red, int warp, int lane, F&& middle) {
    float s0 = 0.f, s1 = 0.f;
#pragma unroll
    for (int j = 0; j < 9; j++) {
        s0 += v[4 * j] + v[4 * j + 1];
        s1 += v[4 * j + 2] + v[4 * j + 3];
    }
    row_reduce(s0, s1, red, warp, lane);
    middle();
    const float m0 = s0 * (1.f / DM), m1 = s1 * (1.f / DM);
    s0 = 0.f;
    s1 = 0.f;
#pragma unroll
    for (int j = 0; j < 9; j++) {
        v[4 * j] -= m0;
        v[4 * j + 1] -= m0;
        v[4 * j + 2] -= m1;
        v[4 * j + 3] -= m1;
        s0 += v[4 * j] * v[4 * j] + v[4 * j + 1] * v[4 * j + 1];
        s1 += v[4 * j + 2] * v[4 * j + 2] + v[4 * j + 3] * v[4 * j + 3];
    }
    row_reduce(s0, s1, red + 512, warp, lane);
    const float r0 = rsqrtf(s0 * (1.f / DM) + 1e-5f), r1 = rsqrtf(s1 * (1.f / DM) + 1e-5f);
#pragma unroll
    for (int j = 0; j < 9; j++) {
        v[4 * j] *= r0;
        v[4 * j + 1] *= r0;
        v[4 * j + 2] *= r1;
        v[4 * j + 3] *= r1;
    }
}
__device__ __forceinline__ void mod_to_smem(uint32_t dst, const uint32_t* src, uint32_t tag) {
    const uint32_t t0 = clk32();
    uint4 u;
    while (true) {
        u = ld128(reinterpret_cast<const uint4*>(src));
        const uint32_t bad = ((u.x ^ tag) | (u.y ^ tag) | (u.z ^ tag) | (u.w ^ tag)) & 0xffffu;
        if (__all_sync(0xffffffffu, bad == 0) || clk32() - t0 > WAIT_LIMIT) break;
        __nanosleep(64);
    }
    sts128(dst, u.x & 0xffff0000u, u.y & 0xffff0000u, u.z & 0xffff0000u, u.w & 0xffff0000u);
}
__device__ __forceinline__ void lds_mod(float (&m)[18], uint32_t src  , int warp) {
#pragma unroll
    for (int j = 0; j < 9; j++)
        asm volatile("ld.shared.v2.f32 {%0,%1}, [%2];"
                     : "=f"(m[2 * j]), "=f"(m[2 * j + 1])
                     : "r"(src + own_col(j) * 4 - (j == 8 ? warp * 32 : 0))
                     : "memory");
}
__device__ __forceinline__ void modulate_store(const float (&v)[36], const float (&shift)[18], const float (&scale)[18],
                                               float post, uint4* hbuf  , int warp, int lane) {
    uint32_t o[18];
#pragma unroll
    for (int j = 0; j < 9; j++) {
        const uint32_t cc = pack_bf16(1.f + scale[2 * j], 1.f + scale[2 * j + 1]);
        const float c0 = bf_lo(cc) * post, c1 = bf_hi(cc) * post, s0 = shift[2 * j] * post, s1 = shift[2 * j + 1] * post;
        o[2 * j] = max(pack_bf16(fmaf(v[4 * j], c0, s0), fmaf(v[4 * j + 1], c1, s1)), 1u);
        o[2 * j + 1] = max(pack_bf16(fmaf(v[4 * j + 2], c0, s0), fmaf(v[4 * j + 3], c1, s1)), 1u);
    }
#pragma unroll
    for (int i = 0; i < 4; i++) st128(hbuf + (i * 8 + warp) * 32 + lane, o[4 * i], o[4 * i + 1], o[4 * i + 2], o[4 * i + 3]);
    st64(reinterpret_cast<uint2*>(hbuf + 32 * 32) + warp * 32 + lane, o[16], o[17]);
}
__device__ __forceinline__ void sum_partials(float (&v)[36], const uint4* src  , uint32_t tag) {
    const uint32_t t0 = clk32();
    while (true) {
        uint4 t[8][4];
#pragma unroll
        for (int s = 0; s < 8; s++)
#pragma unroll
            for (int i = 0; i < 4; i++) t[s][i] = ld128(src + (s * 36 + i * 8) * 32);
        uint32_t bad = 0;
#pragma unroll
        for (int i = 0; i < 32; i++) v[i] = 0.f;
#pragma unroll
        for (int s = 0; s < 8; s++)
#pragma unroll
            for (int i = 0; i < 4; i++) {
                bad |= t[s][i].x ^ tag;
                v[8 * i] += bf_lo(t[s][i].x);
                v[8 * i + 1] += bf_hi(t[s][i].x);
                v[8 * i + 2] += bf_lo(t[s][i].y);
                v[8 * i + 3] += bf_hi(t[s][i].y);
                v[8 * i + 4] += bf_lo(t[s][i].z);
                v[8 * i + 5] += bf_hi(t[s][i].z);
                v[8 * i + 6] += bf_lo(t[s][i].w);
                v[8 * i + 7] += bf_hi(t[s][i].w);
            }
        if (__all_sync(0xffffffffu, (bad & 1u) == 0) || clk32() - t0 > WAIT_LIMIT) break;
    }
}
__device__ __forceinline__ void sum_tail(float (&v)[36], const uint2* src  , uint32_t tag) {
    const uint32_t t0 = clk32();
    while (true) {
        uint2 t[8];
#pragma unroll
        for (int s = 0; s < 8; s++) t[s] = ld64(src + s * 72 * 32);
        uint32_t bad = 0;
        v[32] = v[33] = v[34] = v[35] = 0.f;
#pragma unroll
        for (int s = 0; s < 8; s++) {
            bad |= t[s].x ^ tag;
            v[32] += bf_lo(t[s].x);
            v[33] += bf_hi(t[s].x);
            v[34] += bf_lo(t[s].y);
            v[35] += bf_hi(t[s].y);
        }
        if (__all_sync(0xffffffffu, (bad & 1u) == 0) || clk32() - t0 > WAIT_LIMIT) break;
    }
}
__device__ __forceinline__ void poll_tail(uint32_t (&a)[144], const uint2* src  ) {
    const uint32_t t0 = clk32();
    while (true) {
        uint32_t m = 0xffffffffu;
#pragma unroll
        for (int j = 0; j < 8; j++) {
            const uint2 t = ld64(src + j * 32);
            a[128 + 2 * j] = t.x;
            a[129 + 2 * j] = t.y;
        }
#pragma unroll
        for (int j = 0; j < 16; j++) m = min(m, a[128 + j]);
        if (__all_sync(0xffffffffu, m != 0) || clk32() - t0 > WAIT_LIMIT) break;
    }
}
template <int K0, int K1>
__device__ __forceinline__ void poll_frags(uint32_t (&a)[144], const uint4* src  , bool kick) {
    const uint32_t t0 = clk32();
    while (true) {
#pragma unroll
        for (int k = K0; k < K1; k++)
            asm volatile("ld.relaxed.gpu.global.v4.u32 {%0,%1,%2,%3}, [%4];"
                         : "=r"(a[4 * k]), "=r"(a[4 * k + 1]), "=r"(a[4 * k + 2]), "=r"(a[4 * k + 3])
                         : "l"(src + k * 32));
        if (kick) bar_arrive(5, 256);
        kick = false;
        uint32_t m0 = a[4 * K0], m1 = a[4 * K0 + 1];
#pragma unroll
        for (int i = 4 * K0 + 2; i < 4 * K1; i += 2) {
            m0 = min(m0, a[i]);
            m1 = min(m1, a[i + 1]);
        }
        if (__all_sync(0xffffffffu, min(m0, m1) != 0) || clk32() - t0 > WAIT_LIMIT) break;
    }
}

constexpr float SM_SCALE = 0.08838834764831845f * 1.4426950408889634f;
constexpr float SM_HI = 1.2089258e24f;
constexpr float SM_LO = 9.0949470e-13f;
__device__ __forceinline__ void qk_step(float (&s)[32], const uint32_t (&q)[32], uint64_t dk) {
#pragma unroll
    for (int k = 0; k < 8; k++) {
        if (k == 0)
            wgmma_n64_z<0>(s, q[0], q[1], q[2], q[3], dk);
        else
            wgmma_n64<0>(s, q[4 * k], q[4 * k + 1], q[4 * k + 2], q[4 * k + 3], dk + (k >> 2) * 512 + (k & 3) * 2);
    }
}
__device__ __forceinline__ void pv_step(float (&o)[64], const uint32_t (&p)[16], uint64_t dv, int acc) {
#pragma unroll
    for (int k = 0; k < 4; k++)
        wgmma_n128<1>(o, p[4 * k], p[4 * k + 1], p[4 * k + 2], p[4 * k + 3], dv + k * 128, k != 0 ? 1 : acc);
}
template <bool SHIFT>
__device__ __forceinline__ void exp_step(const float (&s)[32], uint32_t (&p)[16], float n0, float n1, float& s0,
                                         float& s1) {
#pragma unroll
    for (int i = 0; i < 8; i++) {
        const float e0 = ex2(SHIFT ? s[4 * i] + n0 : s[4 * i]), e1 = ex2(SHIFT ? s[4 * i + 1] + n0 : s[4 * i + 1]);
        const float e2 = ex2(SHIFT ? s[4 * i + 2] + n1 : s[4 * i + 2]), e3 = ex2(SHIFT ? s[4 * i + 3] + n1 : s[4 * i + 3]);
        if (i == 0) {
            s0 = e0 + e1;
            s1 = e2 + e3;
        } else {
            s0 += e0 + e1;
            s1 += e2 + e3;
        }
        p[2 * i] = pack_bf16(e0, e1);
        p[2 * i + 1] = pack_bf16(e2, e3);
    }
}
__device__ __forceinline__ void row_max(const float (&sa)[32], const float (&sb)[32], float& x0, float& x1) {
    float xa[8];
#pragma unroll
    for (int i = 0; i < 8; i++) xa[i] = fmaxf(sa[i], sb[i]);
#pragma unroll
    for (int k = 1; k < 4; k++)
#pragma unroll
        for (int i = 0; i < 8; i++) xa[i] = fmaxf(xa[i], fmaxf(sa[8 * k + i], sb[8 * k + i]));
    x0 = fmaxf(fmaxf(xa[0], xa[1]), fmaxf(xa[4], xa[5]));
    x1 = fmaxf(fmaxf(xa[2], xa[3]), fmaxf(xa[6], xa[7]));
    x0 = fmaxf(x0, __shfl_xor_sync(0xffffffffu, x0, 1));
    x1 = fmaxf(x1, __shfl_xor_sync(0xffffffffu, x1, 1));
    x0 = fmaxf(x0, __shfl_xor_sync(0xffffffffu, x0, 2));
    x1 = fmaxf(x1, __shfl_xor_sync(0xffffffffu, x1, 2));
}
__device__ __forceinline__ void inv_row_sums(float l0, float l1, float& i0, float& i1) {
    l0 += __shfl_xor_sync(0xffffffffu, l0, 1);
    l1 += __shfl_xor_sync(0xffffffffu, l1, 1);
    l0 += __shfl_xor_sync(0xffffffffu, l0, 2);
    l1 += __shfl_xor_sync(0xffffffffu, l1, 2);
    i0 = rcp(l0);
    i1 = rcp(l1);
}

__device__ __forceinline__ uint32_t get_epoch(uint32_t sbase) { return __float_as_uint(lds32f(sbase + OFF_EPOCH)); }
__device__ __forceinline__ float silu_bf16(unsigned short c) {
    const float cv = bf_lo(c);
    return round_bf16(cv * rcp(1.f + ex2(-1.4426950408889634f * cv)));
}
__device__ __forceinline__ void st_mod(uint32_t* p, float v, uint32_t tag) {
    asm volatile("st.relaxed.gpu.global.u32 [%0], %1;" ::"l"(p), "r"(__float_as_uint(round_bf16(v)) | tag)
                 : "memory");
}
__device__ __forceinline__ void fma8(float (&acc)[8], float sc, const uint4& w) {
    acc[0] = fmaf(sc, bf_lo(w.x), acc[0]);
    acc[1] = fmaf(sc, bf_hi(w.x), acc[1]);
    acc[2] = fmaf(sc, bf_lo(w.y), acc[2]);
    acc[3] = fmaf(sc, bf_hi(w.y), acc[3]);
    acc[4] = fmaf(sc, bf_lo(w.z), acc[4]);
    acc[5] = fmaf(sc, bf_hi(w.z), acc[5]);
    acc[6] = fmaf(sc, bf_lo(w.w), acc[6]);
    acc[7] = fmaf(sc, bf_hi(w.w), acc[7]);
}
__device__ __forceinline__ void modp_load(uint4 (&u)[6], const uint32_t* src) {
#pragma unroll
    for (int i = 0; i < 6; i++) u[i] = ld128(reinterpret_cast<const uint4*>(src + i * 2 * DM));
}
__device__ __forceinline__ void modp_to_smem(uint4 (&u)[6], uint32_t dst, const uint32_t* src, uint32_t tag) {
    const uint32_t t0 = clk32();
    while (true) {
        uint32_t bad = 0;
#pragma unroll
        for (int i = 0; i < 6; i++) bad |= (u[i].x ^ tag) | (u[i].y ^ tag) | (u[i].z ^ tag) | (u[i].w ^ tag);
        if (__all_sync(0xffffffffu, (bad & 0xffu) == 0) || clk32() - t0 > WAIT_LIMIT) break;
        modp_load(u, src);
    }
    float s0 = 0.f, s1 = 0.f, s2 = 0.f, s3 = 0.f;
#pragma unroll
    for (int i = 0; i < 6; i++) {
        s0 += __uint_as_float(u[i].x & ~0xffu);
        s1 += __uint_as_float(u[i].y & ~0xffu);
        s2 += __uint_as_float(u[i].z & ~0xffu);
        s3 += __uint_as_float(u[i].w & ~0xffu);
    }
    const uint32_t p0 = pack_bf16(s0, s1), p1 = pack_bf16(s2, s3);
    sts128(dst, p0 << 16, p0 & 0xffff0000u, p1 << 16, p1 & 0xffff0000u);
}

__global__ void __cluster_dims__(2, 1, 1) __launch_bounds__(384, 1)
    fused_block_kernel(const __grid_constant__ Params maps) {
    extern __shared__ uint8_t smem_raw[];
    uint32_t sbase = (smem_u32(smem_raw) + 1023u) & ~1023u;
    asm volatile("" : "+r"(sbase));
    const int b = blockIdx.x;
    const int rank = b & 1;
    const int mt = ((b >> 1) & 7) * 2 + rank;
    const int g = b >> 4;
    const int warp = __shfl_sync(0xffffffffu, threadIdx.x >> 5, 0);
    const int lane = threadIdx.x & 31;
    Scratch* const sc_ = maps.sc;
    const __nv_bfloat16* const wmod = maps.wmod;
    const __nv_bfloat16* const cvec = maps.cvec;

#define SPROF(i)

    if (warp >= 8) {
        asm volatile("setmaxnreg.dec.sync.aligned.u32 24;");
        if (warp == 8 && lane == 0) {
#pragma unroll
            for (int i = 0; i < 8; i++) {
                mbar_init(sbase + OFF_FULL + i * 8, 1);
                mbar_init(sbase + OFF_EMPTY + i * 8, 4);
            }
            mbar_init(sbase + OFF_XBAR, 1);
            asm volatile("fence.mbarrier_init.release.cluster;" ::: "memory");
            asm volatile("barrier.cluster.arrive.relaxed;\nbarrier.cluster.wait;" ::: "memory");
            uint32_t slot = 0, phase = 1;
            const uint32_t dst0 = sbase + rank * BOX_BYTES;
            auto acquire = [&](uint32_t bytes) {
                mbar_wait(sbase + OFF_EMPTY + slot * 8, phase);
                mbar_expect_tx(sbase + OFF_FULL + slot * 8, bytes);
            };
            auto adv8 = [&]() {
                if (++slot == 8) {
                    slot = 0;
                    phase ^= 1;
                }
            };
#pragma unroll 1
            for (int hq = 0; hq < 4; hq++) {
                const int col = (g * 4 + ((hq + 1) & 3)) * 128 + rank * 64;
                if (hq == 2) {
                    l2_prefetch(maps.kc + (size_t)(g * 4 * 2048 + (b & 15) * 64) * 128, SLOT_BYTES);
                    l2_prefetch(maps.vc + (size_t)(g * 4 * 2048 + (b & 15) * 64) * 128, SLOT_BYTES);
                }
#pragma unroll 1
                for (int kc = 0; kc < 9; kc++) {
                    acquire(SLOT_BYTES);
                    tma_mc(dst0 + slot * SLOT_BYTES, &maps.wq, col, kc * 64, sbase + OFF_FULL + slot * 8);
                    adv8();
                }
            }
            const int row0 = g * 4 * 2048;
#pragma unroll 1
            for (int n = 0; n < 128; n++) {
                if (n < 4) mbar_wait(sbase + OFF_EMPTY + (slot + 1) * 8, phase);
                acquire(2 * SLOT_BYTES);
                const uint32_t bar = sbase + OFF_FULL + slot * 8;
                const int r0 = n == 0 ? 0 : (n == 127 ? 126 : n + 1);
                const int r1 = n == 0 ? 1 : (n == 127 ? 127 : n - 1);
                tma_mc(dst0 + slot * SLOT_BYTES, n == 127 ? &maps.v : &maps.k, rank * 64, row0 + r0 * 64, bar);
                tma_mc(dst0 + (slot + 1) * SLOT_BYTES, n == 0 ? &maps.k : &maps.v, rank * 64, row0 + r1 * 64, bar);
                adv8();
                adv8();
                const int u = n + KV_AHEAD;
                if (u < 128 && (u & 15) == (b & 15)) {
                    l2_prefetch(maps.kc + (size_t)(row0 + u * 64) * 128, SLOT_BYTES);
                    l2_prefetch(maps.vc + (size_t)(row0 + u * 64) * 128, SLOT_BYTES);
                }
            }
#pragma unroll 1
            for (int p = 0; p < 4; p++)
#pragma unroll 1
                for (int kc = 0; kc < 8; kc++) {
                    acquire(SLOT_BYTES);
                    tma_mc(dst0 + slot * SLOT_BYTES, &maps.wo, p * 128 + rank * 64, g * 512 + ((kc + 6) & 7) * 64,
                           sbase + OFF_FULL + slot * 8);
                    adv8();
                }
#pragma unroll 1
            for (int kc = 0; kc < 4; kc++) {
                acquire(SLOT_BYTES);
                tma_mc(dst0 + slot * SLOT_BYTES, &maps.wo, 512, g * 512 + ((kc + 3) & 3) * 128 + rank * 64,
                       sbase + OFF_FULL + slot * 8);
                adv8();
            }
            const CUtensorMap* mg = rank ? &maps.wu : &maps.wg;
#pragma unroll 1
            for (int ch = 0; ch < 9; ch++)
#pragma unroll 1
                for (int kc = 0; kc < 9; kc++) {
                    acquire(SLOT_BYTES);
                    tma_mc(dst0 + slot * SLOT_BYTES, mg, g * 576 + ch * 64, kc * 64, sbase + OFF_FULL + slot * 8);
                    adv8();
                }
#pragma unroll 1
            for (int p = 0; p < 4; p++)
#pragma unroll 1
                for (int i = 0; i < 9; i++) {
                    acquire(SLOT_BYTES);
                    tma_mc(dst0 + slot * SLOT_BYTES, &maps.wd, p * 128 + rank * 64,
                           g * 576 + (i == 0 ? 8 : (i < 7 ? i + 1 : i - 7)) * 64, sbase + OFF_FULL + slot * 8);
                    adv8();
                }
#pragma unroll 1
            for (int i2 = 0; i2 < 5; i2++) {
                acquire(i2 < 4 ? SLOT_BYTES : BOX_BYTES);
                const int i = 2 * i2 + rank;
                if (i < 9)
                    tma_mc(dst0 + slot * SLOT_BYTES, &maps.wd, 512, g * 576 + (i == 0 ? 8 : (i < 7 ? i + 1 : i - 7)) * 64,
                           sbase + OFF_FULL + slot * 8);
                adv8();
            }
        } else if (warp == 11) {
            asm volatile("barrier.cluster.arrive.relaxed.aligned;" ::: "memory");
            bar_sync(6, 160);
            uint4* hz = sc_->h[(get_epoch(sbase) & 1) ^ 1][0] + (size_t)b * 72 * 32 + lane;
#pragma unroll 1
            for (int i = 0; i < 72; i++) {
                hz[i * 32] = make_uint4(0, 0, 0, 0);
                __nanosleep(200);
            }
            bar_sync(6, 160);
            if (lane == 0) {
#pragma unroll 1
                for (int i = 0; i < 9; i++) {
                    l2_prefetch((const char*)maps.wo_p + (size_t)b * 36864 + i * 4096, 4096);
                    __nanosleep(400);
                    l2_prefetch((const char*)maps.wg_p + (size_t)b * 41472 + i * 4608, 4608);
                    __nanosleep(400);
                    l2_prefetch((const char*)maps.wu_p + (size_t)b * 41472 + i * 4608, 4608);
                    __nanosleep(400);
                    l2_prefetch((const char*)maps.wd_p + (size_t)b * 41472 + i * 4608, 4608);
                    __nanosleep(400);
                }
            }
        } else if (warp == 9 || warp == 10) {
            asm volatile("barrier.cluster.arrive.relaxed.aligned;" ::: "memory");
            if (warp == 10) {
                bar_sync(11, 288);
                if (lane < 9) l2_prefetch((const char*)maps.wq_p + (size_t)b * 36864 + lane * 4096, 4096);
                __syncwarp();
            }
            bar_sync(4, 320);
            const uint32_t tag = (get_epoch(sbase) + 1) & 0xffffu;
            const int blk = warp == 9 ? 72 + b : 200 + b;
            if (blk < 216) {
                float acc[8];
#pragma unroll
                for (int e = 0; e < 8; e++) acc[e] = 0.f;
                const uint4* wp = reinterpret_cast<const uint4*>(wmod + (size_t)(lane >> 1) * (6 * DM) + blk * 16) + (lane & 1);
                const unsigned short* cp = reinterpret_cast<const unsigned short*>(cvec) + (lane >> 1);
#pragma unroll 1
                for (int i = 0; i < 36; i++) {
                    const uint4 w = __ldg(wp + (size_t)i * (16 * 6 * DM / 8));
                    const float sc = silu_bf16(__ldg(cp + i * 16));
                    fma8(acc, sc, w);
                }
#pragma unroll
                for (int o = 2; o < 32; o <<= 1)
#pragma unroll
                    for (int e = 0; e < 8; e++) acc[e] += __shfl_xor_sync(0xffffffffu, acc[e], o);
                if (lane < 2) {
#pragma unroll
                    for (int e = 0; e < 8; e++) st_mod(sc_->mod + blk * 16 + lane * 8 + e, acc[e], tag);
                }
            }
            if (warp == 9) {
#pragma unroll 1
                for (int st = 1; st <= 2; st++) {
                    bar_sync(7, 160);
                    const uint32_t* src = sc_->mod + (st * 3 - 1) * DM;
                    const int n = st == 1 ? 3 * DM : DM;
#pragma unroll 1
                    for (int i = lane * 4; i < n + 127 - ((n + 127) & 127); i += 128)
                        mod_to_smem(sbase + OFF_MODT + min(i, n - 4) * 4, src + min(i, n - 4), tag);
                    __syncwarp();
                    if (lane == 0) rows_load(sbase, st == 1 ? &maps.rx : &maps.rx2, (mt * 8 + g) * 16);
                    if (st == 1) {
                        bar_sync(7, 160);
                        if (lane == 0) {
                            rows_store(sbase, &maps.rx2, (mt * 8 + g) * 16);
                            rows_store_wait();
                        }
                        __syncwarp();
                        bar_arrive(10, 160);
                    }
                }
            }
        }
    } else {
        uint4 w1[3], xw[5], ew = make_uint4(0, 0, 0, 0);
        unsigned short cu[3];
        {
            const int t = threadIdx.x, bw = min(b, 107);
            const int row = (bw / 18) * 96 + (t >> 3);
#pragma unroll
            for (int i = 0; i < 3; i++) {
                w1[i] = ldg128(reinterpret_cast<const uint4*>(wmod + (size_t)(row + 32 * i) * (6 * DM)) + (bw % 18) * 8 + (t & 7));
                asm volatile("ld.global.nc.u16 %0, [%1];" : "=h"(cu[i]) : "l"(cvec + row + 32 * i));
            }
            if (t == 0) ew = ld128(reinterpret_cast<const uint4*>(&sc_->epoch[b * 32]));
#pragma unroll
            for (int i = 0; i < 5; i++)
                xw[i] = ldg128(reinterpret_cast<const uint4*>(maps.x + (size_t)(mt * 8 + g) * 16 * DM) + min(t + 256 * i, 1151));
        }
        if (threadIdx.x == 160) SPROF(5);
        asm volatile("setmaxnreg.inc.sync.aligned.u32 240;");
        if (threadIdx.x == 160) SPROF(6);
        const int wg = warp >> 2;
        const int tid = threadIdx.x;
        Ctx cx;
        cx.sbase = sbase;
        cx.wg = wg;
        if (wg == 1) bar_arrive(8, 256);
        cx.rel_cta = (lane == 0 && (warp & 3) < 2) ? (warp & 3) : 2;
        const uint32_t red = sbase + OFF_RED;
        const int own = mt * 8 + g;
        const int wown = mt * 8 + warp;
        PROF(0);
        PROFG(30);
        PROFR(17);
        {
            asm volatile("barrier.cluster.arrive.relaxed.aligned;" ::: "memory");
            float acc[8];
#pragma unroll
            for (int e = 0; e < 8; e++) acc[e] = 0.f;
#pragma unroll
            for (int i = 0; i < 3; i++) fma8(acc, silu_bf16(cu[i]), w1[i]);
#pragma unroll
            for (int o = 8; o < 32; o <<= 1)
#pragma unroll
                for (int e = 0; e < 8; e++) acc[e] += __shfl_xor_sync(0xffffffffu, acc[e], o);
            PROFR(19);
            if (lane < 8) {
                const uint32_t dst = sbase + OFF_MRED + warp * 256 + lane * 32;
                sts128(dst, __float_as_uint(acc[0]), __float_as_uint(acc[1]), __float_as_uint(acc[2]), __float_as_uint(acc[3]));
                sts128(dst + 16, __float_as_uint(acc[4]), __float_as_uint(acc[5]), __float_as_uint(acc[6]), __float_as_uint(acc[7]));
            }
            if (tid == 0) sts128(sbase + OFF_EPOCH, ew.x, ew.y, ew.z, ew.w);
            bar_sync(3, 256);
            PROFR(20);
            if (tid < 64 && b < 108) {
                float sum = 0.f;
#pragma unroll
                for (int w8 = 0; w8 < 8; w8++) sum += lds32f(sbase + OFF_MRED + w8 * 256 + tid * 4);
                asm volatile("st.relaxed.gpu.global.u32 [%0], %1;" ::"l"(&sc_->modp[b / 18][(b % 18) * 64 + tid]),
                             "r"((__float_as_uint(sum) & ~0xffu) | ((get_epoch(sbase) + 1) & 0xffu))
                             : "memory");
            }
            PROFR(21);
#pragma unroll
            for (int i = 0; i < 5; i++) {
                const int vi = min(tid + 256 * i, 1151), ln = vi >> 3;
                sts128(sbase + OFF_ROWS + ln * 128 + (((vi & 7) ^ (ln & 7)) << 4), xw[i].x, xw[i].y, xw[i].z, xw[i].w);
            }
            bar_sync(3, 256);
            bar_arrive(11, 288);
        }

        Ring ring{0u, 0u};
        int stage = 0;
        asm volatile("" : "+r"(stage));
#pragma unroll 1
        for (;; stage++) {
            int tid, lane;
            asm volatile("mov.u32 %0, %%tid.x;" : "=r"(tid));
            lane = tid & 31;
            const uint32_t epoch = get_epoch(sbase);
            {
                float v[36];
                const uint32_t modt = sbase + OFF_MODT + (warp * 16 + (lane & 3) * 2) * 4;
                if (stage == 0) {
#pragma unroll
                    for (int i = 0; i < 36; i++) v[i] = 0.f;
                } else {
                    const uint4* psrc = sc_->part + (size_t)own * 8 * 36 * 32;
                    sum_partials(v, psrc + tid, stage & 1);
                    PROF(stage == 1 ? 8 : 15);
                    sum_tail(v, reinterpret_cast<const uint2*>(psrc + 32 * 32) + tid, stage & 1);
                }
                if (stage) mbar_wait(sbase + OFF_XBAR, stage - 1);
                if (stage == 0) PROFR(22);
                {
                    const float gs = stage == 2 ? 0.5f : 1.f;
                    float gate[18];
                    lds_mod(gate, modt, warp);
                    const int r = lane >> 2;
                    const uint32_t rows = sbase + OFF_ROWS + r * (DM * 2) + (lane & 3) * 4;
#pragma unroll
                    for (int j = 0; j < 9; j++) {
                        const int ch = j < 8 ? (j >> 1) * 2 + (warp >> 2) : 8, c16 = j < 8 ? (warp & 3) * 2 + (j & 1) : warp;
                        const uint32_t ad = rows + ch * 128 + ((c16 ^ ((r + ch) & 7)) << 4);
                        const uint32_t u0 = __float_as_uint(lds32f(ad)), u1 = __float_as_uint(lds32f(ad + 8 * DM * 2));
                        const float g0 = stage ? gate[2 * j] * gs : 0.f, g1 = stage ? gate[2 * j + 1] * gs : 0.f;
                        v[4 * j] = fmaf(g0, v[4 * j], bf_lo(u0));
                        v[4 * j + 1] = fmaf(g1, v[4 * j + 1], bf_hi(u0));
                        v[4 * j + 2] = fmaf(g0, v[4 * j + 2], bf_lo(u1));
                        v[4 * j + 3] = fmaf(g1, v[4 * j + 3], bf_hi(u1));
                        sts32f(ad, __uint_as_float(pack_bf16(v[4 * j], v[4 * j + 1])));
                        sts32f(ad + 8 * DM * 2, __uint_as_float(pack_bf16(v[4 * j + 2], v[4 * j + 3])));
                    }
                    asm volatile("fence.proxy.async.shared::cta;" ::: "memory");
                }
                if (stage == 2) break;
                PROF(stage == 0 ? 1 : 9);
                uint4 ua[6], ub[6];
#pragma unroll
                for (int i = 0; i < 6; i++) ua[i] = ub[i] = make_uint4(0, 0, 0, 0);
                layernorm_rows(v, red, warp, lane, [&]() {
                    if (stage == 0) {
                        modp_load(ua, sc_->modp[0] + tid * 4);
                        if (warp == 0) modp_load(ub, sc_->modp[0] + 1024 + tid * 4);
                    }
                });
                if (stage == 0) PROFR(27);
                if (stage == 0) {
                    const uint32_t tag = (epoch + 1) & 0xffu;
                    modp_to_smem(ua, sbase + OFF_MODT + (DM + tid * 4) * 4, sc_->modp[0] + tid * 4, tag);
                    if (warp == 0)
                        modp_to_smem(ub, sbase + OFF_MODT + (DM + 1024 + tid * 4) * 4, sc_->modp[0] + 1024 + tid * 4, tag);
                    bar_sync(3, 256);
                }
                float shift[18], scale[18];
                lds_mod(shift, modt + DM * 4, warp);
                lds_mod(scale, modt + 2 * DM * 4, warp);
                if (stage == 0) PROFR(28);
                PROF(stage == 0 ? 2 : 10);
                modulate_store(v, shift, scale, stage == 0 ? SM_SCALE : 1.f, sc_->h[epoch & 1][stage] + (size_t)own * 36 * 32, warp, lane);
                if (stage == 0) asm volatile("barrier.cluster.wait.aligned;" ::: "memory");
            }

            const uint32_t spill = sbase + 8 * SLOT_BYTES + wg * 3 * SLOT_BYTES + (tid & 127) * 16;
            uint32_t a[144];
            PROF(stage == 0 ? 3 : 11);
            {
                const uint4* hsrc = sc_->h[epoch & 1][stage] + (size_t)wown * 36 * 32 + lane;
                __nanosleep(PROBE_NS);
                poll_tail(a, reinterpret_cast<const uint2*>(hsrc - lane + 32 * 32) + lane);
                PROF(stage == 0 ? 4 : 12);
                if (stage == 1) PROFG(25);
                TG(stage * 32 + 30);
                if (wg == 1) bar_sync(5, 256);
                poll_frags<0, 32>(a, hsrc, wg == 0);
                if (stage == 0) bar_arrive(4, 320);
            }
            uint4* hhbuf = sc_->hh + (size_t)b * 8 * 256 + tid;
            float d[64];
#pragma unroll 1
            for (int ch = 0;; ch++) {
                TG(stage * 32 + ch * 2);
                gemm_n128(d, a, cx, ring, true, stage && wg);
                TG(stage * 32 + ch * 2 + 1);
                if (stage == 0) {
                    if (ch == 3) break;
#pragma unroll
                    for (int v = 0; v < 8; v++)
                        sts128(spill + (ch * 8 + v) * 2048, pack_bf16(d[8 * v], d[8 * v + 1]),
                               pack_bf16(d[8 * v + 2], d[8 * v + 3]), pack_bf16(d[8 * v + 4], d[8 * v + 5]),
                               pack_bf16(d[8 * v + 6], d[8 * v + 7]));
                } else {
#pragma unroll
                    for (int i = 0; i < 32; i++) {
                        const float gv = d[i], gu = gv * d[32 + i];
                        const float z = gv * fmaf(gv * gv, 0.7978845608028654f * 0.044715f, 0.7978845608028654f);
                        d[i] = fmaf(gu, tanh_fast(z), gu);
                    }
                    if (ch == 8) break;
                    if (wg == 0) {
                        if (ch == 0) bar_arrive(7, 160);
                        if (ch == 2) bar_sync(10, 160);
                    }
#pragma unroll
                    for (int v = 0; v < 4; v++) {
                        const uint4 h4 = make_uint4(pack_bf16(d[8 * v], d[8 * v + 1]), pack_bf16(d[8 * v + 2], d[8 * v + 3]),
                                                    pack_bf16(d[8 * v + 4], d[8 * v + 5]), pack_bf16(d[8 * v + 6], d[8 * v + 7]));
                        if (ch < 2)
                            __stcg(hhbuf + (ch * 4 + v) * 256, h4);
                        else
                            sts128(spill + ((ch - 2) * 4 + v) * 2048, h4.x, h4.y, h4.z, h4.w);
                    }
                }
            }
            if (stage == 0) {
                uint32_t q[32];
#pragma unroll
                for (int i = 0; i < 32; i++) q[i] = pack_bf16(d[2 * i], d[2 * i + 1]);
                PROF(5);
                PROFG(23);
                if (wg == 0) bar_arrive(6, 160);
                {
                    float o[64], sa[32], sb[32];
                    uint32_t pa[16], pb[16];
#pragma unroll
                    for (int i = 0; i < 64; i++) o[i] = 0.f;
                    float n0 = 0.f, n1 = 0.f, l0 = 1.f, l1 = 1.f;
                    bool shifted = false;
                    const uint64_t dbase = desc_of(sbase);
                    const uint64_t dbk = dbase - (511u << 16);
                    const int my_bar = 1 + wg, other_bar = 2 - wg;

                    auto softmax_a = [&](bool first, float& s0, float& s1) {
                        if (first) {
                            shifted = false;
                            n0 = n1 = 0.f;
                            l0 = l1 = 0.f;
                        }
                        if (shifted)
                            exp_step<true>(sa, pa, n0, n1, s0, s1);
                        else
                            exp_step<false>(sa, pa, n0, n1, s0, s1);
                    };
                    auto softmax_b = [&](bool first, float s0, float s1) {
                        float u0, u1;
                        if (shifted)
                            exp_step<true>(sb, pb, n0, n1, u0, u1);
                        else
                            exp_step<false>(sb, pb, n0, n1, u0, u1);
                        s0 += u0;
                        s1 += u1;
                        bool bad = !(fmaxf(s0, s1) <= SM_HI);
                        if (first) {
                            float r0 = s0 + __shfl_xor_sync(0xffffffffu, s0, 1), r1 = s1 + __shfl_xor_sync(0xffffffffu, s1, 1);
                            r0 += __shfl_xor_sync(0xffffffffu, r0, 2);
                            r1 += __shfl_xor_sync(0xffffffffu, r1, 2);
                            bad = bad || !(fminf(r0, r1) >= SM_LO);
                        }
                        if (__any_sync(0xffffffffu, bad)) {
                            float x0, x1;
                            row_max(sa, sb, x0, x1);
                            x0 = -x0;
                            x1 = -x1;
                            if (!first) {
                                x0 = fminf(x0, n0);
                                x1 = fminf(x1, n1);
                                const float al0 = ex2(x0 - n0), al1 = ex2(x1 - n1);
                                l0 *= al0;
                                l1 *= al1;
#pragma unroll
                                for (int i = 0; i < 16; i++) {
                                    o[4 * i] *= al0;
                                    o[4 * i + 1] *= al0;
                                    o[4 * i + 2] *= al1;
                                    o[4 * i + 3] *= al1;
                                }
                            }
                            n0 = x0;
                            n1 = x1;
                            shifted = true;
                            exp_step<true>(sa, pa, n0, n1, s0, s1);
                            exp_step<true>(sb, pb, n0, n1, u0, u1);
                            s0 += u0;
                            s1 += u1;
                        }
                        l0 += s0;
                        l1 += s1;
                    };

                    cx.wait_full(4, 0);
                    if (wg == 1) bar_sync(my_bar, 256);
                    wg_fence();
                    qk_step(sa, q, dbk + 4 * 1024);
                    qk_step(sb, q, dbk + 5 * 1024);
                    wg_commit();
                    bar_arrive(other_bar, 256);
                    wg_wait<0>();
                    pin(sa);
                    pin(sb);
                    cx.release(4);
                    cx.wait_full(6, 0);
                    {
                        float s0, s1;
                        softmax_a(true, s0, s1);
                        softmax_b(true, s0, s1);
                    }
                    uint32_t alo = (uint32_t)dbase + 6 * 1024, blo = (uint32_t)dbase;
                    const uint32_t dhi = (uint32_t)(dbase >> 32);
#pragma unroll 1
                    for (int t = 1; t < 64; t++) {
                        const int j = t & 15;
                        const uint32_t sA = 2 + 4 * (t & 1), sB = 4 - 4 * (t & 1);
                        const uint64_t da = ((uint64_t)dhi << 32) | alo, db = ((uint64_t)dhi << 32) | blo;
                        TL(0);
                        bar_sync(my_bar, 256);
                        TL(2);
                        wg_fence();
                        pv_step(o, pa, da + 1024, j != 1);
                        qk_step(sa, q, da - (511u << 16));
                        wg_commit();
                        cx.wait_full(sB, ((36 + 4 * t) >> 3) & 1);
                        wg_fence();
                        qk_step(sb, q, db - (511u << 16));
                        pv_step(o, pb, db + 1024, 1);
                        wg_commit();
                        bar_arrive(other_bar, 256);
                        alo ^= 4096;
                        blo ^= 4096;
                        asm volatile("" : "+r"(alo), "+r"(blo));
                        TL(3);
                        wg_wait<1>();
                        pin(sa);
                        pin(pa);
                        TL(4);
                        cx.release(sA);
                        const float lp0 = l0, lp1 = l1;
                        float s0, s1;
                        softmax_a(j == 0, s0, s1);
                        TL(5);
                        wg_wait<0>();
                        pin(o);
                        pin(sb);
                        pin(pb);
                        TL(6);
                        cx.release(sB);
                        if (j == 0) {
                            float i0, i1;
                            inv_row_sums(lp0, lp1, i0, i1);
                            const uint32_t dst = spill + ((t >> 4) - 1) * 16384;
#pragma unroll
                            for (int v = 0; v < 8; v++)
                                sts128(dst + v * 2048, pack_bf16(o[8 * v] * i0, o[8 * v + 1] * i0),
                                       pack_bf16(o[8 * v + 2] * i1, o[8 * v + 3] * i1),
                                       pack_bf16(o[8 * v + 4] * i0, o[8 * v + 5] * i0),
                                       pack_bf16(o[8 * v + 6] * i1, o[8 * v + 7] * i1));
                        }
                        const uint32_t bn = sbase + OFF_FULL + (8 - sA) * 8, pn = ((38 + 4 * t) >> 3) & 1;
                        const bool okn = mbar_try(bn, pn);
                        TL(1);
                        softmax_b(j == 0, s0, s1);
                        if (!okn || j == 15) {
                            mbar_wait(bn, pn);
                            if (t == 47 && wg == 0) bar_arrive(6, 160);
                            if (j == 15 && t < 63) {
                                const uint32_t src = spill + (t >> 4) * 16384;
#pragma unroll
                                for (int v = 0; v < 8; v++)
                                    lds128(src + v * 2048, q[4 * v], q[4 * v + 1], q[4 * v + 2], q[4 * v + 3]);
                            }
                        }
                        TL(7);
                    }
                    bar_sync(my_bar, 256);
                    wg_fence();
                    pv_step(o, pa, dbase + 2 * 1024, 1);
                    pv_step(o, pb, dbase + 3 * 1024, 1);
                    wg_commit();
                    if (wg == 0) bar_arrive(other_bar, 256);
                    float i0, i1;
                    inv_row_sums(l0, l1, i0, i1);
                    wg_wait<0>();
                    pin(o);
                    cx.release(2);
#pragma unroll
                    for (int i = 0; i < 16; i++) {
                        a[2 * i] = pack_bf16(o[4 * i] * i0, o[4 * i + 1] * i0);
                        a[2 * i + 1] = pack_bf16(o[4 * i + 2] * i1, o[4 * i + 3] * i1);
                    }
#pragma unroll
                    for (int v = 0; v < 24; v++)
                        lds128(spill + v * 2048, a[32 + 4 * v], a[33 + 4 * v], a[34 + 4 * v], a[35 + 4 * v]);
#pragma unroll
                    for (int i = 128; i < 144; i++) a[i] = 0;
                }
                ring.slot = 4;
                ring.phase = 0;
                PROF(6);
                PROFG(24);
            } else {
#pragma unroll
                for (int v = 0; v < 8; v++) {
                    const uint4 t = __ldcg(hhbuf + v * 256);
                    a[112 + 4 * v] = t.x;
                    a[113 + 4 * v] = t.y;
                    a[114 + 4 * v] = t.z;
                    a[115 + 4 * v] = t.w;
                }
#pragma unroll
                for (int i = 0; i < 16; i++) a[i] = pack_bf16(d[2 * i], d[2 * i + 1]);
#pragma unroll
                for (int v = 0; v < 24; v++)
                    lds128(spill + v * 2048, a[16 + 4 * v], a[17 + 4 * v], a[18 + 4 * v], a[19 + 4 * v]);
                PROF(13);
            }

            {
                uint4* dst = sc_->part + ((size_t)wown * 8 + g) * 36 * 32 + lane;
                const uint32_t ptag = (stage + 1) & 1;
#pragma unroll 1
                for (int p = 0; p < 4; p++) {
                    TG(stage * 32 + 18 + p * 2);
                    gemm_n128(d, a, cx, ring, stage != 0, stage && wg);
                    TG(stage * 32 + 19 + p * 2);
#pragma unroll
                    for (int u = 0; u < 8; u++)
                        st128(dst + (p * 8 + u) * 32, (pack_bf16(d[8 * u], d[8 * u + 1]) & ~1u) | ptag,
                              pack_bf16(d[8 * u + 2], d[8 * u + 3]), pack_bf16(d[8 * u + 4], d[8 * u + 5]),
                              pack_bf16(d[8 * u + 6], d[8 * u + 7]));
                    if (p == 0 && wg == 0) bar_arrive(7, 160);
                }
                float e[32];
                TG(stage * 32 + 26);
                gemm_n64(e, a, cx, ring, stage != 0);
                TG(stage * 32 + 27);
                uint2* dst2 = reinterpret_cast<uint2*>(dst - lane + 32 * 32) + lane;
#pragma unroll
                for (int j = 0; j < 8; j++)
                    st64(dst2 + j * 32, (pack_bf16(e[4 * j], e[4 * j + 1]) & ~1u) | ptag, pack_bf16(e[4 * j + 2], e[4 * j + 3]));
            }
            PROF(stage == 0 ? 7 : 14);
            if (stage == 1) {
                PROFG(26);
                asm volatile("barrier.cluster.arrive.relaxed.aligned;" ::: "memory");
            }
        }
        if (wg == 0) bar_sync(8, 256);
        bar_sync(3, 256);
        if (tid == 32) sc_->epoch[b * 32] = get_epoch(sbase) + 1;
        if (tid == 0) {
            rows_store(sbase, &maps.rout, own * 16);
            rows_store_wait();
        }
        __syncwarp();
        PROF(16);
        PROFG(31);
        asm volatile("barrier.cluster.wait.aligned;" ::: "memory");
    }
}

typedef CUresult (*EncodeFn)(CUtensorMap*, CUtensorMapDataType, cuuint32_t, void*, const cuuint64_t*, const cuuint64_t*,
                             const cuuint32_t*, const cuuint32_t*, CUtensorMapInterleave, CUtensorMapSwizzle,
                             CUtensorMapL2promotion, CUtensorMapFloatOOBfill);

void make_map(EncodeFn enc, CUtensorMap* m, const void* ptr, uint64_t rows, uint64_t cols, bool narrow = false) {
    cuuint64_t gdim[2] = {cols, rows};
    cuuint64_t gstr[1] = {cols * 2};
    cuuint32_t box[2] = {narrow ? 16u : 64u, narrow ? 192u : 64u};
    cuuint32_t estr[2] = {1, 1};
    enc(m, CU_TENSOR_MAP_DATA_TYPE_BFLOAT16, 2, const_cast<void*>(ptr), gdim, gstr, box, estr,
        CU_TENSOR_MAP_INTERLEAVE_NONE, narrow ? CU_TENSOR_MAP_SWIZZLE_NONE : CU_TENSOR_MAP_SWIZZLE_128B,
        CU_TENSOR_MAP_L2_PROMOTION_L2_128B,
        CU_TENSOR_MAP_FLOAT_OOB_FILL_NONE);
}

void make_rows_map(EncodeFn enc, CUtensorMap* m, const void* ptr) {
    cuuint64_t gdim[3] = {64, 9, 2048};
    cuuint64_t gstr[2] = {128, DM * 2};
    cuuint32_t box[3] = {64, 9, 16};
    cuuint32_t estr[3] = {1, 1, 1};
    enc(m, CU_TENSOR_MAP_DATA_TYPE_BFLOAT16, 3, const_cast<void*>(ptr), gdim, gstr, box, estr,
        CU_TENSOR_MAP_INTERLEAVE_NONE, CU_TENSOR_MAP_SWIZZLE_128B, CU_TENSOR_MAP_L2_PROMOTION_L2_128B,
        CU_TENSOR_MAP_FLOAT_OOB_FILL_NONE);
}

}

extern "C" void kernel_launch(void* const* d_in, const int* in_sizes, int n_in, void* d_out, int out_size) {
    (void)in_sizes;
    (void)n_in;
    (void)out_size;
    void* fn = nullptr;
    cudaDriverEntryPointQueryResult qr;
    cudaGetDriverEntryPoint("cuTensorMapEncodeTiled", &fn, cudaEnableDefault, &qr);
    EncodeFn enc = (EncodeFn)fn;
    Params maps;
    maps.x = (const __nv_bfloat16*)d_in[0];
    maps.cvec = (const __nv_bfloat16*)d_in[9];
    maps.wmod = (const __nv_bfloat16*)d_in[10];
    maps.kc = (const __nv_bfloat16*)d_in[1];
    maps.vc = (const __nv_bfloat16*)d_in[2];
    maps.wq_p = (const __nv_bfloat16*)d_in[3];
    maps.wo_p = (const __nv_bfloat16*)d_in[4];
    maps.wg_p = (const __nv_bfloat16*)d_in[6];
    maps.wu_p = (const __nv_bfloat16*)d_in[7];
    maps.wd_p = (const __nv_bfloat16*)d_in[8];
    maps.out = (__nv_bfloat16*)d_out;
    void* scp = nullptr;
    cudaGetSymbolAddress(&scp, g_scratch);
    maps.sc = (Scratch*)scp;
    make_map(enc, &maps.k, d_in[1], 32 * 2048, 128);
    make_map(enc, &maps.v, d_in[2], 32 * 2048, 128);
    make_map(enc, &maps.wq, d_in[3], 576, 4096);
    make_map(enc, &maps.wo, d_in[4], 4096, 576);
    make_map(enc, &maps.wg, d_in[6], 576, 4608);
    make_map(enc, &maps.wu, d_in[7], 576, 4608);
    make_map(enc, &maps.wd, d_in[8], 4608, 576);
    make_rows_map(enc, &maps.rx, d_in[0]);
    make_rows_map(enc, &maps.rx2, (char*)scp + offsetof(Scratch, x2));
    make_rows_map(enc, &maps.rout, d_out);
    cudaFuncSetAttribute(fused_block_kernel, cudaFuncAttributeMaxDynamicSharedMemorySize, SMEM_BYTES);
    fused_block_kernel<<<128, 384, SMEM_BYTES>>>(maps);
}
```

```cpp
#include <cuda_runtime.h>
#include <cuda_bf16.h>
#include <cuda.h>
#include <stdint.h>
#include <stddef.h>

namespace {

constexpr int DM = 576;
constexpr int SLOT_BYTES = 16384;
constexpr int BOX_BYTES = 8192;
constexpr int NUNITS = 14;
constexpr int SMEM_TAIL = NUNITS * SLOT_BYTES;
constexpr int SMEM_BYTES = SMEM_TAIL + 2048 + 1024;
constexpr int OFF_FULL = SMEM_TAIL;
constexpr int OFF_EMPTY = SMEM_TAIL + 64;
constexpr int OFF_RED = SMEM_TAIL + 128;

constexpr int KV_AHEAD = 16;
#define GATE_SLOT 4
#define PROBE_NS 300
constexpr int OFF_XBAR = SMEM_TAIL + 1792;
constexpr int OFF_ROWS = 8 * SLOT_BYTES;
constexpr int OFF_MODT = OFF_ROWS + 20480;
constexpr int OFF_EPOCH = SMEM_TAIL + 1808;
constexpr int OFF_MRED = OFF_ROWS + 28672;

struct Scratch {
    unsigned epoch[128 * 32];
    uint32_t mod[6 * DM];
    uint32_t modp[6][2 * DM];
    uint4 h[2][2][128 * 36 * 32];
    uint4 part[128 * 8 * 36 * 32];
    uint4 hh[128 * 8 * 256];
    __nv_bfloat16 x2[2048 * DM];
};
__device__ Scratch g_scratch;

#define TG(i)
#define TL(i)
#define PROFR(i)
#define PROF(i)
#define PROFG(i)

struct Params {
    const __nv_bfloat16 *x, *cvec, *wmod, *kc, *vc, *wq_p, *wo_p, *wg_p, *wu_p, *wd_p;
    __nv_bfloat16* out;
    Scratch* sc;
    CUtensorMap k, v, wq, wo, wg, wu, wd, rx, rx2, rout;
};

__device__ __forceinline__ uint32_t smem_u32(const void* p) { return (uint32_t)__cvta_generic_to_shared(p); }
__device__ __forceinline__ void mbar_init(uint32_t a, uint32_t c) {
    asm volatile("mbarrier.init.shared::cta.b64 [%0], %1;" ::"r"(a), "r"(c) : "memory");
}
__device__ __forceinline__ void mbar_expect_tx(uint32_t a, uint32_t bytes) {
    asm volatile("mbarrier.arrive.expect_tx.shared::cta.b64 _, [%0], %1;" ::"r"(a), "r"(bytes) : "memory");
}
__device__ __forceinline__ bool mbar_try(uint32_t a, uint32_t ph) {
    uint32_t ok;
    asm volatile(
        "{\n.reg .pred p;\nmbarrier.try_wait.parity.shared::cta.b64 p, [%1], %2;\nselp.u32 %0, 1, 0, p;\n}"
        : "=r"(ok)
        : "r"(a), "r"(ph)
        : "memory");
    return ok != 0;
}
__device__ __forceinline__ uint32_t clk32() {
    uint32_t c;
    asm volatile("mov.u32 %0, %%clock;" : "=r"(c));
    return c;
}
constexpr uint32_t WAIT_LIMIT = 1u << 30;
__device__ __forceinline__ void mbar_wait(uint32_t a, uint32_t ph) {
    if (mbar_try(a, ph)) return;
    uint32_t t0 = clk32();
    while (!mbar_try(a, ph)) {
        if (clk32() - t0 > WAIT_LIMIT) break;
    }
}
__device__ __forceinline__ void mbar_arrive_cluster(uint32_t a, uint32_t cta) {
    asm volatile(
        "{\n.reg .b32 ra;\nmapa.shared::cluster.u32 ra, %0, %1;\nmbarrier.arrive.shared::cluster.b64 _, [ra];\n}" ::"r"(a),
        "r"(cta)
        : "memory");
}
__device__ __forceinline__ void tma_mc(uint32_t dst, const CUtensorMap* m, int c0, int c1, uint32_t bar) {
    asm volatile(
        "cp.async.bulk.tensor.2d.shared::cluster.global.mbarrier::complete_tx::bytes.multicast::cluster"
        " [%0], [%1, {%3, %4}], [%2], %5;" ::"r"(dst),
        "l"(m), "r"(bar), "r"(c0), "r"(c1), "h"((uint16_t)3)
        : "memory");
}
__device__ __forceinline__ void bulk_load(uint32_t dst, const void* src, uint32_t bytes, uint32_t bar) {
    asm volatile("cp.async.bulk.shared::cluster.global.mbarrier::complete_tx::bytes [%0], [%1], %2, [%3];" ::"r"(dst),
                 "l"(src), "r"(bytes), "r"(bar)
                 : "memory");
}
__device__ __forceinline__ void l2_prefetch(const void* p, uint32_t bytes) {
    asm volatile("cp.async.bulk.prefetch.L2.global [%0], %1;" ::"l"(p), "r"(bytes) : "memory");
}
__device__ __forceinline__ void bar_sync(int id, int n) { asm volatile("bar.sync %0, %1;" ::"r"(id), "r"(n) : "memory"); }
__device__ __forceinline__ void bar_arrive(int id, int n) {
    asm volatile("bar.arrive %0, %1;" ::"r"(id), "r"(n) : "memory");
}
__device__ __forceinline__ void wg_fence() { asm volatile("wgmma.fence.sync.aligned;" ::: "memory"); }
__device__ __forceinline__ void wg_commit() { asm volatile("wgmma.commit_group.sync.aligned;" ::: "memory"); }
template <int N>
__device__ __forceinline__ void wg_wait() {
    asm volatile("wgmma.wait_group.sync.aligned %0;" ::"n"(N) : "memory");
}
template <int N>
__device__ __forceinline__ void pin(float (&d)[N]) {
#pragma unroll
    for (int i = 0; i < N; i++) asm volatile("" : "+f"(d[i])::"memory");
}
template <int N>
__device__ __forceinline__ void pin(uint32_t (&d)[N]) {
#pragma unroll
    for (int i = 0; i < N; i++) asm volatile("" : "+r"(d[i])::"memory");
}
__device__ __forceinline__ uint32_t pack_bf16(float lo, float hi) {
    uint32_t r;
    asm("cvt.rn.bf16x2.f32 %0, %1, %2;" : "=r"(r) : "f"(hi), "f"(lo));
    return r;
}
__device__ __forceinline__ float bf_lo(uint32_t v) { return __uint_as_float(v << 16); }
__device__ __forceinline__ float bf_hi(uint32_t v) { return __uint_as_float(v & 0xffff0000u); }
__device__ __forceinline__ float round_bf16(float v) { return __bfloat162float(__float2bfloat16_rn(v)); }
__device__ __forceinline__ float ex2(float x) {
    float y;
    asm("ex2.approx.ftz.f32 %0, %1;" : "=f"(y) : "f"(x));
    return y;
}
__device__ __forceinline__ float rcp(float x) {
    float y;
    asm("rcp.approx.ftz.f32 %0, %1;" : "=f"(y) : "f"(x));
    return y;
}
__device__ __forceinline__ float tanh_fast(float x) {
    float y;
    asm("tanh.approx.f32 %0, %1;" : "=f"(y) : "f"(x));
    return y;
}
__device__ __forceinline__ void sts128(uint32_t a, uint32_t x, uint32_t y, uint32_t z, uint32_t w) {
    asm volatile("st.shared.v4.b32 [%0], {%1,%2,%3,%4};" ::"r"(a), "r"(x), "r"(y), "r"(z), "r"(w) : "memory");
}
__device__ __forceinline__ void lds128(uint32_t a, uint32_t& x, uint32_t& y, uint32_t& z, uint32_t& w) {
    asm volatile("ld.shared.v4.b32 {%0,%1,%2,%3}, [%4];" : "=r"(x), "=r"(y), "=r"(z), "=r"(w) : "r"(a) : "memory");
}
__device__ __forceinline__ void sts32f(uint32_t a, float v) {
    asm volatile("st.shared.f32 [%0], %1;" ::"r"(a), "f"(v) : "memory");
}
__device__ __forceinline__ float lds32f(uint32_t a) {
    float v;
    asm volatile("ld.shared.f32 %0, [%1];" : "=f"(v) : "r"(a) : "memory");
    return v;
}
#define F8(d, b) \
    "+f"(d[b]), "+f"(d[b + 1]), "+f"(d[b + 2]), "+f"(d[b + 3]), "+f"(d[b + 4]), "+f"(d[b + 5]), "+f"(d[b + 6]), "+f"(d[b + 7])

template <int TB>
__device__ __forceinline__ void wgmma_n128(float (&d)[64], uint32_t a0, uint32_t a1, uint32_t a2, uint32_t a3,
                                           uint64_t db, int sc) {
    asm volatile(
        "{\n.reg .pred p;\nsetp.ne.b32 p, %69, 0;\n"
        "wgmma.mma_async.sync.aligned.m64n128k16.f32.bf16.bf16 "
        "{%0,%1,%2,%3,%4,%5,%6,%7,%8,%9,%10,%11,%12,%13,%14,%15,%16,%17,%18,%19,%20,%21,%22,%23,%24,%25,%26,%27,%28,%29,%30,%31,"
        "%32,%33,%34,%35,%36,%37,%38,%39,%40,%41,%42,%43,%44,%45,%46,%47,%48,%49,%50,%51,%52,%53,%54,%55,%56,%57,%58,%59,%60,%61,%62,%63},"
        "{%64,%65,%66,%67}, %68, p, 1, 1, %70;\n}"
        : F8(d, 0), F8(d, 8), F8(d, 16), F8(d, 24), F8(d, 32), F8(d, 40), F8(d, 48), F8(d, 56)
        : "r"(a0), "r"(a1), "r"(a2), "r"(a3), "l"(db), "r"(sc), "n"(TB));
}
#define O8(d, b) \
    "=f"(d[b]), "=f"(d[b + 1]), "=f"(d[b + 2]), "=f"(d[b + 3]), "=f"(d[b + 4]), "=f"(d[b + 5]), "=f"(d[b + 6]), "=f"(d[b + 7])
template <int TB>
__device__ __forceinline__ void wgmma_n128_z(float (&d)[64], uint32_t a0, uint32_t a1, uint32_t a2, uint32_t a3,
                                             uint64_t db) {
    asm volatile(
        "wgmma.mma_async.sync.aligned.m64n128k16.f32.bf16.bf16 "
        "{%0,%1,%2,%3,%4,%5,%6,%7,%8,%9,%10,%11,%12,%13,%14,%15,%16,%17,%18,%19,%20,%21,%22,%23,%24,%25,%26,%27,%28,%29,%30,%31,"
        "%32,%33,%34,%35,%36,%37,%38,%39,%40,%41,%42,%43,%44,%45,%46,%47,%48,%49,%50,%51,%52,%53,%54,%55,%56,%57,%58,%59,%60,%61,%62,%63},"
        "{%64,%65,%66,%67}, %68, 0, 1, 1, %69;"
        : O8(d, 0), O8(d, 8), O8(d, 16), O8(d, 24), O8(d, 32), O8(d, 40), O8(d, 48), O8(d, 56)
        : "r"(a0), "r"(a1), "r"(a2), "r"(a3), "l"(db), "n"(TB));
}
template <int TB>
__device__ __forceinline__ void wgmma_n64_z(float (&d)[32], uint32_t a0, uint32_t a1, uint32_t a2, uint32_t a3,
                                            uint64_t db) {
    asm volatile(
        "wgmma.mma_async.sync.aligned.m64n64k16.f32.bf16.bf16 "
        "{%0,%1,%2,%3,%4,%5,%6,%7,%8,%9,%10,%11,%12,%13,%14,%15,%16,%17,%18,%19,%20,%21,%22,%23,%24,%25,%26,%27,%28,%29,%30,%31},"
        "{%32,%33,%34,%35}, %36, 0, 1, 1, %37;"
        : O8(d, 0), O8(d, 8), O8(d, 16), O8(d, 24)
        : "r"(a0), "r"(a1), "r"(a2), "r"(a3), "l"(db), "n"(TB));
}
template <int TB>
__device__ __forceinline__ void wgmma_n64(float (&d)[32], uint32_t a0, uint32_t a1, uint32_t a2, uint32_t a3,
                                          uint64_t db) {
    asm volatile(
        "wgmma.mma_async.sync.aligned.m64n64k16.f32.bf16.bf16 "
        "{%0,%1,%2,%3,%4,%5,%6,%7,%8,%9,%10,%11,%12,%13,%14,%15,%16,%17,%18,%19,%20,%21,%22,%23,%24,%25,%26,%27,%28,%29,%30,%31},"
        "{%32,%33,%34,%35}, %36, 1, 1, 1, %37;"
        : F8(d, 0), F8(d, 8), F8(d, 16), F8(d, 24)
        : "r"(a0), "r"(a1), "r"(a2), "r"(a3), "l"(db), "n"(TB));
}

__device__ __forceinline__ uint64_t desc_of(uint32_t saddr) {
    return (uint64_t)(((saddr >> 4) & 0x3FFFu) | (512u << 16)) | ((uint64_t)(64u | (1u << 30)) << 32);
}

struct Ring {
    uint32_t slot;
    uint32_t phase;
    __device__ __forceinline__ void next() {
        if (++slot == 8) {
            slot = 0;
            phase ^= 1;
        }
    }
};

struct Ctx {
    uint32_t sbase;
    int wg;
    uint32_t rel_cta;
    __device__ __forceinline__ void wait_full(uint32_t slot, uint32_t phase) const {
        mbar_wait(sbase + OFF_FULL + slot * 8, phase);
    }
    __device__ __forceinline__ void release(uint32_t slot) const {
        if (rel_cta < 2) mbar_arrive_cluster(sbase + OFF_EMPTY + slot * 8, rel_cta);
    }
};

__device__ __forceinline__ void gemm_n128(float (&d)[64], const uint32_t (&a)[144], const Ctx& c, Ring& r, bool nine,
                                          bool early) {
    uint32_t prev = 0;
#pragma unroll
    for (int s = 0; s < 9; s++) {
        if (s < 8 || nine) {
            if (s == GATE_SLOT) {
                if (early) {
                    wg_wait<0>();
                    c.release(prev);
                }
                bar_sync(8 + c.wg, 256);
            }
            c.wait_full(r.slot, r.phase);
            uint64_t db = desc_of(c.sbase + r.slot * SLOT_BYTES);
            wg_fence();
#pragma unroll
            for (int k = 0; k < 4; k++) {
                if ((s | k) == 0)
                    wgmma_n128_z<1>(d, a[0], a[1], a[2], a[3], db);
                else
                    wgmma_n128<1>(d, a[s * 16 + k * 4], a[s * 16 + k * 4 + 1], a[s * 16 + k * 4 + 2],
                                  a[s * 16 + k * 4 + 3], db + k * 128, 1);
            }
            wg_commit();
            if (s == 8 || (s == 7 && !nine)) bar_arrive(9 - c.wg, 256);
            if (s > 0) {
                wg_wait<1>();
                if (s != GATE_SLOT || !early) c.release(prev);
            }
            prev = r.slot;
            r.next();
        }
    }
    wg_wait<0>();
    c.release(prev);
    pin(d);
}
__device__ __forceinline__ void gemm_n64(float (&d)[32], const uint32_t (&a)[144], const Ctx& c, Ring& r, bool nine) {
    uint32_t prev = 0;
#pragma unroll
    for (int s = 0; s < 5; s++) {
        if (s < 4 || nine) {
            c.wait_full(r.slot, r.phase);
            uint64_t db = desc_of(c.sbase + r.slot * SLOT_BYTES);
            wg_fence();
#pragma unroll
            for (int k = 0; k < 8; k++) {
                if ((s | k) == 0)
                    wgmma_n64_z<1>(d, a[0], a[1], a[2], a[3], db);
                else if (s * 8 + k < 36)
                    wgmma_n64<1>(d, a[s * 32 + k * 4], a[s * 32 + k * 4 + 1], a[s * 32 + k * 4 + 2],
                                 a[s * 32 + k * 4 + 3], db + k * 128);
            }
            wg_commit();
            if (s > 0) {
                wg_wait<1>();
                c.release(prev);
            }
            prev = r.slot;
            r.next();
        }
    }
    wg_wait<0>();
    c.release(prev);
    pin(d);
}
__device__ __forceinline__ void st128(uint4* p, uint32_t x, uint32_t y, uint32_t z, uint32_t w) {
    asm volatile(
        "{\n.reg .b64 lo, hi;\n.reg .b128 t;\nmov.b64 lo, {%1, %2};\nmov.b64 hi, {%3, %4};\nmov.b128 t, {lo, hi};\n"
        "st.relaxed.gpu.global.b128 [%0], t;\n}" ::"l"(p),
        "r"(x), "r"(y), "r"(z), "r"(w)
        : "memory");
}
__device__ __forceinline__ uint4 ld128(const uint4* p) {
    uint4 r;
    asm volatile(
        "{\n.reg .b64 lo, hi;\n.reg .b128 t;\nld.relaxed.gpu.global.b128 t, [%4];\nmov.b128 {lo, hi}, t;\n"
        "mov.b64 {%0, %1}, lo;\nmov.b64 {%2, %3}, hi;\n}"
        : "=r"(r.x), "=r"(r.y), "=r"(r.z), "=r"(r.w)
        : "l"(p));
    return r;
}
__device__ __forceinline__ uint4 ldg128(const uint4* p) {
    uint4 r;
    asm volatile("ld.global.nc.v4.u32 {%0,%1,%2,%3}, [%4];" : "=r"(r.x), "=r"(r.y), "=r"(r.z), "=r"(r.w) : "l"(p));
    return r;
}
__device__ __forceinline__ void st64(void* p, uint32_t x, uint32_t y) {
    asm volatile("{\n.reg .b64 t;\nmov.b64 t, {%1, %2};\nst.relaxed.gpu.global.b64 [%0], t;\n}" ::"l"(p), "r"(x), "r"(y)
                 : "memory");
}
__device__ __forceinline__ uint2 ld64(const void* p) {
    uint2 r;
    asm volatile("{\n.reg .b64 t;\nld.relaxed.gpu.global.b64 t, [%2];\nmov.b64 {%0, %1}, t;\n}"
                 : "=r"(r.x), "=r"(r.y)
                 : "l"(p));
    return r;
}
__device__ __forceinline__ void rows_load(uint32_t sbase, const CUtensorMap* m, int row0) {
    mbar_expect_tx(sbase + OFF_XBAR, 16 * DM * 2);
    asm volatile(
        "cp.async.bulk.tensor.3d.shared::cluster.global.mbarrier::complete_tx::bytes [%0], [%1, {%3, %3, %4}], [%2];" ::"r"(
            sbase + OFF_ROWS),
        "l"(m), "r"(sbase + OFF_XBAR), "r"(0), "r"(row0)
        : "memory");
}
__device__ __forceinline__ void rows_store(uint32_t sbase, const CUtensorMap* m, int row0) {
    asm volatile("cp.async.bulk.tensor.3d.global.shared::cta.bulk_group [%0, {%2, %2, %3}], [%1];" ::"l"(m),
                 "r"(sbase + OFF_ROWS), "r"(0), "r"(row0)
                 : "memory");
    asm volatile("cp.async.bulk.commit_group;" ::: "memory");
}
__device__ __forceinline__ void rows_store_wait() { asm volatile("cp.async.bulk.wait_group 0;" ::: "memory"); }

__device__ __forceinline__ constexpr int own_col(int j) { return j < 8 ? (j >> 1) * 128 + (j & 1) * 8 : 512; }
__device__ __forceinline__ void row_reduce(float& s0, float& s1, uint32_t red, int warp, int lane) {
    s0 += __shfl_xor_sync(0xffffffffu, s0, 1);
    s1 += __shfl_xor_sync(0xffffffffu, s1, 1);
    s0 += __shfl_xor_sync(0xffffffffu, s0, 2);
    s1 += __shfl_xor_sync(0xffffffffu, s1, 2);
    if ((lane & 3) == 0) {
        sts32f(red + (warp * 16 + (lane >> 2)) * 4, s0);
        sts32f(red + (warp * 16 + 8 + (lane >> 2)) * 4, s1);
    }
    bar_sync(3, 256);
    s0 = 0.f;
    s1 = 0.f;
#pragma unroll
    for (int w = 0; w < 8; w++) {
        s0 += lds32f(red + (w * 16 + (lane >> 2)) * 4);
        s1 += lds32f(red + (w * 16 + 8 + (lane >> 2)) * 4);
    }
}
template <class F>
__device__ __forceinline__ void layernorm_rows(float (&v)[36], uint32_t red, int warp, int lane, F&& middle) {
    float s0 = 0.f, s1 = 0.f;
#pragma unroll
    for (int j = 0; j < 9; j++) {
        s0 += v[4 * j] + v[4 * j + 1];
        s1 += v[4 * j + 2] + v[4 * j + 3];
    }
    row_reduce(s0, s1, red, warp, lane);
    middle();
    const float m0 = s0 * (1.f / DM), m1 = s1 * (1.f / DM);
    s0 = 0.f;
    s1 = 0.f;
#pragma unroll
    for (int j = 0; j < 9; j++) {
        v[4 * j] -= m0;
        v[4 * j + 1] -= m0;
        v[4 * j + 2] -= m1;
        v[4 * j + 3] -= m1;
        s0 += v[4 * j] * v[4 * j] + v[4 * j + 1] * v[4 * j + 1];
        s1 += v[4 * j + 2] * v[4 * j + 2] + v[4 * j + 3] * v[4 * j + 3];
    }
    row_reduce(s0, s1, red + 512, warp, lane);
    const float r0 = rsqrtf(s0 * (1.f / DM) + 1e-5f), r1 = rsqrtf(s1 * (1.f / DM) + 1e-5f);
#pragma unroll
    for (int j = 0; j < 9; j++) {
        v[4 * j] *= r0;
        v[4 * j + 1] *= r0;
        v[4 * j + 2] *= r1;
        v[4 * j + 3] *= r1;
    }
}
__device__ __forceinline__ void mod_to_smem(uint4 u  , uint32_t dst, const uint32_t* src, uint32_t tag) {
    const uint32_t t0 = clk32();
    while (true) {
        const uint32_t bad = ((u.x ^ tag) | (u.y ^ tag) | (u.z ^ tag) | (u.w ^ tag)) & 0xffffu;
        if (__all_sync(0xffffffffu, bad == 0) || clk32() - t0 > WAIT_LIMIT) break;
        u = ld128(reinterpret_cast<const uint4*>(src));
    }
    sts128(dst, u.x & 0xffff0000u, u.y & 0xffff0000u, u.z & 0xffff0000u, u.w & 0xffff0000u);
}
__device__ __forceinline__ void lds_mod(float (&m)[18], uint32_t src  , int warp) {
#pragma unroll
    for (int j = 0; j < 9; j++)
        asm volatile("ld.shared.v2.f32 {%0,%1}, [%2];"
                     : "=f"(m[2 * j]), "=f"(m[2 * j + 1])
                     : "r"(src + own_col(j) * 4 - (j == 8 ? warp * 32 : 0))
                     : "memory");
}
__device__ __forceinline__ void modulate_store(const float (&v)[36], const float (&shift)[18], const float (&scale)[18],
                                               float post, uint4* hbuf  , int warp, int lane) {
    uint32_t o[18];
#pragma unroll
    for (int j = 0; j < 9; j++) {
        const uint32_t cc = pack_bf16(1.f + scale[2 * j], 1.f + scale[2 * j + 1]);
        const float c0 = bf_lo(cc) * post, c1 = bf_hi(cc) * post, s0 = shift[2 * j] * post, s1 = shift[2 * j + 1] * post;
        o[2 * j] = max(pack_bf16(fmaf(v[4 * j], c0, s0), fmaf(v[4 * j + 1], c1, s1)), 1u);
        o[2 * j + 1] = max(pack_bf16(fmaf(v[4 * j + 2], c0, s0), fmaf(v[4 * j + 3], c1, s1)), 1u);
    }
#pragma unroll
    for (int i = 0; i < 4; i++) st128(hbuf + (i * 8 + warp) * 32 + lane, o[4 * i], o[4 * i + 1], o[4 * i + 2], o[4 * i + 3]);
    st64(reinterpret_cast<uint2*>(hbuf + 32 * 32) + warp * 32 + lane, o[16], o[17]);
}
__device__ __forceinline__ void sum_partials(float (&v)[36], const uint4* src  , uint32_t tag) {
    const uint32_t t0 = clk32();
    while (true) {
        uint4 t[8][4];
#pragma unroll
        for (int s = 0; s < 8; s++)
#pragma unroll
            for (int i = 0; i < 4; i++) t[s][i] = ld128(src + (s * 36 + i * 8) * 32);
        uint32_t bad = 0;
#pragma unroll
        for (int i = 0; i < 32; i++) v[i] = 0.f;
#pragma unroll
        for (int s = 0; s < 8; s++)
#pragma unroll
            for (int i = 0; i < 4; i++) {
                bad |= t[s][i].x ^ tag;
                v[8 * i] += bf_lo(t[s][i].x);
                v[8 * i + 1] += bf_hi(t[s][i].x);
                v[8 * i + 2] += bf_lo(t[s][i].y);
                v[8 * i + 3] += bf_hi(t[s][i].y);
                v[8 * i + 4] += bf_lo(t[s][i].z);
                v[8 * i + 5] += bf_hi(t[s][i].z);
                v[8 * i + 6] += bf_lo(t[s][i].w);
                v[8 * i + 7] += bf_hi(t[s][i].w);
            }
        if (__all_sync(0xffffffffu, (bad & 1u) == 0) || clk32() - t0 > WAIT_LIMIT) break;
    }
}
__device__ __forceinline__ void sum_tail(float (&v)[36], const uint2* src  , uint32_t tag) {
    const uint32_t t0 = clk32();
    while (true) {
        uint2 t[8];
#pragma unroll
        for (int s = 0; s < 8; s++) t[s] = ld64(src + s * 72 * 32);
        uint32_t bad = 0;
        v[32] = v[33] = v[34] = v[35] = 0.f;
#pragma unroll
        for (int s = 0; s < 8; s++) {
            bad |= t[s].x ^ tag;
            v[32] += bf_lo(t[s].x);
            v[33] += bf_hi(t[s].x);
            v[34] += bf_lo(t[s].y);
            v[35] += bf_hi(t[s].y);
        }
        if (__all_sync(0xffffffffu, (bad & 1u) == 0) || clk32() - t0 > WAIT_LIMIT) break;
    }
}
__device__ __forceinline__ void poll_tail(uint32_t (&a)[144], const uint2* src  ) {
    const uint32_t t0 = clk32();
    while (true) {
        uint32_t m = 0xffffffffu;
#pragma unroll
        for (int j = 0; j < 8; j++) {
            const uint2 t = ld64(src + j * 32);
            a[128 + 2 * j] = t.x;
            a[129 + 2 * j] = t.y;
        }
#pragma unroll
        for (int j = 0; j < 16; j++) m = min(m, a[128 + j]);
        if (__all_sync(0xffffffffu, m != 0) || clk32() - t0 > WAIT_LIMIT) break;
    }
}
template <int K0, int K1>
__device__ __forceinline__ void poll_frags(uint32_t (&a)[144], const uint4* src  , bool kick) {
    const uint32_t t0 = clk32();
    while (true) {
#pragma unroll
        for (int k = K0; k < K1; k++)
            asm volatile("ld.relaxed.gpu.global.v4.u32 {%0,%1,%2,%3}, [%4];"
                         : "=r"(a[4 * k]), "=r"(a[4 * k + 1]), "=r"(a[4 * k + 2]), "=r"(a[4 * k + 3])
                         : "l"(src + k * 32));
        if (kick) bar_arrive(5, 256);
        kick = false;
        uint32_t m0 = a[4 * K0], m1 = a[4 * K0 + 1];
#pragma unroll
        for (int i = 4 * K0 + 2; i < 4 * K1; i += 2) {
            m0 = min(m0, a[i]);
            m1 = min(m1, a[i + 1]);
        }
        if (__all_sync(0xffffffffu, min(m0, m1) != 0) || clk32() - t0 > WAIT_LIMIT) break;
    }
}

constexpr float SM_SCALE = 0.08838834764831845f * 1.4426950408889634f;
constexpr float SM_HI = 1.2089258e24f;
constexpr float SM_LO = 9.0949470e-13f;
__device__ __forceinline__ void qk_step(float (&s)[32], const uint32_t (&q)[32], uint64_t dk) {
#pragma unroll
    for (int k = 0; k < 8; k++) {
        if (k == 0)
            wgmma_n64_z<0>(s, q[0], q[1], q[2], q[3], dk);
        else
            wgmma_n64<0>(s, q[4 * k], q[4 * k + 1], q[4 * k + 2], q[4 * k + 3], dk + (k >> 2) * 512 + (k & 3) * 2);
    }
}
__device__ __forceinline__ void pv_step(float (&o)[64], const uint32_t (&p)[16], uint64_t dv, int acc) {
#pragma unroll
    for (int k = 0; k < 4; k++)
        wgmma_n128<1>(o, p[4 * k], p[4 * k + 1], p[4 * k + 2], p[4 * k + 3], dv + k * 128, k != 0 ? 1 : acc);
}
template <bool SHIFT>
__device__ __forceinline__ void exp_step(const float (&s)[32], uint32_t (&p)[16], float n0, float n1, float& s0,
                                         float& s1) {
#pragma unroll
    for (int i = 0; i < 8; i++) {
        const float e0 = ex2(SHIFT ? s[4 * i] + n0 : s[4 * i]), e1 = ex2(SHIFT ? s[4 * i + 1] + n0 : s[4 * i + 1]);
        const float e2 = ex2(SHIFT ? s[4 * i + 2] + n1 : s[4 * i + 2]), e3 = ex2(SHIFT ? s[4 * i + 3] + n1 : s[4 * i + 3]);
        if (i == 0) {
            s0 = e0 + e1;
            s1 = e2 + e3;
        } else {
            s0 += e0 + e1;
            s1 += e2 + e3;
        }
        p[2 * i] = pack_bf16(e0, e1);
        p[2 * i + 1] = pack_bf16(e2, e3);
    }
}
__device__ __forceinline__ void row_max(const float (&sa)[32], const float (&sb)[32], float& x0, float& x1) {
    float xa[8];
#pragma unroll
    for (int i = 0; i < 8; i++) xa[i] = fmaxf(sa[i], sb[i]);
#pragma unroll
    for (int k = 1; k < 4; k++)
#pragma unroll
        for (int i = 0; i < 8; i++) xa[i] = fmaxf(xa[i], fmaxf(sa[8 * k + i], sb[8 * k + i]));
    x0 = fmaxf(fmaxf(xa[0], xa[1]), fmaxf(xa[4], xa[5]));
    x1 = fmaxf(fmaxf(xa[2], xa[3]), fmaxf(xa[6], xa[7]));
    x0 = fmaxf(x0, __shfl_xor_sync(0xffffffffu, x0, 1));
    x1 = fmaxf(x1, __shfl_xor_sync(0xffffffffu, x1, 1));
    x0 = fmaxf(x0, __shfl_xor_sync(0xffffffffu, x0, 2));
    x1 = fmaxf(x1, __shfl_xor_sync(0xffffffffu, x1, 2));
}
__device__ __forceinline__ void inv_row_sums(float l0, float l1, float& i0, float& i1) {
    l0 += __shfl_xor_sync(0xffffffffu, l0, 1);
    l1 += __shfl_xor_sync(0xffffffffu, l1, 1);
    l0 += __shfl_xor_sync(0xffffffffu, l0, 2);
    l1 += __shfl_xor_sync(0xffffffffu, l1, 2);
    i0 = rcp(l0);
    i1 = rcp(l1);
}

__device__ __forceinline__ uint32_t get_epoch(uint32_t sbase) { return __float_as_uint(lds32f(sbase + OFF_EPOCH)); }
__device__ __forceinline__ float silu_bf16(unsigned short c) {
    const float cv = bf_lo(c);
    return round_bf16(cv * rcp(1.f + ex2(-1.4426950408889634f * cv)));
}
__device__ __forceinline__ void st_mod(uint32_t* p, float v, uint32_t tag) {
    asm volatile("st.relaxed.gpu.global.u32 [%0], %1;" ::"l"(p), "r"(__float_as_uint(round_bf16(v)) | tag)
                 : "memory");
}
__device__ __forceinline__ void fma8(float (&acc)[8], float sc, const uint4& w) {
    acc[0] = fmaf(sc, bf_lo(w.x), acc[0]);
    acc[1] = fmaf(sc, bf_hi(w.x), acc[1]);
    acc[2] = fmaf(sc, bf_lo(w.y), acc[2]);
    acc[3] = fmaf(sc, bf_hi(w.y), acc[3]);
    acc[4] = fmaf(sc, bf_lo(w.z), acc[4]);
    acc[5] = fmaf(sc, bf_hi(w.z), acc[5]);
    acc[6] = fmaf(sc, bf_lo(w.w), acc[6]);
    acc[7] = fmaf(sc, bf_hi(w.w), acc[7]);
}
__global__ void __cluster_dims__(2, 1, 1) __launch_bounds__(384, 1)
    fused_block_kernel(const __grid_constant__ Params maps) {
    extern __shared__ uint8_t smem_raw[];
    uint32_t sbase = (smem_u32(smem_raw) + 1023u) & ~1023u;
    asm volatile("" : "+r"(sbase));
    const int b = blockIdx.x;
    const int rank = b & 1;
    const int mt = ((b >> 1) & 7) * 2 + rank;
    const int g = b >> 4;
    const int warp = __shfl_sync(0xffffffffu, threadIdx.x >> 5, 0);
    const int lane = threadIdx.x & 31;
    Scratch* const sc_ = maps.sc;
    const __nv_bfloat16* const wmod = maps.wmod;
    const __nv_bfloat16* const cvec = maps.cvec;

#define SPROF(i)

    if (warp >= 8) {
        asm volatile("setmaxnreg.dec.sync.aligned.u32 24;");
        if (warp == 8 && lane == 0) {
#pragma unroll
            for (int i = 0; i < 8; i++) {
                mbar_init(sbase + OFF_FULL + i * 8, 1);
                mbar_init(sbase + OFF_EMPTY + i * 8, 4);
            }
            mbar_init(sbase + OFF_XBAR, 1);
            asm volatile("fence.mbarrier_init.release.cluster;" ::: "memory");
            asm volatile("barrier.cluster.arrive.relaxed;\nbarrier.cluster.wait;" ::: "memory");
            uint32_t slot = 0, phase = 1;
            const uint32_t dst0 = sbase + rank * BOX_BYTES;
            auto acquire = [&](uint32_t bytes) {
                mbar_wait(sbase + OFF_EMPTY + slot * 8, phase);
                mbar_expect_tx(sbase + OFF_FULL + slot * 8, bytes);
            };
            auto adv8 = [&]() {
                if (++slot == 8) {
                    slot = 0;
                    phase ^= 1;
                }
            };
#pragma unroll 1
            for (int hq = 0; hq < 4; hq++) {
                const int col = (g * 4 + ((hq + 1) & 3)) * 128 + rank * 64;
                if (hq == 2) {
                    l2_prefetch(maps.kc + (size_t)(g * 4 * 2048 + (b & 15) * 64) * 128, SLOT_BYTES);
                    l2_prefetch(maps.vc + (size_t)(g * 4 * 2048 + (b & 15) * 64) * 128, SLOT_BYTES);
                }
#pragma unroll 1
                for (int kc = 0; kc < 9; kc++) {
                    acquire(SLOT_BYTES);
                    tma_mc(dst0 + slot * SLOT_BYTES, &maps.wq, col, kc * 64, sbase + OFF_FULL + slot * 8);
                    adv8();
                }
            }
            const int row0 = g * 4 * 2048;
#pragma unroll 1
            for (int n = 0; n < 128; n++) {
                if (n < 4) mbar_wait(sbase + OFF_EMPTY + (slot + 1) * 8, phase);
                acquire(2 * SLOT_BYTES);
                const uint32_t bar = sbase + OFF_FULL + slot * 8;
                const int r0 = n == 0 ? 0 : (n == 127 ? 126 : n + 1);
                const int r1 = n == 0 ? 1 : (n == 127 ? 127 : n - 1);
                tma_mc(dst0 + slot * SLOT_BYTES, n == 127 ? &maps.v : &maps.k, rank * 64, row0 + r0 * 64, bar);
                tma_mc(dst0 + (slot + 1) * SLOT_BYTES, n == 0 ? &maps.k : &maps.v, rank * 64, row0 + r1 * 64, bar);
                adv8();
                adv8();
                const int u = n + KV_AHEAD;
                if (u < 128 && (u & 15) == (b & 15)) {
                    l2_prefetch(maps.kc + (size_t)(row0 + u * 64) * 128, SLOT_BYTES);
                    l2_prefetch(maps.vc + (size_t)(row0 + u * 64) * 128, SLOT_BYTES);
                }
            }
#pragma unroll 1
            for (int p = 0; p < 4; p++)
#pragma unroll 1
                for (int kc = 0; kc < 8; kc++) {
                    acquire(SLOT_BYTES);
                    tma_mc(dst0 + slot * SLOT_BYTES, &maps.wo, p * 128 + rank * 64, g * 512 + ((kc + 6) & 7) * 64,
                           sbase + OFF_FULL + slot * 8);
                    adv8();
                }
#pragma unroll 1
            for (int kc = 0; kc < 4; kc++) {
                acquire(SLOT_BYTES);
                tma_mc(dst0 + slot * SLOT_BYTES, &maps.wo, 512, g * 512 + ((kc + 3) & 3) * 128 + rank * 64,
                       sbase + OFF_FULL + slot * 8);
                adv8();
            }
            const CUtensorMap* mg = rank ? &maps.wu : &maps.wg;
#pragma unroll 1
            for (int ch = 0; ch < 9; ch++)
#pragma unroll 1
                for (int kc = 0; kc < 9; kc++) {
                    acquire(SLOT_BYTES);
                    tma_mc(dst0 + slot * SLOT_BYTES, mg, g * 576 + ch * 64, kc * 64, sbase + OFF_FULL + slot * 8);
                    adv8();
                }
#pragma unroll 1
            for (int p = 0; p < 4; p++)
#pragma unroll 1
                for (int i = 0; i < 9; i++) {
                    acquire(SLOT_BYTES);
                    tma_mc(dst0 + slot * SLOT_BYTES, &maps.wd, p * 128 + rank * 64,
                           g * 576 + (i == 0 ? 8 : (i < 7 ? i + 1 : i - 7)) * 64, sbase + OFF_FULL + slot * 8);
                    adv8();
                }
#pragma unroll 1
            for (int i2 = 0; i2 < 5; i2++) {
                acquire(i2 < 4 ? SLOT_BYTES : BOX_BYTES);
                const int i = 2 * i2 + rank;
                if (i < 9)
                    tma_mc(dst0 + slot * SLOT_BYTES, &maps.wd, 512, g * 576 + (i == 0 ? 8 : (i < 7 ? i + 1 : i - 7)) * 64,
                           sbase + OFF_FULL + slot * 8);
                adv8();
            }
        } else if (warp == 11) {
            asm volatile("barrier.cluster.arrive.relaxed.aligned;" ::: "memory");
            bar_sync(6, 160);
            uint4* hz = sc_->h[(get_epoch(sbase) & 1) ^ 1][0] + (size_t)b * 72 * 32 + lane;
#pragma unroll 1
            for (int i = 0; i < 72; i++) {
                hz[i * 32] = make_uint4(0, 0, 0, 0);
                __nanosleep(200);
            }
            bar_sync(6, 160);
            if (lane == 0) {
#pragma unroll 1
                for (int i = 0; i < 9; i++) {
                    l2_prefetch((const char*)maps.wo_p + (size_t)b * 36864 + i * 4096, 4096);
                    __nanosleep(400);
                    l2_prefetch((const char*)maps.wg_p + (size_t)b * 41472 + i * 4608, 4608);
                    __nanosleep(400);
                    l2_prefetch((const char*)maps.wu_p + (size_t)b * 41472 + i * 4608, 4608);
                    __nanosleep(400);
                    l2_prefetch((const char*)maps.wd_p + (size_t)b * 41472 + i * 4608, 4608);
                    __nanosleep(400);
                }
            }
        } else if (warp == 9 || warp == 10) {
            asm volatile("barrier.cluster.arrive.relaxed.aligned;" ::: "memory");
            bar_sync(11, 320);
            if (warp == 10) {
                if (lane < 9) l2_prefetch((const char*)maps.wq_p + (size_t)b * 36864 + lane * 4096, 4096);
                __syncwarp();
            } else if (b < 36) {
                const uint32_t ep = get_epoch(sbase) + 1, t0 = clk32();
                const uint32_t* src = sc_->modp[0] + b * 32 + lane;
                uint32_t u[6];
                while (true) {
                    uint32_t bad = 0;
#pragma unroll
                    for (int i = 0; i < 6; i++)
                        asm volatile("ld.relaxed.gpu.global.u32 %0, [%1];" : "=r"(u[i]) : "l"(src + i * 2 * DM));
#pragma unroll
                    for (int i = 0; i < 6; i++) bad |= u[i] ^ ep;
                    if (__all_sync(0xffffffffu, (bad & 0xffu) == 0) || clk32() - t0 > WAIT_LIMIT) break;
                }
                float sum = 0.f;
#pragma unroll
                for (int i = 0; i < 6; i++) sum += __uint_as_float(u[i] & ~0xffu);
                st_mod(sc_->mod + b * 32 + lane, sum, ep & 0xffffu);
            }
            bar_sync(4, 320);
            const uint32_t tag = (get_epoch(sbase) + 1) & 0xffffu;
            const int blk = warp == 9 ? 72 + b : 200 + b;
            if (blk < 216) {
                float acc[8];
#pragma unroll
                for (int e = 0; e < 8; e++) acc[e] = 0.f;
                const uint4* wp = reinterpret_cast<const uint4*>(wmod + (size_t)(lane >> 1) * (6 * DM) + blk * 16) + (lane & 1);
                const unsigned short* cp = reinterpret_cast<const unsigned short*>(cvec) + (lane >> 1);
#pragma unroll 1
                for (int i = 0; i < 36; i++) {
                    const uint4 w = __ldg(wp + (size_t)i * (16 * 6 * DM / 8));
                    const float sc = silu_bf16(__ldg(cp + i * 16));
                    fma8(acc, sc, w);
                }
#pragma unroll
                for (int o = 2; o < 32; o <<= 1)
#pragma unroll
                    for (int e = 0; e < 8; e++) acc[e] += __shfl_xor_sync(0xffffffffu, acc[e], o);
                if (lane < 2) {
#pragma unroll
                    for (int e = 0; e < 8; e++) st_mod(sc_->mod + blk * 16 + lane * 8 + e, acc[e], tag);
                }
            }
            if (warp == 9) {
#pragma unroll 1
                for (int st = 1; st <= 2; st++) {
                    bar_sync(7, 160);
                    const uint32_t* src = sc_->mod + (st * 3 - 1) * DM;
                    const int n = st == 1 ? 3 * DM : DM;
#pragma unroll 1
                    for (int i = lane * 4; i < n + 127 - ((n + 127) & 127); i += 128)
                        mod_to_smem(ld128(reinterpret_cast<const uint4*>(src + min(i, n - 4))), sbase + OFF_MODT + min(i, n - 4) * 4,
                                    src + min(i, n - 4), tag);
                    __syncwarp();
                    if (lane == 0) rows_load(sbase, st == 1 ? &maps.rx : &maps.rx2, (mt * 8 + g) * 16);
                    if (st == 1) {
                        bar_sync(7, 160);
                        if (lane == 0) {
                            rows_store(sbase, &maps.rx2, (mt * 8 + g) * 16);
                            rows_store_wait();
                        }
                        __syncwarp();
                        bar_arrive(10, 160);
                    }
                }
            }
        }
    } else {
        uint4 w1[3], xw[5], ew = make_uint4(0, 0, 0, 0);
        unsigned short cu[3];
        {
            const int t = threadIdx.x, bw = min(b, 107);
            const int row = (bw / 18) * 96 + (t >> 3);
#pragma unroll
            for (int i = 0; i < 3; i++) {
                w1[i] = ldg128(reinterpret_cast<const uint4*>(wmod + (size_t)(row + 32 * i) * (6 * DM)) + (bw % 18) * 8 + (t & 7));
                asm volatile("ld.global.nc.u16 %0, [%1];" : "=h"(cu[i]) : "l"(cvec + row + 32 * i));
            }
            if (t == 0) ew = ld128(reinterpret_cast<const uint4*>(&sc_->epoch[b * 32]));
#pragma unroll
            for (int i = 0; i < 5; i++)
                xw[i] = ldg128(reinterpret_cast<const uint4*>(maps.x + (size_t)(mt * 8 + g) * 16 * DM) + min(t + 256 * i, 1151));
        }
        if (threadIdx.x == 160) SPROF(5);
        asm volatile("setmaxnreg.inc.sync.aligned.u32 240;");
        if (threadIdx.x == 160) SPROF(6);
        const int wg = warp >> 2;
        const int tid = threadIdx.x;
        Ctx cx;
        cx.sbase = sbase;
        cx.wg = wg;
        if (wg == 1) bar_arrive(8, 256);
        cx.rel_cta = (lane == 0 && (warp & 3) < 2) ? (warp & 3) : 2;
        const uint32_t red = sbase + OFF_RED;
        const int own = mt * 8 + g;
        const int wown = mt * 8 + warp;
        PROF(0);
        PROFG(30);
        PROFR(17);
        {
            asm volatile("barrier.cluster.arrive.relaxed.aligned;" ::: "memory");
            float acc[8];
#pragma unroll
            for (int e = 0; e < 8; e++) acc[e] = 0.f;
#pragma unroll
            for (int i = 0; i < 3; i++) fma8(acc, silu_bf16(cu[i]), w1[i]);
#pragma unroll
            for (int o = 8; o < 32; o <<= 1)
#pragma unroll
                for (int e = 0; e < 8; e++) acc[e] += __shfl_xor_sync(0xffffffffu, acc[e], o);
            PROFR(19);
            if (lane < 8) {
                const uint32_t dst = sbase + OFF_MRED + warp * 256 + lane * 32;
                sts128(dst, __float_as_uint(acc[0]), __float_as_uint(acc[1]), __float_as_uint(acc[2]), __float_as_uint(acc[3]));
                sts128(dst + 16, __float_as_uint(acc[4]), __float_as_uint(acc[5]), __float_as_uint(acc[6]), __float_as_uint(acc[7]));
            }
            if (tid == 0) sts128(sbase + OFF_EPOCH, ew.x, ew.y, ew.z, ew.w);
            bar_sync(3, 256);
            PROFR(20);
            if (tid < 64 && b < 108) {
                float sum = 0.f;
#pragma unroll
                for (int w8 = 0; w8 < 8; w8++) sum += lds32f(sbase + OFF_MRED + w8 * 256 + tid * 4);
                asm volatile("st.relaxed.gpu.global.u32 [%0], %1;" ::"l"(&sc_->modp[b / 18][(b % 18) * 64 + tid]),
                             "r"((__float_as_uint(sum) & ~0xffu) | ((get_epoch(sbase) + 1) & 0xffu))
                             : "memory");
            }
            PROFR(21);
#pragma unroll
            for (int i = 0; i < 5; i++) {
                const int vi = min(tid + 256 * i, 1151), ln = vi >> 3;
                sts128(sbase + OFF_ROWS + ln * 128 + (((vi & 7) ^ (ln & 7)) << 4), xw[i].x, xw[i].y, xw[i].z, xw[i].w);
            }
            bar_sync(3, 256);
            bar_arrive(11, 320);
        }

        Ring ring{0u, 0u};
        int stage = 0;
        asm volatile("" : "+r"(stage));
#pragma unroll 1
        for (;; stage++) {
            int tid, lane;
            asm volatile("mov.u32 %0, %%tid.x;" : "=r"(tid));
            lane = tid & 31;
            const uint32_t epoch = get_epoch(sbase);
            {
                float v[36];
                const uint32_t modt = sbase + OFF_MODT + (warp * 16 + (lane & 3) * 2) * 4;
                if (stage == 0) {
#pragma unroll
                    for (int i = 0; i < 36; i++) v[i] = 0.f;
                } else {
                    const uint4* psrc = sc_->part + (size_t)own * 8 * 36 * 32;
                    sum_partials(v, psrc + tid, stage & 1);
                    PROF(stage == 1 ? 8 : 15);
                    sum_tail(v, reinterpret_cast<const uint2*>(psrc + 32 * 32) + tid, stage & 1);
                }
                if (stage) mbar_wait(sbase + OFF_XBAR, stage - 1);
                if (stage == 0) PROFR(22);
                {
                    const float gs = stage == 2 ? 0.5f : 1.f;
                    float gate[18];
                    lds_mod(gate, modt, warp);
                    const int r = lane >> 2;
                    const uint32_t rows = sbase + OFF_ROWS + r * (DM * 2) + (lane & 3) * 4;
#pragma unroll
                    for (int j = 0; j < 9; j++) {
                        const int ch = j < 8 ? (j >> 1) * 2 + (warp >> 2) : 8, c16 = j < 8 ? (warp & 3) * 2 + (j & 1) : warp;
                        const uint32_t ad = rows + ch * 128 + ((c16 ^ ((r + ch) & 7)) << 4);
                        const uint32_t u0 = __float_as_uint(lds32f(ad)), u1 = __float_as_uint(lds32f(ad + 8 * DM * 2));
                        const float g0 = stage ? gate[2 * j] * gs : 0.f, g1 = stage ? gate[2 * j + 1] * gs : 0.f;
                        v[4 * j] = fmaf(g0, v[4 * j], bf_lo(u0));
                        v[4 * j + 1] = fmaf(g1, v[4 * j + 1], bf_hi(u0));
                        v[4 * j + 2] = fmaf(g0, v[4 * j + 2], bf_lo(u1));
                        v[4 * j + 3] = fmaf(g1, v[4 * j + 3], bf_hi(u1));
                        sts32f(ad, __uint_as_float(pack_bf16(v[4 * j], v[4 * j + 1])));
                        sts32f(ad + 8 * DM * 2, __uint_as_float(pack_bf16(v[4 * j + 2], v[4 * j + 3])));
                    }
                    asm volatile("fence.proxy.async.shared::cta;" ::: "memory");
                }
                if (stage == 2) break;
                PROF(stage == 0 ? 1 : 9);
                layernorm_rows(v, red, warp, lane, []() {});
                if (stage == 0) PROFR(27);
                if (stage == 0) {
                    const uint32_t tag = (epoch + 1) & 0xffffu;
                    const uint32_t* ms = sc_->mod + tid * 4;
                    const uint4 ua = ld128(reinterpret_cast<const uint4*>(ms));
                    if (warp == 0)
                        mod_to_smem(ld128(reinterpret_cast<const uint4*>(ms + 1024)), sbase + OFF_MODT + (DM + 1024 + tid * 4) * 4,
                                    ms + 1024, tag);
                    mod_to_smem(ua, sbase + OFF_MODT + (DM + tid * 4) * 4, ms, tag);
                    bar_sync(3, 256);
                }
                float shift[18], scale[18];
                lds_mod(shift, modt + DM * 4, warp);
                lds_mod(scale, modt + 2 * DM * 4, warp);
                if (stage == 0) PROFR(28);
                PROF(stage == 0 ? 2 : 10);
                modulate_store(v, shift, scale, stage == 0 ? SM_SCALE : 1.f, sc_->h[epoch & 1][stage] + (size_t)own * 36 * 32, warp, lane);
                if (stage == 0) asm volatile("barrier.cluster.wait.aligned;" ::: "memory");
            }

            const uint32_t spill = sbase + 8 * SLOT_BYTES + wg * 3 * SLOT_BYTES + (tid & 127) * 16;
            uint32_t a[144];
            PROF(stage == 0 ? 3 : 11);
            {
                const uint4* hsrc = sc_->h[epoch & 1][stage] + (size_t)wown * 36 * 32 + lane;
                __nanosleep(PROBE_NS);
                poll_tail(a, reinterpret_cast<const uint2*>(hsrc - lane + 32 * 32) + lane);
                PROF(stage == 0 ? 4 : 12);
                if (stage == 1) PROFG(25);
                TG(stage * 32 + 30);
                if (wg == 1) bar_sync(5, 256);
                poll_frags<0, 32>(a, hsrc, wg == 0);
                if (stage == 0) bar_arrive(4, 320);
            }
            uint4* hhbuf = sc_->hh + (size_t)b * 8 * 256 + tid;
            float d[64];
#pragma unroll 1
            for (int ch = 0;; ch++) {
                TG(stage * 32 + ch * 2);
                gemm_n128(d, a, cx, ring, true, stage && wg);
                TG(stage * 32 + ch * 2 + 1);
                if (stage == 0) {
                    if (ch == 3) break;
#pragma unroll
                    for (int v = 0; v < 8; v++)
                        sts128(spill + (ch * 8 + v) * 2048, pack_bf16(d[8 * v], d[8 * v + 1]),
                               pack_bf16(d[8 * v + 2], d[8 * v + 3]), pack_bf16(d[8 * v + 4], d[8 * v + 5]),
                               pack_bf16(d[8 * v + 6], d[8 * v + 7]));
                } else {
#pragma unroll
                    for (int i = 0; i < 32; i++) {
                        const float gv = d[i], gu = gv * d[32 + i];
                        const float z = gv * fmaf(gv * gv, 0.7978845608028654f * 0.044715f, 0.7978845608028654f);
                        d[i] = fmaf(gu, tanh_fast(z), gu);
                    }
                    if (ch == 8) break;
                    if (wg == 0) {
                        if (ch == 0) bar_arrive(7, 160);
                        if (ch == 2) bar_sync(10, 160);
                    }
#pragma unroll
                    for (int v = 0; v < 4; v++) {
                        const uint4 h4 = make_uint4(pack_bf16(d[8 * v], d[8 * v + 1]), pack_bf16(d[8 * v + 2], d[8 * v + 3]),
                                                    pack_bf16(d[8 * v + 4], d[8 * v + 5]), pack_bf16(d[8 * v + 6], d[8 * v + 7]));
                        if (ch < 2)
                            __stcg(hhbuf + (ch * 4 + v) * 256, h4);
                        else
                            sts128(spill + ((ch - 2) * 4 + v) * 2048, h4.x, h4.y, h4.z, h4.w);
                    }
                }
            }
            if (stage == 0) {
                uint32_t q[32];
#pragma unroll
                for (int i = 0; i < 32; i++) q[i] = pack_bf16(d[2 * i], d[2 * i + 1]);
                PROF(5);
                PROFG(23);
                if (wg == 0) bar_arrive(6, 160);
                {
                    float o[64], sa[32], sb[32];
                    uint32_t pa[16], pb[16];
#pragma unroll
                    for (int i = 0; i < 64; i++) o[i] = 0.f;
                    float n0 = 0.f, n1 = 0.f, l0 = 1.f, l1 = 1.f;
                    bool shifted = false;
                    const uint64_t dbase = desc_of(sbase);
                    const uint64_t dbk = dbase - (511u << 16);
                    const int my_bar = 1 + wg, other_bar = 2 - wg;

                    auto softmax_a = [&](bool first, float& s0, float& s1) {
                        if (first) {
                            shifted = false;
                            n0 = n1 = 0.f;
                            l0 = l1 = 0.f;
                        }
                        if (shifted)
                            exp_step<true>(sa, pa, n0, n1, s0, s1);
                        else
                            exp_step<false>(sa, pa, n0, n1, s0, s1);
                    };
                    auto softmax_b = [&](bool first, float s0, float s1) {
                        float u0, u1;
                        if (shifted)
                            exp_step<true>(sb, pb, n0, n1, u0, u1);
                        else
                            exp_step<false>(sb, pb, n0, n1, u0, u1);
                        s0 += u0;
                        s1 += u1;
                        bool bad = !(fmaxf(s0, s1) <= SM_HI);
                        if (first) {
                            float r0 = s0 + __shfl_xor_sync(0xffffffffu, s0, 1), r1 = s1 + __shfl_xor_sync(0xffffffffu, s1, 1);
                            r0 += __shfl_xor_sync(0xffffffffu, r0, 2);
                            r1 += __shfl_xor_sync(0xffffffffu, r1, 2);
                            bad = bad || !(fminf(r0, r1) >= SM_LO);
                        }
                        if (__any_sync(0xffffffffu, bad)) {
                            float x0, x1;
                            row_max(sa, sb, x0, x1);
                            x0 = -x0;
                            x1 = -x1;
                            if (!first) {
                                x0 = fminf(x0, n0);
                                x1 = fminf(x1, n1);
                                const float al0 = ex2(x0 - n0), al1 = ex2(x1 - n1);
                                l0 *= al0;
                                l1 *= al1;
#pragma unroll
                                for (int i = 0; i < 16; i++) {
                                    o[4 * i] *= al0;
                                    o[4 * i + 1] *= al0;
                                    o[4 * i + 2] *= al1;
                                    o[4 * i + 3] *= al1;
                                }
                            }
                            n0 = x0;
                            n1 = x1;
                            shifted = true;
                            exp_step<true>(sa, pa, n0, n1, s0, s1);
                            exp_step<true>(sb, pb, n0, n1, u0, u1);
                            s0 += u0;
                            s1 += u1;
                        }
                        l0 += s0;
                        l1 += s1;
                    };

                    cx.wait_full(4, 0);
                    if (wg == 1) bar_sync(my_bar, 256);
                    wg_fence();
                    qk_step(sa, q, dbk + 4 * 1024);
                    qk_step(sb, q, dbk + 5 * 1024);
                    wg_commit();
                    bar_arrive(other_bar, 256);
                    wg_wait<0>();
                    pin(sa);
                    pin(sb);
                    cx.release(4);
                    cx.wait_full(6, 0);
                    {
                        float s0, s1;
                        softmax_a(true, s0, s1);
                        softmax_b(true, s0, s1);
                    }
                    uint32_t alo = (uint32_t)dbase + 6 * 1024, blo = (uint32_t)dbase;
                    const uint32_t dhi = (uint32_t)(dbase >> 32);
#pragma unroll 1
                    for (int t = 1; t < 64; t++) {
                        const int j = t & 15;
                        const uint32_t sA = 2 + 4 * (t & 1), sB = 4 - 4 * (t & 1);
                        const uint64_t da = ((uint64_t)dhi << 32) | alo, db = ((uint64_t)dhi << 32) | blo;
                        TL(0);
                        bar_sync(my_bar, 256);
                        TL(2);
                        wg_fence();
                        pv_step(o, pa, da + 1024, j != 1);
                        qk_step(sa, q, da - (511u << 16));
                        wg_commit();
                        cx.wait_full(sB, ((36 + 4 * t) >> 3) & 1);
                        wg_fence();
                        qk_step(sb, q, db - (511u << 16));
                        pv_step(o, pb, db + 1024, 1);
                        wg_commit();
                        bar_arrive(other_bar, 256);
                        alo ^= 4096;
                        blo ^= 4096;
                        asm volatile("" : "+r"(alo), "+r"(blo));
                        TL(3);
                        wg_wait<1>();
                        pin(sa);
                        pin(pa);
                        TL(4);
                        cx.release(sA);
                        const float lp0 = l0, lp1 = l1;
                        float s0, s1;
                        softmax_a(j == 0, s0, s1);
                        TL(5);
                        wg_wait<0>();
                        pin(o);
                        pin(sb);
                        pin(pb);
                        TL(6);
                        cx.release(sB);
                        if (j == 0) {
                            float i0, i1;
                            inv_row_sums(lp0, lp1, i0, i1);
                            const uint32_t dst = spill + ((t >> 4) - 1) * 16384;
#pragma unroll
                            for (int v = 0; v < 8; v++)
                                sts128(dst + v * 2048, pack_bf16(o[8 * v] * i0, o[8 * v + 1] * i0),
                                       pack_bf16(o[8 * v + 2] * i1, o[8 * v + 3] * i1),
                                       pack_bf16(o[8 * v + 4] * i0, o[8 * v + 5] * i0),
                                       pack_bf16(o[8 * v + 6] * i1, o[8 * v + 7] * i1));
                        }
                        const uint32_t bn = sbase + OFF_FULL + (8 - sA) * 8, pn = ((38 + 4 * t) >> 3) & 1;
                        const bool okn = mbar_try(bn, pn);
                        TL(1);
                        softmax_b(j == 0, s0, s1);
                        if (!okn || j == 15) {
                            mbar_wait(bn, pn);
                            if (t == 47 && wg == 0) bar_arrive(6, 160);
                            if (j == 15 && t < 63) {
                                const uint32_t src = spill + (t >> 4) * 16384;
#pragma unroll
                                for (int v = 0; v < 8; v++)
                                    lds128(src + v * 2048, q[4 * v], q[4 * v + 1], q[4 * v + 2], q[4 * v + 3]);
                            }
                        }
                        TL(7);
                    }
                    bar_sync(my_bar, 256);
                    wg_fence();
                    pv_step(o, pa, dbase + 2 * 1024, 1);
                    pv_step(o, pb, dbase + 3 * 1024, 1);
                    wg_commit();
                    if (wg == 0) bar_arrive(other_bar, 256);
                    float i0, i1;
                    inv_row_sums(l0, l1, i0, i1);
                    wg_wait<0>();
                    pin(o);
                    cx.release(2);
#pragma unroll
                    for (int i = 0; i < 16; i++) {
                        a[2 * i] = pack_bf16(o[4 * i] * i0, o[4 * i + 1] * i0);
                        a[2 * i + 1] = pack_bf16(o[4 * i + 2] * i1, o[4 * i + 3] * i1);
                    }
#pragma unroll
                    for (int v = 0; v < 24; v++)
                        lds128(spill + v * 2048, a[32 + 4 * v], a[33 + 4 * v], a[34 + 4 * v], a[35 + 4 * v]);
#pragma unroll
                    for (int i = 128; i < 144; i++) a[i] = 0;
                }
                ring.slot = 4;
                ring.phase = 0;
                PROF(6);
                PROFG(24);
            } else {
#pragma unroll
                for (int v = 0; v < 8; v++) {
                    const uint4 t = __ldcg(hhbuf + v * 256);
                    a[112 + 4 * v] = t.x;
                    a[113 + 4 * v] = t.y;
                    a[114 + 4 * v] = t.z;
                    a[115 + 4 * v] = t.w;
                }
#pragma unroll
                for (int i = 0; i < 16; i++) a[i] = pack_bf16(d[2 * i], d[2 * i + 1]);
#pragma unroll
                for (int v = 0; v < 24; v++)
                    lds128(spill + v * 2048, a[16 + 4 * v], a[17 + 4 * v], a[18 + 4 * v], a[19 + 4 * v]);
                PROF(13);
            }

            {
                uint4* dst = sc_->part + ((size_t)wown * 8 + g) * 36 * 32 + lane;
                const uint32_t ptag = (stage + 1) & 1;
#pragma unroll 1
                for (int p = 0; p < 4; p++) {
                    TG(stage * 32 + 18 + p * 2);
                    gemm_n128(d, a, cx, ring, stage != 0, stage && wg);
                    TG(stage * 32 + 19 + p * 2);
#pragma unroll
                    for (int u = 0; u < 8; u++)
                        st128(dst + (p * 8 + u) * 32, (pack_bf16(d[8 * u], d[8 * u + 1]) & ~1u) | ptag,
                              pack_bf16(d[8 * u + 2], d[8 * u + 3]), pack_bf16(d[8 * u + 4], d[8 * u + 5]),
                              pack_bf16(d[8 * u + 6], d[8 * u + 7]));
                    if (p == 0 && wg == 0) bar_arrive(7, 160);
                }
                float e[32];
                TG(stage * 32 + 26);
                gemm_n64(e, a, cx, ring, stage != 0);
                TG(stage * 32 + 27);
                uint2* dst2 = reinterpret_cast<uint2*>(dst - lane + 32 * 32) + lane;
#pragma unroll
                for (int j = 0; j < 8; j++)
                    st64(dst2 + j * 32, (pack_bf16(e[4 * j], e[4 * j + 1]) & ~1u) | ptag, pack_bf16(e[4 * j + 2], e[4 * j + 3]));
            }
            PROF(stage == 0 ? 7 : 14);
            if (stage == 1) {
                PROFG(26);
                asm volatile("barrier.cluster.arrive.relaxed.aligned;" ::: "memory");
            }
        }
        if (wg == 0) bar_sync(8, 256);
        bar_sync(3, 256);
        if (tid == 32) sc_->epoch[b * 32] = get_epoch(sbase) + 1;
        if (tid == 0) {
            rows_store(sbase, &maps.rout, own * 16);
            rows_store_wait();
        }
        __syncwarp();
        PROF(16);
        PROFG(31);
        asm volatile("barrier.cluster.wait.aligned;" ::: "memory");
    }
}

typedef CUresult (*EncodeFn)(CUtensorMap*, CUtensorMapDataType, cuuint32_t, void*, const cuuint64_t*, const cuuint64_t*,
                             const cuuint32_t*, const cuuint32_t*, CUtensorMapInterleave, CUtensorMapSwizzle,
                             CUtensorMapL2promotion, CUtensorMapFloatOOBfill);

void make_map(EncodeFn enc, CUtensorMap* m, const void* ptr, uint64_t rows, uint64_t cols, bool narrow = false) {
    cuuint64_t gdim[2] = {cols, rows};
    cuuint64_t gstr[1] = {cols * 2};
    cuuint32_t box[2] = {narrow ? 16u : 64u, narrow ? 192u : 64u};
    cuuint32_t estr[2] = {1, 1};
    enc(m, CU_TENSOR_MAP_DATA_TYPE_BFLOAT16, 2, const_cast<void*>(ptr), gdim, gstr, box, estr,
        CU_TENSOR_MAP_INTERLEAVE_NONE, narrow ? CU_TENSOR_MAP_SWIZZLE_NONE : CU_TENSOR_MAP_SWIZZLE_128B,
        CU_TENSOR_MAP_L2_PROMOTION_L2_128B,
        CU_TENSOR_MAP_FLOAT_OOB_FILL_NONE);
}

void make_rows_map(EncodeFn enc, CUtensorMap* m, const void* ptr) {
    cuuint64_t gdim[3] = {64, 9, 2048};
    cuuint64_t gstr[2] = {128, DM * 2};
    cuuint32_t box[3] = {64, 9, 16};
    cuuint32_t estr[3] = {1, 1, 1};
    enc(m, CU_TENSOR_MAP_DATA_TYPE_BFLOAT16, 3, const_cast<void*>(ptr), gdim, gstr, box, estr,
        CU_TENSOR_MAP_INTERLEAVE_NONE, CU_TENSOR_MAP_SWIZZLE_128B, CU_TENSOR_MAP_L2_PROMOTION_L2_128B,
        CU_TENSOR_MAP_FLOAT_OOB_FILL_NONE);
}

}

extern "C" void kernel_launch(void* const* d_in, const int* in_sizes, int n_in, void* d_out, int out_size) {
    (void)in_sizes;
    (void)n_in;
    (void)out_size;
    void* fn = nullptr;
    cudaDriverEntryPointQueryResult qr;
    cudaGetDriverEntryPoint("cuTensorMapEncodeTiled", &fn, cudaEnableDefault, &qr);
    EncodeFn enc = (EncodeFn)fn;
    Params maps;
    maps.x = (const __nv_bfloat16*)d_in[0];
    maps.cvec = (const __nv_bfloat16*)d_in[9];
    maps.wmod = (const __nv_bfloat16*)d_in[10];
    maps.kc = (const __nv_bfloat16*)d_in[1];
    maps.vc = (const __nv_bfloat16*)d_in[2];
    maps.wq_p = (const __nv_bfloat16*)d_in[3];
    maps.wo_p = (const __nv_bfloat16*)d_in[4];
    maps.wg_p = (const __nv_bfloat16*)d_in[6];
    maps.wu_p = (const __nv_bfloat16*)d_in[7];
    maps.wd_p = (const __nv_bfloat16*)d_in[8];
    maps.out = (__nv_bfloat16*)d_out;
    void* scp = nullptr;
    cudaGetSymbolAddress(&scp, g_scratch);
    maps.sc = (Scratch*)scp;
    make_map(enc, &maps.k, d_in[1], 32 * 2048, 128);
    make_map(enc, &maps.v, d_in[2], 32 * 2048, 128);
    make_map(enc, &maps.wq, d_in[3], 576, 4096);
    make_map(enc, &maps.wo, d_in[4], 4096, 576);
    make_map(enc, &maps.wg, d_in[6], 576, 4608);
    make_map(enc, &maps.wu, d_in[7], 576, 4608);
    make_map(enc, &maps.wd, d_in[8], 4608, 576);
    make_rows_map(enc, &maps.rx, d_in[0]);
    make_rows_map(enc, &maps.rx2, (char*)scp + offsetof(Scratch, x2));
    make_rows_map(enc, &maps.rout, d_out);
    cudaFuncSetAttribute(fused_block_kernel, cudaFuncAttributeMaxDynamicSharedMemorySize, SMEM_BYTES);
    fused_block_kernel<<<128, 384, SMEM_BYTES>>>(maps);
}
```

```cpp
#include <cuda_runtime.h>
#include <cuda_bf16.h>
#include <cuda.h>
#include <stdint.h>
#include <stddef.h>

namespace {

constexpr int DM = 576;
constexpr int SLOT_BYTES = 16384;
constexpr int BOX_BYTES = 8192;
constexpr int NUNITS = 14;
constexpr int SMEM_TAIL = NUNITS * SLOT_BYTES;
constexpr int SMEM_BYTES = SMEM_TAIL + 2048 + 1024;
constexpr int OFF_FULL = SMEM_TAIL;
constexpr int OFF_EMPTY = SMEM_TAIL + 64;
constexpr int OFF_RED = SMEM_TAIL + 128;

constexpr int KV_AHEAD = 16;
#define GATE_SLOT 4
#define PROBE0_NS 700
#define PROBE_NS 300
constexpr int OFF_XBAR = SMEM_TAIL + 1792;
constexpr int OFF_ROWS = 8 * SLOT_BYTES;
constexpr int OFF_MODT = OFF_ROWS + 20480;
constexpr int OFF_EPOCH = SMEM_TAIL + 1808;
constexpr int OFF_MRED = OFF_ROWS + 28672;

struct Scratch {
    unsigned epoch[128 * 32];
    uint32_t mod[6 * DM];
    uint32_t modp[3][2 * DM];
    uint4 h[2][2][128 * 36 * 32];
    uint4 part[128 * 8 * 36 * 32];
    uint4 hh[128 * 8 * 256];
    __nv_bfloat16 x2[2048 * DM];
};
__device__ Scratch g_scratch;

#define TG(i)
#define TL(i)
#define PROFR(i)
#define PROF(i)
#define PROFG(i)

struct Params {
    const __nv_bfloat16 *x, *cvec, *wmod, *kc, *vc, *wq_p, *wo_p, *wg_p, *wu_p, *wd_p;
    __nv_bfloat16* out;
    Scratch* sc;
    CUtensorMap k, v, wq, wo, wg, wu, wd, rx, rx2, rout;
};

__device__ __forceinline__ uint32_t smem_u32(const void* p) { return (uint32_t)__cvta_generic_to_shared(p); }
__device__ __forceinline__ void mbar_init(uint32_t a, uint32_t c) {
    asm volatile("mbarrier.init.shared::cta.b64 [%0], %1;" ::"r"(a), "r"(c) : "memory");
}
__device__ __forceinline__ void mbar_expect_tx(uint32_t a, uint32_t bytes) {
    asm volatile("mbarrier.arrive.expect_tx.shared::cta.b64 _, [%0], %1;" ::"r"(a), "r"(bytes) : "memory");
}
__device__ __forceinline__ bool mbar_try(uint32_t a, uint32_t ph) {
    uint32_t ok;
    asm volatile(
        "{\n.reg .pred p;\nmbarrier.try_wait.parity.shared::cta.b64 p, [%1], %2;\nselp.u32 %0, 1, 0, p;\n}"
        : "=r"(ok)
        : "r"(a), "r"(ph)
        : "memory");
    return ok != 0;
}
__device__ __forceinline__ uint32_t clk32() {
    uint32_t c;
    asm volatile("mov.u32 %0, %%clock;" : "=r"(c));
    return c;
}
constexpr uint32_t WAIT_LIMIT = 1u << 30;
__device__ __forceinline__ void mbar_wait(uint32_t a, uint32_t ph) {
    if (mbar_try(a, ph)) return;
    uint32_t t0 = clk32();
    while (!mbar_try(a, ph)) {
        if (clk32() - t0 > WAIT_LIMIT) break;
    }
}
__device__ __forceinline__ void mbar_arrive_cluster(uint32_t a, uint32_t cta) {
    asm volatile(
        "{\n.reg .b32 ra;\nmapa.shared::cluster.u32 ra, %0, %1;\nmbarrier.arrive.shared::cluster.b64 _, [ra];\n}" ::"r"(a),
        "r"(cta)
        : "memory");
}
__device__ __forceinline__ void tma_mc(uint32_t dst, const CUtensorMap* m, int c0, int c1, uint32_t bar) {
    asm volatile(
        "cp.async.bulk.tensor.2d.shared::cluster.global.mbarrier::complete_tx::bytes.multicast::cluster"
        " [%0], [%1, {%3, %4}], [%2], %5;" ::"r"(dst),
        "l"(m), "r"(bar), "r"(c0), "r"(c1), "h"((uint16_t)3)
        : "memory");
}
__device__ __forceinline__ void bulk_load(uint32_t dst, const void* src, uint32_t bytes, uint32_t bar) {
    asm volatile("cp.async.bulk.shared::cluster.global.mbarrier::complete_tx::bytes [%0], [%1], %2, [%3];" ::"r"(dst),
                 "l"(src), "r"(bytes), "r"(bar)
                 : "memory");
}
__device__ __forceinline__ void l2_prefetch(const void* p, uint32_t bytes) {
    asm volatile("cp.async.bulk.prefetch.L2.global [%0], %1;" ::"l"(p), "r"(bytes) : "memory");
}
__device__ __forceinline__ void bar_sync(int id, int n) { asm volatile("bar.sync %0, %1;" ::"r"(id), "r"(n) : "memory"); }
__device__ __forceinline__ void bar_arrive(int id, int n) {
    asm volatile("bar.arrive %0, %1;" ::"r"(id), "r"(n) : "memory");
}
__device__ __forceinline__ void wg_fence() { asm volatile("wgmma.fence.sync.aligned;" ::: "memory"); }
__device__ __forceinline__ void wg_commit() { asm volatile("wgmma.commit_group.sync.aligned;" ::: "memory"); }
template <int N>
__device__ __forceinline__ void wg_wait() {
    asm volatile("wgmma.wait_group.sync.aligned %0;" ::"n"(N) : "memory");
}
template <int N>
__device__ __forceinline__ void pin(float (&d)[N]) {
#pragma unroll
    for (int i = 0; i < N; i++) asm volatile("" : "+f"(d[i])::"memory");
}
template <int N>
__device__ __forceinline__ void pin(uint32_t (&d)[N]) {
#pragma unroll
    for (int i = 0; i < N; i++) asm volatile("" : "+r"(d[i])::"memory");
}
__device__ __forceinline__ uint32_t pack_bf16(float lo, float hi) {
    uint32_t r;
    asm("cvt.rn.bf16x2.f32 %0, %1, %2;" : "=r"(r) : "f"(hi), "f"(lo));
    return r;
}
__device__ __forceinline__ float bf_lo(uint32_t v) { return __uint_as_float(v << 16); }
__device__ __forceinline__ float bf_hi(uint32_t v) { return __uint_as_float(v & 0xffff0000u); }
__device__ __forceinline__ float round_bf16(float v) { return __bfloat162float(__float2bfloat16_rn(v)); }
__device__ __forceinline__ float ex2(float x) {
    float y;
    asm("ex2.approx.ftz.f32 %0, %1;" : "=f"(y) : "f"(x));
    return y;
}
__device__ __forceinline__ float rcp(float x) {
    float y;
    asm("rcp.approx.ftz.f32 %0, %1;" : "=f"(y) : "f"(x));
    return y;
}
__device__ __forceinline__ float tanh_fast(float x) {
    float y;
    asm("tanh.approx.f32 %0, %1;" : "=f"(y) : "f"(x));
    return y;
}
__device__ __forceinline__ void sts128(uint32_t a, uint32_t x, uint32_t y, uint32_t z, uint32_t w) {
    asm volatile("st.shared.v4.b32 [%0], {%1,%2,%3,%4};" ::"r"(a), "r"(x), "r"(y), "r"(z), "r"(w) : "memory");
}
__device__ __forceinline__ void lds128(uint32_t a, uint32_t& x, uint32_t& y, uint32_t& z, uint32_t& w) {
    asm volatile("ld.shared.v4.b32 {%0,%1,%2,%3}, [%4];" : "=r"(x), "=r"(y), "=r"(z), "=r"(w) : "r"(a) : "memory");
}
__device__ __forceinline__ void sts32f(uint32_t a, float v) {
    asm volatile("st.shared.f32 [%0], %1;" ::"r"(a), "f"(v) : "memory");
}
__device__ __forceinline__ float lds32f(uint32_t a) {
    float v;
    asm volatile("ld.shared.f32 %0, [%1];" : "=f"(v) : "r"(a) : "memory");
    return v;
}
#define F8(d, b) \
    "+f"(d[b]), "+f"(d[b + 1]), "+f"(d[b + 2]), "+f"(d[b + 3]), "+f"(d[b + 4]), "+f"(d[b + 5]), "+f"(d[b + 6]), "+f"(d[b + 7])

template <int TB>
__device__ __forceinline__ void wgmma_n128(float (&d)[64], uint32_t a0, uint32_t a1, uint32_t a2, uint32_t a3,
                                           uint64_t db, int sc) {
    asm volatile(
        "{\n.reg .pred p;\nsetp.ne.b32 p, %69, 0;\n"
        "wgmma.mma_async.sync.aligned.m64n128k16.f32.bf16.bf16 "
        "{%0,%1,%2,%3,%4,%5,%6,%7,%8,%9,%10,%11,%12,%13,%14,%15,%16,%17,%18,%19,%20,%21,%22,%23,%24,%25,%26,%27,%28,%29,%30,%31,"
        "%32,%33,%34,%35,%36,%37,%38,%39,%40,%41,%42,%43,%44,%45,%46,%47,%48,%49,%50,%51,%52,%53,%54,%55,%56,%57,%58,%59,%60,%61,%62,%63},"
        "{%64,%65,%66,%67}, %68, p, 1, 1, %70;\n}"
        : F8(d, 0), F8(d, 8), F8(d, 16), F8(d, 24), F8(d, 32), F8(d, 40), F8(d, 48), F8(d, 56)
        : "r"(a0), "r"(a1), "r"(a2), "r"(a3), "l"(db), "r"(sc), "n"(TB));
}
#define O8(d, b) \
    "=f"(d[b]), "=f"(d[b + 1]), "=f"(d[b + 2]), "=f"(d[b + 3]), "=f"(d[b + 4]), "=f"(d[b + 5]), "=f"(d[b + 6]), "=f"(d[b + 7])
template <int TB>
__device__ __forceinline__ void wgmma_n128_z(float (&d)[64], uint32_t a0, uint32_t a1, uint32_t a2, uint32_t a3,
                                             uint64_t db) {
    asm volatile(
        "wgmma.mma_async.sync.aligned.m64n128k16.f32.bf16.bf16 "
        "{%0,%1,%2,%3,%4,%5,%6,%7,%8,%9,%10,%11,%12,%13,%14,%15,%16,%17,%18,%19,%20,%21,%22,%23,%24,%25,%26,%27,%28,%29,%30,%31,"
        "%32,%33,%34,%35,%36,%37,%38,%39,%40,%41,%42,%43,%44,%45,%46,%47,%48,%49,%50,%51,%52,%53,%54,%55,%56,%57,%58,%59,%60,%61,%62,%63},"
        "{%64,%65,%66,%67}, %68, 0, 1, 1, %69;"
        : O8(d, 0), O8(d, 8), O8(d, 16), O8(d, 24), O8(d, 32), O8(d, 40), O8(d, 48), O8(d, 56)
        : "r"(a0), "r"(a1), "r"(a2), "r"(a3), "l"(db), "n"(TB));
}
template <int TB>
__device__ __forceinline__ void wgmma_n64_z(float (&d)[32], uint32_t a0, uint32_t a1, uint32_t a2, uint32_t a3,
                                            uint64_t db) {
    asm volatile(
        "wgmma.mma_async.sync.aligned.m64n64k16.f32.bf16.bf16 "
        "{%0,%1,%2,%3,%4,%5,%6,%7,%8,%9,%10,%11,%12,%13,%14,%15,%16,%17,%18,%19,%20,%21,%22,%23,%24,%25,%26,%27,%28,%29,%30,%31},"
        "{%32,%33,%34,%35}, %36, 0, 1, 1, %37;"
        : O8(d, 0), O8(d, 8), O8(d, 16), O8(d, 24)
        : "r"(a0), "r"(a1), "r"(a2), "r"(a3), "l"(db), "n"(TB));
}
template <int TB>
__device__ __forceinline__ void wgmma_n64(float (&d)[32], uint32_t a0, uint32_t a1, uint32_t a2, uint32_t a3,
                                          uint64_t db) {
    asm volatile(
        "wgmma.mma_async.sync.aligned.m64n64k16.f32.bf16.bf16 "
        "{%0,%1,%2,%3,%4,%5,%6,%7,%8,%9,%10,%11,%12,%13,%14,%15,%16,%17,%18,%19,%20,%21,%22,%23,%24,%25,%26,%27,%28,%29,%30,%31},"
        "{%32,%33,%34,%35}, %36, 1, 1, 1, %37;"
        : F8(d, 0), F8(d, 8), F8(d, 16), F8(d, 24)
        : "r"(a0), "r"(a1), "r"(a2), "r"(a3), "l"(db), "n"(TB));
}

__device__ __forceinline__ uint64_t desc_of(uint32_t saddr) {
    return (uint64_t)(((saddr >> 4) & 0x3FFFu) | (512u << 16)) | ((uint64_t)(64u | (1u << 30)) << 32);
}

struct Ring {
    uint32_t slot;
    uint32_t phase;
    __device__ __forceinline__ void next() {
        if (++slot == 8) {
            slot = 0;
            phase ^= 1;
        }
    }
};

struct Ctx {
    uint32_t sbase;
    int wg;
    uint32_t rel_cta;
    __device__ __forceinline__ void wait_full(uint32_t slot, uint32_t phase) const {
        mbar_wait(sbase + OFF_FULL + slot * 8, phase);
    }
    __device__ __forceinline__ void release(uint32_t slot) const {
        if (rel_cta < 2) mbar_arrive_cluster(sbase + OFF_EMPTY + slot * 8, rel_cta);
    }
};

__device__ __forceinline__ void gemm_n128(float (&d)[64], const uint32_t (&a)[144], const Ctx& c, Ring& r, bool nine,
                                          bool early) {
    uint32_t prev = 0;
#pragma unroll
    for (int s = 0; s < 9; s++) {
        if (s < 8 || nine) {
            if (s == GATE_SLOT) {
                if (early) {
                    wg_wait<0>();
                    c.release(prev);
                }
                bar_sync(8 + c.wg, 256);
            }
            c.wait_full(r.slot, r.phase);
            uint64_t db = desc_of(c.sbase + r.slot * SLOT_BYTES);
            wg_fence();
#pragma unroll
            for (int k = 0; k < 4; k++) {
                if ((s | k) == 0)
                    wgmma_n128_z<1>(d, a[0], a[1], a[2], a[3], db);
                else
                    wgmma_n128<1>(d, a[s * 16 + k * 4], a[s * 16 + k * 4 + 1], a[s * 16 + k * 4 + 2],
                                  a[s * 16 + k * 4 + 3], db + k * 128, 1);
            }
            wg_commit();
            if (s == 8 || (s == 7 && !nine)) bar_arrive(9 - c.wg, 256);
            if (s > 0) {
                wg_wait<1>();
                if (s != GATE_SLOT || !early) c.release(prev);
            }
            prev = r.slot;
            r.next();
        }
    }
    wg_wait<0>();
    c.release(prev);
    pin(d);
}
__device__ __forceinline__ void gemm_n64(float (&d)[32], const uint32_t (&a)[144], const Ctx& c, Ring& r, bool nine) {
    uint32_t prev = 0;
#pragma unroll
    for (int s = 0; s < 5; s++) {
        if (s < 4 || nine) {
            c.wait_full(r.slot, r.phase);
            uint64_t db = desc_of(c.sbase + r.slot * SLOT_BYTES);
            wg_fence();
#pragma unroll
            for (int k = 0; k < 8; k++) {
                if ((s | k) == 0)
                    wgmma_n64_z<1>(d, a[0], a[1], a[2], a[3], db);
                else if (s * 8 + k < 36)
                    wgmma_n64<1>(d, a[s * 32 + k * 4], a[s * 32 + k * 4 + 1], a[s * 32 + k * 4 + 2],
                                 a[s * 32 + k * 4 + 3], db + k * 128);
            }
            wg_commit();
            if (s > 0) {
                wg_wait<1>();
                c.release(prev);
            }
            prev = r.slot;
            r.next();
        }
    }
    wg_wait<0>();
    c.release(prev);
    pin(d);
}
__device__ __forceinline__ void st128(uint4* p, uint32_t x, uint32_t y, uint32_t z, uint32_t w) {
    asm volatile(
        "{\n.reg .b64 lo, hi;\n.reg .b128 t;\nmov.b64 lo, {%1, %2};\nmov.b64 hi, {%3, %4};\nmov.b128 t, {lo, hi};\n"
        "st.relaxed.gpu.global.b128 [%0], t;\n}" ::"l"(p),
        "r"(x), "r"(y), "r"(z), "r"(w)
        : "memory");
}
__device__ __forceinline__ uint4 ld128(const uint4* p) {
    uint4 r;
    asm volatile(
        "{\n.reg .b64 lo, hi;\n.reg .b128 t;\nld.relaxed.gpu.global.b128 t, [%4];\nmov.b128 {lo, hi}, t;\n"
        "mov.b64 {%0, %1}, lo;\nmov.b64 {%2, %3}, hi;\n}"
        : "=r"(r.x), "=r"(r.y), "=r"(r.z), "=r"(r.w)
        : "l"(p));
    return r;
}
__device__ __forceinline__ uint4 ldg128(const uint4* p) {
    uint4 r;
    asm volatile("ld.global.nc.v4.u32 {%0,%1,%2,%3}, [%4];" : "=r"(r.x), "=r"(r.y), "=r"(r.z), "=r"(r.w) : "l"(p));
    return r;
}
__device__ __forceinline__ void st64(void* p, uint32_t x, uint32_t y) {
    asm volatile("{\n.reg .b64 t;\nmov.b64 t, {%1, %2};\nst.relaxed.gpu.global.b64 [%0], t;\n}" ::"l"(p), "r"(x), "r"(y)
                 : "memory");
}
__device__ __forceinline__ uint2 ld64(const void* p) {
    uint2 r;
    asm volatile("{\n.reg .b64 t;\nld.relaxed.gpu.global.b64 t, [%2];\nmov.b64 {%0, %1}, t;\n}"
                 : "=r"(r.x), "=r"(r.y)
                 : "l"(p));
    return r;
}
__device__ __forceinline__ void rows_load(uint32_t sbase, const CUtensorMap* m, int row0) {
    mbar_expect_tx(sbase + OFF_XBAR, 16 * DM * 2);
    asm volatile(
        "cp.async.bulk.tensor.3d.shared::cluster.global.mbarrier::complete_tx::bytes [%0], [%1, {%3, %3, %4}], [%2];" ::"r"(
            sbase + OFF_ROWS),
        "l"(m), "r"(sbase + OFF_XBAR), "r"(0), "r"(row0)
        : "memory");
}
__device__ __forceinline__ void rows_store(uint32_t sbase, const CUtensorMap* m, int row0) {
    asm volatile("cp.async.bulk.tensor.3d.global.shared::cta.bulk_group [%0, {%2, %2, %3}], [%1];" ::"l"(m),
                 "r"(sbase + OFF_ROWS), "r"(0), "r"(row0)
                 : "memory");
    asm volatile("cp.async.bulk.commit_group;" ::: "memory");
}
__device__ __forceinline__ void rows_store_wait() { asm volatile("cp.async.bulk.wait_group 0;" ::: "memory"); }

__device__ __forceinline__ constexpr int own_col(int j) { return j < 8 ? (j >> 1) * 128 + (j & 1) * 8 : 512; }
__device__ __forceinline__ void row_reduce(float& s0, float& s1, uint32_t red, int warp, int lane) {
    s0 += __shfl_xor_sync(0xffffffffu, s0, 1);
    s1 += __shfl_xor_sync(0xffffffffu, s1, 1);
    s0 += __shfl_xor_sync(0xffffffffu, s0, 2);
    s1 += __shfl_xor_sync(0xffffffffu, s1, 2);
    if ((lane & 3) == 0) {
        sts32f(red + (warp * 16 + (lane >> 2)) * 4, s0);
        sts32f(red + (warp * 16 + 8 + (lane >> 2)) * 4, s1);
    }
    bar_sync(3, 256);
    s0 = 0.f;
    s1 = 0.f;
#pragma unroll
    for (int w = 0; w < 8; w++) {
        s0 += lds32f(red + (w * 16 + (lane >> 2)) * 4);
        s1 += lds32f(red + (w * 16 + 8 + (lane >> 2)) * 4);
    }
}
template <class F>
__device__ __forceinline__ void layernorm_rows(float (&v)[36], uint32_t red, int warp, int lane, F&& middle) {
    float s0 = 0.f, s1 = 0.f;
#pragma unroll
    for (int j = 0; j < 9; j++) {
        s0 += v[4 * j] + v[4 * j + 1];
        s1 += v[4 * j + 2] + v[4 * j + 3];
    }
    row_reduce(s0, s1, red, warp, lane);
    middle();
    const float m0 = s0 * (1.f / DM), m1 = s1 * (1.f / DM);
    s0 = 0.f;
    s1 = 0.f;
#pragma unroll
    for (int j = 0; j < 9; j++) {
        v[4 * j] -= m0;
        v[4 * j + 1] -= m0;
        v[4 * j + 2] -= m1;
        v[4 * j + 3] -= m1;
        s0 += v[4 * j] * v[4 * j] + v[4 * j + 1] * v[4 * j + 1];
        s1 += v[4 * j + 2] * v[4 * j + 2] + v[4 * j + 3] * v[4 * j + 3];
    }
    row_reduce(s0, s1, red + 512, warp, lane);
    const float r0 = rsqrtf(s0 * (1.f / DM) + 1e-5f), r1 = rsqrtf(s1 * (1.f / DM) + 1e-5f);
#pragma unroll
    for (int j = 0; j < 9; j++) {
        v[4 * j] *= r0;
        v[4 * j + 1] *= r0;
        v[4 * j + 2] *= r1;
        v[4 * j + 3] *= r1;
    }
}
__device__ __forceinline__ void mod_to_smem(uint32_t dst, const uint32_t* src, uint32_t tag) {
    const uint32_t t0 = clk32();
    uint4 u;
    while (true) {
        u = ld128(reinterpret_cast<const uint4*>(src));
        const uint32_t bad = ((u.x ^ tag) | (u.y ^ tag) | (u.z ^ tag) | (u.w ^ tag)) & 0xffffu;
        if (__all_sync(0xffffffffu, bad == 0) || clk32() - t0 > WAIT_LIMIT) break;
        __nanosleep(64);
    }
    sts128(dst, u.x & 0xffff0000u, u.y & 0xffff0000u, u.z & 0xffff0000u, u.w & 0xffff0000u);
}
__device__ __forceinline__ void lds_mod(float (&m)[18], uint32_t src  , int warp) {
#pragma unroll
    for (int j = 0; j < 9; j++)
        asm volatile("ld.shared.v2.f32 {%0,%1}, [%2];"
                     : "=f"(m[2 * j]), "=f"(m[2 * j + 1])
                     : "r"(src + own_col(j) * 4 - (j == 8 ? warp * 32 : 0))
                     : "memory");
}
__device__ __forceinline__ void modulate_store(const float (&v)[36], const float (&shift)[18], const float (&scale)[18],
                                               float post, uint4* hbuf  , int warp, int lane) {
    uint32_t o[18];
#pragma unroll
    for (int j = 0; j < 9; j++) {
        const uint32_t cc = pack_bf16(1.f + scale[2 * j], 1.f + scale[2 * j + 1]);
        const float c0 = bf_lo(cc) * post, c1 = bf_hi(cc) * post, s0 = shift[2 * j] * post, s1 = shift[2 * j + 1] * post;
        o[2 * j] = pack_bf16(fmaf(v[4 * j], c0, s0), fmaf(v[4 * j + 1], c1, s1));
        o[2 * j + 1] = pack_bf16(fmaf(v[4 * j + 2], c0, s0), fmaf(v[4 * j + 3], c1, s1));
        if ((j & 1) == 0) o[2 * j] = max(o[2 * j], 1u);
    }
#pragma unroll
    for (int i = 0; i < 4; i++) st128(hbuf + (i * 8 + warp) * 32 + lane, o[4 * i], o[4 * i + 1], o[4 * i + 2], o[4 * i + 3]);
    st64(reinterpret_cast<uint2*>(hbuf + 32 * 32) + warp * 32 + lane, o[16], o[17]);
}
__device__ __forceinline__ void sum_partials(float (&v)[36], const uint4* src  , uint32_t tag) {
    const uint32_t t0 = clk32();
    while (true) {
        uint4 t[8][4];
#pragma unroll
        for (int s = 0; s < 8; s++)
#pragma unroll
            for (int i = 0; i < 4; i++) t[s][i] = ld128(src + (s * 36 + i * 8) * 32);
        uint32_t bad = 0;
#pragma unroll
        for (int i = 0; i < 32; i++) v[i] = 0.f;
#pragma unroll
        for (int s = 0; s < 8; s++)
#pragma unroll
            for (int i = 0; i < 4; i++) {
                bad |= t[s][i].x ^ tag;
                v[8 * i] += bf_lo(t[s][i].x);
                v[8 * i + 1] += bf_hi(t[s][i].x);
                v[8 * i + 2] += bf_lo(t[s][i].y);
                v[8 * i + 3] += bf_hi(t[s][i].y);
                v[8 * i + 4] += bf_lo(t[s][i].z);
                v[8 * i + 5] += bf_hi(t[s][i].z);
                v[8 * i + 6] += bf_lo(t[s][i].w);
                v[8 * i + 7] += bf_hi(t[s][i].w);
                asm volatile("" : "+r"(bad));
            }
#pragma unroll
        for (int i = 0; i < 32; i++) asm volatile("" : "+f"(v[i]));
        if (__all_sync(0xffffffffu, (bad & 1u) == 0) || clk32() - t0 > WAIT_LIMIT) break;
    }
}
__device__ __forceinline__ void sum_tail(float (&v)[36], const uint2* src  , uint32_t tag) {
    const uint32_t t0 = clk32();
    while (true) {
        uint2 t[8];
#pragma unroll
        for (int s = 0; s < 8; s++) t[s] = ld64(src + s * 72 * 32);
        uint32_t bad = 0;
        v[32] = v[33] = v[34] = v[35] = 0.f;
#pragma unroll
        for (int s = 0; s < 8; s++) {
            bad |= t[s].x ^ tag;
            v[32] += bf_lo(t[s].x);
            v[33] += bf_hi(t[s].x);
            v[34] += bf_lo(t[s].y);
            v[35] += bf_hi(t[s].y);
        }
        if (__all_sync(0xffffffffu, (bad & 1u) == 0) || clk32() - t0 > WAIT_LIMIT) break;
    }
}
__device__ __forceinline__ void poll_tail(uint32_t (&a)[144], const uint2* src  ) {
    const uint32_t t0 = clk32();
    while (true) {
        uint32_t m = 0xffffffffu;
#pragma unroll
        for (int j = 0; j < 8; j++) {
            const uint2 t = ld64(src + j * 32);
            a[128 + 2 * j] = t.x;
            a[129 + 2 * j] = t.y;
        }
#pragma unroll
        for (int j = 0; j < 8; j++) m = min(m, a[128 + 2 * j]);
        if (__all_sync(0xffffffffu, m != 0) || clk32() - t0 > WAIT_LIMIT) break;
    }
}
template <int K0, int K1>
__device__ __forceinline__ void poll_frags(uint32_t (&a)[144], const uint4* src  , bool kick) {
    const uint32_t t0 = clk32();
    while (true) {
#pragma unroll
        for (int k = K0; k < K1; k++) {
            const uint4 t = ld128(src + k * 32);
            a[4 * k] = t.x;
            a[4 * k + 1] = t.y;
            a[4 * k + 2] = t.z;
            a[4 * k + 3] = t.w;
        }
        if (kick) bar_arrive(5, 256);
        kick = false;
        uint32_t m0 = a[4 * K0], m1 = a[4 * K0 + 4];
#pragma unroll
        for (int k = K0 + 2; k < K1; k += 2) {
            m0 = min(m0, a[4 * k]);
            m1 = min(m1, a[4 * k + 4]);
        }
        if (__all_sync(0xffffffffu, min(m0, m1) != 0) || clk32() - t0 > WAIT_LIMIT) break;
    }
}

constexpr float SM_SCALE = 0.08838834764831845f * 1.4426950408889634f;
constexpr float SM_HI = 1.2089258e24f;
constexpr float SM_LO = 9.0949470e-13f;
__device__ __forceinline__ void qk_step(float (&s)[32], const uint32_t (&q)[32], uint64_t dk) {
#pragma unroll
    for (int k = 0; k < 8; k++) {
        if (k == 0)
            wgmma_n64_z<0>(s, q[0], q[1], q[2], q[3], dk);
        else
            wgmma_n64<0>(s, q[4 * k], q[4 * k + 1], q[4 * k + 2], q[4 * k + 3], dk + (k >> 2) * 512 + (k & 3) * 2);
    }
}
__device__ __forceinline__ void pv_step(float (&o)[64], const uint32_t (&p)[16], uint64_t dv, int acc) {
#pragma unroll
    for (int k = 0; k < 4; k++)
        wgmma_n128<1>(o, p[4 * k], p[4 * k + 1], p[4 * k + 2], p[4 * k + 3], dv + k * 128, k != 0 ? 1 : acc);
}
template <bool SHIFT>
__device__ __forceinline__ void exp_step(const float (&s)[32], uint32_t (&p)[16], float n0, float n1, float& s0,
                                         float& s1) {
#pragma unroll
    for (int i = 0; i < 8; i++) {
        const float e0 = ex2(SHIFT ? s[4 * i] + n0 : s[4 * i]), e1 = ex2(SHIFT ? s[4 * i + 1] + n0 : s[4 * i + 1]);
        const float e2 = ex2(SHIFT ? s[4 * i + 2] + n1 : s[4 * i + 2]), e3 = ex2(SHIFT ? s[4 * i + 3] + n1 : s[4 * i + 3]);
        if (i == 0) {
            s0 = e0 + e1;
            s1 = e2 + e3;
        } else {
            s0 += e0 + e1;
            s1 += e2 + e3;
        }
        p[2 * i] = pack_bf16(e0, e1);
        p[2 * i + 1] = pack_bf16(e2, e3);
    }
}
__device__ __forceinline__ void row_max(const float (&sa)[32], const float (&sb)[32], float& x0, float& x1) {
    float xa[8];
#pragma unroll
    for (int i = 0; i < 8; i++) xa[i] = fmaxf(sa[i], sb[i]);
#pragma unroll
    for (int k = 1; k < 4; k++)
#pragma unroll
        for (int i = 0; i < 8; i++) xa[i] = fmaxf(xa[i], fmaxf(sa[8 * k + i], sb[8 * k + i]));
    x0 = fmaxf(fmaxf(xa[0], xa[1]), fmaxf(xa[4], xa[5]));
    x1 = fmaxf(fmaxf(xa[2], xa[3]), fmaxf(xa[6], xa[7]));
    x0 = fmaxf(x0, __shfl_xor_sync(0xffffffffu, x0, 1));
    x1 = fmaxf(x1, __shfl_xor_sync(0xffffffffu, x1, 1));
    x0 = fmaxf(x0, __shfl_xor_sync(0xffffffffu, x0, 2));
    x1 = fmaxf(x1, __shfl_xor_sync(0xffffffffu, x1, 2));
}
__device__ __forceinline__ void inv_row_sums(float l0, float l1, float& i0, float& i1) {
    l0 += __shfl_xor_sync(0xffffffffu, l0, 1);
    l1 += __shfl_xor_sync(0xffffffffu, l1, 1);
    l0 += __shfl_xor_sync(0xffffffffu, l0, 2);
    l1 += __shfl_xor_sync(0xffffffffu, l1, 2);
    i0 = rcp(l0);
    i1 = rcp(l1);
}

__device__ __forceinline__ uint32_t get_epoch(uint32_t sbase) { return __float_as_uint(lds32f(sbase + OFF_EPOCH)); }
__device__ __forceinline__ float silu_bf16(unsigned short c) {
    const float cv = bf_lo(c);
    return round_bf16(cv * rcp(1.f + ex2(-1.4426950408889634f * cv)));
}
__device__ __forceinline__ void st_mod(uint32_t* p, float v, uint32_t tag) {
    asm volatile("st.relaxed.gpu.global.u32 [%0], %1;" ::"l"(p), "r"(__float_as_uint(round_bf16(v)) | tag)
                 : "memory");
}
__device__ __forceinline__ void fma8(float (&acc)[8], float sc, const uint4& w) {
    acc[0] = fmaf(sc, bf_lo(w.x), acc[0]);
    acc[1] = fmaf(sc, bf_hi(w.x), acc[1]);
    acc[2] = fmaf(sc, bf_lo(w.y), acc[2]);
    acc[3] = fmaf(sc, bf_hi(w.y), acc[3]);
    acc[4] = fmaf(sc, bf_lo(w.z), acc[4]);
    acc[5] = fmaf(sc, bf_hi(w.z), acc[5]);
    acc[6] = fmaf(sc, bf_lo(w.w), acc[6]);
    acc[7] = fmaf(sc, bf_hi(w.w), acc[7]);
}
__device__ __forceinline__ void modp_load(uint4 (&u)[3], const uint32_t* src) {
#pragma unroll
    for (int i = 0; i < 3; i++) u[i] = ld128(reinterpret_cast<const uint4*>(src + i * 2 * DM));
}
__device__ __forceinline__ void modp_to_smem(uint4 (&u)[3], uint32_t dst, const uint32_t* src, uint32_t tag) {
    const uint32_t t0 = clk32();
    while (true) {
        uint32_t bad = 0;
#pragma unroll
        for (int i = 0; i < 3; i++) bad |= (u[i].x ^ tag) | (u[i].y ^ tag) | (u[i].z ^ tag) | (u[i].w ^ tag);
        if (__all_sync(0xffffffffu, (bad & 0xffu) == 0) || clk32() - t0 > WAIT_LIMIT) break;
        modp_load(u, src);
    }
    float s0 = 0.f, s1 = 0.f, s2 = 0.f, s3 = 0.f;
#pragma unroll
    for (int i = 0; i < 3; i++) {
        s0 += __uint_as_float(u[i].x & ~0xffu);
        s1 += __uint_as_float(u[i].y & ~0xffu);
        s2 += __uint_as_float(u[i].z & ~0xffu);
        s3 += __uint_as_float(u[i].w & ~0xffu);
    }
    const uint32_t p0 = pack_bf16(s0, s1), p1 = pack_bf16(s2, s3);
    sts128(dst, p0 << 16, p0 & 0xffff0000u, p1 << 16, p1 & 0xffff0000u);
}

__global__ void __cluster_dims__(2, 1, 1) __launch_bounds__(384, 1)
    fused_block_kernel(const __grid_constant__ Params maps) {
    extern __shared__ uint8_t smem_raw[];
    uint32_t sbase = (smem_u32(smem_raw) + 1023u) & ~1023u;
    asm volatile("" : "+r"(sbase));
    const int b = blockIdx.x;
    const int rank = b & 1;
    const int mt = ((b >> 1) & 7) * 2 + rank;
    const int g = b >> 4;
    const int warp = __shfl_sync(0xffffffffu, threadIdx.x >> 5, 0);
    const int lane = threadIdx.x & 31;
    Scratch* const sc_ = maps.sc;
    const __nv_bfloat16* const wmod = maps.wmod;
    const __nv_bfloat16* const cvec = maps.cvec;

#define SPROF(i)

    if (warp >= 8) {
        asm volatile("setmaxnreg.dec.sync.aligned.u32 24;");
        if (warp == 8 && lane == 0) {
#pragma unroll
            for (int i = 0; i < 8; i++) {
                mbar_init(sbase + OFF_FULL + i * 8, 1);
                mbar_init(sbase + OFF_EMPTY + i * 8, 4);
            }
            mbar_init(sbase + OFF_XBAR, 1);
            asm volatile("fence.mbarrier_init.release.cluster;" ::: "memory");
            asm volatile("barrier.cluster.arrive.relaxed;\nbarrier.cluster.wait;" ::: "memory");
            uint32_t slot = 0, phase = 1;
            const uint32_t dst0 = sbase + rank * BOX_BYTES;
            auto acquire = [&](uint32_t bytes) {
                mbar_wait(sbase + OFF_EMPTY + slot * 8, phase);
                mbar_expect_tx(sbase + OFF_FULL + slot * 8, bytes);
            };
            auto adv8 = [&]() {
                if (++slot == 8) {
                    slot = 0;
                    phase ^= 1;
                }
            };
#pragma unroll 1
            for (int hq = 0; hq < 4; hq++) {
                const int col = (g * 4 + ((hq + 1) & 3)) * 128 + rank * 64;
                if (hq == 2) {
                    l2_prefetch(maps.kc + (size_t)(g * 4 * 2048 + (b & 15) * 64) * 128, SLOT_BYTES);
                    l2_prefetch(maps.vc + (size_t)(g * 4 * 2048 + (b & 15) * 64) * 128, SLOT_BYTES);
                }
#pragma unroll 1
                for (int kc = 0; kc < 9; kc++) {
                    acquire(SLOT_BYTES);
                    tma_mc(dst0 + slot * SLOT_BYTES, &maps.wq, col, kc * 64, sbase + OFF_FULL + slot * 8);
                    adv8();
                }
            }
            const int row0 = g * 4 * 2048;
#pragma unroll 1
            for (int n = 0; n < 128; n++) {
                if (n < 4) mbar_wait(sbase + OFF_EMPTY + (slot + 1) * 8, phase);
                acquire(2 * SLOT_BYTES);
                const uint32_t bar = sbase + OFF_FULL + slot * 8;
                const int r0 = n == 0 ? 0 : (n == 127 ? 126 : n + 1);
                const int r1 = n == 0 ? 1 : (n == 127 ? 127 : n - 1);
                tma_mc(dst0 + slot * SLOT_BYTES, n == 127 ? &maps.v : &maps.k, rank * 64, row0 + r0 * 64, bar);
                tma_mc(dst0 + (slot + 1) * SLOT_BYTES, n == 0 ? &maps.k : &maps.v, rank * 64, row0 + r1 * 64, bar);
                adv8();
                adv8();
                const int u = n + KV_AHEAD;
                if (u < 128 && (u & 15) == (b & 15)) {
                    l2_prefetch(maps.kc + (size_t)(row0 + u * 64) * 128, SLOT_BYTES);
                    l2_prefetch(maps.vc + (size_t)(row0 + u * 64) * 128, SLOT_BYTES);
                }
            }
#pragma unroll 1
            for (int p = 0; p < 4; p++)
#pragma unroll 1
                for (int kc = 0; kc < 8; kc++) {
                    acquire(SLOT_BYTES);
                    tma_mc(dst0 + slot * SLOT_BYTES, &maps.wo, p * 128 + rank * 64, g * 512 + ((kc + 6) & 7) * 64,
                           sbase + OFF_FULL + slot * 8);
                    adv8();
                }
#pragma unroll 1
            for (int kc = 0; kc < 4; kc++) {
                acquire(SLOT_BYTES);
                tma_mc(dst0 + slot * SLOT_BYTES, &maps.wo, 512, g * 512 + ((kc + 3) & 3) * 128 + rank * 64,
                       sbase + OFF_FULL + slot * 8);
                adv8();
            }
            const CUtensorMap* mg = rank ? &maps.wu : &maps.wg;
#pragma unroll 1
            for (int ch = 0; ch < 9; ch++)
#pragma unroll 1
                for (int kc = 0; kc < 9; kc++) {
                    acquire(SLOT_BYTES);
                    tma_mc(dst0 + slot * SLOT_BYTES, mg, g * 576 + ch * 64, kc * 64, sbase + OFF_FULL + slot * 8);
                    adv8();
                }
#pragma unroll 1
            for (int p = 0; p < 4; p++)
#pragma unroll 1
                for (int i = 0; i < 9; i++) {
                    acquire(SLOT_BYTES);
                    tma_mc(dst0 + slot * SLOT_BYTES, &maps.wd, p * 128 + rank * 64,
                           g * 576 + (i == 0 ? 8 : (i < 7 ? i + 1 : i - 7)) * 64, sbase + OFF_FULL + slot * 8);
                    adv8();
                }
#pragma unroll 1
            for (int i2 = 0; i2 < 5; i2++) {
                acquire(i2 < 4 ? SLOT_BYTES : BOX_BYTES);
                const int i = 2 * i2 + rank;
                if (i < 9)
                    tma_mc(dst0 + slot * SLOT_BYTES, &maps.wd, 512, g * 576 + (i == 0 ? 8 : (i < 7 ? i + 1 : i - 7)) * 64,
                           sbase + OFF_FULL + slot * 8);
                adv8();
            }
        } else if (warp == 11) {
            asm volatile("barrier.cluster.arrive.relaxed.aligned;" ::: "memory");
            bar_sync(6, 160);
            uint4* hz = sc_->h[(get_epoch(sbase) & 1) ^ 1][0] + (size_t)b * 72 * 32 + lane;
#pragma unroll 1
            for (int i = 0; i < 72; i++) {
                hz[i * 32] = make_uint4(0, 0, 0, 0);
                __nanosleep(200);
            }
            bar_sync(6, 160);
            if (lane == 0) {
#pragma unroll 1
                for (int i = 0; i < 9; i++) {
                    l2_prefetch((const char*)maps.wo_p + (size_t)b * 36864 + i * 4096, 4096);
                    __nanosleep(400);
                    l2_prefetch((const char*)maps.wg_p + (size_t)b * 41472 + i * 4608, 4608);
                    __nanosleep(400);
                    l2_prefetch((const char*)maps.wu_p + (size_t)b * 41472 + i * 4608, 4608);
                    __nanosleep(400);
                    l2_prefetch((const char*)maps.wd_p + (size_t)b * 41472 + i * 4608, 4608);
                    __nanosleep(400);
                }
            }
        } else if (warp == 9 || warp == 10) {
            asm volatile("barrier.cluster.arrive.relaxed.aligned;" ::: "memory");
            if (warp == 10) {
                bar_sync(11, 288);
                if (lane < 9) l2_prefetch((const char*)maps.wq_p + (size_t)b * 36864 + lane * 4096, 4096);
                __syncwarp();
            }
            bar_sync(4, 320);
            const uint32_t tag = (get_epoch(sbase) + 1) & 0xffffu;
            const int blk = warp == 9 ? 72 + b : 200 + b;
            if (blk < 216) {
                float acc[8];
#pragma unroll
                for (int e = 0; e < 8; e++) acc[e] = 0.f;
                const uint4* wp = reinterpret_cast<const uint4*>(wmod + (size_t)(lane >> 1) * (6 * DM) + blk * 16) + (lane & 1);
                const unsigned short* cp = reinterpret_cast<const unsigned short*>(cvec) + (lane >> 1);
#pragma unroll 1
                for (int i = 0; i < 36; i++) {
                    const uint4 w = __ldg(wp + (size_t)i * (16 * 6 * DM / 8));
                    const float sc = silu_bf16(__ldg(cp + i * 16));
                    fma8(acc, sc, w);
                }
#pragma unroll
                for (int o = 2; o < 32; o <<= 1)
#pragma unroll
                    for (int e = 0; e < 8; e++) acc[e] += __shfl_xor_sync(0xffffffffu, acc[e], o);
                if (lane < 2) {
#pragma unroll
                    for (int e = 0; e < 8; e++) st_mod(sc_->mod + blk * 16 + lane * 8 + e, acc[e], tag);
                }
            }
            if (warp == 9) {
#pragma unroll 1
                for (int st = 1; st <= 2; st++) {
                    bar_sync(7, 160);
                    const uint32_t* src = sc_->mod + (st * 3 - 1) * DM;
                    const int n = st == 1 ? 3 * DM : DM;
#pragma unroll 1
                    for (int i = lane * 4; i < n + 127 - ((n + 127) & 127); i += 128)
                        mod_to_smem(sbase + OFF_MODT + min(i, n - 4) * 4, src + min(i, n - 4), tag);
                    __syncwarp();
                    if (lane == 0) rows_load(sbase, st == 1 ? &maps.rx : &maps.rx2, (mt * 8 + g) * 16);
                    if (st == 1) {
                        bar_sync(7, 160);
                        if (lane == 0) {
                            rows_store(sbase, &maps.rx2, (mt * 8 + g) * 16);
                            rows_store_wait();
                        }
                        __syncwarp();
                        bar_arrive(10, 160);
                    }
                }
            }
        }
    } else {
        uint4 w1[3], xw[5], ew = make_uint4(0, 0, 0, 0);
        unsigned short cu[3];
        {
            const int t = threadIdx.x, bw = min(b, 107);
            const int row = (bw / 36) * 192 + (t >> 2);
#pragma unroll
            for (int i = 0; i < 3; i++) {
                w1[i] = ldg128(reinterpret_cast<const uint4*>(wmod + (size_t)(row + 64 * i) * (6 * DM)) + (bw % 36) * 4 + (t & 3));
                asm volatile("ld.global.nc.u16 %0, [%1];" : "=h"(cu[i]) : "l"(cvec + row + 64 * i));
            }
            if (t == 0) ew = ld128(reinterpret_cast<const uint4*>(&sc_->epoch[b * 32]));
#pragma unroll
            for (int i = 0; i < 5; i++)
                xw[i] = ldg128(reinterpret_cast<const uint4*>(maps.x + (size_t)(mt * 8 + g) * 16 * DM) + min(t + 256 * i, 1151));
        }
        if (threadIdx.x == 160) SPROF(5);
        asm volatile("setmaxnreg.inc.sync.aligned.u32 240;");
        if (threadIdx.x == 160) SPROF(6);
        const int wg = warp >> 2;
        const int tid = threadIdx.x;
        Ctx cx;
        cx.sbase = sbase;
        cx.wg = wg;
        if (wg == 1) bar_arrive(8, 256);
        cx.rel_cta = (lane == 0 && (warp & 3) < 2) ? (warp & 3) : 2;
        const uint32_t red = sbase + OFF_RED;
        const int own = mt * 8 + g;
        const int wown = mt * 8 + warp;
        PROF(0);
        PROFG(30);
        PROFR(17);
        {
            asm volatile("barrier.cluster.arrive.relaxed.aligned;" ::: "memory");
            float acc[8];
#pragma unroll
            for (int e = 0; e < 8; e++) acc[e] = 0.f;
#pragma unroll
            for (int i = 0; i < 3; i++) fma8(acc, silu_bf16(cu[i]), w1[i]);
#pragma unroll
            for (int o = 4; o < 32; o <<= 1)
#pragma unroll
                for (int e = 0; e < 8; e++) acc[e] += __shfl_xor_sync(0xffffffffu, acc[e], o);
            PROFR(19);
            if (lane < 4) {
                const uint32_t dst = sbase + OFF_MRED + warp * 128 + lane * 32;
                sts128(dst, __float_as_uint(acc[0]), __float_as_uint(acc[1]), __float_as_uint(acc[2]), __float_as_uint(acc[3]));
                sts128(dst + 16, __float_as_uint(acc[4]), __float_as_uint(acc[5]), __float_as_uint(acc[6]), __float_as_uint(acc[7]));
            }
            if (tid == 0) sts128(sbase + OFF_EPOCH, ew.x, ew.y, ew.z, ew.w);
            bar_sync(3, 256);
            PROFR(20);
            if (tid < 32 && b < 108) {
                float sum = 0.f;
#pragma unroll
                for (int w8 = 0; w8 < 8; w8++) sum += lds32f(sbase + OFF_MRED + w8 * 128 + tid * 4);
                asm volatile("st.relaxed.gpu.global.u32 [%0], %1;" ::"l"(&sc_->modp[b / 36][(b % 36) * 32 + tid]),
                             "r"((__float_as_uint(sum) & ~0xffu) | ((get_epoch(sbase) + 1) & 0xffu))
                             : "memory");
            }
            PROFR(21);
#pragma unroll
            for (int i = 0; i < 5; i++) {
                const int vi = min(tid + 256 * i, 1151), ln = vi >> 3;
                sts128(sbase + OFF_ROWS + ln * 128 + (((vi & 7) ^ (ln & 7)) << 4), xw[i].x, xw[i].y, xw[i].z, xw[i].w);
            }
            bar_sync(3, 256);
            bar_arrive(11, 288);
        }

        Ring ring{0u, 0u};
        int stage = 0;
        asm volatile("" : "+r"(stage));
#pragma unroll 1
        for (;; stage++) {
            int tid, lane;
            asm volatile("mov.u32 %0, %%tid.x;" : "=r"(tid));
            lane = tid & 31;
            const uint32_t epoch = get_epoch(sbase);
            {
                float v[36];
                const uint32_t modt = sbase + OFF_MODT + (warp * 16 + (lane & 3) * 2) * 4;
                if (stage == 0) {
#pragma unroll
                    for (int i = 0; i < 36; i++) v[i] = 0.f;
                } else {
                    const uint4* psrc = sc_->part + (size_t)own * 8 * 36 * 32;
                    sum_partials(v, psrc + tid, stage & 1);
                    PROF(stage == 1 ? 8 : 15);
                    sum_tail(v, reinterpret_cast<const uint2*>(psrc + 32 * 32) + tid, stage & 1);
                }
                if (stage) mbar_wait(sbase + OFF_XBAR, stage - 1);
                if (stage == 0) PROFR(22);
                {
                    const float gs = stage == 2 ? 0.5f : 1.f;
                    float gate[18];
                    lds_mod(gate, modt, warp);
                    const int r = lane >> 2;
                    const uint32_t rows = sbase + OFF_ROWS + r * (DM * 2) + (lane & 3) * 4;
#pragma unroll
                    for (int j = 0; j < 9; j++) {
                        const int ch = j < 8 ? (j >> 1) * 2 + (warp >> 2) : 8, c16 = j < 8 ? (warp & 3) * 2 + (j & 1) : warp;
                        const uint32_t ad = rows + ch * 128 + ((c16 ^ ((r + ch) & 7)) << 4);
                        const uint32_t u0 = __float_as_uint(lds32f(ad)), u1 = __float_as_uint(lds32f(ad + 8 * DM * 2));
                        const float g0 = stage ? gate[2 * j] * gs : 0.f, g1 = stage ? gate[2 * j + 1] * gs : 0.f;
                        v[4 * j] = fmaf(g0, v[4 * j], bf_lo(u0));
                        v[4 * j + 1] = fmaf(g1, v[4 * j + 1], bf_hi(u0));
                        v[4 * j + 2] = fmaf(g0, v[4 * j + 2], bf_lo(u1));
                        v[4 * j + 3] = fmaf(g1, v[4 * j + 3], bf_hi(u1));
                        sts32f(ad, __uint_as_float(pack_bf16(v[4 * j], v[4 * j + 1])));
                        sts32f(ad + 8 * DM * 2, __uint_as_float(pack_bf16(v[4 * j + 2], v[4 * j + 3])));
                    }
                    asm volatile("fence.proxy.async.shared::cta;" ::: "memory");
                }
                if (stage == 2) break;
                PROF(stage == 0 ? 1 : 9);
                uint4 ua[3], ub[3];
#pragma unroll
                for (int i = 0; i < 3; i++) ua[i] = ub[i] = make_uint4(0, 0, 0, 0);
                layernorm_rows(v, red, warp, lane, [&]() {
                    if (stage == 0) {
                        modp_load(ua, sc_->modp[0] + tid * 4);
                        if (warp == 0) modp_load(ub, sc_->modp[0] + 1024 + tid * 4);
                    }
                });
                if (stage == 0) PROFR(27);
                if (stage == 0) {
                    const uint32_t tag = (epoch + 1) & 0xffu;
                    modp_to_smem(ua, sbase + OFF_MODT + (DM + tid * 4) * 4, sc_->modp[0] + tid * 4, tag);
                    if (warp == 0)
                        modp_to_smem(ub, sbase + OFF_MODT + (DM + 1024 + tid * 4) * 4, sc_->modp[0] + 1024 + tid * 4, tag);
                    bar_sync(3, 256);
                }
                float shift[18], scale[18];
                lds_mod(shift, modt + DM * 4, warp);
                lds_mod(scale, modt + 2 * DM * 4, warp);
                if (stage == 0) PROFR(28);
                PROF(stage == 0 ? 2 : 10);
                modulate_store(v, shift, scale, stage == 0 ? SM_SCALE : 1.f, sc_->h[epoch & 1][stage] + (size_t)own * 36 * 32, warp, lane);
                if (stage == 0) asm volatile("barrier.cluster.wait.aligned;" ::: "memory");
            }

            const uint32_t spill = sbase + 8 * SLOT_BYTES + wg * 3 * SLOT_BYTES + (tid & 127) * 16;
            uint32_t a[144];
            PROF(stage == 0 ? 3 : 11);
            {
                const uint4* hsrc = sc_->h[epoch & 1][stage] + (size_t)wown * 36 * 32 + lane;
                __nanosleep(stage == 0 ? PROBE0_NS : PROBE_NS);
                poll_tail(a, reinterpret_cast<const uint2*>(hsrc - lane + 32 * 32) + lane);
                PROF(stage == 0 ? 4 : 12);
                if (stage == 1) PROFG(25);
                TG(stage * 32 + 30);
                if (wg == 1) bar_sync(5, 256);
                poll_frags<0, 32>(a, hsrc, wg == 0);
                if (stage == 0) bar_arrive(4, 320);
            }
            uint4* hhbuf = sc_->hh + (size_t)b * 8 * 256 + tid;
            float d[64];
#pragma unroll 1
            for (int ch = 0;; ch++) {
                TG(stage * 32 + ch * 2);
                gemm_n128(d, a, cx, ring, true, stage && wg);
                TG(stage * 32 + ch * 2 + 1);
                if (stage == 0) {
                    if (ch == 3) break;
#pragma unroll
                    for (int v = 0; v < 8; v++)
                        sts128(spill + (ch * 8 + v) * 2048, pack_bf16(d[8 * v], d[8 * v + 1]),
                               pack_bf16(d[8 * v + 2], d[8 * v + 3]), pack_bf16(d[8 * v + 4], d[8 * v + 5]),
                               pack_bf16(d[8 * v + 6], d[8 * v + 7]));
                } else {
#pragma unroll
                    for (int i = 0; i < 32; i++) {
                        const float gv = d[i], gu = gv * d[32 + i];
                        const float z = gv * fmaf(gv * gv, 0.7978845608028654f * 0.044715f, 0.7978845608028654f);
                        d[i] = fmaf(gu, tanh_fast(z), gu);
                    }
                    if (ch == 8) break;
                    if (wg == 0) {
                        if (ch == 0) bar_arrive(7, 160);
                        if (ch == 2) bar_sync(10, 160);
                    }
#pragma unroll
                    for (int v = 0; v < 4; v++) {
                        const uint4 h4 = make_uint4(pack_bf16(d[8 * v], d[8 * v + 1]), pack_bf16(d[8 * v + 2], d[8 * v + 3]),
                                                    pack_bf16(d[8 * v + 4], d[8 * v + 5]), pack_bf16(d[8 * v + 6], d[8 * v + 7]));
                        if (ch < 2)
                            __stcg(hhbuf + (ch * 4 + v) * 256, h4);
                        else
                            sts128(spill + ((ch - 2) * 4 + v) * 2048, h4.x, h4.y, h4.z, h4.w);
                    }
                }
            }
            if (stage == 0) {
                uint32_t q[32];
#pragma unroll
                for (int i = 0; i < 32; i++) q[i] = pack_bf16(d[2 * i], d[2 * i + 1]);
                PROF(5);
                PROFG(23);
                if (wg == 0) bar_arrive(6, 160);
                {
                    float o[64], sa[32], sb[32];
                    uint32_t pa[16], pb[16];
#pragma unroll
                    for (int i = 0; i < 64; i++) o[i] = 0.f;
                    float n0 = 0.f, n1 = 0.f, l0 = 1.f, l1 = 1.f;
                    bool shifted = false;
                    const uint64_t dbase = desc_of(sbase);
                    const uint64_t dbk = dbase - (511u << 16);
                    const int my_bar = 1 + wg, other_bar = 2 - wg;

                    auto softmax_a = [&](bool first, float& s0, float& s1) {
                        if (first) {
                            shifted = false;
                            n0 = n1 = 0.f;
                            l0 = l1 = 0.f;
                        }
                        if (shifted)
                            exp_step<true>(sa, pa, n0, n1, s0, s1);
                        else
                            exp_step<false>(sa, pa, n0, n1, s0, s1);
                    };
                    auto softmax_b = [&](bool first, float s0, float s1) {
                        float u0, u1;
                        if (shifted)
                            exp_step<true>(sb, pb, n0, n1, u0, u1);
                        else
                            exp_step<false>(sb, pb, n0, n1, u0, u1);
                        s0 += u0;
                        s1 += u1;
                        bool bad = !(fmaxf(s0, s1) <= SM_HI);
                        if (first) {
                            float r0 = s0 + __shfl_xor_sync(0xffffffffu, s0, 1), r1 = s1 + __shfl_xor_sync(0xffffffffu, s1, 1);
                            r0 += __shfl_xor_sync(0xffffffffu, r0, 2);
                            r1 += __shfl_xor_sync(0xffffffffu, r1, 2);
                            bad = bad || !(fminf(r0, r1) >= SM_LO);
                        }
                        if (__any_sync(0xffffffffu, bad)) {
                            float x0, x1;
                            row_max(sa, sb, x0, x1);
                            x0 = -x0;
                            x1 = -x1;
                            if (!first) {
                                x0 = fminf(x0, n0);
                                x1 = fminf(x1, n1);
                                const float al0 = ex2(x0 - n0), al1 = ex2(x1 - n1);
                                l0 *= al0;
                                l1 *= al1;
#pragma unroll
                                for (int i = 0; i < 16; i++) {
                                    o[4 * i] *= al0;
                                    o[4 * i + 1] *= al0;
                                    o[4 * i + 2] *= al1;
                                    o[4 * i + 3] *= al1;
                                }
                            }
                            n0 = x0;
                            n1 = x1;
                            shifted = true;
                            exp_step<true>(sa, pa, n0, n1, s0, s1);
                            exp_step<true>(sb, pb, n0, n1, u0, u1);
                            s0 += u0;
                            s1 += u1;
                        }
                        l0 += s0;
                        l1 += s1;
                    };

                    cx.wait_full(4, 0);
                    if (wg == 1) bar_sync(my_bar, 256);
                    wg_fence();
                    qk_step(sa, q, dbk + 4 * 1024);
                    qk_step(sb, q, dbk + 5 * 1024);
                    wg_commit();
                    bar_arrive(other_bar, 256);
                    wg_wait<0>();
                    pin(sa);
                    pin(sb);
                    cx.release(4);
                    cx.wait_full(6, 0);
                    {
                        float s0, s1;
                        softmax_a(true, s0, s1);
                        softmax_b(true, s0, s1);
                    }
                    uint32_t alo = (uint32_t)dbase + 6 * 1024, blo = (uint32_t)dbase;
                    const uint32_t dhi = (uint32_t)(dbase >> 32);
#pragma unroll 1
                    for (int t = 1; t < 64; t++) {
                        const int j = t & 15;
                        const uint32_t sA = 2 + 4 * (t & 1), sB = 4 - 4 * (t & 1);
                        const uint64_t da = ((uint64_t)dhi << 32) | alo, db = ((uint64_t)dhi << 32) | blo;
                        TL(0);
                        bar_sync(my_bar, 256);
                        TL(2);
                        wg_fence();
                        qk_step(sa, q, da - (511u << 16));
                        pv_step(o, pa, da + 1024, j != 1);
                        wg_commit();
                        cx.wait_full(sB, ((36 + 4 * t) >> 3) & 1);
                        wg_fence();
                        qk_step(sb, q, db - (511u << 16));
                        pv_step(o, pb, db + 1024, 1);
                        wg_commit();
                        bar_arrive(other_bar, 256);
                        alo ^= 4096;
                        blo ^= 4096;
                        asm volatile("" : "+r"(alo), "+r"(blo));
                        TL(3);
                        wg_wait<1>();
                        pin(sa);
                        pin(pa);
                        TL(4);
                        cx.release(sA);
                        const float lp0 = l0, lp1 = l1;
                        float s0, s1;
                        softmax_a(j == 0, s0, s1);
                        TL(5);
                        wg_wait<0>();
                        pin(o);
                        pin(sb);
                        pin(pb);
                        TL(6);
                        cx.release(sB);
                        if (j == 0) {
                            float i0, i1;
                            inv_row_sums(lp0, lp1, i0, i1);
                            const uint32_t dst = spill + ((t >> 4) - 1) * 16384;
#pragma unroll
                            for (int v = 0; v < 8; v++)
                                sts128(dst + v * 2048, pack_bf16(o[8 * v] * i0, o[8 * v + 1] * i0),
                                       pack_bf16(o[8 * v + 2] * i1, o[8 * v + 3] * i1),
                                       pack_bf16(o[8 * v + 4] * i0, o[8 * v + 5] * i0),
                                       pack_bf16(o[8 * v + 6] * i1, o[8 * v + 7] * i1));
                        }
                        const uint32_t bn = sbase + OFF_FULL + (8 - sA) * 8, pn = ((38 + 4 * t) >> 3) & 1;
                        const bool okn = mbar_try(bn, pn);
                        TL(1);
                        softmax_b(j == 0, s0, s1);
                        if (!okn || j == 15) {
                            mbar_wait(bn, pn);
                            if (t == 47 && wg == 0) bar_arrive(6, 160);
                            if (j == 15 && t < 63) {
                                const uint32_t src = spill + (t >> 4) * 16384;
#pragma unroll
                                for (int v = 0; v < 8; v++)
                                    lds128(src + v * 2048, q[4 * v], q[4 * v + 1], q[4 * v + 2], q[4 * v + 3]);
                            }
                        }
                        TL(7);
                    }
                    bar_sync(my_bar, 256);
                    wg_fence();
                    pv_step(o, pa, dbase + 2 * 1024, 1);
                    pv_step(o, pb, dbase + 3 * 1024, 1);
                    wg_commit();
                    if (wg == 0) bar_arrive(other_bar, 256);
                    float i0, i1;
                    inv_row_sums(l0, l1, i0, i1);
                    wg_wait<0>();
                    pin(o);
                    cx.release(2);
#pragma unroll
                    for (int i = 0; i < 16; i++) {
                        a[2 * i] = pack_bf16(o[4 * i] * i0, o[4 * i + 1] * i0);
                        a[2 * i + 1] = pack_bf16(o[4 * i + 2] * i1, o[4 * i + 3] * i1);
                    }
#pragma unroll
                    for (int v = 0; v < 24; v++)
                        lds128(spill + v * 2048, a[32 + 4 * v], a[33 + 4 * v], a[34 + 4 * v], a[35 + 4 * v]);
#pragma unroll
                    for (int i = 128; i < 144; i++) a[i] = 0;
                }
                ring.slot = 4;
                ring.phase = 0;
                PROF(6);
                PROFG(24);
            } else {
#pragma unroll
                for (int v = 0; v < 8; v++) {
                    const uint4 t = __ldcg(hhbuf + v * 256);
                    a[112 + 4 * v] = t.x;
                    a[113 + 4 * v] = t.y;
                    a[114 + 4 * v] = t.z;
                    a[115 + 4 * v] = t.w;
                }
#pragma unroll
                for (int i = 0; i < 16; i++) a[i] = pack_bf16(d[2 * i], d[2 * i + 1]);
#pragma unroll
                for (int v = 0; v < 24; v++)
                    lds128(spill + v * 2048, a[16 + 4 * v], a[17 + 4 * v], a[18 + 4 * v], a[19 + 4 * v]);
                PROF(13);
            }

            {
                uint4* dst = sc_->part + ((size_t)wown * 8 + g) * 36 * 32 + lane;
                const uint32_t ptag = (stage + 1) & 1;
#pragma unroll 1
                for (int p = 0; p < 4; p++) {
                    TG(stage * 32 + 18 + p * 2);
                    gemm_n128(d, a, cx, ring, stage != 0, stage && wg);
                    TG(stage * 32 + 19 + p * 2);
#pragma unroll
                    for (int u = 0; u < 8; u++)
                        st128(dst + (p * 8 + u) * 32, (pack_bf16(d[8 * u], d[8 * u + 1]) & ~1u) | ptag,
                              pack_bf16(d[8 * u + 2], d[8 * u + 3]), pack_bf16(d[8 * u + 4], d[8 * u + 5]),
                              pack_bf16(d[8 * u + 6], d[8 * u + 7]));
                    if (p == 0 && wg == 0) bar_arrive(7, 160);
                }
                float e[32];
                TG(stage * 32 + 26);
                gemm_n64(e, a, cx, ring, stage != 0);
                TG(stage * 32 + 27);
                uint2* dst2 = reinterpret_cast<uint2*>(dst - lane + 32 * 32) + lane;
#pragma unroll
                for (int j = 0; j < 8; j++)
                    st64(dst2 + j * 32, (pack_bf16(e[4 * j], e[4 * j + 1]) & ~1u) | ptag, pack_bf16(e[4 * j + 2], e[4 * j + 3]));
            }
            PROF(stage == 0 ? 7 : 14);
            if (stage == 1) {
                PROFG(26);
                asm volatile("barrier.cluster.arrive.relaxed.aligned;" ::: "memory");
            }
        }
        if (wg == 0) bar_sync(8, 256);
        bar_sync(3, 256);
        if (tid == 32) sc_->epoch[b * 32] = get_epoch(sbase) + 1;
        if (tid == 0) {
            rows_store(sbase, &maps.rout, own * 16);
            rows_store_wait();
        }
        __syncwarp();
        PROF(16);
        PROFG(31);
        asm volatile("barrier.cluster.wait.aligned;" ::: "memory");
    }
}

typedef CUresult (*EncodeFn)(CUtensorMap*, CUtensorMapDataType, cuuint32_t, void*, const cuuint64_t*, const cuuint64_t*,
                             const cuuint32_t*, const cuuint32_t*, CUtensorMapInterleave, CUtensorMapSwizzle,
                             CUtensorMapL2promotion, CUtensorMapFloatOOBfill);

void make_map(EncodeFn enc, CUtensorMap* m, const void* ptr, uint64_t rows, uint64_t cols, bool narrow = false) {
    cuuint64_t gdim[2] = {cols, rows};
    cuuint64_t gstr[1] = {cols * 2};
    cuuint32_t box[2] = {narrow ? 16u : 64u, narrow ? 192u : 64u};
    cuuint32_t estr[2] = {1, 1};
    enc(m, CU_TENSOR_MAP_DATA_TYPE_BFLOAT16, 2, const_cast<void*>(ptr), gdim, gstr, box, estr,
        CU_TENSOR_MAP_INTERLEAVE_NONE, narrow ? CU_TENSOR_MAP_SWIZZLE_NONE : CU_TENSOR_MAP_SWIZZLE_128B,
        CU_TENSOR_MAP_L2_PROMOTION_L2_128B,
        CU_TENSOR_MAP_FLOAT_OOB_FILL_NONE);
}

void make_rows_map(EncodeFn enc, CUtensorMap* m, const void* ptr) {
    cuuint64_t gdim[3] = {64, 9, 2048};
    cuuint64_t gstr[2] = {128, DM * 2};
    cuuint32_t box[3] = {64, 9, 16};
    cuuint32_t estr[3] = {1, 1, 1};
    enc(m, CU_TENSOR_MAP_DATA_TYPE_BFLOAT16, 3, const_cast<void*>(ptr), gdim, gstr, box, estr,
        CU_TENSOR_MAP_INTERLEAVE_NONE, CU_TENSOR_MAP_SWIZZLE_128B, CU_TENSOR_MAP_L2_PROMOTION_L2_128B,
        CU_TENSOR_MAP_FLOAT_OOB_FILL_NONE);
}

}

extern "C" void kernel_launch(void* const* d_in, const int* in_sizes, int n_in, void* d_out, int out_size) {
    (void)in_sizes;
    (void)n_in;
    (void)out_size;
    void* fn = nullptr;
    cudaDriverEntryPointQueryResult qr;
    cudaGetDriverEntryPoint("cuTensorMapEncodeTiled", &fn, cudaEnableDefault, &qr);
    EncodeFn enc = (EncodeFn)fn;
    Params maps;
    maps.x = (const __nv_bfloat16*)d_in[0];
    maps.cvec = (const __nv_bfloat16*)d_in[9];
    maps.wmod = (const __nv_bfloat16*)d_in[10];
    maps.kc = (const __nv_bfloat16*)d_in[1];
    maps.vc = (const __nv_bfloat16*)d_in[2];
    maps.wq_p = (const __nv_bfloat16*)d_in[3];
    maps.wo_p = (const __nv_bfloat16*)d_in[4];
    maps.wg_p = (const __nv_bfloat16*)d_in[6];
    maps.wu_p = (const __nv_bfloat16*)d_in[7];
    maps.wd_p = (const __nv_bfloat16*)d_in[8];
    maps.out = (__nv_bfloat16*)d_out;
    void* scp = nullptr;
    cudaGetSymbolAddress(&scp, g_scratch);
    maps.sc = (Scratch*)scp;
    make_map(enc, &maps.k, d_in[1], 32 * 2048, 128);
    make_map(enc, &maps.v, d_in[2], 32 * 2048, 128);
    make_map(enc, &maps.wq, d_in[3], 576, 4096);
    make_map(enc, &maps.wo, d_in[4], 4096, 576);
    make_map(enc, &maps.wg, d_in[6], 576, 4608);
    make_map(enc, &maps.wu, d_in[7], 576, 4608);
    make_map(enc, &maps.wd, d_in[8], 4608, 576);
    make_rows_map(enc, &maps.rx, d_in[0]);
    make_rows_map(enc, &maps.rx2, (char*)scp + offsetof(Scratch, x2));
    make_rows_map(enc, &maps.rout, d_out);
    cudaFuncSetAttribute(fused_block_kernel, cudaFuncAttributeMaxDynamicSharedMemorySize, SMEM_BYTES);
    fused_block_kernel<<<128, 384, SMEM_BYTES>>>(maps);
}
```

```cpp
#include <cuda_runtime.h>
#include <cuda_bf16.h>
#include <cuda.h>
#include <stdint.h>
#include <stddef.h>

namespace {

constexpr int DM = 576;
constexpr int SLOT_BYTES = 16384;
constexpr int BOX_BYTES = 8192;
constexpr int NUNITS = 14;
constexpr int SMEM_TAIL = NUNITS * SLOT_BYTES;
constexpr int SMEM_BYTES = SMEM_TAIL + 2048 + 1024;
constexpr int OFF_FULL = SMEM_TAIL;
constexpr int OFF_EMPTY = SMEM_TAIL + 64;
constexpr int OFF_RED = SMEM_TAIL + 128;

constexpr int KV_AHEAD = 16;
#define GATE_SLOT 4
#define PROBE0_NS 700
#define PROBE_NS 300
#define GPOINT 1
constexpr int OFF_XBAR = SMEM_TAIL + 1792;
constexpr int OFF_ROWS = 8 * SLOT_BYTES;
constexpr int OFF_MODT = OFF_ROWS + 20480;
constexpr int OFF_GBAR = SMEM_TAIL + 1800;
constexpr int OFF_EPOCH = SMEM_TAIL + 1808;
constexpr int OFF_MRED = OFF_ROWS + 28672;

struct Scratch {
    unsigned epoch[128 * 32];
    uint32_t mod[6 * DM];
    uint32_t modp[3][2 * DM];
    uint4 h[2][2][128 * 36 * 32];
    uint4 part[128 * 8 * 36 * 32];
    uint4 hh[128 * 8 * 256];
    __nv_bfloat16 x2[2048 * DM];
};
__device__ Scratch g_scratch;

#define TG(i)
#define TL(i)
#define PROFR(i)
#define PROF(i)
#define PROFG(i)

struct Params {
    const __nv_bfloat16 *x, *cvec, *wmod, *kc, *vc, *wq_p, *wo_p, *wg_p, *wu_p, *wd_p;
    __nv_bfloat16* out;
    Scratch* sc;
    CUtensorMap k, v, wq, wo, wg, wu, wd, rx, rx2, rout;
};

__device__ __forceinline__ uint32_t smem_u32(const void* p) { return (uint32_t)__cvta_generic_to_shared(p); }
__device__ __forceinline__ void mbar_init(uint32_t a, uint32_t c) {
    asm volatile("mbarrier.init.shared::cta.b64 [%0], %1;" ::"r"(a), "r"(c) : "memory");
}
__device__ __forceinline__ void mbar_expect_tx(uint32_t a, uint32_t bytes) {
    asm volatile("mbarrier.arrive.expect_tx.shared::cta.b64 _, [%0], %1;" ::"r"(a), "r"(bytes) : "memory");
}
__device__ __forceinline__ bool mbar_try(uint32_t a, uint32_t ph) {
    uint32_t ok;
    asm volatile(
        "{\n.reg .pred p;\nmbarrier.try_wait.parity.shared::cta.b64 p, [%1], %2;\nselp.u32 %0, 1, 0, p;\n}"
        : "=r"(ok)
        : "r"(a), "r"(ph)
        : "memory");
    return ok != 0;
}
__device__ __forceinline__ uint32_t clk32() {
    uint32_t c;
    asm volatile("mov.u32 %0, %%clock;" : "=r"(c));
    return c;
}
constexpr uint32_t WAIT_LIMIT = 1u << 30;
__device__ __forceinline__ void mbar_wait(uint32_t a, uint32_t ph) {
    if (mbar_try(a, ph)) return;
    uint32_t t0 = clk32();
    while (!mbar_try(a, ph)) {
        if (clk32() - t0 > WAIT_LIMIT) break;
    }
}
__device__ __forceinline__ void mbar_arrive_cluster(uint32_t a, uint32_t cta) {
    asm volatile(
        "{\n.reg .b32 ra;\nmapa.shared::cluster.u32 ra, %0, %1;\nmbarrier.arrive.shared::cluster.b64 _, [ra];\n}" ::"r"(a),
        "r"(cta)
        : "memory");
}
__device__ __forceinline__ void tma_mc(uint32_t dst, const CUtensorMap* m, int c0, int c1, uint32_t bar) {
    asm volatile(
        "cp.async.bulk.tensor.2d.shared::cluster.global.mbarrier::complete_tx::bytes.multicast::cluster"
        " [%0], [%1, {%3, %4}], [%2], %5;" ::"r"(dst),
        "l"(m), "r"(bar), "r"(c0), "r"(c1), "h"((uint16_t)3)
        : "memory");
}
__device__ __forceinline__ void bulk_load(uint32_t dst, const void* src, uint32_t bytes, uint32_t bar) {
    asm volatile("cp.async.bulk.shared::cluster.global.mbarrier::complete_tx::bytes [%0], [%1], %2, [%3];" ::"r"(dst),
                 "l"(src), "r"(bytes), "r"(bar)
                 : "memory");
}
__device__ __forceinline__ void l2_prefetch(const void* p, uint32_t bytes) {
    asm volatile("cp.async.bulk.prefetch.L2.global [%0], %1;" ::"l"(p), "r"(bytes) : "memory");
}
__device__ __forceinline__ void bar_sync(int id, int n) { asm volatile("bar.sync %0, %1;" ::"r"(id), "r"(n) : "memory"); }
__device__ __forceinline__ void bar_arrive(int id, int n) {
    asm volatile("bar.arrive %0, %1;" ::"r"(id), "r"(n) : "memory");
}
__device__ __forceinline__ void wg_fence() { asm volatile("wgmma.fence.sync.aligned;" ::: "memory"); }
__device__ __forceinline__ void wg_commit() { asm volatile("wgmma.commit_group.sync.aligned;" ::: "memory"); }
template <int N>
__device__ __forceinline__ void wg_wait() {
    asm volatile("wgmma.wait_group.sync.aligned %0;" ::"n"(N) : "memory");
}
template <int N>
__device__ __forceinline__ void pin(float (&d)[N]) {
#pragma unroll
    for (int i = 0; i < N; i++) asm volatile("" : "+f"(d[i])::"memory");
}
template <int N>
__device__ __forceinline__ void pin(uint32_t (&d)[N]) {
#pragma unroll
    for (int i = 0; i < N; i++) asm volatile("" : "+r"(d[i])::"memory");
}
__device__ __forceinline__ uint32_t pack_bf16(float lo, float hi) {
    uint32_t r;
    asm("cvt.rn.bf16x2.f32 %0, %1, %2;" : "=r"(r) : "f"(hi), "f"(lo));
    return r;
}
__device__ __forceinline__ float bf_lo(uint32_t v) { return __uint_as_float(v << 16); }
__device__ __forceinline__ float bf_hi(uint32_t v) { return __uint_as_float(v & 0xffff0000u); }
__device__ __forceinline__ float round_bf16(float v) { return __bfloat162float(__float2bfloat16_rn(v)); }
__device__ __forceinline__ float ex2(float x) {
    float y;
    asm("ex2.approx.ftz.f32 %0, %1;" : "=f"(y) : "f"(x));
    return y;
}
__device__ __forceinline__ float rcp(float x) {
    float y;
    asm("rcp.approx.ftz.f32 %0, %1;" : "=f"(y) : "f"(x));
    return y;
}
__device__ __forceinline__ float tanh_fast(float x) {
    float y;
    asm("tanh.approx.f32 %0, %1;" : "=f"(y) : "f"(x));
    return y;
}
__device__ __forceinline__ void sts128(uint32_t a, uint32_t x, uint32_t y, uint32_t z, uint32_t w) {
    asm volatile("st.shared.v4.b32 [%0], {%1,%2,%3,%4};" ::"r"(a), "r"(x), "r"(y), "r"(z), "r"(w) : "memory");
}
__device__ __forceinline__ void lds128(uint32_t a, uint32_t& x, uint32_t& y, uint32_t& z, uint32_t& w) {
    asm volatile("ld.shared.v4.b32 {%0,%1,%2,%3}, [%4];" : "=r"(x), "=r"(y), "=r"(z), "=r"(w) : "r"(a) : "memory");
}
__device__ __forceinline__ void sts32f(uint32_t a, float v) {
    asm volatile("st.shared.f32 [%0], %1;" ::"r"(a), "f"(v) : "memory");
}
__device__ __forceinline__ float lds32f(uint32_t a) {
    float v;
    asm volatile("ld.shared.f32 %0, [%1];" : "=f"(v) : "r"(a) : "memory");
    return v;
}
#define F8(d, b) \
    "+f"(d[b]), "+f"(d[b + 1]), "+f"(d[b + 2]), "+f"(d[b + 3]), "+f"(d[b + 4]), "+f"(d[b + 5]), "+f"(d[b + 6]), "+f"(d[b + 7])

template <int TB>
__device__ __forceinline__ void wgmma_n128(float (&d)[64], uint32_t a0, uint32_t a1, uint32_t a2, uint32_t a3,
                                           uint64_t db, int sc) {
    asm volatile(
        "{\n.reg .pred p;\nsetp.ne.b32 p, %69, 0;\n"
        "wgmma.mma_async.sync.aligned.m64n128k16.f32.bf16.bf16 "
        "{%0,%1,%2,%3,%4,%5,%6,%7,%8,%9,%10,%11,%12,%13,%14,%15,%16,%17,%18,%19,%20,%21,%22,%23,%24,%25,%26,%27,%28,%29,%30,%31,"
        "%32,%33,%34,%35,%36,%37,%38,%39,%40,%41,%42,%43,%44,%45,%46,%47,%48,%49,%50,%51,%52,%53,%54,%55,%56,%57,%58,%59,%60,%61,%62,%63},"
        "{%64,%65,%66,%67}, %68, p, 1, 1, %70;\n}"
        : F8(d, 0), F8(d, 8), F8(d, 16), F8(d, 24), F8(d, 32), F8(d, 40), F8(d, 48), F8(d, 56)
        : "r"(a0), "r"(a1), "r"(a2), "r"(a3), "l"(db), "r"(sc), "n"(TB));
}
#define O8(d, b) \
    "=f"(d[b]), "=f"(d[b + 1]), "=f"(d[b + 2]), "=f"(d[b + 3]), "=f"(d[b + 4]), "=f"(d[b + 5]), "=f"(d[b + 6]), "=f"(d[b + 7])
template <int TB>
__device__ __forceinline__ void wgmma_n128_z(float (&d)[64], uint32_t a0, uint32_t a1, uint32_t a2, uint32_t a3,
                                             uint64_t db) {
    asm volatile(
        "wgmma.mma_async.sync.aligned.m64n128k16.f32.bf16.bf16 "
        "{%0,%1,%2,%3,%4,%5,%6,%7,%8,%9,%10,%11,%12,%13,%14,%15,%16,%17,%18,%19,%20,%21,%22,%23,%24,%25,%26,%27,%28,%29,%30,%31,"
        "%32,%33,%34,%35,%36,%37,%38,%39,%40,%41,%42,%43,%44,%45,%46,%47,%48,%49,%50,%51,%52,%53,%54,%55,%56,%57,%58,%59,%60,%61,%62,%63},"
        "{%64,%65,%66,%67}, %68, 0, 1, 1, %69;"
        : O8(d, 0), O8(d, 8), O8(d, 16), O8(d, 24), O8(d, 32), O8(d, 40), O8(d, 48), O8(d, 56)
        : "r"(a0), "r"(a1), "r"(a2), "r"(a3), "l"(db), "n"(TB));
}
template <int TB>
__device__ __forceinline__ void wgmma_n64_z(float (&d)[32], uint32_t a0, uint32_t a1, uint32_t a2, uint32_t a3,
                                            uint64_t db) {
    asm volatile(
        "wgmma.mma_async.sync.aligned.m64n64k16.f32.bf16.bf16 "
        "{%0,%1,%2,%3,%4,%5,%6,%7,%8,%9,%10,%11,%12,%13,%14,%15,%16,%17,%18,%19,%20,%21,%22,%23,%24,%25,%26,%27,%28,%29,%30,%31},"
        "{%32,%33,%34,%35}, %36, 0, 1, 1, %37;"
        : O8(d, 0), O8(d, 8), O8(d, 16), O8(d, 24)
        : "r"(a0), "r"(a1), "r"(a2), "r"(a3), "l"(db), "n"(TB));
}
template <int TB>
__device__ __forceinline__ void wgmma_n64(float (&d)[32], uint32_t a0, uint32_t a1, uint32_t a2, uint32_t a3,
                                          uint64_t db) {
    asm volatile(
        "wgmma.mma_async.sync.aligned.m64n64k16.f32.bf16.bf16 "
        "{%0,%1,%2,%3,%4,%5,%6,%7,%8,%9,%10,%11,%12,%13,%14,%15,%16,%17,%18,%19,%20,%21,%22,%23,%24,%25,%26,%27,%28,%29,%30,%31},"
        "{%32,%33,%34,%35}, %36, 1, 1, 1, %37;"
        : F8(d, 0), F8(d, 8), F8(d, 16), F8(d, 24)
        : "r"(a0), "r"(a1), "r"(a2), "r"(a3), "l"(db), "n"(TB));
}

__device__ __forceinline__ uint64_t desc_of(uint32_t saddr) {
    return (uint64_t)(((saddr >> 4) & 0x3FFFu) | (512u << 16)) | ((uint64_t)(64u | (1u << 30)) << 32);
}

struct Ring {
    uint32_t slot;
    uint32_t phase;
    __device__ __forceinline__ void next() {
        if (++slot == 8) {
            slot = 0;
            phase ^= 1;
        }
    }
};

struct Ctx {
    uint32_t sbase;
    int wg;
    uint32_t rel_cta;
    __device__ __forceinline__ void wait_full(uint32_t slot, uint32_t phase) const {
        mbar_wait(sbase + OFF_FULL + slot * 8, phase);
    }
    __device__ __forceinline__ void release(uint32_t slot) const {
        if (rel_cta < 2) mbar_arrive_cluster(sbase + OFF_EMPTY + slot * 8, rel_cta);
    }
};

__device__ __forceinline__ void gemm_n128(float (&d)[64], const uint32_t (&a)[144], const Ctx& c, Ring& r, bool nine,
                                          bool early) {
    uint32_t prev = 0;
#pragma unroll
    for (int s = 0; s < 9; s++) {
        if (s < 8 || nine) {
            if (s == GATE_SLOT) {
                if (early) {
                    wg_wait<0>();
                    c.release(prev);
                }
                bar_sync(8 + c.wg, 256);
            }
            c.wait_full(r.slot, r.phase);
            uint64_t db = desc_of(c.sbase + r.slot * SLOT_BYTES);
            wg_fence();
#pragma unroll
            for (int k = 0; k < 4; k++) {
                if ((s | k) == 0)
                    wgmma_n128_z<1>(d, a[0], a[1], a[2], a[3], db);
                else
                    wgmma_n128<1>(d, a[s * 16 + k * 4], a[s * 16 + k * 4 + 1], a[s * 16 + k * 4 + 2],
                                  a[s * 16 + k * 4 + 3], db + k * 128, 1);
            }
            wg_commit();
            if (s == 8 || (s == 7 && !nine)) bar_arrive(9 - c.wg, 256);
            if (s > 0) {
                wg_wait<1>();
                if (s != GATE_SLOT || !early) c.release(prev);
            }
            prev = r.slot;
            r.next();
        }
    }
    wg_wait<0>();
    c.release(prev);
    pin(d);
}
__device__ __forceinline__ void gemm_n64(float (&d)[32], const uint32_t (&a)[144], const Ctx& c, Ring& r, bool nine) {
    uint32_t prev = 0;
#pragma unroll
    for (int s = 0; s < 5; s++) {
        if (s < 4 || nine) {
            c.wait_full(r.slot, r.phase);
            uint64_t db = desc_of(c.sbase + r.slot * SLOT_BYTES);
            wg_fence();
#pragma unroll
            for (int k = 0; k < 8; k++) {
                if ((s | k) == 0)
                    wgmma_n64_z<1>(d, a[0], a[1], a[2], a[3], db);
                else if (s * 8 + k < 36)
                    wgmma_n64<1>(d, a[s * 32 + k * 4], a[s * 32 + k * 4 + 1], a[s * 32 + k * 4 + 2],
                                 a[s * 32 + k * 4 + 3], db + k * 128);
            }
            wg_commit();
            if (s > 0) {
                wg_wait<1>();
                c.release(prev);
            }
            prev = r.slot;
            r.next();
        }
    }
    wg_wait<0>();
    c.release(prev);
    pin(d);
}
__device__ __forceinline__ void st128(uint4* p, uint32_t x, uint32_t y, uint32_t z, uint32_t w) {
    asm volatile(
        "{\n.reg .b64 lo, hi;\n.reg .b128 t;\nmov.b64 lo, {%1, %2};\nmov.b64 hi, {%3, %4};\nmov.b128 t, {lo, hi};\n"
        "st.relaxed.gpu.global.b128 [%0], t;\n}" ::"l"(p),
        "r"(x), "r"(y), "r"(z), "r"(w)
        : "memory");
}
__device__ __forceinline__ uint4 ld128(const uint4* p) {
    uint4 r;
    asm volatile(
        "{\n.reg .b64 lo, hi;\n.reg .b128 t;\nld.relaxed.gpu.global.b128 t, [%4];\nmov.b128 {lo, hi}, t;\n"
        "mov.b64 {%0, %1}, lo;\nmov.b64 {%2, %3}, hi;\n}"
        : "=r"(r.x), "=r"(r.y), "=r"(r.z), "=r"(r.w)
        : "l"(p));
    return r;
}
__device__ __forceinline__ uint4 ldg128(const uint4* p) {
    uint4 r;
    asm volatile("ld.global.nc.v4.u32 {%0,%1,%2,%3}, [%4];" : "=r"(r.x), "=r"(r.y), "=r"(r.z), "=r"(r.w) : "l"(p));
    return r;
}
__device__ __forceinline__ void st64(void* p, uint32_t x, uint32_t y) {
    asm volatile("{\n.reg .b64 t;\nmov.b64 t, {%1, %2};\nst.relaxed.gpu.global.b64 [%0], t;\n}" ::"l"(p), "r"(x), "r"(y)
                 : "memory");
}
__device__ __forceinline__ uint2 ld64(const void* p) {
    uint2 r;
    asm volatile("{\n.reg .b64 t;\nld.relaxed.gpu.global.b64 t, [%2];\nmov.b64 {%0, %1}, t;\n}"
                 : "=r"(r.x), "=r"(r.y)
                 : "l"(p));
    return r;
}
__device__ __forceinline__ void rows_load(uint32_t sbase, const CUtensorMap* m, int row0) {
    mbar_expect_tx(sbase + OFF_XBAR, 16 * DM * 2);
    asm volatile(
        "cp.async.bulk.tensor.3d.shared::cluster.global.mbarrier::complete_tx::bytes [%0], [%1, {%3, %3, %4}], [%2];" ::"r"(
            sbase + OFF_ROWS),
        "l"(m), "r"(sbase + OFF_XBAR), "r"(0), "r"(row0)
        : "memory");
}
__device__ __forceinline__ void rows_store(uint32_t sbase, const CUtensorMap* m, int row0) {
    asm volatile("cp.async.bulk.tensor.3d.global.shared::cta.bulk_group [%0, {%2, %2, %3}], [%1];" ::"l"(m),
                 "r"(sbase + OFF_ROWS), "r"(0), "r"(row0)
                 : "memory");
    asm volatile("cp.async.bulk.commit_group;" ::: "memory");
}
__device__ __forceinline__ void rows_store_wait() { asm volatile("cp.async.bulk.wait_group 0;" ::: "memory"); }

__device__ __forceinline__ constexpr int own_col(int j) { return j < 8 ? (j >> 1) * 128 + (j & 1) * 8 : 512; }
__device__ __forceinline__ void row_reduce(float& s0, float& s1, uint32_t red, int warp, int lane) {
    s0 += __shfl_xor_sync(0xffffffffu, s0, 1);
    s1 += __shfl_xor_sync(0xffffffffu, s1, 1);
    s0 += __shfl_xor_sync(0xffffffffu, s0, 2);
    s1 += __shfl_xor_sync(0xffffffffu, s1, 2);
    if ((lane & 3) == 0) {
        sts32f(red + (warp * 16 + (lane >> 2)) * 4, s0);
        sts32f(red + (warp * 16 + 8 + (lane >> 2)) * 4, s1);
    }
    bar_sync(3, 256);
    s0 = 0.f;
    s1 = 0.f;
#pragma unroll
    for (int w = 0; w < 8; w++) {
        s0 += lds32f(red + (w * 16 + (lane >> 2)) * 4);
        s1 += lds32f(red + (w * 16 + 8 + (lane >> 2)) * 4);
    }
}
template <class F>
__device__ __forceinline__ void layernorm_rows(float (&v)[36], uint32_t red, int warp, int lane, F&& middle) {
    float s0 = 0.f, s1 = 0.f;
#pragma unroll
    for (int j = 0; j < 9; j++) {
        s0 += v[4 * j] + v[4 * j + 1];
        s1 += v[4 * j + 2] + v[4 * j + 3];
    }
    row_reduce(s0, s1, red, warp, lane);
    middle();
    const float m0 = s0 * (1.f / DM), m1 = s1 * (1.f / DM);
    s0 = 0.f;
    s1 = 0.f;
#pragma unroll
    for (int j = 0; j < 9; j++) {
        v[4 * j] -= m0;
        v[4 * j + 1] -= m0;
        v[4 * j + 2] -= m1;
        v[4 * j + 3] -= m1;
        s0 += v[4 * j] * v[4 * j] + v[4 * j + 1] * v[4 * j + 1];
        s1 += v[4 * j + 2] * v[4 * j + 2] + v[4 * j + 3] * v[4 * j + 3];
    }
    row_reduce(s0, s1, red + 512, warp, lane);
    const float r0 = rsqrtf(s0 * (1.f / DM) + 1e-5f), r1 = rsqrtf(s1 * (1.f / DM) + 1e-5f);
#pragma unroll
    for (int j = 0; j < 9; j++) {
        v[4 * j] *= r0;
        v[4 * j + 1] *= r0;
        v[4 * j + 2] *= r1;
        v[4 * j + 3] *= r1;
    }
}
__device__ __forceinline__ void mod_to_smem(uint32_t dst, const uint32_t* src, uint32_t tag) {
    const uint32_t t0 = clk32();
    uint4 u;
    while (true) {
        u = ld128(reinterpret_cast<const uint4*>(src));
        const uint32_t bad = ((u.x ^ tag) | (u.y ^ tag) | (u.z ^ tag) | (u.w ^ tag)) & 0xffffu;
        if (__all_sync(0xffffffffu, bad == 0) || clk32() - t0 > WAIT_LIMIT) break;
        __nanosleep(64);
    }
    sts128(dst, u.x & 0xffff0000u, u.y & 0xffff0000u, u.z & 0xffff0000u, u.w & 0xffff0000u);
}
__device__ __forceinline__ void lds_mod(float (&m)[18], uint32_t src  , int warp) {
#pragma unroll
    for (int j = 0; j < 9; j++)
        asm volatile("ld.shared.v2.f32 {%0,%1}, [%2];"
                     : "=f"(m[2 * j]), "=f"(m[2 * j + 1])
                     : "r"(src + own_col(j) * 4 - (j == 8 ? warp * 32 : 0))
                     : "memory");
}
__device__ __forceinline__ void modulate_store(const float (&v)[36], const float (&shift)[18], const float (&scale)[18],
                                               float post, uint4* hbuf  , int warp, int lane) {
    uint32_t o[18];
#pragma unroll
    for (int j = 0; j < 9; j++) {
        const uint32_t cc = pack_bf16(1.f + scale[2 * j], 1.f + scale[2 * j + 1]);
        const float c0 = bf_lo(cc) * post, c1 = bf_hi(cc) * post, s0 = shift[2 * j] * post, s1 = shift[2 * j + 1] * post;
        o[2 * j] = pack_bf16(fmaf(v[4 * j], c0, s0), fmaf(v[4 * j + 1], c1, s1));
        o[2 * j + 1] = pack_bf16(fmaf(v[4 * j + 2], c0, s0), fmaf(v[4 * j + 3], c1, s1));
        if ((j & 1) == 0) o[2 * j] = max(o[2 * j], 1u);
    }
#pragma unroll
    for (int i = 0; i < 4; i++) st128(hbuf + (i * 8 + warp) * 32 + lane, o[4 * i], o[4 * i + 1], o[4 * i + 2], o[4 * i + 3]);
    st64(reinterpret_cast<uint2*>(hbuf + 32 * 32) + warp * 32 + lane, o[16], o[17]);
}
__device__ __forceinline__ void sum_partials(float (&v)[36], const uint4* src  , uint32_t tag) {
    const uint32_t t0 = clk32();
    while (true) {
        uint4 t[8][4];
#pragma unroll
        for (int s = 0; s < 8; s++)
#pragma unroll
            for (int i = 0; i < 4; i++) t[s][i] = ld128(src + (s * 36 + i * 8) * 32);
        uint32_t bad = 0;
#pragma unroll
        for (int i = 0; i < 32; i++) v[i] = 0.f;
#pragma unroll
        for (int s = 0; s < 8; s++)
#pragma unroll
            for (int i = 0; i < 4; i++) {
                bad |= t[s][i].x ^ tag;
                v[8 * i] += bf_lo(t[s][i].x);
                v[8 * i + 1] += bf_hi(t[s][i].x);
                v[8 * i + 2] += bf_lo(t[s][i].y);
                v[8 * i + 3] += bf_hi(t[s][i].y);
                v[8 * i + 4] += bf_lo(t[s][i].z);
                v[8 * i + 5] += bf_hi(t[s][i].z);
                v[8 * i + 6] += bf_lo(t[s][i].w);
                v[8 * i + 7] += bf_hi(t[s][i].w);
                asm volatile("" : "+r"(bad));
            }
#pragma unroll
        for (int i = 0; i < 32; i++) asm volatile("" : "+f"(v[i]));
        if (__all_sync(0xffffffffu, (bad & 1u) == 0) || clk32() - t0 > WAIT_LIMIT) break;
    }
}
__device__ __forceinline__ void sum_tail(float (&v)[36], const uint2* src  , uint32_t tag) {
    const uint32_t t0 = clk32();
    while (true) {
        uint2 t[8];
#pragma unroll
        for (int s = 0; s < 8; s++) t[s] = ld64(src + s * 72 * 32);
        uint32_t bad = 0;
        v[32] = v[33] = v[34] = v[35] = 0.f;
#pragma unroll
        for (int s = 0; s < 8; s++) {
            bad |= t[s].x ^ tag;
            v[32] += bf_lo(t[s].x);
            v[33] += bf_hi(t[s].x);
            v[34] += bf_lo(t[s].y);
            v[35] += bf_hi(t[s].y);
        }
        if (__all_sync(0xffffffffu, (bad & 1u) == 0) || clk32() - t0 > WAIT_LIMIT) break;
    }
}
__device__ __forceinline__ void poll_tail(uint32_t (&a)[144], const uint2* src  ) {
    const uint32_t t0 = clk32();
    while (true) {
        uint32_t m = 0xffffffffu;
#pragma unroll
        for (int j = 0; j < 8; j++) {
            const uint2 t = ld64(src + j * 32);
            a[128 + 2 * j] = t.x;
            a[129 + 2 * j] = t.y;
        }
#pragma unroll
        for (int j = 0; j < 8; j++) m = min(m, a[128 + 2 * j]);
        if (__all_sync(0xffffffffu, m != 0) || clk32() - t0 > WAIT_LIMIT) break;
    }
}
template <int K0, int K1>
__device__ __forceinline__ void poll_frags(uint32_t (&a)[144], const uint4* src  , bool kick) {
    const uint32_t t0 = clk32();
    while (true) {
#pragma unroll
        for (int k = K0; k < K1; k++) {
            const uint4 t = ld128(src + k * 32);
            a[4 * k] = t.x;
            a[4 * k + 1] = t.y;
            a[4 * k + 2] = t.z;
            a[4 * k + 3] = t.w;
        }
        if (kick) bar_arrive(5, 256);
        kick = false;
        uint32_t m0 = a[4 * K0], m1 = a[4 * K0 + 4];
#pragma unroll
        for (int k = K0 + 2; k < K1; k += 2) {
            m0 = min(m0, a[4 * k]);
            m1 = min(m1, a[4 * k + 4]);
        }
        if (__all_sync(0xffffffffu, min(m0, m1) != 0) || clk32() - t0 > WAIT_LIMIT) break;
    }
}

constexpr float SM_SCALE = 0.08838834764831845f * 1.4426950408889634f;
constexpr float SM_HI = 1.2089258e24f;
constexpr float SM_LO = 9.0949470e-13f;
__device__ __forceinline__ void qk_step(float (&s)[32], const uint32_t (&q)[32], uint64_t dk) {
#pragma unroll
    for (int k = 0; k < 8; k++) {
        if (k == 0)
            wgmma_n64_z<0>(s, q[0], q[1], q[2], q[3], dk);
        else
            wgmma_n64<0>(s, q[4 * k], q[4 * k + 1], q[4 * k + 2], q[4 * k + 3], dk + (k >> 2) * 512 + (k & 3) * 2);
    }
}
__device__ __forceinline__ void pv_step(float (&o)[64], const uint32_t (&p)[16], uint64_t dv, int acc) {
#pragma unroll
    for (int k = 0; k < 4; k++)
        wgmma_n128<1>(o, p[4 * k], p[4 * k + 1], p[4 * k + 2], p[4 * k + 3], dv + k * 128, k != 0 ? 1 : acc);
}
template <bool SHIFT>
__device__ __forceinline__ void exp_step(const float (&s)[32], uint32_t (&p)[16], float n0, float n1, float& s0,
                                         float& s1) {
#pragma unroll
    for (int i = 0; i < 8; i++) {
        const float e0 = ex2(SHIFT ? s[4 * i] + n0 : s[4 * i]), e1 = ex2(SHIFT ? s[4 * i + 1] + n0 : s[4 * i + 1]);
        const float e2 = ex2(SHIFT ? s[4 * i + 2] + n1 : s[4 * i + 2]), e3 = ex2(SHIFT ? s[4 * i + 3] + n1 : s[4 * i + 3]);
        if (i == 0) {
            s0 = e0 + e1;
            s1 = e2 + e3;
        } else {
            s0 += e0 + e1;
            s1 += e2 + e3;
        }
        p[2 * i] = pack_bf16(e0, e1);
        p[2 * i + 1] = pack_bf16(e2, e3);
    }
}
__device__ __forceinline__ void row_max(const float (&sa)[32], const float (&sb)[32], float& x0, float& x1) {
    float xa[8];
#pragma unroll
    for (int i = 0; i < 8; i++) xa[i] = fmaxf(sa[i], sb[i]);
#pragma unroll
    for (int k = 1; k < 4; k++)
#pragma unroll
        for (int i = 0; i < 8; i++) xa[i] = fmaxf(xa[i], fmaxf(sa[8 * k + i], sb[8 * k + i]));
    x0 = fmaxf(fmaxf(xa[0], xa[1]), fmaxf(xa[4], xa[5]));
    x1 = fmaxf(fmaxf(xa[2], xa[3]), fmaxf(xa[6], xa[7]));
    x0 = fmaxf(x0, __shfl_xor_sync(0xffffffffu, x0, 1));
    x1 = fmaxf(x1, __shfl_xor_sync(0xffffffffu, x1, 1));
    x0 = fmaxf(x0, __shfl_xor_sync(0xffffffffu, x0, 2));
    x1 = fmaxf(x1, __shfl_xor_sync(0xffffffffu, x1, 2));
}
__device__ __forceinline__ void inv_row_sums(float l0, float l1, float& i0, float& i1) {
    l0 += __shfl_xor_sync(0xffffffffu, l0, 1);
    l1 += __shfl_xor_sync(0xffffffffu, l1, 1);
    l0 += __shfl_xor_sync(0xffffffffu, l0, 2);
    l1 += __shfl_xor_sync(0xffffffffu, l1, 2);
    i0 = rcp(l0);
    i1 = rcp(l1);
}

__device__ __forceinline__ uint32_t get_epoch(uint32_t sbase) { return __float_as_uint(lds32f(sbase + OFF_EPOCH)); }
__device__ __forceinline__ float silu_bf16(unsigned short c) {
    const float cv = bf_lo(c);
    return round_bf16(cv * rcp(1.f + ex2(-1.4426950408889634f * cv)));
}
__device__ __forceinline__ void st_mod(uint32_t* p, float v, uint32_t tag) {
    asm volatile("st.relaxed.gpu.global.u32 [%0], %1;" ::"l"(p), "r"(__float_as_uint(round_bf16(v)) | tag)
                 : "memory");
}
__device__ __forceinline__ void fma8(float (&acc)[8], float sc, const uint4& w) {
    acc[0] = fmaf(sc, bf_lo(w.x), acc[0]);
    acc[1] = fmaf(sc, bf_hi(w.x), acc[1]);
    acc[2] = fmaf(sc, bf_lo(w.y), acc[2]);
    acc[3] = fmaf(sc, bf_hi(w.y), acc[3]);
    acc[4] = fmaf(sc, bf_lo(w.z), acc[4]);
    acc[5] = fmaf(sc, bf_hi(w.z), acc[5]);
    acc[6] = fmaf(sc, bf_lo(w.w), acc[6]);
    acc[7] = fmaf(sc, bf_hi(w.w), acc[7]);
}
__device__ __forceinline__ void modp_load(uint4 (&u)[3], const uint32_t* src) {
#pragma unroll
    for (int i = 0; i < 3; i++) u[i] = ld128(reinterpret_cast<const uint4*>(src + i * 2 * DM));
}
__device__ __forceinline__ void modp_to_smem(uint4 (&u)[3], uint32_t dst, const uint32_t* src, uint32_t tag) {
    const uint32_t t0 = clk32();
    while (true) {
        uint32_t bad = 0;
#pragma unroll
        for (int i = 0; i < 3; i++) bad |= (u[i].x ^ tag) | (u[i].y ^ tag) | (u[i].z ^ tag) | (u[i].w ^ tag);
        if (__all_sync(0xffffffffu, (bad & 0xffu) == 0) || clk32() - t0 > WAIT_LIMIT) break;
        modp_load(u, src);
    }
    float s0 = 0.f, s1 = 0.f, s2 = 0.f, s3 = 0.f;
#pragma unroll
    for (int i = 0; i < 3; i++) {
        s0 += __uint_as_float(u[i].x & ~0xffu);
        s1 += __uint_as_float(u[i].y & ~0xffu);
        s2 += __uint_as_float(u[i].z & ~0xffu);
        s3 += __uint_as_float(u[i].w & ~0xffu);
    }
    const uint32_t p0 = pack_bf16(s0, s1), p1 = pack_bf16(s2, s3);
    sts128(dst, p0 << 16, p0 & 0xffff0000u, p1 << 16, p1 & 0xffff0000u);
}

__global__ void __cluster_dims__(2, 1, 1) __launch_bounds__(384, 1)
    fused_block_kernel(const __grid_constant__ Params maps) {
    extern __shared__ uint8_t smem_raw[];
    uint32_t sbase = (smem_u32(smem_raw) + 1023u) & ~1023u;
    asm volatile("" : "+r"(sbase));
    const int b = blockIdx.x;
    const int rank = b & 1;
    const int mt = ((b >> 1) & 7) * 2 + rank;
    const int g = b >> 4;
    const int warp = __shfl_sync(0xffffffffu, threadIdx.x >> 5, 0);
    const int lane = threadIdx.x & 31;
    Scratch* const sc_ = maps.sc;
    const __nv_bfloat16* const wmod = maps.wmod;
    const __nv_bfloat16* const cvec = maps.cvec;

#define SPROF(i)

    if (warp >= 8) {
        asm volatile("setmaxnreg.dec.sync.aligned.u32 24;");
        if (warp == 8 && lane == 0) {
#pragma unroll
            for (int i = 0; i < 8; i++) {
                mbar_init(sbase + OFF_FULL + i * 8, 1);
                mbar_init(sbase + OFF_EMPTY + i * 8, 4);
            }
            mbar_init(sbase + OFF_XBAR, 1);
            mbar_init(sbase + OFF_GBAR, 8);
            asm volatile("fence.mbarrier_init.release.cluster;" ::: "memory");
            asm volatile("barrier.cluster.arrive.relaxed;\nbarrier.cluster.wait;" ::: "memory");
            uint32_t slot = 0, phase = 1;
            const uint32_t dst0 = sbase + rank * BOX_BYTES;
            auto acquire = [&](uint32_t bytes) {
                mbar_wait(sbase + OFF_EMPTY + slot * 8, phase);
                mbar_expect_tx(sbase + OFF_FULL + slot * 8, bytes);
            };
            auto adv8 = [&]() {
                if (++slot == 8) {
                    slot = 0;
                    phase ^= 1;
                }
            };
#pragma unroll 1
            for (int hq = 0; hq < 4; hq++) {
                const int col = (g * 4 + ((hq + 1) & 3)) * 128 + rank * 64;
                if (hq == 2) {
                    l2_prefetch(maps.kc + (size_t)(g * 4 * 2048 + (b & 15) * 64) * 128, SLOT_BYTES);
                    l2_prefetch(maps.vc + (size_t)(g * 4 * 2048 + (b & 15) * 64) * 128, SLOT_BYTES);
                }
#pragma unroll 1
                for (int kc = 0; kc < 9; kc++) {
                    acquire(SLOT_BYTES);
                    tma_mc(dst0 + slot * SLOT_BYTES, &maps.wq, col, kc * 64, sbase + OFF_FULL + slot * 8);
                    adv8();
                }
            }
            const int row0 = g * 4 * 2048;
#pragma unroll 1
            for (int n = 0; n < 128; n++) {
                if (n < 4) mbar_wait(sbase + OFF_EMPTY + (slot + 1) * 8, phase);
                acquire(2 * SLOT_BYTES);
                const uint32_t bar = sbase + OFF_FULL + slot * 8;
                const int r0 = n == 0 ? 0 : (n == 127 ? 126 : n + 1);
                const int r1 = n == 0 ? 1 : (n == 127 ? 127 : n - 1);
                tma_mc(dst0 + slot * SLOT_BYTES, n == 127 ? &maps.v : &maps.k, rank * 64, row0 + r0 * 64, bar);
                tma_mc(dst0 + (slot + 1) * SLOT_BYTES, n == 0 ? &maps.k : &maps.v, rank * 64, row0 + r1 * 64, bar);
                adv8();
                adv8();
                const int u = n + KV_AHEAD;
                if (u < 128 && (u & 15) == (b & 15)) {
                    l2_prefetch(maps.kc + (size_t)(row0 + u * 64) * 128, SLOT_BYTES);
                    l2_prefetch(maps.vc + (size_t)(row0 + u * 64) * 128, SLOT_BYTES);
                }
            }
#pragma unroll 1
            for (int p = 0; p < 4; p++)
#pragma unroll 1
                for (int kc = 0; kc < 8; kc++) {
                    acquire(SLOT_BYTES);
                    tma_mc(dst0 + slot * SLOT_BYTES, &maps.wo, p * 128 + rank * 64, g * 512 + ((kc + 6) & 7) * 64,
                           sbase + OFF_FULL + slot * 8);
                    adv8();
                }
#pragma unroll 1
            for (int kc = 0; kc < 4; kc++) {
                acquire(SLOT_BYTES);
                tma_mc(dst0 + slot * SLOT_BYTES, &maps.wo, 512, g * 512 + ((kc + 3) & 3) * 128 + rank * 64,
                       sbase + OFF_FULL + slot * 8);
                adv8();
            }
            mbar_wait(sbase + OFF_GBAR, 0);
            const CUtensorMap* mg = rank ? &maps.wu : &maps.wg;
#pragma unroll 1
            for (int ch = 0; ch < 9; ch++)
#pragma unroll 1
                for (int kc = 0; kc < 9; kc++) {
                    acquire(SLOT_BYTES);
                    tma_mc(dst0 + slot * SLOT_BYTES, mg, g * 576 + ch * 64, kc * 64, sbase + OFF_FULL + slot * 8);
                    adv8();
                }
#pragma unroll 1
            for (int p = 0; p < 4; p++)
#pragma unroll 1
                for (int i = 0; i < 9; i++) {
                    acquire(SLOT_BYTES);
                    tma_mc(dst0 + slot * SLOT_BYTES, &maps.wd, p * 128 + rank * 64,
                           g * 576 + (i == 0 ? 8 : (i < 7 ? i + 1 : i - 7)) * 64, sbase + OFF_FULL + slot * 8);
                    adv8();
                }
#pragma unroll 1
            for (int i2 = 0; i2 < 5; i2++) {
                acquire(i2 < 4 ? SLOT_BYTES : BOX_BYTES);
                const int i = 2 * i2 + rank;
                if (i < 9)
                    tma_mc(dst0 + slot * SLOT_BYTES, &maps.wd, 512, g * 576 + (i == 0 ? 8 : (i < 7 ? i + 1 : i - 7)) * 64,
                           sbase + OFF_FULL + slot * 8);
                adv8();
            }
        } else if (warp == 11) {
            asm volatile("barrier.cluster.arrive.relaxed.aligned;" ::: "memory");
            bar_sync(6, 160);
            uint4* hz = sc_->h[(get_epoch(sbase) & 1) ^ 1][0] + (size_t)b * 72 * 32 + lane;
#pragma unroll 1
            for (int i = 0; i < 72; i++) {
                hz[i * 32] = make_uint4(0, 0, 0, 0);
                __nanosleep(200);
            }
            bar_sync(6, 160);
            if (lane == 0) {
#pragma unroll 1
                for (int i = 0; i < 9; i++) {
                    l2_prefetch((const char*)maps.wo_p + (size_t)b * 36864 + i * 4096, 4096);
                    __nanosleep(400);
                    l2_prefetch((const char*)maps.wg_p + (size_t)b * 41472 + i * 4608, 4608);
                    __nanosleep(400);
                    l2_prefetch((const char*)maps.wu_p + (size_t)b * 41472 + i * 4608, 4608);
                    __nanosleep(400);
                    l2_prefetch((const char*)maps.wd_p + (size_t)b * 41472 + i * 4608, 4608);
                    __nanosleep(400);
                }
            }
        } else if (warp == 9 || warp == 10) {
            asm volatile("barrier.cluster.arrive.relaxed.aligned;" ::: "memory");
            if (warp == 10) {
                bar_sync(11, 288);
                if (lane < 9) l2_prefetch((const char*)maps.wq_p + (size_t)b * 36864 + lane * 4096, 4096);
                __syncwarp();
            }
            bar_sync(4, 320);
            const uint32_t tag = (get_epoch(sbase) + 1) & 0xffffu;
            const int blk = warp == 9 ? 72 + b : 200 + b;
            if (blk < 216) {
                float acc[8];
#pragma unroll
                for (int e = 0; e < 8; e++) acc[e] = 0.f;
                const uint4* wp = reinterpret_cast<const uint4*>(wmod + (size_t)(lane >> 1) * (6 * DM) + blk * 16) + (lane & 1);
                const unsigned short* cp = reinterpret_cast<const unsigned short*>(cvec) + (lane >> 1);
#pragma unroll 1
                for (int i = 0; i < 36; i++) {
                    const uint4 w = __ldg(wp + (size_t)i * (16 * 6 * DM / 8));
                    const float sc = silu_bf16(__ldg(cp + i * 16));
                    fma8(acc, sc, w);
                }
#pragma unroll
                for (int o = 2; o < 32; o <<= 1)
#pragma unroll
                    for (int e = 0; e < 8; e++) acc[e] += __shfl_xor_sync(0xffffffffu, acc[e], o);
                if (lane < 2) {
#pragma unroll
                    for (int e = 0; e < 8; e++) st_mod(sc_->mod + blk * 16 + lane * 8 + e, acc[e], tag);
                }
            }
            if (warp == 9) {
#pragma unroll 1
                for (int st = 1; st <= 2; st++) {
                    bar_sync(7, 160);
                    const uint32_t* src = sc_->mod + (st * 3 - 1) * DM;
                    const int n = st == 1 ? 3 * DM : DM;
#pragma unroll 1
                    for (int i = lane * 4; i < n + 127 - ((n + 127) & 127); i += 128)
                        mod_to_smem(sbase + OFF_MODT + min(i, n - 4) * 4, src + min(i, n - 4), tag);
                    __syncwarp();
                    if (lane == 0) rows_load(sbase, st == 1 ? &maps.rx : &maps.rx2, (mt * 8 + g) * 16);
                    if (st == 1) {
                        bar_sync(7, 160);
                        if (lane == 0) {
                            rows_store(sbase, &maps.rx2, (mt * 8 + g) * 16);
                            rows_store_wait();
                        }
                        __syncwarp();
                        bar_arrive(10, 160);
                    }
                }
            }
        }
    } else {
        uint4 w1[3], xw[5], ew = make_uint4(0, 0, 0, 0);
        unsigned short cu[3];
        {
            const int t = threadIdx.x, bw = min(b, 107);
            const int row = (bw / 36) * 192 + (t >> 2);
#pragma unroll
            for (int i = 0; i < 3; i++) {
                w1[i] = ldg128(reinterpret_cast<const uint4*>(wmod + (size_t)(row + 64 * i) * (6 * DM)) + (bw % 36) * 4 + (t & 3));
                asm volatile("ld.global.nc.u16 %0, [%1];" : "=h"(cu[i]) : "l"(cvec + row + 64 * i));
            }
            if (t == 0) ew = ld128(reinterpret_cast<const uint4*>(&sc_->epoch[b * 32]));
        }
        if (threadIdx.x == 160) SPROF(5);
        asm volatile("setmaxnreg.inc.sync.aligned.u32 240;");
        if (threadIdx.x == 160) SPROF(6);
        const int wg = warp >> 2;
        const int tid = threadIdx.x;
        Ctx cx;
        cx.sbase = sbase;
        cx.wg = wg;
        if (wg == 1) bar_arrive(8, 256);
        cx.rel_cta = (lane == 0 && (warp & 3) < 2) ? (warp & 3) : 2;
        const uint32_t red = sbase + OFF_RED;
        const int own = mt * 8 + g;
        const int wown = mt * 8 + warp;
        PROF(0);
        PROFG(30);
        PROFR(17);
        {
            float acc[8];
#pragma unroll
            for (int e = 0; e < 8; e++) acc[e] = 0.f;
#pragma unroll
            for (int i = 0; i < 3; i++) fma8(acc, silu_bf16(cu[i]), w1[i]);
            {
                int off = tid;
                asm volatile("{\n.reg .pred p;\nsetp.gt.f32 p, %1, 0f00000000;\n@p add.s32 %0, %0, %2;\n}"
                             : "+r"(off)
                             : "f"(acc[7]), "r"((int)gridDim.y - 1));
#pragma unroll
                for (int i = 0; i < 5; i++)
                    xw[i] = ldg128(reinterpret_cast<const uint4*>(maps.x + (size_t)own * 16 * DM) + min(off + 256 * i, 1151));
                asm volatile("barrier.cluster.arrive.relaxed.aligned;" ::: "memory");
            }
#pragma unroll
            for (int o = 4; o < 32; o <<= 1)
#pragma unroll
                for (int e = 0; e < 8; e++) acc[e] += __shfl_xor_sync(0xffffffffu, acc[e], o);
            PROFR(19);
            if (lane < 4) {
                const uint32_t dst = sbase + OFF_MRED + warp * 128 + lane * 32;
                sts128(dst, __float_as_uint(acc[0]), __float_as_uint(acc[1]), __float_as_uint(acc[2]), __float_as_uint(acc[3]));
                sts128(dst + 16, __float_as_uint(acc[4]), __float_as_uint(acc[5]), __float_as_uint(acc[6]), __float_as_uint(acc[7]));
            }
            if (tid == 0) sts128(sbase + OFF_EPOCH, ew.x, ew.y, ew.z, ew.w);
            bar_sync(3, 256);
            PROFR(20);
            if (tid < 32 && b < 108) {
                float sum = 0.f;
#pragma unroll
                for (int w8 = 0; w8 < 8; w8++) sum += lds32f(sbase + OFF_MRED + w8 * 128 + tid * 4);
                asm volatile("st.relaxed.gpu.global.u32 [%0], %1;" ::"l"(&sc_->modp[b / 36][(b % 36) * 32 + tid]),
                             "r"((__float_as_uint(sum) & ~0xffu) | ((get_epoch(sbase) + 1) & 0xffu))
                             : "memory");
            }
            PROFR(21);
#pragma unroll
            for (int i = 0; i < 5; i++) {
                const int vi = min(tid + 256 * i, 1151), ln = vi >> 3;
                sts128(sbase + OFF_ROWS + ln * 128 + (((vi & 7) ^ (ln & 7)) << 4), xw[i].x, xw[i].y, xw[i].z, xw[i].w);
            }
            bar_sync(3, 256);
            bar_arrive(11, 288);
        }

        Ring ring{0u, 0u};
        int stage = 0;
        asm volatile("" : "+r"(stage));
#pragma unroll 1
        for (;; stage++) {
            int tid, lane;
            asm volatile("mov.u32 %0, %%tid.x;" : "=r"(tid));
            lane = tid & 31;
            const uint32_t epoch = get_epoch(sbase);
            {
                float v[36];
                const uint32_t modt = sbase + OFF_MODT + (warp * 16 + (lane & 3) * 2) * 4;
                if (stage == 0) {
#pragma unroll
                    for (int i = 0; i < 36; i++) v[i] = 0.f;
                } else {
                    const uint4* psrc = sc_->part + (size_t)own * 8 * 36 * 32;
                    sum_partials(v, psrc + tid, stage & 1);
                    PROF(stage == 1 ? 8 : 15);
                    if (lane == 0) asm volatile("mbarrier.arrive.shared::cta.b64 _, [%0];" ::"r"(sbase + OFF_GBAR) : "memory");
                    sum_tail(v, reinterpret_cast<const uint2*>(psrc + 32 * 32) + tid, stage & 1);
                }
                if (stage) mbar_wait(sbase + OFF_XBAR, stage - 1);
                if (stage == 0) PROFR(22);
                {
                    const float gs = stage == 2 ? 0.5f : 1.f;
                    float gate[18];
                    lds_mod(gate, modt, warp);
                    const int r = lane >> 2;
                    const uint32_t rows = sbase + OFF_ROWS + r * (DM * 2) + (lane & 3) * 4;
#pragma unroll
                    for (int j = 0; j < 9; j++) {
                        const int ch = j < 8 ? (j >> 1) * 2 + (warp >> 2) : 8, c16 = j < 8 ? (warp & 3) * 2 + (j & 1) : warp;
                        const uint32_t ad = rows + ch * 128 + ((c16 ^ ((r + ch) & 7)) << 4);
                        const uint32_t u0 = __float_as_uint(lds32f(ad)), u1 = __float_as_uint(lds32f(ad + 8 * DM * 2));
                        const float g0 = stage ? gate[2 * j] * gs : 0.f, g1 = stage ? gate[2 * j + 1] * gs : 0.f;
                        v[4 * j] = fmaf(g0, v[4 * j], bf_lo(u0));
                        v[4 * j + 1] = fmaf(g1, v[4 * j + 1], bf_hi(u0));
                        v[4 * j + 2] = fmaf(g0, v[4 * j + 2], bf_lo(u1));
                        v[4 * j + 3] = fmaf(g1, v[4 * j + 3], bf_hi(u1));
                        sts32f(ad, __uint_as_float(pack_bf16(v[4 * j], v[4 * j + 1])));
                        sts32f(ad + 8 * DM * 2, __uint_as_float(pack_bf16(v[4 * j + 2], v[4 * j + 3])));
                    }
                    asm volatile("fence.proxy.async.shared::cta;" ::: "memory");
                }
                if (stage == 2) break;
                PROF(stage == 0 ? 1 : 9);
                uint4 ua[3], ub[3];
#pragma unroll
                for (int i = 0; i < 3; i++) ua[i] = ub[i] = make_uint4(0, 0, 0, 0);
                layernorm_rows(v, red, warp, lane, [&]() {
                    if (stage == 0) {
                        modp_load(ua, sc_->modp[0] + tid * 4);
                        if (warp == 0) modp_load(ub, sc_->modp[0] + 1024 + tid * 4);
                    }
                });
                if (stage == 0) PROFR(27);
                if (stage == 0) {
                    const uint32_t tag = (epoch + 1) & 0xffu;
                    modp_to_smem(ua, sbase + OFF_MODT + (DM + tid * 4) * 4, sc_->modp[0] + tid * 4, tag);
                    if (warp == 0)
                        modp_to_smem(ub, sbase + OFF_MODT + (DM + 1024 + tid * 4) * 4, sc_->modp[0] + 1024 + tid * 4, tag);
                    bar_sync(3, 256);
                }
                float shift[18], scale[18];
                lds_mod(shift, modt + DM * 4, warp);
                lds_mod(scale, modt + 2 * DM * 4, warp);
                if (stage == 0) PROFR(28);
                PROF(stage == 0 ? 2 : 10);
                modulate_store(v, shift, scale, stage == 0 ? SM_SCALE : 1.f, sc_->h[epoch & 1][stage] + (size_t)own * 36 * 32, warp, lane);
                if (stage == 0) asm volatile("barrier.cluster.wait.aligned;" ::: "memory");
            }

            const uint32_t spill = sbase + 8 * SLOT_BYTES + wg * 3 * SLOT_BYTES + (tid & 127) * 16;
            uint32_t a[144];
            PROF(stage == 0 ? 3 : 11);
            {
                const uint4* hsrc = sc_->h[epoch & 1][stage] + (size_t)wown * 36 * 32 + lane;
                __nanosleep(stage == 0 ? PROBE0_NS : PROBE_NS);
                poll_tail(a, reinterpret_cast<const uint2*>(hsrc - lane + 32 * 32) + lane);
                PROF(stage == 0 ? 4 : 12);
                if (stage == 1) PROFG(25);
                TG(stage * 32 + 30);
                if (wg == 1) bar_sync(5, 256);
                poll_frags<0, 32>(a, hsrc, wg == 0);
                if (stage == 0) bar_arrive(4, 320);
            }
            uint4* hhbuf = sc_->hh + (size_t)b * 8 * 256 + tid;
            float d[64];
#pragma unroll 1
            for (int ch = 0;; ch++) {
                TG(stage * 32 + ch * 2);
                gemm_n128(d, a, cx, ring, true, stage && wg);
                TG(stage * 32 + ch * 2 + 1);
                if (stage == 0) {
                    if (ch == 3) break;
#pragma unroll
                    for (int v = 0; v < 8; v++)
                        sts128(spill + (ch * 8 + v) * 2048, pack_bf16(d[8 * v], d[8 * v + 1]),
                               pack_bf16(d[8 * v + 2], d[8 * v + 3]), pack_bf16(d[8 * v + 4], d[8 * v + 5]),
                               pack_bf16(d[8 * v + 6], d[8 * v + 7]));
                } else {
#pragma unroll
                    for (int i = 0; i < 32; i++) {
                        const float gv = d[i], gu = gv * d[32 + i];
                        const float z = gv * fmaf(gv * gv, 0.7978845608028654f * 0.044715f, 0.7978845608028654f);
                        d[i] = fmaf(gu, tanh_fast(z), gu);
                    }
                    if (ch == 8) break;
                    if (wg == 0) {
                        if (ch == 0) bar_arrive(7, 160);
                        if (ch == 2) bar_sync(10, 160);
                    }
#pragma unroll
                    for (int v = 0; v < 4; v++) {
                        const uint4 h4 = make_uint4(pack_bf16(d[8 * v], d[8 * v + 1]), pack_bf16(d[8 * v + 2], d[8 * v + 3]),
                                                    pack_bf16(d[8 * v + 4], d[8 * v + 5]), pack_bf16(d[8 * v + 6], d[8 * v + 7]));
                        if (ch < 2)
                            __stcg(hhbuf + (ch * 4 + v) * 256, h4);
                        else
                            sts128(spill + ((ch - 2) * 4 + v) * 2048, h4.x, h4.y, h4.z, h4.w);
                    }
                }
            }
            if (stage == 0) {
                uint32_t q[32];
#pragma unroll
                for (int i = 0; i < 32; i++) q[i] = pack_bf16(d[2 * i], d[2 * i + 1]);
                PROF(5);
                PROFG(23);
                if (wg == 0) bar_arrive(6, 160);
                {
                    float o[64], sa[32], sb[32];
                    uint32_t pa[16], pb[16];
#pragma unroll
                    for (int i = 0; i < 64; i++) o[i] = 0.f;
                    float n0 = 0.f, n1 = 0.f, l0 = 1.f, l1 = 1.f;
                    bool shifted = false;
                    const uint64_t dbase = desc_of(sbase);
                    const uint64_t dbk = dbase - (511u << 16);
                    const int my_bar = 1 + wg, other_bar = 2 - wg;

                    auto softmax_a = [&](bool first, float& s0, float& s1) {
                        if (first) {
                            shifted = false;
                            n0 = n1 = 0.f;
                            l0 = l1 = 0.f;
                        }
                        if (shifted)
                            exp_step<true>(sa, pa, n0, n1, s0, s1);
                        else
                            exp_step<false>(sa, pa, n0, n1, s0, s1);
                    };
                    auto softmax_b = [&](bool first, float s0, float s1) {
                        float u0, u1;
                        if (shifted)
                            exp_step<true>(sb, pb, n0, n1, u0, u1);
                        else
                            exp_step<false>(sb, pb, n0, n1, u0, u1);
                        s0 += u0;
                        s1 += u1;
                        bool bad = !(fmaxf(s0, s1) <= SM_HI);
                        if (first) {
                            float r0 = s0 + __shfl_xor_sync(0xffffffffu, s0, 1), r1 = s1 + __shfl_xor_sync(0xffffffffu, s1, 1);
                            r0 += __shfl_xor_sync(0xffffffffu, r0, 2);
                            r1 += __shfl_xor_sync(0xffffffffu, r1, 2);
                            bad = bad || !(fminf(r0, r1) >= SM_LO);
                        }
                        if (__any_sync(0xffffffffu, bad)) {
                            float x0, x1;
                            row_max(sa, sb, x0, x1);
                            x0 = -x0;
                            x1 = -x1;
                            if (!first) {
                                x0 = fminf(x0, n0);
                                x1 = fminf(x1, n1);
                                const float al0 = ex2(x0 - n0), al1 = ex2(x1 - n1);
                                l0 *= al0;
                                l1 *= al1;
#pragma unroll
                                for (int i = 0; i < 16; i++) {
                                    o[4 * i] *= al0;
                                    o[4 * i + 1] *= al0;
                                    o[4 * i + 2] *= al1;
                                    o[4 * i + 3] *= al1;
                                }
                            }
                            n0 = x0;
                            n1 = x1;
                            shifted = true;
                            exp_step<true>(sa, pa, n0, n1, s0, s1);
                            exp_step<true>(sb, pb, n0, n1, u0, u1);
                            s0 += u0;
                            s1 += u1;
                        }
                        l0 += s0;
                        l1 += s1;
                    };

                    cx.wait_full(4, 0);
                    if (wg == 1) bar_sync(my_bar, 256);
                    wg_fence();
                    qk_step(sa, q, dbk + 4 * 1024);
                    qk_step(sb, q, dbk + 5 * 1024);
                    wg_commit();
                    bar_arrive(other_bar, 256);
                    wg_wait<0>();
                    pin(sa);
                    pin(sb);
                    cx.release(4);
                    cx.wait_full(6, 0);
                    {
                        float s0, s1;
                        softmax_a(true, s0, s1);
                        softmax_b(true, s0, s1);
                    }
                    uint32_t alo = (uint32_t)dbase + 6 * 1024, blo = (uint32_t)dbase;
                    const uint32_t dhi = (uint32_t)(dbase >> 32);
#pragma unroll 1
                    for (int t = 1; t < 64; t++) {
                        const int j = t & 15;
                        const uint32_t sA = 2 + 4 * (t & 1), sB = 4 - 4 * (t & 1);
                        const uint64_t da = ((uint64_t)dhi << 32) | alo, db = ((uint64_t)dhi << 32) | blo;
                        TL(0);
                        bar_sync(my_bar, 256);
                        TL(2);
                        wg_fence();
                        qk_step(sa, q, da - (511u << 16));
                        pv_step(o, pa, da + 1024, j != 1);
                        wg_commit();
                        cx.wait_full(sB, ((36 + 4 * t) >> 3) & 1);
                        wg_fence();
                        qk_step(sb, q, db - (511u << 16));
                        pv_step(o, pb, db + 1024, 1);
                        wg_commit();
                        bar_arrive(other_bar, 256);
                        alo ^= 4096;
                        blo ^= 4096;
                        asm volatile("" : "+r"(alo), "+r"(blo));
                        TL(3);
                        wg_wait<1>();
                        pin(sa);
                        pin(pa);
                        TL(4);
                        cx.release(sA);
                        const float lp0 = l0, lp1 = l1;
                        float s0, s1;
                        softmax_a(j == 0, s0, s1);
                        TL(5);
                        wg_wait<0>();
                        pin(o);
                        pin(sb);
                        pin(pb);
                        TL(6);
                        cx.release(sB);
                        if (j == 0) {
                            float i0, i1;
                            inv_row_sums(lp0, lp1, i0, i1);
                            const uint32_t dst = spill + ((t >> 4) - 1) * 16384;
#pragma unroll
                            for (int v = 0; v < 8; v++)
                                sts128(dst + v * 2048, pack_bf16(o[8 * v] * i0, o[8 * v + 1] * i0),
                                       pack_bf16(o[8 * v + 2] * i1, o[8 * v + 3] * i1),
                                       pack_bf16(o[8 * v + 4] * i0, o[8 * v + 5] * i0),
                                       pack_bf16(o[8 * v + 6] * i1, o[8 * v + 7] * i1));
                        }
                        const uint32_t bn = sbase + OFF_FULL + (8 - sA) * 8, pn = ((38 + 4 * t) >> 3) & 1;
                        const bool okn = mbar_try(bn, pn);
                        TL(1);
                        softmax_b(j == 0, s0, s1);
                        if (!okn || j == 15) {
                            mbar_wait(bn, pn);
                            if (t == 47 && wg == 0) bar_arrive(6, 160);
                            if (j == 15 && t < 63) {
                                const uint32_t src = spill + (t >> 4) * 16384;
#pragma unroll
                                for (int v = 0; v < 8; v++)
                                    lds128(src + v * 2048, q[4 * v], q[4 * v + 1], q[4 * v + 2], q[4 * v + 3]);
                            }
                        }
                        TL(7);
                    }
                    bar_sync(my_bar, 256);
                    wg_fence();
                    pv_step(o, pa, dbase + 2 * 1024, 1);
                    pv_step(o, pb, dbase + 3 * 1024, 1);
                    wg_commit();
                    if (wg == 0) bar_arrive(other_bar, 256);
                    float i0, i1;
                    inv_row_sums(l0, l1, i0, i1);
                    wg_wait<0>();
                    pin(o);
                    cx.release(2);
#pragma unroll
                    for (int i = 0; i < 16; i++) {
                        a[2 * i] = pack_bf16(o[4 * i] * i0, o[4 * i + 1] * i0);
                        a[2 * i + 1] = pack_bf16(o[4 * i + 2] * i1, o[4 * i + 3] * i1);
                    }
#pragma unroll
                    for (int v = 0; v < 24; v++)
                        lds128(spill + v * 2048, a[32 + 4 * v], a[33 + 4 * v], a[34 + 4 * v], a[35 + 4 * v]);
#pragma unroll
                    for (int i = 128; i < 144; i++) a[i] = 0;
                }
                ring.slot = 4;
                ring.phase = 0;
                PROF(6);
                PROFG(24);
            } else {
#pragma unroll
                for (int v = 0; v < 8; v++) {
                    const uint4 t = __ldcg(hhbuf + v * 256);
                    a[112 + 4 * v] = t.x;
                    a[113 + 4 * v] = t.y;
                    a[114 + 4 * v] = t.z;
                    a[115 + 4 * v] = t.w;
                }
#pragma unroll
                for (int i = 0; i < 16; i++) a[i] = pack_bf16(d[2 * i], d[2 * i + 1]);
#pragma unroll
                for (int v = 0; v < 24; v++)
                    lds128(spill + v * 2048, a[16 + 4 * v], a[17 + 4 * v], a[18 + 4 * v], a[19 + 4 * v]);
                PROF(13);
            }

            {
                uint4* dst = sc_->part + ((size_t)wown * 8 + g) * 36 * 32 + lane;
                const uint32_t ptag = (stage + 1) & 1;
#pragma unroll 1
                for (int p = 0; p < 4; p++) {
                    TG(stage * 32 + 18 + p * 2);
                    gemm_n128(d, a, cx, ring, stage != 0, stage && wg);
                    TG(stage * 32 + 19 + p * 2);
#pragma unroll
                    for (int u = 0; u < 8; u++)
                        st128(dst + (p * 8 + u) * 32, (pack_bf16(d[8 * u], d[8 * u + 1]) & ~1u) | ptag,
                              pack_bf16(d[8 * u + 2], d[8 * u + 3]), pack_bf16(d[8 * u + 4], d[8 * u + 5]),
                              pack_bf16(d[8 * u + 6], d[8 * u + 7]));
                    if (p == 0 && wg == 0) bar_arrive(7, 160);
                }
                float e[32];
                TG(stage * 32 + 26);
                gemm_n64(e, a, cx, ring, stage != 0);
                TG(stage * 32 + 27);
                uint2* dst2 = reinterpret_cast<uint2*>(dst - lane + 32 * 32) + lane;
#pragma unroll
                for (int j = 0; j < 8; j++)
                    st64(dst2 + j * 32, (pack_bf16(e[4 * j], e[4 * j + 1]) & ~1u) | ptag, pack_bf16(e[4 * j + 2], e[4 * j + 3]));
            }
            PROF(stage == 0 ? 7 : 14);
            if (stage == 1) {
                PROFG(26);
                asm volatile("barrier.cluster.arrive.relaxed.aligned;" ::: "memory");
            }
        }
        if (wg == 0) bar_sync(8, 256);
        bar_sync(3, 256);
        if (tid == 32) sc_->epoch[b * 32] = get_epoch(sbase) + 1;
        if (tid == 0) {
            rows_store(sbase, &maps.rout, own * 16);
            rows_store_wait();
        }
        __syncwarp();
        PROF(16);
        PROFG(31);
        asm volatile("barrier.cluster.wait.aligned;" ::: "memory");
    }
}

typedef CUresult (*EncodeFn)(CUtensorMap*, CUtensorMapDataType, cuuint32_t, void*, const cuuint64_t*, const cuuint64_t*,
                             const cuuint32_t*, const cuuint32_t*, CUtensorMapInterleave, CUtensorMapSwizzle,
                             CUtensorMapL2promotion, CUtensorMapFloatOOBfill);

void make_map(EncodeFn enc, CUtensorMap* m, const void* ptr, uint64_t rows, uint64_t cols, bool narrow = false) {
    cuuint64_t gdim[2] = {cols, rows};
    cuuint64_t gstr[1] = {cols * 2};
    cuuint32_t box[2] = {narrow ? 16u : 64u, narrow ? 192u : 64u};
    cuuint32_t estr[2] = {1, 1};
    enc(m, CU_TENSOR_MAP_DATA_TYPE_BFLOAT16, 2, const_cast<void*>(ptr), gdim, gstr, box, estr,
        CU_TENSOR_MAP_INTERLEAVE_NONE, narrow ? CU_TENSOR_MAP_SWIZZLE_NONE : CU_TENSOR_MAP_SWIZZLE_128B,
        CU_TENSOR_MAP_L2_PROMOTION_L2_128B,
        CU_TENSOR_MAP_FLOAT_OOB_FILL_NONE);
}

void make_rows_map(EncodeFn enc, CUtensorMap* m, const void* ptr) {
    cuuint64_t gdim[3] = {64, 9, 2048};
    cuuint64_t gstr[2] = {128, DM * 2};
    cuuint32_t box[3] = {64, 9, 16};
    cuuint32_t estr[3] = {1, 1, 1};
    enc(m, CU_TENSOR_MAP_DATA_TYPE_BFLOAT16, 3, const_cast<void*>(ptr), gdim, gstr, box, estr,
        CU_TENSOR_MAP_INTERLEAVE_NONE, CU_TENSOR_MAP_SWIZZLE_128B, CU_TENSOR_MAP_L2_PROMOTION_L2_128B,
        CU_TENSOR_MAP_FLOAT_OOB_FILL_NONE);
}

}

extern "C" void kernel_launch(void* const* d_in, const int* in_sizes, int n_in, void* d_out, int out_size) {
    (void)in_sizes;
    (void)n_in;
    (void)out_size;
    void* fn = nullptr;
    cudaDriverEntryPointQueryResult qr;
    cudaGetDriverEntryPoint("cuTensorMapEncodeTiled", &fn, cudaEnableDefault, &qr);
    EncodeFn enc = (EncodeFn)fn;
    Params maps;
    maps.x = (const __nv_bfloat16*)d_in[0];
    maps.cvec = (const __nv_bfloat16*)d_in[9];
    maps.wmod = (const __nv_bfloat16*)d_in[10];
    maps.kc = (const __nv_bfloat16*)d_in[1];
    maps.vc = (const __nv_bfloat16*)d_in[2];
    maps.wq_p = (const __nv_bfloat16*)d_in[3];
    maps.wo_p = (const __nv_bfloat16*)d_in[4];
    maps.wg_p = (const __nv_bfloat16*)d_in[6];
    maps.wu_p = (const __nv_bfloat16*)d_in[7];
    maps.wd_p = (const __nv_bfloat16*)d_in[8];
    maps.out = (__nv_bfloat16*)d_out;
    void* scp = nullptr;
    cudaGetSymbolAddress(&scp, g_scratch);
    maps.sc = (Scratch*)scp;
    make_map(enc, &maps.k, d_in[1], 32 * 2048, 128);
    make_map(enc, &maps.v, d_in[2], 32 * 2048, 128);
    make_map(enc, &maps.wq, d_in[3], 576, 4096);
    make_map(enc, &maps.wo, d_in[4], 4096, 576);
    make_map(enc, &maps.wg, d_in[6], 576, 4608);
    make_map(enc, &maps.wu, d_in[7], 576, 4608);
    make_map(enc, &maps.wd, d_in[8], 4608, 576);
    make_rows_map(enc, &maps.rx, d_in[0]);
    make_rows_map(enc, &maps.rx2, (char*)scp + offsetof(Scratch, x2));
    make_rows_map(enc, &maps.rout, d_out);
    cudaFuncSetAttribute(fused_block_kernel, cudaFuncAttributeMaxDynamicSharedMemorySize, SMEM_BYTES);
    fused_block_kernel<<<128, 384, SMEM_BYTES>>>(maps);
}
```

```cpp
#include <cuda_runtime.h>
#include <cuda_bf16.h>
#include <cuda.h>
#include <stdint.h>
#include <stddef.h>

namespace {

constexpr int DM = 576;
constexpr int SLOT_BYTES = 16384;
constexpr int BOX_BYTES = 8192;
constexpr int NUNITS = 14;
constexpr int SMEM_TAIL = NUNITS * SLOT_BYTES;
constexpr int SMEM_BYTES = SMEM_TAIL + 2048 + 1024;
constexpr int OFF_FULL = SMEM_TAIL;
constexpr int OFF_EMPTY = SMEM_TAIL + 64;
constexpr int OFF_RED = SMEM_TAIL + 128;

constexpr int KV_AHEAD = 16;
#define GATE_SLOT 4
#define PROBE0_NS 700
#define PROBE_NS 300
#define GPOINT 1
constexpr int OFF_XBAR = SMEM_TAIL + 1792;
constexpr int OFF_ROWS = 8 * SLOT_BYTES;
constexpr int OFF_MODT = OFF_ROWS + 20480;
constexpr int OFF_GBAR = SMEM_TAIL + 1800;
constexpr int OFF_EPOCH = SMEM_TAIL + 1808;
constexpr int OFF_MRED = OFF_ROWS + 28672;

struct Scratch {
    unsigned epoch[128 * 32];
    uint32_t mod[6 * DM];
    uint32_t modp[3][2 * DM];
    uint4 h[2][2][128 * 36 * 32];
    uint4 part[128 * 8 * 36 * 32];
    uint4 hh[128 * 8 * 256];
    __nv_bfloat16 x2[2048 * DM];
};
__device__ Scratch g_scratch;

#define TG(i)
#define TL(i)
#define PROFR(i)
#define PROF(i)
#define PROFG(i)

struct Params {
    const __nv_bfloat16 *x, *cvec, *wmod, *kc, *vc, *wq_p, *wo_p, *wg_p, *wu_p, *wd_p;
    __nv_bfloat16* out;
    Scratch* sc;
    CUtensorMap k, v, wq, wo, wg, wu, wd, rx, rx2, rout;
};

__device__ __forceinline__ uint32_t smem_u32(const void* p) { return (uint32_t)__cvta_generic_to_shared(p); }
__device__ __forceinline__ void mbar_init(uint32_t a, uint32_t c) {
    asm volatile("mbarrier.init.shared::cta.b64 [%0], %1;" ::"r"(a), "r"(c) : "memory");
}
__device__ __forceinline__ void mbar_expect_tx(uint32_t a, uint32_t bytes) {
    asm volatile("mbarrier.arrive.expect_tx.shared::cta.b64 _, [%0], %1;" ::"r"(a), "r"(bytes) : "memory");
}
__device__ __forceinline__ bool mbar_try(uint32_t a, uint32_t ph) {
    uint32_t ok;
    asm volatile(
        "{\n.reg .pred p;\nmbarrier.try_wait.parity.shared::cta.b64 p, [%1], %2;\nselp.u32 %0, 1, 0, p;\n}"
        : "=r"(ok)
        : "r"(a), "r"(ph)
        : "memory");
    return ok != 0;
}
__device__ __forceinline__ uint32_t clk32() {
    uint32_t c;
    asm volatile("mov.u32 %0, %%clock;" : "=r"(c));
    return c;
}
constexpr uint32_t WAIT_LIMIT = 1u << 30;
__device__ __forceinline__ void mbar_wait(uint32_t a, uint32_t ph) {
    if (mbar_try(a, ph)) return;
    uint32_t t0 = clk32();
    while (!mbar_try(a, ph)) {
        if (clk32() - t0 > WAIT_LIMIT) break;
    }
}
__device__ __forceinline__ void mbar_arrive_cluster(uint32_t a, uint32_t cta) {
    asm volatile(
        "{\n.reg .b32 ra;\nmapa.shared::cluster.u32 ra, %0, %1;\nmbarrier.arrive.shared::cluster.b64 _, [ra];\n}" ::"r"(a),
        "r"(cta)
        : "memory");
}
__device__ __forceinline__ void tma_mc(uint32_t dst, const CUtensorMap* m, int c0, int c1, uint32_t bar) {
    asm volatile(
        "cp.async.bulk.tensor.2d.shared::cluster.global.mbarrier::complete_tx::bytes.multicast::cluster"
        " [%0], [%1, {%3, %4}], [%2], %5;" ::"r"(dst),
        "l"(m), "r"(bar), "r"(c0), "r"(c1), "h"((uint16_t)3)
        : "memory");
}
__device__ __forceinline__ void bulk_load(uint32_t dst, const void* src, uint32_t bytes, uint32_t bar) {
    asm volatile("cp.async.bulk.shared::cluster.global.mbarrier::complete_tx::bytes [%0], [%1], %2, [%3];" ::"r"(dst),
                 "l"(src), "r"(bytes), "r"(bar)
                 : "memory");
}
__device__ __forceinline__ void l2_prefetch(const void* p, uint32_t bytes) {
    asm volatile("cp.async.bulk.prefetch.L2.global [%0], %1;" ::"l"(p), "r"(bytes) : "memory");
}
__device__ __forceinline__ void bar_sync(int id, int n) { asm volatile("bar.sync %0, %1;" ::"r"(id), "r"(n) : "memory"); }
__device__ __forceinline__ void bar_arrive(int id, int n) {
    asm volatile("bar.arrive %0, %1;" ::"r"(id), "r"(n) : "memory");
}
__device__ __forceinline__ void wg_fence() { asm volatile("wgmma.fence.sync.aligned;" ::: "memory"); }
__device__ __forceinline__ void wg_commit() { asm volatile("wgmma.commit_group.sync.aligned;" ::: "memory"); }
template <int N>
__device__ __forceinline__ void wg_wait() {
    asm volatile("wgmma.wait_group.sync.aligned %0;" ::"n"(N) : "memory");
}
template <int N>
__device__ __forceinline__ void pin(float (&d)[N]) {
#pragma unroll
    for (int i = 0; i < N; i++) asm volatile("" : "+f"(d[i])::"memory");
}
template <int N>
__device__ __forceinline__ void pin(uint32_t (&d)[N]) {
#pragma unroll
    for (int i = 0; i < N; i++) asm volatile("" : "+r"(d[i])::"memory");
}
__device__ __forceinline__ uint32_t pack_bf16(float lo, float hi) {
    uint32_t r;
    asm("cvt.rn.bf16x2.f32 %0, %1, %2;" : "=r"(r) : "f"(hi), "f"(lo));
    return r;
}
__device__ __forceinline__ float bf_lo(uint32_t v) { return __uint_as_float(v << 16); }
__device__ __forceinline__ float bf_hi(uint32_t v) { return __uint_as_float(v & 0xffff0000u); }
__device__ __forceinline__ float round_bf16(float v) { return __bfloat162float(__float2bfloat16_rn(v)); }
__device__ __forceinline__ float ex2(float x) {
    float y;
    asm("ex2.approx.ftz.f32 %0, %1;" : "=f"(y) : "f"(x));
    return y;
}
__device__ __forceinline__ float rcp(float x) {
    float y;
    asm("rcp.approx.ftz.f32 %0, %1;" : "=f"(y) : "f"(x));
    return y;
}
__device__ __forceinline__ float tanh_fast(float x) {
    float y;
    asm("tanh.approx.f32 %0, %1;" : "=f"(y) : "f"(x));
    return y;
}
__device__ __forceinline__ void sts128(uint32_t a, uint32_t x, uint32_t y, uint32_t z, uint32_t w) {
    asm volatile("st.shared.v4.b32 [%0], {%1,%2,%3,%4};" ::"r"(a), "r"(x), "r"(y), "r"(z), "r"(w) : "memory");
}
__device__ __forceinline__ void sts128_if(bool p, uint32_t a, uint32_t x, uint32_t y, uint32_t z, uint32_t w) {
    asm volatile("{\n.reg .pred p;\nsetp.ne.b32 p, %5, 0;\n@p st.shared.v4.b32 [%0], {%1,%2,%3,%4};\n}" ::"r"(a), "r"(x),
                 "r"(y), "r"(z), "r"(w), "r"((int)p));
}
__device__ __forceinline__ void lds128(uint32_t a, uint32_t& x, uint32_t& y, uint32_t& z, uint32_t& w) {
    asm volatile("ld.shared.v4.b32 {%0,%1,%2,%3}, [%4];" : "=r"(x), "=r"(y), "=r"(z), "=r"(w) : "r"(a) : "memory");
}
__device__ __forceinline__ void sts32f(uint32_t a, float v) {
    asm volatile("st.shared.f32 [%0], %1;" ::"r"(a), "f"(v) : "memory");
}
__device__ __forceinline__ float lds32f(uint32_t a) {
    float v;
    asm volatile("ld.shared.f32 %0, [%1];" : "=f"(v) : "r"(a) : "memory");
    return v;
}
#define F8(d, b) \
    "+f"(d[b]), "+f"(d[b + 1]), "+f"(d[b + 2]), "+f"(d[b + 3]), "+f"(d[b + 4]), "+f"(d[b + 5]), "+f"(d[b + 6]), "+f"(d[b + 7])

template <int TB>
__device__ __forceinline__ void wgmma_n128(float (&d)[64], uint32_t a0, uint32_t a1, uint32_t a2, uint32_t a3,
                                           uint64_t db, int sc) {
    asm volatile(
        "{\n.reg .pred p;\nsetp.ne.b32 p, %69, 0;\n"
        "wgmma.mma_async.sync.aligned.m64n128k16.f32.bf16.bf16 "
        "{%0,%1,%2,%3,%4,%5,%6,%7,%8,%9,%10,%11,%12,%13,%14,%15,%16,%17,%18,%19,%20,%21,%22,%23,%24,%25,%26,%27,%28,%29,%30,%31,"
        "%32,%33,%34,%35,%36,%37,%38,%39,%40,%41,%42,%43,%44,%45,%46,%47,%48,%49,%50,%51,%52,%53,%54,%55,%56,%57,%58,%59,%60,%61,%62,%63},"
        "{%64,%65,%66,%67}, %68, p, 1, 1, %70;\n}"
        : F8(d, 0), F8(d, 8), F8(d, 16), F8(d, 24), F8(d, 32), F8(d, 40), F8(d, 48), F8(d, 56)
        : "r"(a0), "r"(a1), "r"(a2), "r"(a3), "l"(db), "r"(sc), "n"(TB));
}
#define O8(d, b) \
    "=f"(d[b]), "=f"(d[b + 1]), "=f"(d[b + 2]), "=f"(d[b + 3]), "=f"(d[b + 4]), "=f"(d[b + 5]), "=f"(d[b + 6]), "=f"(d[b + 7])
template <int TB>
__device__ __forceinline__ void wgmma_n128_z(float (&d)[64], uint32_t a0, uint32_t a1, uint32_t a2, uint32_t a3,
                                             uint64_t db) {
    asm volatile(
        "wgmma.mma_async.sync.aligned.m64n128k16.f32.bf16.bf16 "
        "{%0,%1,%2,%3,%4,%5,%6,%7,%8,%9,%10,%11,%12,%13,%14,%15,%16,%17,%18,%19,%20,%21,%22,%23,%24,%25,%26,%27,%28,%29,%30,%31,"
        "%32,%33,%34,%35,%36,%37,%38,%39,%40,%41,%42,%43,%44,%45,%46,%47,%48,%49,%50,%51,%52,%53,%54,%55,%56,%57,%58,%59,%60,%61,%62,%63},"
        "{%64,%65,%66,%67}, %68, 0, 1, 1, %69;"
        : O8(d, 0), O8(d, 8), O8(d, 16), O8(d, 24), O8(d, 32), O8(d, 40), O8(d, 48), O8(d, 56)
        : "r"(a0), "r"(a1), "r"(a2), "r"(a3), "l"(db), "n"(TB));
}
template <int TB>
__device__ __forceinline__ void wgmma_n64_z(float (&d)[32], uint32_t a0, uint32_t a1, uint32_t a2, uint32_t a3,
                                            uint64_t db) {
    asm volatile(
        "wgmma.mma_async.sync.aligned.m64n64k16.f32.bf16.bf16 "
        "{%0,%1,%2,%3,%4,%5,%6,%7,%8,%9,%10,%11,%12,%13,%14,%15,%16,%17,%18,%19,%20,%21,%22,%23,%24,%25,%26,%27,%28,%29,%30,%31},"
        "{%32,%33,%34,%35}, %36, 0, 1, 1, %37;"
        : O8(d, 0), O8(d, 8), O8(d, 16), O8(d, 24)
        : "r"(a0), "r"(a1), "r"(a2), "r"(a3), "l"(db), "n"(TB));
}
template <int TB>
__device__ __forceinline__ void wgmma_n64(float (&d)[32], uint32_t a0, uint32_t a1, uint32_t a2, uint32_t a3,
                                          uint64_t db) {
    asm volatile(
        "wgmma.mma_async.sync.aligned.m64n64k16.f32.bf16.bf16 "
        "{%0,%1,%2,%3,%4,%5,%6,%7,%8,%9,%10,%11,%12,%13,%14,%15,%16,%17,%18,%19,%20,%21,%22,%23,%24,%25,%26,%27,%28,%29,%30,%31},"
        "{%32,%33,%34,%35}, %36, 1, 1, 1, %37;"
        : F8(d, 0), F8(d, 8), F8(d, 16), F8(d, 24)
        : "r"(a0), "r"(a1), "r"(a2), "r"(a3), "l"(db), "n"(TB));
}

__device__ __forceinline__ uint64_t desc_of(uint32_t saddr) {
    return (uint64_t)(((saddr >> 4) & 0x3FFFu) | (512u << 16)) | ((uint64_t)(64u | (1u << 30)) << 32);
}

struct Ring {
    uint32_t slot;
    uint32_t phase;
    __device__ __forceinline__ void next() {
        if (++slot == 8) {
            slot = 0;
            phase ^= 1;
        }
    }
};

struct Ctx {
    uint32_t sbase;
    int wg;
    uint32_t rel_cta;
    __device__ __forceinline__ void wait_full(uint32_t slot, uint32_t phase) const {
        mbar_wait(sbase + OFF_FULL + slot * 8, phase);
    }
    __device__ __forceinline__ void release(uint32_t slot) const {
        if (rel_cta < 2) mbar_arrive_cluster(sbase + OFF_EMPTY + slot * 8, rel_cta);
    }
};

__device__ __forceinline__ void gemm_n128(float (&d)[64], const uint32_t (&a)[144], const Ctx& c, Ring& r, bool nine,
                                          bool early) {
    uint32_t prev = 0;
#pragma unroll
    for (int s = 0; s < 9; s++) {
        if (s < 8 || nine) {
            if (s == GATE_SLOT) {
                if (early) {
                    wg_wait<0>();
                    c.release(prev);
                }
                bar_sync(8 + c.wg, 256);
            }
            c.wait_full(r.slot, r.phase);
            uint64_t db = desc_of(c.sbase + r.slot * SLOT_BYTES);
            wg_fence();
#pragma unroll
            for (int k = 0; k < 4; k++) {
                if ((s | k) == 0)
                    wgmma_n128_z<1>(d, a[0], a[1], a[2], a[3], db);
                else
                    wgmma_n128<1>(d, a[s * 16 + k * 4], a[s * 16 + k * 4 + 1], a[s * 16 + k * 4 + 2],
                                  a[s * 16 + k * 4 + 3], db + k * 128, 1);
            }
            wg_commit();
            if (s == 8 || (s == 7 && !nine)) bar_arrive(9 - c.wg, 256);
            if (s > 0) {
                wg_wait<1>();
                if (s != GATE_SLOT || !early) c.release(prev);
            }
            prev = r.slot;
            r.next();
        }
    }
    wg_wait<0>();
    c.release(prev);
    pin(d);
}
__device__ __forceinline__ void gemm_n64(float (&d)[32], const uint32_t (&a)[144], const Ctx& c, Ring& r, bool nine) {
    uint32_t prev = 0;
#pragma unroll
    for (int s = 0; s < 5; s++) {
        if (s < 4 || nine) {
            c.wait_full(r.slot, r.phase);
            uint64_t db = desc_of(c.sbase + r.slot * SLOT_BYTES);
            wg_fence();
#pragma unroll
            for (int k = 0; k < 8; k++) {
                if ((s | k) == 0)
                    wgmma_n64_z<1>(d, a[0], a[1], a[2], a[3], db);
                else if (s * 8 + k < 36)
                    wgmma_n64<1>(d, a[s * 32 + k * 4], a[s * 32 + k * 4 + 1], a[s * 32 + k * 4 + 2],
                                 a[s * 32 + k * 4 + 3], db + k * 128);
            }
            wg_commit();
            if (s > 0) {
                wg_wait<1>();
                c.release(prev);
            }
            prev = r.slot;
            r.next();
        }
    }
    wg_wait<0>();
    c.release(prev);
    pin(d);
}
__device__ __forceinline__ void st128(uint4* p, uint32_t x, uint32_t y, uint32_t z, uint32_t w) {
    asm volatile(
        "{\n.reg .b64 lo, hi;\n.reg .b128 t;\nmov.b64 lo, {%1, %2};\nmov.b64 hi, {%3, %4};\nmov.b128 t, {lo, hi};\n"
        "st.relaxed.gpu.global.b128 [%0], t;\n}" ::"l"(p),
        "r"(x), "r"(y), "r"(z), "r"(w)
        : "memory");
}
__device__ __forceinline__ uint4 ld128(const uint4* p) {
    uint4 r;
    asm volatile(
        "{\n.reg .b64 lo, hi;\n.reg .b128 t;\nld.relaxed.gpu.global.b128 t, [%4];\nmov.b128 {lo, hi}, t;\n"
        "mov.b64 {%0, %1}, lo;\nmov.b64 {%2, %3}, hi;\n}"
        : "=r"(r.x), "=r"(r.y), "=r"(r.z), "=r"(r.w)
        : "l"(p));
    return r;
}
__device__ __forceinline__ uint4 ldg128(const uint4* p) {
    uint4 r;
    asm volatile("ld.global.nc.v4.u32 {%0,%1,%2,%3}, [%4];" : "=r"(r.x), "=r"(r.y), "=r"(r.z), "=r"(r.w) : "l"(p));
    return r;
}
__device__ __forceinline__ void st64(void* p, uint32_t x, uint32_t y) {
    asm volatile("{\n.reg .b64 t;\nmov.b64 t, {%1, %2};\nst.relaxed.gpu.global.b64 [%0], t;\n}" ::"l"(p), "r"(x), "r"(y)
                 : "memory");
}
__device__ __forceinline__ uint2 ld64(const void* p) {
    uint2 r;
    asm volatile("{\n.reg .b64 t;\nld.relaxed.gpu.global.b64 t, [%2];\nmov.b64 {%0, %1}, t;\n}"
                 : "=r"(r.x), "=r"(r.y)
                 : "l"(p));
    return r;
}
__device__ __forceinline__ void rows_load(uint32_t sbase, const CUtensorMap* m, int row0) {
    mbar_expect_tx(sbase + OFF_XBAR, 16 * DM * 2);
    asm volatile(
        "cp.async.bulk.tensor.3d.shared::cluster.global.mbarrier::complete_tx::bytes [%0], [%1, {%3, %3, %4}], [%2];" ::"r"(
            sbase + OFF_ROWS),
        "l"(m), "r"(sbase + OFF_XBAR), "r"(0), "r"(row0)
        : "memory");
}
__device__ __forceinline__ void rows_store(uint32_t sbase, const CUtensorMap* m, int row0) {
    asm volatile("cp.async.bulk.tensor.3d.global.shared::cta.bulk_group [%0, {%2, %2, %3}], [%1];" ::"l"(m),
                 "r"(sbase + OFF_ROWS), "r"(0), "r"(row0)
                 : "memory");
    asm volatile("cp.async.bulk.commit_group;" ::: "memory");
}
__device__ __forceinline__ void rows_store_wait() { asm volatile("cp.async.bulk.wait_group 0;" ::: "memory"); }

__device__ __forceinline__ constexpr int own_col(int j) { return j < 8 ? (j >> 1) * 128 + (j & 1) * 8 : 512; }
__device__ __forceinline__ void row_reduce(float& s0, float& s1, uint32_t red, int warp, int lane) {
    s0 += __shfl_xor_sync(0xffffffffu, s0, 1);
    s1 += __shfl_xor_sync(0xffffffffu, s1, 1);
    s0 += __shfl_xor_sync(0xffffffffu, s0, 2);
    s1 += __shfl_xor_sync(0xffffffffu, s1, 2);
    if ((lane & 3) == 0) {
        sts32f(red + (warp * 16 + (lane >> 2)) * 4, s0);
        sts32f(red + (warp * 16 + 8 + (lane >> 2)) * 4, s1);
    }
    bar_sync(3, 256);
    s0 = 0.f;
    s1 = 0.f;
#pragma unroll
    for (int w = 0; w < 8; w++) {
        s0 += lds32f(red + (w * 16 + (lane >> 2)) * 4);
        s1 += lds32f(red + (w * 16 + 8 + (lane >> 2)) * 4);
    }
}
template <class F>
__device__ __forceinline__ void layernorm_rows(float (&v)[36], uint32_t red, int warp, int lane, F&& middle) {
    float s0 = 0.f, s1 = 0.f;
#pragma unroll
    for (int j = 0; j < 9; j++) {
        s0 += v[4 * j] + v[4 * j + 1];
        s1 += v[4 * j + 2] + v[4 * j + 3];
    }
    row_reduce(s0, s1, red, warp, lane);
    middle();
    const float m0 = s0 * (1.f / DM), m1 = s1 * (1.f / DM);
    s0 = 0.f;
    s1 = 0.f;
#pragma unroll
    for (int j = 0; j < 9; j++) {
        v[4 * j] -= m0;
        v[4 * j + 1] -= m0;
        v[4 * j + 2] -= m1;
        v[4 * j + 3] -= m1;
        s0 += v[4 * j] * v[4 * j] + v[4 * j + 1] * v[4 * j + 1];
        s1 += v[4 * j + 2] * v[4 * j + 2] + v[4 * j + 3] * v[4 * j + 3];
    }
    row_reduce(s0, s1, red + 512, warp, lane);
    const float r0 = rsqrtf(s0 * (1.f / DM) + 1e-5f), r1 = rsqrtf(s1 * (1.f / DM) + 1e-5f);
#pragma unroll
    for (int j = 0; j < 9; j++) {
        v[4 * j] *= r0;
        v[4 * j + 1] *= r0;
        v[4 * j + 2] *= r1;
        v[4 * j + 3] *= r1;
    }
}
__device__ __forceinline__ void mod_to_smem(uint32_t dst, const uint32_t* src, uint32_t tag) {
    const uint32_t t0 = clk32();
    uint4 u;
    while (true) {
        u = ld128(reinterpret_cast<const uint4*>(src));
        const uint32_t bad = ((u.x ^ tag) | (u.y ^ tag) | (u.z ^ tag) | (u.w ^ tag)) & 0xffffu;
        if (__all_sync(0xffffffffu, bad == 0) || clk32() - t0 > WAIT_LIMIT) break;
        __nanosleep(64);
    }
    sts128(dst, u.x & 0xffff0000u, u.y & 0xffff0000u, u.z & 0xffff0000u, u.w & 0xffff0000u);
}
__device__ __forceinline__ void lds_mod(float (&m)[18], uint32_t src  , int warp) {
#pragma unroll
    for (int j = 0; j < 9; j++)
        asm volatile("ld.shared.v2.f32 {%0,%1}, [%2];"
                     : "=f"(m[2 * j]), "=f"(m[2 * j + 1])
                     : "r"(src + own_col(j) * 4 - (j == 8 ? warp * 32 : 0))
                     : "memory");
}
__device__ __forceinline__ void modulate_store(const float (&v)[36], const float (&shift)[18], const float (&scale)[18],
                                               float post, uint4* hbuf  , int warp, int lane) {
    uint32_t o[18];
#pragma unroll
    for (int j = 0; j < 9; j++) {
        const uint32_t cc = pack_bf16(1.f + scale[2 * j], 1.f + scale[2 * j + 1]);
        const float c0 = bf_lo(cc) * post, c1 = bf_hi(cc) * post, s0 = shift[2 * j] * post, s1 = shift[2 * j + 1] * post;
        o[2 * j] = pack_bf16(fmaf(v[4 * j], c0, s0), fmaf(v[4 * j + 1], c1, s1));
        o[2 * j + 1] = pack_bf16(fmaf(v[4 * j + 2], c0, s0), fmaf(v[4 * j + 3], c1, s1));
        if ((j & 1) == 0) o[2 * j] = max(o[2 * j], 1u);
    }
#pragma unroll
    for (int i = 0; i < 4; i++) st128(hbuf + (i * 8 + warp) * 32 + lane, o[4 * i], o[4 * i + 1], o[4 * i + 2], o[4 * i + 3]);
    st64(reinterpret_cast<uint2*>(hbuf + 32 * 32) + warp * 32 + lane, o[16], o[17]);
}
__device__ __forceinline__ void sum_partials(float (&v)[36], const uint4* src  , uint32_t tag) {
    const uint32_t t0 = clk32();
    while (true) {
        uint4 t[8][4];
#pragma unroll
        for (int s = 0; s < 8; s++)
#pragma unroll
            for (int i = 0; i < 4; i++) t[s][i] = ld128(src + (s * 36 + i * 8) * 32);
        uint32_t bad = 0;
#pragma unroll
        for (int i = 0; i < 32; i++) v[i] = 0.f;
#pragma unroll
        for (int s = 0; s < 8; s++)
#pragma unroll
            for (int i = 0; i < 4; i++) {
                bad |= t[s][i].x ^ tag;
                v[8 * i] += bf_lo(t[s][i].x);
                v[8 * i + 1] += bf_hi(t[s][i].x);
                v[8 * i + 2] += bf_lo(t[s][i].y);
                v[8 * i + 3] += bf_hi(t[s][i].y);
                v[8 * i + 4] += bf_lo(t[s][i].z);
                v[8 * i + 5] += bf_hi(t[s][i].z);
                v[8 * i + 6] += bf_lo(t[s][i].w);
                v[8 * i + 7] += bf_hi(t[s][i].w);
                asm volatile("" : "+r"(bad));
            }
#pragma unroll
        for (int i = 0; i < 32; i++) asm volatile("" : "+f"(v[i]));
        if (__all_sync(0xffffffffu, (bad & 1u) == 0) || clk32() - t0 > WAIT_LIMIT) break;
    }
}
__device__ __forceinline__ void sum_tail(float (&v)[36], const uint2* src  , uint32_t tag) {
    const uint32_t t0 = clk32();
    while (true) {
        uint2 t[8];
#pragma unroll
        for (int s = 0; s < 8; s++) t[s] = ld64(src + s * 72 * 32);
        uint32_t bad = 0;
        v[32] = v[33] = v[34] = v[35] = 0.f;
#pragma unroll
        for (int s = 0; s < 8; s++) {
            bad |= t[s].x ^ tag;
            v[32] += bf_lo(t[s].x);
            v[33] += bf_hi(t[s].x);
            v[34] += bf_lo(t[s].y);
            v[35] += bf_hi(t[s].y);
        }
        if (__all_sync(0xffffffffu, (bad & 1u) == 0) || clk32() - t0 > WAIT_LIMIT) break;
    }
}
__device__ __forceinline__ void poll_tail(uint32_t (&a)[144], const uint2* src  ) {
    const uint32_t t0 = clk32();
    while (true) {
        uint32_t m = 0xffffffffu;
#pragma unroll
        for (int j = 0; j < 8; j++) {
            const uint2 t = ld64(src + j * 32);
            a[128 + 2 * j] = t.x;
            a[129 + 2 * j] = t.y;
        }
#pragma unroll
        for (int j = 0; j < 8; j++) m = min(m, a[128 + 2 * j]);
        if (__all_sync(0xffffffffu, m != 0) || clk32() - t0 > WAIT_LIMIT) break;
    }
}
template <int K0, int K1>
__device__ __forceinline__ void poll_frags(uint32_t (&a)[144], const uint4* src  , bool kick) {
    const uint32_t t0 = clk32();
    while (true) {
#pragma unroll
        for (int k = K0; k < K1; k++) {
            const uint4 t = ld128(src + k * 32);
            a[4 * k] = t.x;
            a[4 * k + 1] = t.y;
            a[4 * k + 2] = t.z;
            a[4 * k + 3] = t.w;
        }
        if (kick) bar_arrive(5, 256);
        kick = false;
        uint32_t m0 = a[4 * K0], m1 = a[4 * K0 + 4];
#pragma unroll
        for (int k = K0 + 2; k < K1; k += 2) {
            m0 = min(m0, a[4 * k]);
            m1 = min(m1, a[4 * k + 4]);
        }
        if (__all_sync(0xffffffffu, min(m0, m1) != 0) || clk32() - t0 > WAIT_LIMIT) break;
    }
}

constexpr float SM_SCALE = 0.08838834764831845f * 1.4426950408889634f;
constexpr float SM_HI = 1.2089258e24f;
constexpr float SM_LO = 9.0949470e-13f;
__device__ __forceinline__ void qk_step(float (&s)[32], const uint32_t (&q)[32], uint64_t dk) {
#pragma unroll
    for (int k = 0; k < 8; k++) {
        if (k == 0)
            wgmma_n64_z<0>(s, q[0], q[1], q[2], q[3], dk);
        else
            wgmma_n64<0>(s, q[4 * k], q[4 * k + 1], q[4 * k + 2], q[4 * k + 3], dk + (k >> 2) * 512 + (k & 3) * 2);
    }
}
__device__ __forceinline__ void pv_step(float (&o)[64], const uint32_t (&p)[16], uint64_t dv, int acc) {
#pragma unroll
    for (int k = 0; k < 4; k++)
        wgmma_n128<1>(o, p[4 * k], p[4 * k + 1], p[4 * k + 2], p[4 * k + 3], dv + k * 128, k != 0 ? 1 : acc);
}
template <bool SHIFT>
__device__ __forceinline__ void exp_step(const float (&s)[32], uint32_t (&p)[16], float n0, float n1, float& s0,
                                         float& s1) {
#pragma unroll
    for (int i = 0; i < 8; i++) {
        const float e0 = ex2(SHIFT ? s[4 * i] + n0 : s[4 * i]), e1 = ex2(SHIFT ? s[4 * i + 1] + n0 : s[4 * i + 1]);
        const float e2 = ex2(SHIFT ? s[4 * i + 2] + n1 : s[4 * i + 2]), e3 = ex2(SHIFT ? s[4 * i + 3] + n1 : s[4 * i + 3]);
        if (i == 0) {
            s0 = e0 + e1;
            s1 = e2 + e3;
        } else {
            s0 += e0 + e1;
            s1 += e2 + e3;
        }
        p[2 * i] = pack_bf16(e0, e1);
        p[2 * i + 1] = pack_bf16(e2, e3);
    }
}
__device__ __forceinline__ void row_max(const float (&sa)[32], const float (&sb)[32], float& x0, float& x1) {
    float xa[8];
#pragma unroll
    for (int i = 0; i < 8; i++) xa[i] = fmaxf(sa[i], sb[i]);
#pragma unroll
    for (int k = 1; k < 4; k++)
#pragma unroll
        for (int i = 0; i < 8; i++) xa[i] = fmaxf(xa[i], fmaxf(sa[8 * k + i], sb[8 * k + i]));
    x0 = fmaxf(fmaxf(xa[0], xa[1]), fmaxf(xa[4], xa[5]));
    x1 = fmaxf(fmaxf(xa[2], xa[3]), fmaxf(xa[6], xa[7]));
    x0 = fmaxf(x0, __shfl_xor_sync(0xffffffffu, x0, 1));
    x1 = fmaxf(x1, __shfl_xor_sync(0xffffffffu, x1, 1));
    x0 = fmaxf(x0, __shfl_xor_sync(0xffffffffu, x0, 2));
    x1 = fmaxf(x1, __shfl_xor_sync(0xffffffffu, x1, 2));
}
__device__ __forceinline__ void inv_row_sums(float l0, float l1, float& i0, float& i1) {
    l0 += __shfl_xor_sync(0xffffffffu, l0, 1);
    l1 += __shfl_xor_sync(0xffffffffu, l1, 1);
    l0 += __shfl_xor_sync(0xffffffffu, l0, 2);
    l1 += __shfl_xor_sync(0xffffffffu, l1, 2);
    i0 = rcp(l0);
    i1 = rcp(l1);
}

__device__ __forceinline__ uint32_t get_epoch(uint32_t sbase) { return __float_as_uint(lds32f(sbase + OFF_EPOCH)); }
__device__ __forceinline__ float silu_bf16(unsigned short c) {
    const float cv = bf_lo(c);
    return round_bf16(cv * rcp(1.f + ex2(-1.4426950408889634f * cv)));
}
__device__ __forceinline__ void st_mod(uint32_t* p, float v, uint32_t tag) {
    asm volatile("st.relaxed.gpu.global.u32 [%0], %1;" ::"l"(p), "r"(__float_as_uint(round_bf16(v)) | tag)
                 : "memory");
}
__device__ __forceinline__ void fma8(float (&acc)[8], float sc, const uint4& w) {
    acc[0] = fmaf(sc, bf_lo(w.x), acc[0]);
    acc[1] = fmaf(sc, bf_hi(w.x), acc[1]);
    acc[2] = fmaf(sc, bf_lo(w.y), acc[2]);
    acc[3] = fmaf(sc, bf_hi(w.y), acc[3]);
    acc[4] = fmaf(sc, bf_lo(w.z), acc[4]);
    acc[5] = fmaf(sc, bf_hi(w.z), acc[5]);
    acc[6] = fmaf(sc, bf_lo(w.w), acc[6]);
    acc[7] = fmaf(sc, bf_hi(w.w), acc[7]);
}
__device__ __forceinline__ void modp_load(uint4 (&u)[3], const uint32_t* src) {
#pragma unroll
    for (int i = 0; i < 3; i++) u[i] = ld128(reinterpret_cast<const uint4*>(src + i * 2 * DM));
}
__device__ __forceinline__ void modp_to_smem(uint4 (&u)[3], uint32_t dst, const uint32_t* src, uint32_t tag) {
    const uint32_t t0 = clk32();
    while (true) {
        uint32_t bad = 0;
#pragma unroll
        for (int i = 0; i < 3; i++) bad |= (u[i].x ^ tag) | (u[i].y ^ tag) | (u[i].z ^ tag) | (u[i].w ^ tag);
        if (__all_sync(0xffffffffu, (bad & 0xffu) == 0) || clk32() - t0 > WAIT_LIMIT) break;
        modp_load(u, src);
    }
    float s0 = 0.f, s1 = 0.f, s2 = 0.f, s3 = 0.f;
#pragma unroll
    for (int i = 0; i < 3; i++) {
        s0 += __uint_as_float(u[i].x & ~0xffu);
        s1 += __uint_as_float(u[i].y & ~0xffu);
        s2 += __uint_as_float(u[i].z & ~0xffu);
        s3 += __uint_as_float(u[i].w & ~0xffu);
    }
    const uint32_t p0 = pack_bf16(s0, s1), p1 = pack_bf16(s2, s3);
    sts128(dst, p0 << 16, p0 & 0xffff0000u, p1 << 16, p1 & 0xffff0000u);
}

__global__ void __cluster_dims__(2, 1, 1) __launch_bounds__(384, 1)
    fused_block_kernel(const __grid_constant__ Params maps) {
    extern __shared__ uint8_t smem_raw[];
    uint32_t sbase = (smem_u32(smem_raw) + 1023u) & ~1023u;
    asm volatile("" : "+r"(sbase));
    const int b = blockIdx.x;
    const int rank = b & 1;
    const int mt = ((b >> 1) & 7) * 2 + rank;
    const int g = b >> 4;
    const int warp = __shfl_sync(0xffffffffu, threadIdx.x >> 5, 0);
    const int lane = threadIdx.x & 31;
    Scratch* const sc_ = maps.sc;
    const __nv_bfloat16* const wmod = maps.wmod;
    const __nv_bfloat16* const cvec = maps.cvec;

#define SPROF(i)

    if (warp >= 8) {
        asm volatile("setmaxnreg.dec.sync.aligned.u32 24;");
        if (warp == 8 && lane == 0) {
#pragma unroll
            for (int i = 0; i < 8; i++) {
                mbar_init(sbase + OFF_FULL + i * 8, 1);
                mbar_init(sbase + OFF_EMPTY + i * 8, 4);
            }
            mbar_init(sbase + OFF_XBAR, 1);
            mbar_init(sbase + OFF_GBAR, 8);
            asm volatile("fence.mbarrier_init.release.cluster;" ::: "memory");
            asm volatile("barrier.cluster.arrive.relaxed;\nbarrier.cluster.wait;" ::: "memory");
            uint32_t slot = 0, phase = 1;
            const uint32_t dst0 = sbase + rank * BOX_BYTES;
            auto acquire = [&](uint32_t bytes) {
                mbar_wait(sbase + OFF_EMPTY + slot * 8, phase);
                mbar_expect_tx(sbase + OFF_FULL + slot * 8, bytes);
            };
            auto adv8 = [&]() {
                if (++slot == 8) {
                    slot = 0;
                    phase ^= 1;
                }
            };
#pragma unroll 1
            for (int hq = 0; hq < 4; hq++) {
                const int col = (g * 4 + ((hq + 1) & 3)) * 128 + rank * 64;
                if (hq == 2) {
                    l2_prefetch(maps.kc + (size_t)(g * 4 * 2048 + (b & 15) * 64) * 128, SLOT_BYTES);
                    l2_prefetch(maps.vc + (size_t)(g * 4 * 2048 + (b & 15) * 64) * 128, SLOT_BYTES);
                }
#pragma unroll 1
                for (int kc = 0; kc < 9; kc++) {
                    acquire(SLOT_BYTES);
                    tma_mc(dst0 + slot * SLOT_BYTES, &maps.wq, col, kc * 64, sbase + OFF_FULL + slot * 8);
                    adv8();
                }
            }
            const int row0 = g * 4 * 2048;
#pragma unroll 1
            for (int n = 0; n < 128; n++) {
                if (n < 4) mbar_wait(sbase + OFF_EMPTY + (slot + 1) * 8, phase);
                acquire(2 * SLOT_BYTES);
                const uint32_t bar = sbase + OFF_FULL + slot * 8;
                const int r0 = n == 0 ? 0 : (n == 127 ? 126 : n + 1);
                const int r1 = n == 0 ? 1 : (n == 127 ? 127 : n - 1);
                tma_mc(dst0 + slot * SLOT_BYTES, n == 127 ? &maps.v : &maps.k, rank * 64, row0 + r0 * 64, bar);
                tma_mc(dst0 + (slot + 1) * SLOT_BYTES, n == 0 ? &maps.k : &maps.v, rank * 64, row0 + r1 * 64, bar);
                adv8();
                adv8();
                const int u = n + KV_AHEAD;
                if (u < 128 && (u & 15) == (b & 15)) {
                    l2_prefetch(maps.kc + (size_t)(row0 + u * 64) * 128, SLOT_BYTES);
                    l2_prefetch(maps.vc + (size_t)(row0 + u * 64) * 128, SLOT_BYTES);
                }
            }
#pragma unroll 1
            for (int p = 0; p < 4; p++)
#pragma unroll 1
                for (int kc = 0; kc < 8; kc++) {
                    acquire(SLOT_BYTES);
                    tma_mc(dst0 + slot * SLOT_BYTES, &maps.wo, p * 128 + rank * 64, g * 512 + ((kc + 6) & 7) * 64,
                           sbase + OFF_FULL + slot * 8);
                    adv8();
                }
#pragma unroll 1
            for (int kc = 0; kc < 4; kc++) {
                acquire(SLOT_BYTES);
                tma_mc(dst0 + slot * SLOT_BYTES, &maps.wo, 512, g * 512 + ((kc + 3) & 3) * 128 + rank * 64,
                       sbase + OFF_FULL + slot * 8);
                adv8();
            }
            mbar_wait(sbase + OFF_GBAR, 0);
            const CUtensorMap* mg = rank ? &maps.wu : &maps.wg;
#pragma unroll 1
            for (int ch = 0; ch < 9; ch++)
#pragma unroll 1
                for (int kc = 0; kc < 9; kc++) {
                    acquire(SLOT_BYTES);
                    tma_mc(dst0 + slot * SLOT_BYTES, mg, g * 576 + ch * 64, kc * 64, sbase + OFF_FULL + slot * 8);
                    adv8();
                }
#pragma unroll 1
            for (int p = 0; p < 4; p++)
#pragma unroll 1
                for (int i = 0; i < 9; i++) {
                    acquire(SLOT_BYTES);
                    tma_mc(dst0 + slot * SLOT_BYTES, &maps.wd, p * 128 + rank * 64,
                           g * 576 + (i == 0 ? 8 : (i < 7 ? i + 1 : i - 7)) * 64, sbase + OFF_FULL + slot * 8);
                    adv8();
                }
#pragma unroll 1
            for (int i2 = 0; i2 < 5; i2++) {
                acquire(i2 < 4 ? SLOT_BYTES : BOX_BYTES);
                const int i = 2 * i2 + rank;
                if (i < 9)
                    tma_mc(dst0 + slot * SLOT_BYTES, &maps.wd, 512, g * 576 + (i == 0 ? 8 : (i < 7 ? i + 1 : i - 7)) * 64,
                           sbase + OFF_FULL + slot * 8);
                adv8();
            }
        } else if (warp == 11) {
            asm volatile("barrier.cluster.arrive.relaxed.aligned;" ::: "memory");
            bar_sync(6, 160);
            uint4* hz = sc_->h[(get_epoch(sbase) & 1) ^ 1][0] + (size_t)b * 72 * 32 + lane;
#pragma unroll 1
            for (int i = 0; i < 72; i++) {
                hz[i * 32] = make_uint4(0, 0, 0, 0);
                __nanosleep(200);
            }
            bar_sync(6, 160);
            if (lane == 0) {
#pragma unroll 1
                for (int i = 0; i < 9; i++) {
                    l2_prefetch((const char*)maps.wo_p + (size_t)b * 36864 + i * 4096, 4096);
                    __nanosleep(400);
                    l2_prefetch((const char*)maps.wg_p + (size_t)b * 41472 + i * 4608, 4608);
                    __nanosleep(400);
                    l2_prefetch((const char*)maps.wu_p + (size_t)b * 41472 + i * 4608, 4608);
                    __nanosleep(400);
                    l2_prefetch((const char*)maps.wd_p + (size_t)b * 41472 + i * 4608, 4608);
                    __nanosleep(400);
                }
            }
        } else if (warp == 9 || warp == 10) {
            asm volatile("barrier.cluster.arrive.relaxed.aligned;" ::: "memory");
            if (warp == 10) {
                bar_sync(11, 288);
                if (lane < 9) l2_prefetch((const char*)maps.wq_p + (size_t)b * 36864 + lane * 4096, 4096);
                __syncwarp();
            }
            bar_sync(4, 320);
            const uint32_t tag = (get_epoch(sbase) + 1) & 0xffffu;
            const int blk = warp == 9 ? 72 + b : 200 + b;
            if (blk < 216) {
                float acc[8];
#pragma unroll
                for (int e = 0; e < 8; e++) acc[e] = 0.f;
                const uint4* wp = reinterpret_cast<const uint4*>(wmod + (size_t)(lane >> 1) * (6 * DM) + blk * 16) + (lane & 1);
                const unsigned short* cp = reinterpret_cast<const unsigned short*>(cvec) + (lane >> 1);
#pragma unroll 1
                for (int i = 0; i < 36; i++) {
                    const uint4 w = __ldg(wp + (size_t)i * (16 * 6 * DM / 8));
                    const float sc = silu_bf16(__ldg(cp + i * 16));
                    fma8(acc, sc, w);
                }
#pragma unroll
                for (int o = 2; o < 32; o <<= 1)
#pragma unroll
                    for (int e = 0; e < 8; e++) acc[e] += __shfl_xor_sync(0xffffffffu, acc[e], o);
                if (lane < 2) {
#pragma unroll
                    for (int e = 0; e < 8; e++) st_mod(sc_->mod + blk * 16 + lane * 8 + e, acc[e], tag);
                }
            }
            if (warp == 9) {
#pragma unroll 1
                for (int st = 1; st <= 2; st++) {
                    bar_sync(7, 160);
                    const uint32_t* src = sc_->mod + (st * 3 - 1) * DM;
                    const int n = st == 1 ? 3 * DM : DM;
#pragma unroll 1
                    for (int i = lane * 4; i < n + 127 - ((n + 127) & 127); i += 128)
                        mod_to_smem(sbase + OFF_MODT + min(i, n - 4) * 4, src + min(i, n - 4), tag);
                    __syncwarp();
                    if (lane == 0) rows_load(sbase, st == 1 ? &maps.rx : &maps.rx2, (mt * 8 + g) * 16);
                    if (st == 1) {
                        bar_sync(7, 160);
                        if (lane == 0) {
                            rows_store(sbase, &maps.rx2, (mt * 8 + g) * 16);
                            rows_store_wait();
                        }
                        __syncwarp();
                        bar_arrive(10, 160);
                    }
                }
            }
        }
    } else {
        uint4 w1[3], xw[5], ew = make_uint4(0, 0, 0, 0);
        unsigned short cu[3];
        {
            const int t = threadIdx.x, bw = min(b, 107);
            const int row = (bw / 36) * 192 + (t >> 2);
#pragma unroll
            for (int i = 0; i < 3; i++) {
                w1[i] = ldg128(reinterpret_cast<const uint4*>(wmod + (size_t)(row + 64 * i) * (6 * DM)) + (bw % 36) * 4 + (t & 3));
                asm volatile("ld.global.nc.u16 %0, [%1];" : "=h"(cu[i]) : "l"(cvec + row + 64 * i));
            }
            if (t == 0) ew = ld128(reinterpret_cast<const uint4*>(&sc_->epoch[b * 32]));
        }
        if (threadIdx.x == 160) SPROF(5);
        asm volatile("setmaxnreg.inc.sync.aligned.u32 240;");
        if (threadIdx.x == 160) SPROF(6);
        const int wg = warp >> 2;
        const int tid = threadIdx.x;
        Ctx cx;
        cx.sbase = sbase;
        cx.wg = wg;
        if (wg == 1) bar_arrive(8, 256);
        cx.rel_cta = (lane == 0 && (warp & 3) < 2) ? (warp & 3) : 2;
        const uint32_t red = sbase + OFF_RED;
        const int own = mt * 8 + g;
        const int wown = mt * 8 + warp;
        PROF(0);
        PROFG(30);
        PROFR(17);
        {
            float acc[8];
#pragma unroll
            for (int e = 0; e < 8; e++) acc[e] = 0.f;
#pragma unroll
            for (int i = 0; i < 3; i++) fma8(acc, silu_bf16(cu[i]), w1[i]);
            {
                int off = tid;
                asm volatile("{\n.reg .pred p;\nsetp.gt.f32 p, %1, 0f00000000;\n@p add.s32 %0, %0, %2;\n}"
                             : "+r"(off)
                             : "f"(acc[7]), "r"((int)gridDim.y - 1));
#pragma unroll
                for (int i = 0; i < 5; i++)
                    xw[i] = ldg128(reinterpret_cast<const uint4*>(maps.x + (size_t)own * 16 * DM) + min(off + 256 * i, 1151));
                asm volatile("barrier.cluster.arrive.relaxed.aligned;" ::: "memory");
            }
#pragma unroll
            for (int o = 4; o < 32; o <<= 1)
#pragma unroll
                for (int e = 0; e < 8; e++) acc[e] += __shfl_xor_sync(0xffffffffu, acc[e], o);
            PROFR(19);
            if (lane < 4) {
                const uint32_t dst = sbase + OFF_MRED + warp * 128 + lane * 32;
                sts128(dst, __float_as_uint(acc[0]), __float_as_uint(acc[1]), __float_as_uint(acc[2]), __float_as_uint(acc[3]));
                sts128(dst + 16, __float_as_uint(acc[4]), __float_as_uint(acc[5]), __float_as_uint(acc[6]), __float_as_uint(acc[7]));
            }
            if (tid == 0) sts128(sbase + OFF_EPOCH, ew.x, ew.y, ew.z, ew.w);
            bar_sync(3, 256);
            PROFR(20);
            if (tid < 32 && b < 108) {
                float sum = 0.f;
#pragma unroll
                for (int w8 = 0; w8 < 8; w8++) sum += lds32f(sbase + OFF_MRED + w8 * 128 + tid * 4);
                asm volatile("st.relaxed.gpu.global.u32 [%0], %1;" ::"l"(&sc_->modp[b / 36][(b % 36) * 32 + tid]),
                             "r"((__float_as_uint(sum) & ~0xffu) | ((get_epoch(sbase) + 1) & 0xffu))
                             : "memory");
            }
            PROFR(21);
#pragma unroll
            for (int i = 0; i < 5; i++) {
                const int vi = min(tid + 256 * i, 1151), ln = vi >> 3;
                sts128(sbase + OFF_ROWS + ln * 128 + (((vi & 7) ^ (ln & 7)) << 4), xw[i].x, xw[i].y, xw[i].z, xw[i].w);
            }
            bar_sync(3, 256);
            bar_arrive(11, 288);
        }

        Ring ring{0u, 0u};
        int stage = 0;
        asm volatile("" : "+r"(stage));
#pragma unroll 1
        for (;; stage++) {
            int tid, lane;
            asm volatile("mov.u32 %0, %%tid.x;" : "=r"(tid));
            lane = tid & 31;
            const uint32_t epoch = get_epoch(sbase);
            {
                float v[36];
                const uint32_t modt = sbase + OFF_MODT + (warp * 16 + (lane & 3) * 2) * 4;
                if (stage == 0) {
#pragma unroll
                    for (int i = 0; i < 36; i++) v[i] = 0.f;
                } else {
                    const uint4* psrc = sc_->part + (size_t)own * 8 * 36 * 32;
                    sum_partials(v, psrc + tid, stage & 1);
                    PROF(stage == 1 ? 8 : 15);
                    if (lane == 0) asm volatile("mbarrier.arrive.shared::cta.b64 _, [%0];" ::"r"(sbase + OFF_GBAR) : "memory");
                    sum_tail(v, reinterpret_cast<const uint2*>(psrc + 32 * 32) + tid, stage & 1);
                }
                if (stage) mbar_wait(sbase + OFF_XBAR, stage - 1);
                if (stage == 0) PROFR(22);
                {
                    const float gs = stage == 2 ? 0.5f : 1.f;
                    float gate[18];
                    lds_mod(gate, modt, warp);
                    const int r = lane >> 2;
                    const uint32_t rows = sbase + OFF_ROWS + r * (DM * 2) + (lane & 3) * 4;
#pragma unroll
                    for (int j = 0; j < 9; j++) {
                        const int ch = j < 8 ? (j >> 1) * 2 + (warp >> 2) : 8, c16 = j < 8 ? (warp & 3) * 2 + (j & 1) : warp;
                        const uint32_t ad = rows + ch * 128 + ((c16 ^ ((r + ch) & 7)) << 4);
                        const uint32_t u0 = __float_as_uint(lds32f(ad)), u1 = __float_as_uint(lds32f(ad + 8 * DM * 2));
                        const float g0 = stage ? gate[2 * j] * gs : 0.f, g1 = stage ? gate[2 * j + 1] * gs : 0.f;
                        v[4 * j] = fmaf(g0, v[4 * j], bf_lo(u0));
                        v[4 * j + 1] = fmaf(g1, v[4 * j + 1], bf_hi(u0));
                        v[4 * j + 2] = fmaf(g0, v[4 * j + 2], bf_lo(u1));
                        v[4 * j + 3] = fmaf(g1, v[4 * j + 3], bf_hi(u1));
                        sts32f(ad, __uint_as_float(pack_bf16(v[4 * j], v[4 * j + 1])));
                        sts32f(ad + 8 * DM * 2, __uint_as_float(pack_bf16(v[4 * j + 2], v[4 * j + 3])));
                    }
                    asm volatile("fence.proxy.async.shared::cta;" ::: "memory");
                }
                if (stage == 2) break;
                PROF(stage == 0 ? 1 : 9);
                uint4 ua[3], ub[3];
#pragma unroll
                for (int i = 0; i < 3; i++) ua[i] = ub[i] = make_uint4(0, 0, 0, 0);
                layernorm_rows(v, red, warp, lane, [&]() {
                    if (stage == 0) {
                        modp_load(ua, sc_->modp[0] + tid * 4);
                        if (warp == 0) modp_load(ub, sc_->modp[0] + 1024 + tid * 4);
                    }
                });
                if (stage == 0) PROFR(27);
                if (stage == 0) {
                    const uint32_t tag = (epoch + 1) & 0xffu;
                    modp_to_smem(ua, sbase + OFF_MODT + (DM + tid * 4) * 4, sc_->modp[0] + tid * 4, tag);
                    if (warp == 0)
                        modp_to_smem(ub, sbase + OFF_MODT + (DM + 1024 + tid * 4) * 4, sc_->modp[0] + 1024 + tid * 4, tag);
                    bar_sync(3, 256);
                }
                float shift[18], scale[18];
                lds_mod(shift, modt + DM * 4, warp);
                lds_mod(scale, modt + 2 * DM * 4, warp);
                if (stage == 0) PROFR(28);
                PROF(stage == 0 ? 2 : 10);
                modulate_store(v, shift, scale, stage == 0 ? SM_SCALE : 1.f, sc_->h[epoch & 1][stage] + (size_t)own * 36 * 32, warp, lane);
                if (stage == 0) asm volatile("barrier.cluster.wait.aligned;" ::: "memory");
            }

            const uint32_t spill = sbase + 8 * SLOT_BYTES + wg * 3 * SLOT_BYTES + (tid & 127) * 16;
            uint32_t a[144];
            PROF(stage == 0 ? 3 : 11);
            {
                const uint4* hsrc = sc_->h[epoch & 1][stage] + (size_t)wown * 36 * 32 + lane;
                __nanosleep(stage == 0 ? PROBE0_NS : PROBE_NS);
                poll_tail(a, reinterpret_cast<const uint2*>(hsrc - lane + 32 * 32) + lane);
                PROF(stage == 0 ? 4 : 12);
                if (stage == 1) PROFG(25);
                TG(stage * 32 + 30);
                if (wg == 1) bar_sync(5, 256);
                poll_frags<0, 32>(a, hsrc, wg == 0);
                if (stage == 0) bar_arrive(4, 320);
            }
            uint4* hhbuf = sc_->hh + (size_t)b * 8 * 256 + tid;
            float d[64];
#pragma unroll 1
            for (int ch = 0;; ch++) {
                TG(stage * 32 + ch * 2);
                gemm_n128(d, a, cx, ring, true, stage && wg);
                TG(stage * 32 + ch * 2 + 1);
                if (stage == 0) {
                    if (ch == 3) break;
#pragma unroll
                    for (int v = 0; v < 8; v++)
                        sts128(spill + (ch * 8 + v) * 2048, pack_bf16(d[8 * v], d[8 * v + 1]),
                               pack_bf16(d[8 * v + 2], d[8 * v + 3]), pack_bf16(d[8 * v + 4], d[8 * v + 5]),
                               pack_bf16(d[8 * v + 6], d[8 * v + 7]));
                } else {
#pragma unroll
                    for (int i = 0; i < 32; i++) {
                        const float gv = d[i], gu = gv * d[32 + i];
                        const float z = gv * fmaf(gv * gv, 0.7978845608028654f * 0.044715f, 0.7978845608028654f);
                        d[i] = fmaf(gu, tanh_fast(z), gu);
                    }
                    if (ch == 8) break;
                    if (wg == 0) {
                        if (ch == 0) bar_arrive(7, 160);
                        if (ch == 2) bar_sync(10, 160);
                    }
#pragma unroll
                    for (int v = 0; v < 4; v++) {
                        const uint4 h4 = make_uint4(pack_bf16(d[8 * v], d[8 * v + 1]), pack_bf16(d[8 * v + 2], d[8 * v + 3]),
                                                    pack_bf16(d[8 * v + 4], d[8 * v + 5]), pack_bf16(d[8 * v + 6], d[8 * v + 7]));
                        if (ch < 2)
                            __stcg(hhbuf + (ch * 4 + v) * 256, h4);
                        else
                            sts128(spill + ((ch - 2) * 4 + v) * 2048, h4.x, h4.y, h4.z, h4.w);
                    }
                }
            }
            if (stage == 0) {
                uint32_t q[32];
#pragma unroll
                for (int i = 0; i < 32; i++) q[i] = pack_bf16(d[2 * i], d[2 * i + 1]);
                PROF(5);
                PROFG(23);
                if (wg == 0) bar_arrive(6, 160);
                {
                    float o[64], sa[32], sb[32];
                    uint32_t pa[16], pb[16];
#pragma unroll
                    for (int i = 0; i < 64; i++) o[i] = 0.f;
                    float n0 = 0.f, n1 = 0.f, l0 = 1.f, l1 = 1.f;
                    bool shifted = false;
                    const uint64_t dbase = desc_of(sbase);
                    const uint64_t dbk = dbase - (511u << 16);
                    const int my_bar = 1 + wg, other_bar = 2 - wg;

                    auto softmax_a = [&](bool first, float& s0, float& s1) {
                        if (first) {
                            shifted = false;
                            n0 = n1 = 0.f;
                            l0 = l1 = 0.f;
                        }
                        if (shifted)
                            exp_step<true>(sa, pa, n0, n1, s0, s1);
                        else
                            exp_step<false>(sa, pa, n0, n1, s0, s1);
                    };
                    auto softmax_b = [&](bool first, float s0, float s1) {
                        float u0, u1;
                        if (shifted)
                            exp_step<true>(sb, pb, n0, n1, u0, u1);
                        else
                            exp_step<false>(sb, pb, n0, n1, u0, u1);
                        s0 += u0;
                        s1 += u1;
                        bool bad = !(fmaxf(s0, s1) <= SM_HI);
                        if (first) {
                            float r0 = s0 + __shfl_xor_sync(0xffffffffu, s0, 1), r1 = s1 + __shfl_xor_sync(0xffffffffu, s1, 1);
                            r0 += __shfl_xor_sync(0xffffffffu, r0, 2);
                            r1 += __shfl_xor_sync(0xffffffffu, r1, 2);
                            bad = bad || !(fminf(r0, r1) >= SM_LO);
                        }
                        if (__any_sync(0xffffffffu, bad)) {
                            float x0, x1;
                            row_max(sa, sb, x0, x1);
                            x0 = -x0;
                            x1 = -x1;
                            if (!first) {
                                x0 = fminf(x0, n0);
                                x1 = fminf(x1, n1);
                                const float al0 = ex2(x0 - n0), al1 = ex2(x1 - n1);
                                l0 *= al0;
                                l1 *= al1;
#pragma unroll
                                for (int i = 0; i < 16; i++) {
                                    o[4 * i] *= al0;
                                    o[4 * i + 1] *= al0;
                                    o[4 * i + 2] *= al1;
                                    o[4 * i + 3] *= al1;
                                }
                            }
                            n0 = x0;
                            n1 = x1;
                            shifted = true;
                            exp_step<true>(sa, pa, n0, n1, s0, s1);
                            exp_step<true>(sb, pb, n0, n1, u0, u1);
                            s0 += u0;
                            s1 += u1;
                        }
                        l0 += s0;
                        l1 += s1;
                    };

                    cx.wait_full(4, 0);
                    if (wg == 1) bar_sync(my_bar, 256);
                    wg_fence();
                    qk_step(sa, q, dbk + 4 * 1024);
                    qk_step(sb, q, dbk + 5 * 1024);
                    wg_commit();
                    bar_arrive(other_bar, 256);
                    wg_wait<0>();
                    pin(sa);
                    pin(sb);
                    cx.release(4);
                    cx.wait_full(6, 0);
                    {
                        float s0, s1;
                        softmax_a(true, s0, s1);
                        softmax_b(true, s0, s1);
                    }
                    uint32_t alo = (uint32_t)dbase + 6 * 1024, blo = (uint32_t)dbase;
                    const uint32_t dhi = (uint32_t)(dbase >> 32);
                    float lp0 = 0.f, lp1 = 0.f;
#pragma unroll 1
                    for (int t = 1; t < 64; t++) {
                        const int j = t & 15;
                        const uint32_t sA = 2 + 4 * (t & 1), sB = 4 - 4 * (t & 1);
                        const uint64_t da = ((uint64_t)dhi << 32) | alo, db = ((uint64_t)dhi << 32) | blo;
                        TL(0);
                        bar_sync(my_bar, 256);
                        TL(2);
                        if (j != 1) {
                            wg_fence();
                            qk_step(sa, q, da - (511u << 16));
                            pv_step(o, pa, da + 1024, 1);
                            wg_commit();
                            cx.wait_full(sB, ((36 + 4 * t) >> 3) & 1);
                            wg_fence();
                            qk_step(sb, q, db - (511u << 16));
                            pv_step(o, pb, db + 1024, 1);
                            wg_commit();
                        } else {
                            cx.wait_full(sB, ((36 + 4 * t) >> 3) & 1);
                            wg_fence();
                            qk_step(sa, q, da - (511u << 16));
                            qk_step(sb, q, db - (511u << 16));
                            const uint32_t dst = spill + (max(t >> 4, 1) - 1) * 16384;
#pragma unroll
                            for (int v = 0; v < 8; v++)
                                sts128_if(t > 1, dst + v * 2048, pack_bf16(o[8 * v] * lp0, o[8 * v + 1] * lp0),
                                          pack_bf16(o[8 * v + 2] * lp1, o[8 * v + 3] * lp1),
                                          pack_bf16(o[8 * v + 4] * lp0, o[8 * v + 5] * lp0),
                                          pack_bf16(o[8 * v + 6] * lp1, o[8 * v + 7] * lp1));
                            wg_fence();
                            pv_step(o, pa, da + 1024, 0);
                            wg_commit();
                            pv_step(o, pb, db + 1024, 1);
                            wg_commit();
                        }
                        bar_arrive(other_bar, 256);
                        alo ^= 4096;
                        blo ^= 4096;
                        asm volatile("" : "+r"(alo), "+r"(blo));
                        TL(3);
                        wg_wait<1>();
                        pin(sa);
                        pin(pa);
                        TL(4);
                        cx.release(sA);
                        if (j == 0) inv_row_sums(l0, l1, lp0, lp1);
                        float s0, s1;
                        softmax_a(j == 0, s0, s1);
                        TL(5);
                        wg_wait<0>();
                        pin(o);
                        pin(sb);
                        pin(pb);
                        TL(6);
                        cx.release(sB);
                        const uint32_t bn = sbase + OFF_FULL + (8 - sA) * 8, pn = ((38 + 4 * t) >> 3) & 1;
                        const bool okn = mbar_try(bn, pn);
                        TL(1);
                        softmax_b(j == 0, s0, s1);
                        if (!okn || j == 15) {
                            mbar_wait(bn, pn);
                            if (t == 47 && wg == 0) bar_arrive(6, 160);
                            if (j == 15 && t < 63) {
                                const uint32_t src = spill + (t >> 4) * 16384;
#pragma unroll
                                for (int v = 0; v < 8; v++)
                                    lds128(src + v * 2048, q[4 * v], q[4 * v + 1], q[4 * v + 2], q[4 * v + 3]);
                            }
                        }
                        TL(7);
                    }
                    bar_sync(my_bar, 256);
                    wg_fence();
                    pv_step(o, pa, dbase + 2 * 1024, 1);
                    pv_step(o, pb, dbase + 3 * 1024, 1);
                    wg_commit();
                    if (wg == 0) bar_arrive(other_bar, 256);
                    float i0, i1;
                    inv_row_sums(l0, l1, i0, i1);
                    wg_wait<0>();
                    pin(o);
                    cx.release(2);
#pragma unroll
                    for (int i = 0; i < 16; i++) {
                        a[2 * i] = pack_bf16(o[4 * i] * i0, o[4 * i + 1] * i0);
                        a[2 * i + 1] = pack_bf16(o[4 * i + 2] * i1, o[4 * i + 3] * i1);
                    }
#pragma unroll
                    for (int v = 0; v < 24; v++)
                        lds128(spill + v * 2048, a[32 + 4 * v], a[33 + 4 * v], a[34 + 4 * v], a[35 + 4 * v]);
#pragma unroll
                    for (int i = 128; i < 144; i++) a[i] = 0;
                }
                ring.slot = 4;
                ring.phase = 0;
                PROF(6);
                PROFG(24);
            } else {
#pragma unroll
                for (int v = 0; v < 8; v++) {
                    const uint4 t = __ldcg(hhbuf + v * 256);
                    a[112 + 4 * v] = t.x;
                    a[113 + 4 * v] = t.y;
                    a[114 + 4 * v] = t.z;
                    a[115 + 4 * v] = t.w;
                }
#pragma unroll
                for (int i = 0; i < 16; i++) a[i] = pack_bf16(d[2 * i], d[2 * i + 1]);
#pragma unroll
                for (int v = 0; v < 24; v++)
                    lds128(spill + v * 2048, a[16 + 4 * v], a[17 + 4 * v], a[18 + 4 * v], a[19 + 4 * v]);
                PROF(13);
            }

            {
                uint4* dst = sc_->part + ((size_t)wown * 8 + g) * 36 * 32 + lane;
                const uint32_t ptag = (stage + 1) & 1;
#pragma unroll 1
                for (int p = 0; p < 4; p++) {
                    TG(stage * 32 + 18 + p * 2);
                    gemm_n128(d, a, cx, ring, stage != 0, stage && wg);
                    TG(stage * 32 + 19 + p * 2);
#pragma unroll
                    for (int u = 0; u < 8; u++)
                        st128(dst + (p * 8 + u) * 32, (pack_bf16(d[8 * u], d[8 * u + 1]) & ~1u) | ptag,
                              pack_bf16(d[8 * u + 2], d[8 * u + 3]), pack_bf16(d[8 * u + 4], d[8 * u + 5]),
                              pack_bf16(d[8 * u + 6], d[8 * u + 7]));
                    if (p == 0 && wg == 0) bar_arrive(7, 160);
                }
                float e[32];
                TG(stage * 32 + 26);
                gemm_n64(e, a, cx, ring, stage != 0);
                TG(stage * 32 + 27);
                uint2* dst2 = reinterpret_cast<uint2*>(dst - lane + 32 * 32) + lane;
#pragma unroll
                for (int j = 0; j < 8; j++)
                    st64(dst2 + j * 32, (pack_bf16(e[4 * j], e[4 * j + 1]) & ~1u) | ptag, pack_bf16(e[4 * j + 2], e[4 * j + 3]));
            }
            PROF(stage == 0 ? 7 : 14);
            if (stage == 1) {
                PROFG(26);
                asm volatile("barrier.cluster.arrive.relaxed.aligned;" ::: "memory");
            }
        }
        if (wg == 0) bar_sync(8, 256);
        bar_sync(3, 256);
        if (tid == 32) sc_->epoch[b * 32] = get_epoch(sbase) + 1;
        if (tid == 0) {
            rows_store(sbase, &maps.rout, own * 16);
            rows_store_wait();
        }
        __syncwarp();
        PROF(16);
        PROFG(31);
        asm volatile("barrier.cluster.wait.aligned;" ::: "memory");
    }
}

typedef CUresult (*EncodeFn)(CUtensorMap*, CUtensorMapDataType, cuuint32_t, void*, const cuuint64_t*, const cuuint64_t*,
                             const cuuint32_t*, const cuuint32_t*, CUtensorMapInterleave, CUtensorMapSwizzle,
                             CUtensorMapL2promotion, CUtensorMapFloatOOBfill);

void make_map(EncodeFn enc, CUtensorMap* m, const void* ptr, uint64_t rows, uint64_t cols, bool narrow = false) {
    cuuint64_t gdim[2] = {cols, rows};
    cuuint64_t gstr[1] = {cols * 2};
    cuuint32_t box[2] = {narrow ? 16u : 64u, narrow ? 192u : 64u};
    cuuint32_t estr[2] = {1, 1};
    enc(m, CU_TENSOR_MAP_DATA_TYPE_BFLOAT16, 2, const_cast<void*>(ptr), gdim, gstr, box, estr,
        CU_TENSOR_MAP_INTERLEAVE_NONE, narrow ? CU_TENSOR_MAP_SWIZZLE_NONE : CU_TENSOR_MAP_SWIZZLE_128B,
        CU_TENSOR_MAP_L2_PROMOTION_L2_128B,
        CU_TENSOR_MAP_FLOAT_OOB_FILL_NONE);
}

void make_rows_map(EncodeFn enc, CUtensorMap* m, const void* ptr) {
    cuuint64_t gdim[3] = {64, 9, 2048};
    cuuint64_t gstr[2] = {128, DM * 2};
    cuuint32_t box[3] = {64, 9, 16};
    cuuint32_t estr[3] = {1, 1, 1};
    enc(m, CU_TENSOR_MAP_DATA_TYPE_BFLOAT16, 3, const_cast<void*>(ptr), gdim, gstr, box, estr,
        CU_TENSOR_MAP_INTERLEAVE_NONE, CU_TENSOR_MAP_SWIZZLE_128B, CU_TENSOR_MAP_L2_PROMOTION_L2_128B,
        CU_TENSOR_MAP_FLOAT_OOB_FILL_NONE);
}

}

extern "C" void kernel_launch(void* const* d_in, const int* in_sizes, int n_in, void* d_out, int out_size) {
    (void)in_sizes;
    (void)n_in;
    (void)out_size;
    void* fn = nullptr;
    cudaDriverEntryPointQueryResult qr;
    cudaGetDriverEntryPoint("cuTensorMapEncodeTiled", &fn, cudaEnableDefault, &qr);
    EncodeFn enc = (EncodeFn)fn;
    Params maps;
    maps.x = (const __nv_bfloat16*)d_in[0];
    maps.cvec = (const __nv_bfloat16*)d_in[9];
    maps.wmod = (const __nv_bfloat16*)d_in[10];
    maps.kc = (const __nv_bfloat16*)d_in[1];
    maps.vc = (const __nv_bfloat16*)d_in[2];
    maps.wq_p = (const __nv_bfloat16*)d_in[3];
    maps.wo_p = (const __nv_bfloat16*)d_in[4];
    maps.wg_p = (const __nv_bfloat16*)d_in[6];
    maps.wu_p = (const __nv_bfloat16*)d_in[7];
    maps.wd_p = (const __nv_bfloat16*)d_in[8];
    maps.out = (__nv_bfloat16*)d_out;
    void* scp = nullptr;
    cudaGetSymbolAddress(&scp, g_scratch);
    maps.sc = (Scratch*)scp;
    make_map(enc, &maps.k, d_in[1], 32 * 2048, 128);
    make_map(enc, &maps.v, d_in[2], 32 * 2048, 128);
    make_map(enc, &maps.wq, d_in[3], 576, 4096);
    make_map(enc, &maps.wo, d_in[4], 4096, 576);
    make_map(enc, &maps.wg, d_in[6], 576, 4608);
    make_map(enc, &maps.wu, d_in[7], 576, 4608);
    make_map(enc, &maps.wd, d_in[8], 4608, 576);
    make_rows_map(enc, &maps.rx, d_in[0]);
    make_rows_map(enc, &maps.rx2, (char*)scp + offsetof(Scratch, x2));
    make_rows_map(enc, &maps.rout, d_out);
    cudaFuncSetAttribute(fused_block_kernel, cudaFuncAttributeMaxDynamicSharedMemorySize, SMEM_BYTES);
    fused_block_kernel<<<128, 384, SMEM_BYTES>>>(maps);
}
```

```cpp
#include <cuda_runtime.h>
#include <cuda_bf16.h>
#include <cuda.h>
#include <stdint.h>
#include <stddef.h>

namespace {

constexpr int DM = 576;
constexpr int SLOT_BYTES = 16384;
constexpr int BOX_BYTES = 8192;
constexpr int NUNITS = 14;
constexpr int SMEM_TAIL = NUNITS * SLOT_BYTES;
constexpr int SMEM_BYTES = SMEM_TAIL + 2048 + 1024;
constexpr int OFF_FULL = SMEM_TAIL;
constexpr int OFF_EMPTY = SMEM_TAIL + 64;
constexpr int OFF_RED = SMEM_TAIL + 128;

constexpr int KV_AHEAD = 16;
#define GATE_SLOT 4
#define PROBE0_NS 700
#define PROBE_NS 300
#define GPOINT 1
constexpr int OFF_XBAR = SMEM_TAIL + 1792;
constexpr int OFF_ROWS = 8 * SLOT_BYTES;
constexpr int OFF_MODT = OFF_ROWS + 20480;
constexpr int OFF_GBAR = SMEM_TAIL + 1800;
constexpr int OFF_EPOCH = SMEM_TAIL + 1808;
constexpr int OFF_MRED = OFF_ROWS + 28672;

struct Scratch {
    unsigned epoch[128 * 32];
    uint32_t mod[6 * DM];
    uint32_t modp[3][2 * DM];
    uint4 h[2][2][128 * 36 * 32];
    uint4 part[128 * 8 * 36 * 32];
    uint4 hh[128 * 8 * 256];
    __nv_bfloat16 x2[2048 * DM];
};
__device__ Scratch g_scratch;

#define TG(i)
#define TL(i)
#define PROFR(i)
#define PROF(i)
#define PROFG(i)

struct Params {
    const __nv_bfloat16 *x, *cvec, *wmod, *kc, *vc, *wq_p, *wo_p, *wg_p, *wu_p, *wd_p;
    __nv_bfloat16* out;
    Scratch* sc;
    CUtensorMap k, v, wq, wo, wg, wu, wd, rx, rx2, rout;
};

__device__ __forceinline__ uint32_t smem_u32(const void* p) { return (uint32_t)__cvta_generic_to_shared(p); }
__device__ __forceinline__ void mbar_init(uint32_t a, uint32_t c) {
    asm volatile("mbarrier.init.shared::cta.b64 [%0], %1;" ::"r"(a), "r"(c) : "memory");
}
__device__ __forceinline__ void mbar_expect_tx(uint32_t a, uint32_t bytes) {
    asm volatile("mbarrier.arrive.expect_tx.shared::cta.b64 _, [%0], %1;" ::"r"(a), "r"(bytes) : "memory");
}
__device__ __forceinline__ bool mbar_try(uint32_t a, uint32_t ph) {
    uint32_t ok;
    asm volatile(
        "{\n.reg .pred p;\nmbarrier.try_wait.parity.shared::cta.b64 p, [%1], %2;\nselp.u32 %0, 1, 0, p;\n}"
        : "=r"(ok)
        : "r"(a), "r"(ph)
        : "memory");
    return ok != 0;
}
__device__ __forceinline__ uint32_t clk32() {
    uint32_t c;
    asm volatile("mov.u32 %0, %%clock;" : "=r"(c));
    return c;
}
constexpr uint32_t WAIT_LIMIT = 1u << 30;
__device__ __forceinline__ void mbar_wait(uint32_t a, uint32_t ph) {
    if (mbar_try(a, ph)) return;
    uint32_t t0 = clk32();
    while (!mbar_try(a, ph)) {
        if (clk32() - t0 > WAIT_LIMIT) break;
    }
}
__device__ __forceinline__ void mbar_arrive_cluster(uint32_t a, uint32_t cta) {
    asm volatile(
        "{\n.reg .b32 ra;\nmapa.shared::cluster.u32 ra, %0, %1;\nmbarrier.arrive.shared::cluster.b64 _, [ra];\n}" ::"r"(a),
        "r"(cta)
        : "memory");
}
__device__ __forceinline__ void tma_mc(uint32_t dst, const CUtensorMap* m, int c0, int c1, uint32_t bar) {
    asm volatile(
        "cp.async.bulk.tensor.2d.shared::cluster.global.mbarrier::complete_tx::bytes.multicast::cluster"
        " [%0], [%1, {%3, %4}], [%2], %5;" ::"r"(dst),
        "l"(m), "r"(bar), "r"(c0), "r"(c1), "h"((uint16_t)3)
        : "memory");
}
__device__ __forceinline__ void bulk_load(uint32_t dst, const void* src, uint32_t bytes, uint32_t bar) {
    asm volatile("cp.async.bulk.shared::cluster.global.mbarrier::complete_tx::bytes [%0], [%1], %2, [%3];" ::"r"(dst),
                 "l"(src), "r"(bytes), "r"(bar)
                 : "memory");
}
__device__ __forceinline__ void l2_prefetch(const void* p, uint32_t bytes) {
    asm volatile("cp.async.bulk.prefetch.L2.global [%0], %1;" ::"l"(p), "r"(bytes) : "memory");
}
__device__ __forceinline__ void bar_sync(int id, int n) { asm volatile("bar.sync %0, %1;" ::"r"(id), "r"(n) : "memory"); }
__device__ __forceinline__ void bar_arrive(int id, int n) {
    asm volatile("bar.arrive %0, %1;" ::"r"(id), "r"(n) : "memory");
}
__device__ __forceinline__ void wg_fence() { asm volatile("wgmma.fence.sync.aligned;" ::: "memory"); }
__device__ __forceinline__ void wg_commit() { asm volatile("wgmma.commit_group.sync.aligned;" ::: "memory"); }
template <int N>
__device__ __forceinline__ void wg_wait() {
    asm volatile("wgmma.wait_group.sync.aligned %0;" ::"n"(N) : "memory");
}
template <int N>
__device__ __forceinline__ void pin(float (&d)[N]) {
#pragma unroll
    for (int i = 0; i < N; i++) asm volatile("" : "+f"(d[i])::"memory");
}
template <int N>
__device__ __forceinline__ void pin(uint32_t (&d)[N]) {
#pragma unroll
    for (int i = 0; i < N; i++) asm volatile("" : "+r"(d[i])::"memory");
}
__device__ __forceinline__ uint32_t pack_bf16(float lo, float hi) {
    uint32_t r;
    asm("cvt.rn.bf16x2.f32 %0, %1, %2;" : "=r"(r) : "f"(hi), "f"(lo));
    return r;
}
__device__ __forceinline__ float bf_lo(uint32_t v) { return __uint_as_float(v << 16); }
__device__ __forceinline__ float bf_hi(uint32_t v) { return __uint_as_float(v & 0xffff0000u); }
__device__ __forceinline__ float round_bf16(float v) { return __bfloat162float(__float2bfloat16_rn(v)); }
__device__ __forceinline__ float ex2(float x) {
    float y;
    asm("ex2.approx.ftz.f32 %0, %1;" : "=f"(y) : "f"(x));
    return y;
}
__device__ __forceinline__ float rcp(float x) {
    float y;
    asm("rcp.approx.ftz.f32 %0, %1;" : "=f"(y) : "f"(x));
    return y;
}
__device__ __forceinline__ float tanh_fast(float x) {
    float y;
    asm("tanh.approx.f32 %0, %1;" : "=f"(y) : "f"(x));
    return y;
}
__device__ __forceinline__ void sts128(uint32_t a, uint32_t x, uint32_t y, uint32_t z, uint32_t w) {
    asm volatile("st.shared.v4.b32 [%0], {%1,%2,%3,%4};" ::"r"(a), "r"(x), "r"(y), "r"(z), "r"(w) : "memory");
}
__device__ __forceinline__ void lds128(uint32_t a, uint32_t& x, uint32_t& y, uint32_t& z, uint32_t& w) {
    asm volatile("ld.shared.v4.b32 {%0,%1,%2,%3}, [%4];" : "=r"(x), "=r"(y), "=r"(z), "=r"(w) : "r"(a) : "memory");
}
__device__ __forceinline__ void sts32f(uint32_t a, float v) {
    asm volatile("st.shared.f32 [%0], %1;" ::"r"(a), "f"(v) : "memory");
}
__device__ __forceinline__ float lds32f(uint32_t a) {
    float v;
    asm volatile("ld.shared.f32 %0, [%1];" : "=f"(v) : "r"(a) : "memory");
    return v;
}
#define F8(d, b) \
    "+f"(d[b]), "+f"(d[b + 1]), "+f"(d[b + 2]), "+f"(d[b + 3]), "+f"(d[b + 4]), "+f"(d[b + 5]), "+f"(d[b + 6]), "+f"(d[b + 7])

template <int TB>
__device__ __forceinline__ void wgmma_n128(float (&d)[64], uint32_t a0, uint32_t a1, uint32_t a2, uint32_t a3,
                                           uint64_t db, int sc) {
    asm volatile(
        "{\n.reg .pred p;\nsetp.ne.b32 p, %69, 0;\n"
        "wgmma.mma_async.sync.aligned.m64n128k16.f32.bf16.bf16 "
        "{%0,%1,%2,%3,%4,%5,%6,%7,%8,%9,%10,%11,%12,%13,%14,%15,%16,%17,%18,%19,%20,%21,%22,%23,%24,%25,%26,%27,%28,%29,%30,%31,"
        "%32,%33,%34,%35,%36,%37,%38,%39,%40,%41,%42,%43,%44,%45,%46,%47,%48,%49,%50,%51,%52,%53,%54,%55,%56,%57,%58,%59,%60,%61,%62,%63},"
        "{%64,%65,%66,%67}, %68, p, 1, 1, %70;\n}"
        : F8(d, 0), F8(d, 8), F8(d, 16), F8(d, 24), F8(d, 32), F8(d, 40), F8(d, 48), F8(d, 56)
        : "r"(a0), "r"(a1), "r"(a2), "r"(a3), "l"(db), "r"(sc), "n"(TB));
}
#define O8(d, b) \
    "=f"(d[b]), "=f"(d[b + 1]), "=f"(d[b + 2]), "=f"(d[b + 3]), "=f"(d[b + 4]), "=f"(d[b + 5]), "=f"(d[b + 6]), "=f"(d[b + 7])
template <int TB>
__device__ __forceinline__ void wgmma_n128_z(float (&d)[64], uint32_t a0, uint32_t a1, uint32_t a2, uint32_t a3,
                                             uint64_t db) {
    asm volatile(
        "wgmma.mma_async.sync.aligned.m64n128k16.f32.bf16.bf16 "
        "{%0,%1,%2,%3,%4,%5,%6,%7,%8,%9,%10,%11,%12,%13,%14,%15,%16,%17,%18,%19,%20,%21,%22,%23,%24,%25,%26,%27,%28,%29,%30,%31,"
        "%32,%33,%34,%35,%36,%37,%38,%39,%40,%41,%42,%43,%44,%45,%46,%47,%48,%49,%50,%51,%52,%53,%54,%55,%56,%57,%58,%59,%60,%61,%62,%63},"
        "{%64,%65,%66,%67}, %68, 0, 1, 1, %69;"
        : O8(d, 0), O8(d, 8), O8(d, 16), O8(d, 24), O8(d, 32), O8(d, 40), O8(d, 48), O8(d, 56)
        : "r"(a0), "r"(a1), "r"(a2), "r"(a3), "l"(db), "n"(TB));
}
template <int TB>
__device__ __forceinline__ void wgmma_n64_z(float (&d)[32], uint32_t a0, uint32_t a1, uint32_t a2, uint32_t a3,
                                            uint64_t db) {
    asm volatile(
        "wgmma.mma_async.sync.aligned.m64n64k16.f32.bf16.bf16 "
        "{%0,%1,%2,%3,%4,%5,%6,%7,%8,%9,%10,%11,%12,%13,%14,%15,%16,%17,%18,%19,%20,%21,%22,%23,%24,%25,%26,%27,%28,%29,%30,%31},"
        "{%32,%33,%34,%35}, %36, 0, 1, 1, %37;"
        : O8(d, 0), O8(d, 8), O8(d, 16), O8(d, 24)
        : "r"(a0), "r"(a1), "r"(a2), "r"(a3), "l"(db), "n"(TB));
}
template <int TB>
__device__ __forceinline__ void wgmma_n64(float (&d)[32], uint32_t a0, uint32_t a1, uint32_t a2, uint32_t a3,
                                          uint64_t db) {
    asm volatile(
        "wgmma.mma_async.sync.aligned.m64n64k16.f32.bf16.bf16 "
        "{%0,%1,%2,%3,%4,%5,%6,%7,%8,%9,%10,%11,%12,%13,%14,%15,%16,%17,%18,%19,%20,%21,%22,%23,%24,%25,%26,%27,%28,%29,%30,%31},"
        "{%32,%33,%34,%35}, %36, 1, 1, 1, %37;"
        : F8(d, 0), F8(d, 8), F8(d, 16), F8(d, 24)
        : "r"(a0), "r"(a1), "r"(a2), "r"(a3), "l"(db), "n"(TB));
}

__device__ __forceinline__ uint64_t desc_of(uint32_t saddr) {
    return (uint64_t)(((saddr >> 4) & 0x3FFFu) | (512u << 16)) | ((uint64_t)(64u | (1u << 30)) << 32);
}

struct Ring {
    uint32_t slot;
    uint32_t phase;
    __device__ __forceinline__ void next() {
        if (++slot == 8) {
            slot = 0;
            phase ^= 1;
        }
    }
};

struct Ctx {
    uint32_t sbase;
    int wg;
    uint32_t rel_cta;
    __device__ __forceinline__ void wait_full(uint32_t slot, uint32_t phase) const {
        mbar_wait(sbase + OFF_FULL + slot * 8, phase);
    }
    __device__ __forceinline__ void release(uint32_t slot) const {
        if (rel_cta < 2) mbar_arrive_cluster(sbase + OFF_EMPTY + slot * 8, rel_cta);
    }
};

__device__ __forceinline__ void gemm_n128(float (&d)[64], const uint32_t (&a)[144], const Ctx& c, Ring& r, bool nine,
                                          bool early) {
    uint32_t prev = 0;
#pragma unroll
    for (int s = 0; s < 9; s++) {
        if (s < 8 || nine) {
            if (s == GATE_SLOT) {
                if (early) {
                    wg_wait<0>();
                    c.release(prev);
                }
                bar_sync(8 + c.wg, 256);
            }
            c.wait_full(r.slot, r.phase);
            uint64_t db = desc_of(c.sbase + r.slot * SLOT_BYTES);
            wg_fence();
#pragma unroll
            for (int k = 0; k < 4; k++) {
                if ((s | k) == 0)
                    wgmma_n128_z<1>(d, a[0], a[1], a[2], a[3], db);
                else
                    wgmma_n128<1>(d, a[s * 16 + k * 4], a[s * 16 + k * 4 + 1], a[s * 16 + k * 4 + 2],
                                  a[s * 16 + k * 4 + 3], db + k * 128, 1);
            }
            wg_commit();
            if (s == 8 || (s == 7 && !nine)) bar_arrive(9 - c.wg, 256);
            if (s > 0) {
                wg_wait<1>();
                if (s != GATE_SLOT || !early) c.release(prev);
            }
            prev = r.slot;
            r.next();
        }
    }
    wg_wait<0>();
    c.release(prev);
    pin(d);
}
__device__ __forceinline__ void gemm_n64(float (&d)[32], const uint32_t (&a)[144], const Ctx& c, Ring& r, bool nine) {
    uint32_t prev = 0;
#pragma unroll
    for (int s = 0; s < 5; s++) {
        if (s < 4 || nine) {
            c.wait_full(r.slot, r.phase);
            uint64_t db = desc_of(c.sbase + r.slot * SLOT_BYTES);
            wg_fence();
#pragma unroll
            for (int k = 0; k < 8; k++) {
                if ((s | k) == 0)
                    wgmma_n64_z<1>(d, a[0], a[1], a[2], a[3], db);
                else if (s * 8 + k < 36)
                    wgmma_n64<1>(d, a[s * 32 + k * 4], a[s * 32 + k * 4 + 1], a[s * 32 + k * 4 + 2],
                                 a[s * 32 + k * 4 + 3], db + k * 128);
            }
            wg_commit();
            if (s > 0) {
                wg_wait<1>();
                c.release(prev);
            }
            prev = r.slot;
            r.next();
        }
    }
    wg_wait<0>();
    c.release(prev);
    pin(d);
}
__device__ __forceinline__ void st128(uint4* p, uint32_t x, uint32_t y, uint32_t z, uint32_t w) {
    asm volatile(
        "{\n.reg .b64 lo, hi;\n.reg .b128 t;\nmov.b64 lo, {%1, %2};\nmov.b64 hi, {%3, %4};\nmov.b128 t, {lo, hi};\n"
        "st.relaxed.gpu.global.b128 [%0], t;\n}" ::"l"(p),
        "r"(x), "r"(y), "r"(z), "r"(w)
        : "memory");
}
__device__ __forceinline__ uint4 ld128(const uint4* p) {
    uint4 r;
    asm volatile(
        "{\n.reg .b64 lo, hi;\n.reg .b128 t;\nld.relaxed.gpu.global.b128 t, [%4];\nmov.b128 {lo, hi}, t;\n"
        "mov.b64 {%0, %1}, lo;\nmov.b64 {%2, %3}, hi;\n}"
        : "=r"(r.x), "=r"(r.y), "=r"(r.z), "=r"(r.w)
        : "l"(p));
    return r;
}
__device__ __forceinline__ uint4 ldg128(const uint4* p) {
    uint4 r;
    asm volatile("ld.global.nc.v4.u32 {%0,%1,%2,%3}, [%4];" : "=r"(r.x), "=r"(r.y), "=r"(r.z), "=r"(r.w) : "l"(p));
    return r;
}
__device__ __forceinline__ void st64(void* p, uint32_t x, uint32_t y) {
    asm volatile("{\n.reg .b64 t;\nmov.b64 t, {%1, %2};\nst.relaxed.gpu.global.b64 [%0], t;\n}" ::"l"(p), "r"(x), "r"(y)
                 : "memory");
}
__device__ __forceinline__ uint2 ld64(const void* p) {
    uint2 r;
    asm volatile("{\n.reg .b64 t;\nld.relaxed.gpu.global.b64 t, [%2];\nmov.b64 {%0, %1}, t;\n}"
                 : "=r"(r.x), "=r"(r.y)
                 : "l"(p));
    return r;
}
__device__ __forceinline__ void rows_load(uint32_t sbase, const CUtensorMap* m, int row0) {
    mbar_expect_tx(sbase + OFF_XBAR, 16 * DM * 2);
    asm volatile(
        "cp.async.bulk.tensor.3d.shared::cluster.global.mbarrier::complete_tx::bytes [%0], [%1, {%3, %3, %4}], [%2];" ::"r"(
            sbase + OFF_ROWS),
        "l"(m), "r"(sbase + OFF_XBAR), "r"(0), "r"(row0)
        : "memory");
}
__device__ __forceinline__ void rows_store(uint32_t sbase, const CUtensorMap* m, int row0) {
    asm volatile("cp.async.bulk.tensor.3d.global.shared::cta.bulk_group [%0, {%2, %2, %3}], [%1];" ::"l"(m),
                 "r"(sbase + OFF_ROWS), "r"(0), "r"(row0)
                 : "memory");
    asm volatile("cp.async.bulk.commit_group;" ::: "memory");
}
__device__ __forceinline__ void rows_store_wait() { asm volatile("cp.async.bulk.wait_group 0;" ::: "memory"); }

__device__ __forceinline__ constexpr int own_col(int j) { return j < 8 ? (j >> 1) * 128 + (j & 1) * 8 : 512; }
__device__ __forceinline__ void row_reduce(float& s0, float& s1, uint32_t red, int warp, int lane) {
    s0 += __shfl_xor_sync(0xffffffffu, s0, 1);
    s1 += __shfl_xor_sync(0xffffffffu, s1, 1);
    s0 += __shfl_xor_sync(0xffffffffu, s0, 2);
    s1 += __shfl_xor_sync(0xffffffffu, s1, 2);
    if ((lane & 3) == 0) {
        sts32f(red + (warp * 16 + (lane >> 2)) * 4, s0);
        sts32f(red + (warp * 16 + 8 + (lane >> 2)) * 4, s1);
    }
    bar_sync(3, 256);
    s0 = 0.f;
    s1 = 0.f;
#pragma unroll
    for (int w = 0; w < 8; w++) {
        s0 += lds32f(red + (w * 16 + (lane >> 2)) * 4);
        s1 += lds32f(red + (w * 16 + 8 + (lane >> 2)) * 4);
    }
}
template <class F>
__device__ __forceinline__ void layernorm_rows(float (&v)[36], uint32_t red, int warp, int lane, F&& middle) {
    float s0 = 0.f, s1 = 0.f;
#pragma unroll
    for (int j = 0; j < 9; j++) {
        s0 += v[4 * j] + v[4 * j + 1];
        s1 += v[4 * j + 2] + v[4 * j + 3];
    }
    row_reduce(s0, s1, red, warp, lane);
    middle();
    const float m0 = s0 * (1.f / DM), m1 = s1 * (1.f / DM);
    s0 = 0.f;
    s1 = 0.f;
#pragma unroll
    for (int j = 0; j < 9; j++) {
        v[4 * j] -= m0;
        v[4 * j + 1] -= m0;
        v[4 * j + 2] -= m1;
        v[4 * j + 3] -= m1;
        s0 += v[4 * j] * v[4 * j] + v[4 * j + 1] * v[4 * j + 1];
        s1 += v[4 * j + 2] * v[4 * j + 2] + v[4 * j + 3] * v[4 * j + 3];
    }
    row_reduce(s0, s1, red + 512, warp, lane);
    const float r0 = rsqrtf(s0 * (1.f / DM) + 1e-5f), r1 = rsqrtf(s1 * (1.f / DM) + 1e-5f);
#pragma unroll
    for (int j = 0; j < 9; j++) {
        v[4 * j] *= r0;
        v[4 * j + 1] *= r0;
        v[4 * j + 2] *= r1;
        v[4 * j + 3] *= r1;
    }
}
__device__ __forceinline__ void mod_to_smem(uint32_t dst, const uint32_t* src, uint32_t tag) {
    const uint32_t t0 = clk32();
    uint4 u;
    while (true) {
        u = ld128(reinterpret_cast<const uint4*>(src));
        const uint32_t bad = ((u.x ^ tag) | (u.y ^ tag) | (u.z ^ tag) | (u.w ^ tag)) & 0xffffu;
        if (__all_sync(0xffffffffu, bad == 0) || clk32() - t0 > WAIT_LIMIT) break;
        __nanosleep(64);
    }
    sts128(dst, u.x & 0xffff0000u, u.y & 0xffff0000u, u.z & 0xffff0000u, u.w & 0xffff0000u);
}
__device__ __forceinline__ void lds_mod(float (&m)[18], uint32_t src  , int warp) {
#pragma unroll
    for (int j = 0; j < 9; j++)
        asm volatile("ld.shared.v2.f32 {%0,%1}, [%2];"
                     : "=f"(m[2 * j]), "=f"(m[2 * j + 1])
                     : "r"(src + own_col(j) * 4 - (j == 8 ? warp * 32 : 0))
                     : "memory");
}
__device__ __forceinline__ void modulate_store(const float (&v)[36], const float (&shift)[18], const float (&scale)[18],
                                               float post, uint4* hbuf  , int warp, int lane) {
    uint32_t o[18];
#pragma unroll
    for (int j = 0; j < 9; j++) {
        const uint32_t cc = pack_bf16(1.f + scale[2 * j], 1.f + scale[2 * j + 1]);
        const float c0 = bf_lo(cc) * post, c1 = bf_hi(cc) * post, s0 = shift[2 * j] * post, s1 = shift[2 * j + 1] * post;
        o[2 * j] = pack_bf16(fmaf(v[4 * j], c0, s0), fmaf(v[4 * j + 1], c1, s1));
        o[2 * j + 1] = pack_bf16(fmaf(v[4 * j + 2], c0, s0), fmaf(v[4 * j + 3], c1, s1));
        if ((j & 1) == 0) o[2 * j] = max(o[2 * j], 1u);
    }
#pragma unroll
    for (int i = 0; i < 4; i++) st128(hbuf + (i * 8 + warp) * 32 + lane, o[4 * i], o[4 * i + 1], o[4 * i + 2], o[4 * i + 3]);
    st64(reinterpret_cast<uint2*>(hbuf + 32 * 32) + warp * 32 + lane, o[16], o[17]);
}
__device__ __forceinline__ void sum_partials(float (&v)[36], const uint4* src  , uint32_t tag) {
    const uint32_t t0 = clk32();
    while (true) {
        uint4 t[8][4];
#pragma unroll
        for (int s = 0; s < 8; s++)
#pragma unroll
            for (int i = 0; i < 4; i++) t[s][i] = ld128(src + (s * 36 + i * 8) * 32);
        uint32_t bad = 0;
#pragma unroll
        for (int i = 0; i < 32; i++) v[i] = 0.f;
#pragma unroll
        for (int s = 0; s < 8; s++)
#pragma unroll
            for (int i = 0; i < 4; i++) {
                bad |= t[s][i].x ^ tag;
                v[8 * i] += bf_lo(t[s][i].x);
                v[8 * i + 1] += bf_hi(t[s][i].x);
                v[8 * i + 2] += bf_lo(t[s][i].y);
                v[8 * i + 3] += bf_hi(t[s][i].y);
                v[8 * i + 4] += bf_lo(t[s][i].z);
                v[8 * i + 5] += bf_hi(t[s][i].z);
                v[8 * i + 6] += bf_lo(t[s][i].w);
                v[8 * i + 7] += bf_hi(t[s][i].w);
                asm volatile("" : "+r"(bad));
            }
#pragma unroll
        for (int i = 0; i < 32; i++) asm volatile("" : "+f"(v[i]));
        if (__all_sync(0xffffffffu, (bad & 1u) == 0) || clk32() - t0 > WAIT_LIMIT) break;
    }
}
__device__ __forceinline__ void sum_tail(float (&v)[36], const uint2* src  , uint32_t tag) {
    const uint32_t t0 = clk32();
    while (true) {
        uint2 t[8];
#pragma unroll
        for (int s = 0; s < 8; s++) t[s] = ld64(src + s * 72 * 32);
        uint32_t bad = 0;
        v[32] = v[33] = v[34] = v[35] = 0.f;
#pragma unroll
        for (int s = 0; s < 8; s++) {
            bad |= t[s].x ^ tag;
            v[32] += bf_lo(t[s].x);
            v[33] += bf_hi(t[s].x);
            v[34] += bf_lo(t[s].y);
            v[35] += bf_hi(t[s].y);
        }
        if (__all_sync(0xffffffffu, (bad & 1u) == 0) || clk32() - t0 > WAIT_LIMIT) break;
    }
}
__device__ __forceinline__ void poll_tail(uint32_t (&a)[144], const uint2* src  ) {
    const uint32_t t0 = clk32();
    while (true) {
        uint32_t m = 0xffffffffu;
#pragma unroll
        for (int j = 0; j < 8; j++) {
            const uint2 t = ld64(src + j * 32);
            a[128 + 2 * j] = t.x;
            a[129 + 2 * j] = t.y;
        }
#pragma unroll
        for (int j = 0; j < 8; j++) m = min(m, a[128 + 2 * j]);
        if (__all_sync(0xffffffffu, m != 0) || clk32() - t0 > WAIT_LIMIT) break;
    }
}
template <int K0, int K1>
__device__ __forceinline__ void poll_frags(uint32_t (&a)[144], const uint4* src  , bool kick) {
    const uint32_t t0 = clk32();
    while (true) {
#pragma unroll
        for (int k = K0; k < K1; k++) {
            const uint4 t = ld128(src + k * 32);
            a[4 * k] = t.x;
            a[4 * k + 1] = t.y;
            a[4 * k + 2] = t.z;
            a[4 * k + 3] = t.w;
        }
        if (kick) bar_arrive(5, 256);
        kick = false;
        uint32_t m0 = a[4 * K0], m1 = a[4 * K0 + 4];
#pragma unroll
        for (int k = K0 + 2; k < K1; k += 2) {
            m0 = min(m0, a[4 * k]);
            m1 = min(m1, a[4 * k + 4]);
        }
        if (__all_sync(0xffffffffu, min(m0, m1) != 0) || clk32() - t0 > WAIT_LIMIT) break;
    }
}

constexpr float SM_SCALE = 0.08838834764831845f * 1.4426950408889634f;
constexpr float SM_HI = 1.2089258e24f;
constexpr float SM_LO = 9.0949470e-13f;
__device__ __forceinline__ void qk_step(float (&s)[32], const uint32_t (&q)[32], uint64_t dk) {
#pragma unroll
    for (int k = 0; k < 8; k++) {
        if (k == 0)
            wgmma_n64_z<0>(s, q[0], q[1], q[2], q[3], dk);
        else
            wgmma_n64<0>(s, q[4 * k], q[4 * k + 1], q[4 * k + 2], q[4 * k + 3], dk + (k >> 2) * 512 + (k & 3) * 2);
    }
}
__device__ __forceinline__ void pv_step(float (&o)[64], const uint32_t (&p)[16], uint64_t dv, int acc) {
#pragma unroll
    for (int k = 0; k < 4; k++)
        wgmma_n128<1>(o, p[4 * k], p[4 * k + 1], p[4 * k + 2], p[4 * k + 3], dv + k * 128, k != 0 ? 1 : acc);
}
template <bool SHIFT>
__device__ __forceinline__ void exp_step(const float (&s)[32], uint32_t (&p)[16], float n0, float n1, float& s0,
                                         float& s1) {
#pragma unroll
    for (int i = 0; i < 8; i++) {
        const float e0 = ex2(SHIFT ? s[4 * i] + n0 : s[4 * i]), e1 = ex2(SHIFT ? s[4 * i + 1] + n0 : s[4 * i + 1]);
        const float e2 = ex2(SHIFT ? s[4 * i + 2] + n1 : s[4 * i + 2]), e3 = ex2(SHIFT ? s[4 * i + 3] + n1 : s[4 * i + 3]);
        if (i == 0) {
            s0 = e0;
            s1 = e2;
        } else {
            s0 += e0;
            s1 += e2;
        }
        s0 += e1;
        s1 += e3;
        p[2 * i] = pack_bf16(e0, e1);
        p[2 * i + 1] = pack_bf16(e2, e3);
    }
}
__device__ __forceinline__ void row_max(const float (&sa)[32], const float (&sb)[32], float& x0, float& x1) {
    float xa[8];
#pragma unroll
    for (int i = 0; i < 8; i++) xa[i] = fmaxf(sa[i], sb[i]);
#pragma unroll
    for (int k = 1; k < 4; k++)
#pragma unroll
        for (int i = 0; i < 8; i++) xa[i] = fmaxf(xa[i], fmaxf(sa[8 * k + i], sb[8 * k + i]));
    x0 = fmaxf(fmaxf(xa[0], xa[1]), fmaxf(xa[4], xa[5]));
    x1 = fmaxf(fmaxf(xa[2], xa[3]), fmaxf(xa[6], xa[7]));
    x0 = fmaxf(x0, __shfl_xor_sync(0xffffffffu, x0, 1));
    x1 = fmaxf(x1, __shfl_xor_sync(0xffffffffu, x1, 1));
    x0 = fmaxf(x0, __shfl_xor_sync(0xffffffffu, x0, 2));
    x1 = fmaxf(x1, __shfl_xor_sync(0xffffffffu, x1, 2));
}
__device__ __forceinline__ void inv_row_sums(float l0, float l1, float& i0, float& i1) {
    l0 += __shfl_xor_sync(0xffffffffu, l0, 1);
    l1 += __shfl_xor_sync(0xffffffffu, l1, 1);
    l0 += __shfl_xor_sync(0xffffffffu, l0, 2);
    l1 += __shfl_xor_sync(0xffffffffu, l1, 2);
    i0 = rcp(l0);
    i1 = rcp(l1);
}

__device__ __forceinline__ uint32_t get_epoch(uint32_t sbase) { return __float_as_uint(lds32f(sbase + OFF_EPOCH)); }
__device__ __forceinline__ float silu_bf16(unsigned short c) {
    const float cv = bf_lo(c);
    return round_bf16(cv * rcp(1.f + ex2(-1.4426950408889634f * cv)));
}
__device__ __forceinline__ void st_mod(uint32_t* p, float v, uint32_t tag) {
    asm volatile("st.relaxed.gpu.global.u32 [%0], %1;" ::"l"(p), "r"(__float_as_uint(round_bf16(v)) | tag)
                 : "memory");
}
__device__ __forceinline__ void fma8(float (&acc)[8], float sc, const uint4& w) {
    acc[0] = fmaf(sc, bf_lo(w.x), acc[0]);
    acc[1] = fmaf(sc, bf_hi(w.x), acc[1]);
    acc[2] = fmaf(sc, bf_lo(w.y), acc[2]);
    acc[3] = fmaf(sc, bf_hi(w.y), acc[3]);
    acc[4] = fmaf(sc, bf_lo(w.z), acc[4]);
    acc[5] = fmaf(sc, bf_hi(w.z), acc[5]);
    acc[6] = fmaf(sc, bf_lo(w.w), acc[6]);
    acc[7] = fmaf(sc, bf_hi(w.w), acc[7]);
}
__device__ __forceinline__ void modp_load(uint4 (&u)[3], const uint32_t* src) {
#pragma unroll
    for (int i = 0; i < 3; i++) u[i] = ld128(reinterpret_cast<const uint4*>(src + i * 2 * DM));
}
__device__ __forceinline__ void modp_to_smem(uint4 (&u)[3], uint32_t dst, const uint32_t* src, uint32_t tag) {
    const uint32_t t0 = clk32();
    while (true) {
        uint32_t bad = 0;
#pragma unroll
        for (int i = 0; i < 3; i++) bad |= (u[i].x ^ tag) | (u[i].y ^ tag) | (u[i].z ^ tag) | (u[i].w ^ tag);
        if (__all_sync(0xffffffffu, (bad & 0xffu) == 0) || clk32() - t0 > WAIT_LIMIT) break;
        modp_load(u, src);
    }
    float s0 = 0.f, s1 = 0.f, s2 = 0.f, s3 = 0.f;
#pragma unroll
    for (int i = 0; i < 3; i++) {
        s0 += __uint_as_float(u[i].x & ~0xffu);
        s1 += __uint_as_float(u[i].y & ~0xffu);
        s2 += __uint_as_float(u[i].z & ~0xffu);
        s3 += __uint_as_float(u[i].w & ~0xffu);
    }
    const uint32_t p0 = pack_bf16(s0, s1), p1 = pack_bf16(s2, s3);
    sts128(dst, p0 << 16, p0 & 0xffff0000u, p1 << 16, p1 & 0xffff0000u);
}

__global__ void __cluster_dims__(2, 1, 1) __launch_bounds__(384, 1)
    fused_block_kernel(const __grid_constant__ Params maps) {
    extern __shared__ uint8_t smem_raw[];
    uint32_t sbase = (smem_u32(smem_raw) + 1023u) & ~1023u;
    asm volatile("" : "+r"(sbase));
    const int b = blockIdx.x;
    const int rank = b & 1;
    const int mt = ((b >> 1) & 7) * 2 + rank;
    const int g = b >> 4;
    const int warp = __shfl_sync(0xffffffffu, threadIdx.x >> 5, 0);
    const int lane = threadIdx.x & 31;
    Scratch* const sc_ = maps.sc;
    const __nv_bfloat16* const wmod = maps.wmod;
    const __nv_bfloat16* const cvec = maps.cvec;

#define SPROF(i)

    if (warp >= 8) {
        asm volatile("setmaxnreg.dec.sync.aligned.u32 24;");
        if (warp == 8 && lane == 0) {
#pragma unroll
            for (int i = 0; i < 8; i++) {
                mbar_init(sbase + OFF_FULL + i * 8, 1);
                mbar_init(sbase + OFF_EMPTY + i * 8, 4);
            }
            mbar_init(sbase + OFF_XBAR, 1);
            mbar_init(sbase + OFF_GBAR, 8);
            asm volatile("fence.mbarrier_init.release.cluster;" ::: "memory");
            asm volatile("barrier.cluster.arrive.relaxed;\nbarrier.cluster.wait;" ::: "memory");
            uint32_t slot = 0, phase = 1;
            const uint32_t dst0 = sbase + rank * BOX_BYTES;
            auto acquire = [&](uint32_t bytes) {
                mbar_wait(sbase + OFF_EMPTY + slot * 8, phase);
                mbar_expect_tx(sbase + OFF_FULL + slot * 8, bytes);
            };
            auto adv8 = [&]() {
                if (++slot == 8) {
                    slot = 0;
                    phase ^= 1;
                }
            };
#pragma unroll 1
            for (int hq = 0; hq < 4; hq++) {
                const int col = (g * 4 + ((hq + 1) & 3)) * 128 + rank * 64;
                if (hq == 2) {
                    l2_prefetch(maps.kc + (size_t)(g * 4 * 2048 + (b & 15) * 64) * 128, SLOT_BYTES);
                    l2_prefetch(maps.vc + (size_t)(g * 4 * 2048 + (b & 15) * 64) * 128, SLOT_BYTES);
                }
#pragma unroll 1
                for (int kc = 0; kc < 9; kc++) {
                    acquire(SLOT_BYTES);
                    tma_mc(dst0 + slot * SLOT_BYTES, &maps.wq, col, kc * 64, sbase + OFF_FULL + slot * 8);
                    adv8();
                }
            }
            const int row0 = g * 4 * 2048;
#pragma unroll 1
            for (int n = 0; n < 128; n++) {
                if (n < 4) mbar_wait(sbase + OFF_EMPTY + (slot + 1) * 8, phase);
                acquire(2 * SLOT_BYTES);
                const uint32_t bar = sbase + OFF_FULL + slot * 8;
                const int r0 = n == 0 ? 0 : (n == 127 ? 126 : n + 1);
                const int r1 = n == 0 ? 1 : (n == 127 ? 127 : n - 1);
                tma_mc(dst0 + slot * SLOT_BYTES, n == 127 ? &maps.v : &maps.k, rank * 64, row0 + r0 * 64, bar);
                tma_mc(dst0 + (slot + 1) * SLOT_BYTES, n == 0 ? &maps.k : &maps.v, rank * 64, row0 + r1 * 64, bar);
                adv8();
                adv8();
                const int u = n + KV_AHEAD;
                if (u < 128 && (u & 15) == (b & 15)) {
                    l2_prefetch(maps.kc + (size_t)(row0 + u * 64) * 128, SLOT_BYTES);
                    l2_prefetch(maps.vc + (size_t)(row0 + u * 64) * 128, SLOT_BYTES);
                }
            }
#pragma unroll 1
            for (int p = 0; p < 4; p++)
#pragma unroll 1
                for (int kc = 0; kc < 8; kc++) {
                    acquire(SLOT_BYTES);
                    tma_mc(dst0 + slot * SLOT_BYTES, &maps.wo, p * 128 + rank * 64, g * 512 + ((kc + 6) & 7) * 64,
                           sbase + OFF_FULL + slot * 8);
                    adv8();
                }
#pragma unroll 1
            for (int kc = 0; kc < 4; kc++) {
                acquire(SLOT_BYTES);
                tma_mc(dst0 + slot * SLOT_BYTES, &maps.wo, 512, g * 512 + ((kc + 3) & 3) * 128 + rank * 64,
                       sbase + OFF_FULL + slot * 8);
                adv8();
            }
            mbar_wait(sbase + OFF_GBAR, 0);
            const CUtensorMap* mg = rank ? &maps.wu : &maps.wg;
#pragma unroll 1
            for (int ch = 0; ch < 9; ch++)
#pragma unroll 1
                for (int kc = 0; kc < 9; kc++) {
                    acquire(SLOT_BYTES);
                    tma_mc(dst0 + slot * SLOT_BYTES, mg, g * 576 + ch * 64, kc * 64, sbase + OFF_FULL + slot * 8);
                    adv8();
                }
#pragma unroll 1
            for (int p = 0; p < 4; p++)
#pragma unroll 1
                for (int i = 0; i < 9; i++) {
                    acquire(SLOT_BYTES);
                    tma_mc(dst0 + slot * SLOT_BYTES, &maps.wd, p * 128 + rank * 64,
                           g * 576 + (i == 0 ? 8 : (i < 7 ? i + 1 : i - 7)) * 64, sbase + OFF_FULL + slot * 8);
                    adv8();
                }
#pragma unroll 1
            for (int i2 = 0; i2 < 5; i2++) {
                acquire(i2 < 4 ? SLOT_BYTES : BOX_BYTES);
                const int i = 2 * i2 + rank;
                if (i < 9)
                    tma_mc(dst0 + slot * SLOT_BYTES, &maps.wd, 512, g * 576 + (i == 0 ? 8 : (i < 7 ? i + 1 : i - 7)) * 64,
                           sbase + OFF_FULL + slot * 8);
                adv8();
            }
        } else if (warp == 11) {
            asm volatile("barrier.cluster.arrive.relaxed.aligned;" ::: "memory");
            bar_sync(6, 160);
            uint4* hz = sc_->h[(get_epoch(sbase) & 1) ^ 1][0] + (size_t)b * 72 * 32 + lane;
#pragma unroll 1
            for (int i = 0; i < 72; i++) {
                hz[i * 32] = make_uint4(0, 0, 0, 0);
                __nanosleep(200);
            }
            bar_sync(6, 160);
            if (lane == 0) {
#pragma unroll 1
                for (int i = 0; i < 9; i++) {
                    l2_prefetch((const char*)maps.wo_p + (size_t)b * 36864 + i * 4096, 4096);
                    __nanosleep(400);
                    l2_prefetch((const char*)maps.wg_p + (size_t)b * 41472 + i * 4608, 4608);
                    __nanosleep(400);
                    l2_prefetch((const char*)maps.wu_p + (size_t)b * 41472 + i * 4608, 4608);
                    __nanosleep(400);
                    l2_prefetch((const char*)maps.wd_p + (size_t)b * 41472 + i * 4608, 4608);
                    __nanosleep(400);
                }
            }
        } else if (warp == 9 || warp == 10) {
            asm volatile("barrier.cluster.arrive.relaxed.aligned;" ::: "memory");
            if (warp == 10) {
                bar_sync(11, 288);
                if (lane < 9) l2_prefetch((const char*)maps.wq_p + (size_t)b * 36864 + lane * 4096, 4096);
                __syncwarp();
            }
            bar_sync(4, 320);
            const uint32_t tag = (get_epoch(sbase) + 1) & 0xffffu;
            const int blk = warp == 9 ? 72 + b : 200 + b;
            if (blk < 216) {
                float acc[8];
#pragma unroll
                for (int e = 0; e < 8; e++) acc[e] = 0.f;
                const uint4* wp = reinterpret_cast<const uint4*>(wmod + (size_t)(lane >> 1) * (6 * DM) + blk * 16) + (lane & 1);
                const unsigned short* cp = reinterpret_cast<const unsigned short*>(cvec) + (lane >> 1);
#pragma unroll 1
                for (int i = 0; i < 36; i++) {
                    const uint4 w = __ldg(wp + (size_t)i * (16 * 6 * DM / 8));
                    const float sc = silu_bf16(__ldg(cp + i * 16));
                    fma8(acc, sc, w);
                }
#pragma unroll
                for (int o = 2; o < 32; o <<= 1)
#pragma unroll
                    for (int e = 0; e < 8; e++) acc[e] += __shfl_xor_sync(0xffffffffu, acc[e], o);
                if (lane < 2) {
#pragma unroll
                    for (int e = 0; e < 8; e++) st_mod(sc_->mod + blk * 16 + lane * 8 + e, acc[e], tag);
                }
            }
            if (warp == 9) {
#pragma unroll 1
                for (int st = 1; st <= 2; st++) {
                    bar_sync(7, 160);
                    const uint32_t* src = sc_->mod + (st * 3 - 1) * DM;
                    const int n = st == 1 ? 3 * DM : DM;
#pragma unroll 1
                    for (int i = lane * 4; i < n + 127 - ((n + 127) & 127); i += 128)
                        mod_to_smem(sbase + OFF_MODT + min(i, n - 4) * 4, src + min(i, n - 4), tag);
                    __syncwarp();
                    if (lane == 0) rows_load(sbase, st == 1 ? &maps.rx : &maps.rx2, (mt * 8 + g) * 16);
                    if (st == 1) {
                        bar_sync(7, 160);
                        if (lane == 0) {
                            rows_store(sbase, &maps.rx2, (mt * 8 + g) * 16);
                            rows_store_wait();
                        }
                        __syncwarp();
                        bar_arrive(10, 160);
                    }
                }
            }
        }
    } else {
        uint4 w1[3], xw[5], ew = make_uint4(0, 0, 0, 0);
        unsigned short cu[3];
        {
            const int t = threadIdx.x, bw = min(b, 107);
            const int row = (bw / 36) * 192 + (t >> 2);
#pragma unroll
            for (int i = 0; i < 3; i++) {
                w1[i] = ldg128(reinterpret_cast<const uint4*>(wmod + (size_t)(row + 64 * i) * (6 * DM)) + (bw % 36) * 4 + (t & 3));
                asm volatile("ld.global.nc.u16 %0, [%1];" : "=h"(cu[i]) : "l"(cvec + row + 64 * i));
            }
            if (t == 0) ew = ld128(reinterpret_cast<const uint4*>(&sc_->epoch[b * 32]));
        }
        if (threadIdx.x == 160) SPROF(5);
        asm volatile("setmaxnreg.inc.sync.aligned.u32 240;");
        if (threadIdx.x == 160) SPROF(6);
        const int wg = warp >> 2;
        const int tid = threadIdx.x;
        Ctx cx;
        cx.sbase = sbase;
        cx.wg = wg;
        if (wg == 1) bar_arrive(8, 256);
        cx.rel_cta = (lane == 0 && (warp & 3) < 2) ? (warp & 3) : 2;
        const uint32_t red = sbase + OFF_RED;
        const int own = mt * 8 + g;
        const int wown = mt * 8 + warp;
        PROF(0);
        PROFG(30);
        PROFR(17);
        {
            float acc[8];
#pragma unroll
            for (int e = 0; e < 8; e++) acc[e] = 0.f;
#pragma unroll
            for (int i = 0; i < 3; i++) fma8(acc, silu_bf16(cu[i]), w1[i]);
            {
                int off = tid;
                asm volatile("{\n.reg .pred p;\nsetp.gt.f32 p, %1, 0f00000000;\n@p add.s32 %0, %0, %2;\n}"
                             : "+r"(off)
                             : "f"(acc[7]), "r"((int)gridDim.y - 1));
#pragma unroll
                for (int i = 0; i < 5; i++)
                    xw[i] = ldg128(reinterpret_cast<const uint4*>(maps.x + (size_t)own * 16 * DM) + min(off + 256 * i, 1151));
                asm volatile("barrier.cluster.arrive.relaxed.aligned;" ::: "memory");
            }
#pragma unroll
            for (int o = 4; o < 32; o <<= 1)
#pragma unroll
                for (int e = 0; e < 8; e++) acc[e] += __shfl_xor_sync(0xffffffffu, acc[e], o);
            PROFR(19);
            if (lane < 4) {
                const uint32_t dst = sbase + OFF_MRED + warp * 128 + lane * 32;
                sts128(dst, __float_as_uint(acc[0]), __float_as_uint(acc[1]), __float_as_uint(acc[2]), __float_as_uint(acc[3]));
                sts128(dst + 16, __float_as_uint(acc[4]), __float_as_uint(acc[5]), __float_as_uint(acc[6]), __float_as_uint(acc[7]));
            }
            if (tid == 0) sts128(sbase + OFF_EPOCH, ew.x, ew.y, ew.z, ew.w);
            bar_sync(3, 256);
            PROFR(20);
            if (tid < 32 && b < 108) {
                float sum = 0.f;
#pragma unroll
                for (int w8 = 0; w8 < 8; w8++) sum += lds32f(sbase + OFF_MRED + w8 * 128 + tid * 4);
                asm volatile("st.relaxed.gpu.global.u32 [%0], %1;" ::"l"(&sc_->modp[b / 36][(b % 36) * 32 + tid]),
                             "r"((__float_as_uint(sum) & ~0xffu) | ((get_epoch(sbase) + 1) & 0xffu))
                             : "memory");
            }
            PROFR(21);
#pragma unroll
            for (int i = 0; i < 5; i++) {
                const int vi = min(tid + 256 * i, 1151), ln = vi >> 3;
                sts128(sbase + OFF_ROWS + ln * 128 + (((vi & 7) ^ (ln & 7)) << 4), xw[i].x, xw[i].y, xw[i].z, xw[i].w);
            }
            bar_sync(3, 256);
            bar_arrive(11, 288);
        }

        Ring ring{0u, 0u};
        int stage = 0;
        asm volatile("" : "+r"(stage));
#pragma unroll 1
        for (;; stage++) {
            int tid, lane;
            asm volatile("mov.u32 %0, %%tid.x;" : "=r"(tid));
            lane = tid & 31;
            const uint32_t epoch = get_epoch(sbase);
            {
                float v[36];
                const uint32_t modt = sbase + OFF_MODT + (warp * 16 + (lane & 3) * 2) * 4;
                if (stage == 0) {
#pragma unroll
                    for (int i = 0; i < 36; i++) v[i] = 0.f;
                } else {
                    const uint4* psrc = sc_->part + (size_t)own * 8 * 36 * 32;
                    sum_partials(v, psrc + tid, stage & 1);
                    PROF(stage == 1 ? 8 : 15);
                    if (lane == 0) asm volatile("mbarrier.arrive.shared::cta.b64 _, [%0];" ::"r"(sbase + OFF_GBAR) : "memory");
                    sum_tail(v, reinterpret_cast<const uint2*>(psrc + 32 * 32) + tid, stage & 1);
                }
                if (stage) mbar_wait(sbase + OFF_XBAR, stage - 1);
                if (stage == 0) PROFR(22);
                {
                    const float gs = stage == 2 ? 0.5f : 1.f;
                    float gate[18];
                    lds_mod(gate, modt, warp);
                    const int r = lane >> 2;
                    const uint32_t rows = sbase + OFF_ROWS + r * (DM * 2) + (lane & 3) * 4;
#pragma unroll
                    for (int j = 0; j < 9; j++) {
                        const int ch = j < 8 ? (j >> 1) * 2 + (warp >> 2) : 8, c16 = j < 8 ? (warp & 3) * 2 + (j & 1) : warp;
                        const uint32_t ad = rows + ch * 128 + ((c16 ^ ((r + ch) & 7)) << 4);
                        const uint32_t u0 = __float_as_uint(lds32f(ad)), u1 = __float_as_uint(lds32f(ad + 8 * DM * 2));
                        const float g0 = stage ? gate[2 * j] * gs : 0.f, g1 = stage ? gate[2 * j + 1] * gs : 0.f;
                        v[4 * j] = fmaf(g0, v[4 * j], bf_lo(u0));
                        v[4 * j + 1] = fmaf(g1, v[4 * j + 1], bf_hi(u0));
                        v[4 * j + 2] = fmaf(g0, v[4 * j + 2], bf_lo(u1));
                        v[4 * j + 3] = fmaf(g1, v[4 * j + 3], bf_hi(u1));
                        sts32f(ad, __uint_as_float(pack_bf16(v[4 * j], v[4 * j + 1])));
                        sts32f(ad + 8 * DM * 2, __uint_as_float(pack_bf16(v[4 * j + 2], v[4 * j + 3])));
                    }
                    asm volatile("fence.proxy.async.shared::cta;" ::: "memory");
                }
                if (stage == 2) break;
                PROF(stage == 0 ? 1 : 9);
                uint4 ua[3], ub[3];
#pragma unroll
                for (int i = 0; i < 3; i++) ua[i] = ub[i] = make_uint4(0, 0, 0, 0);
                layernorm_rows(v, red, warp, lane, [&]() {
                    if (stage == 0) {
                        modp_load(ua, sc_->modp[0] + tid * 4);
                        if (warp == 0) modp_load(ub, sc_->modp[0] + 1024 + tid * 4);
                    }
                });
                if (stage == 0) PROFR(27);
                if (stage == 0) {
                    const uint32_t tag = (epoch + 1) & 0xffu;
                    modp_to_smem(ua, sbase + OFF_MODT + (DM + tid * 4) * 4, sc_->modp[0] + tid * 4, tag);
                    if (warp == 0)
                        modp_to_smem(ub, sbase + OFF_MODT + (DM + 1024 + tid * 4) * 4, sc_->modp[0] + 1024 + tid * 4, tag);
                    bar_sync(3, 256);
                }
                float shift[18], scale[18];
                lds_mod(shift, modt + DM * 4, warp);
                lds_mod(scale, modt + 2 * DM * 4, warp);
                if (stage == 0) PROFR(28);
                PROF(stage == 0 ? 2 : 10);
                modulate_store(v, shift, scale, stage == 0 ? SM_SCALE : 1.f, sc_->h[epoch & 1][stage] + (size_t)own * 36 * 32, warp, lane);
                if (stage == 0) asm volatile("barrier.cluster.wait.aligned;" ::: "memory");
            }

            const uint32_t spill = sbase + 8 * SLOT_BYTES + wg * 3 * SLOT_BYTES + (tid & 127) * 16;
            uint32_t a[144];
            PROF(stage == 0 ? 3 : 11);
            {
                const uint4* hsrc = sc_->h[epoch & 1][stage] + (size_t)wown * 36 * 32 + lane;
                __nanosleep(stage == 0 ? PROBE0_NS : PROBE_NS);
                poll_tail(a, reinterpret_cast<const uint2*>(hsrc - lane + 32 * 32) + lane);
                PROF(stage == 0 ? 4 : 12);
                if (stage == 1) PROFG(25);
                TG(stage * 32 + 30);
                if (wg == 1) bar_sync(5, 256);
                poll_frags<0, 32>(a, hsrc, wg == 0);
                if (stage == 0) bar_arrive(4, 320);
            }
            uint4* hhbuf = sc_->hh + (size_t)b * 8 * 256 + tid;
            float d[64];
#pragma unroll 1
            for (int ch = 0;; ch++) {
                TG(stage * 32 + ch * 2);
                gemm_n128(d, a, cx, ring, true, stage && wg);
                TG(stage * 32 + ch * 2 + 1);
                if (stage == 0) {
                    if (ch == 3) break;
#pragma unroll
                    for (int v = 0; v < 8; v++)
                        sts128(spill + (ch * 8 + v) * 2048, pack_bf16(d[8 * v], d[8 * v + 1]),
                               pack_bf16(d[8 * v + 2], d[8 * v + 3]), pack_bf16(d[8 * v + 4], d[8 * v + 5]),
                               pack_bf16(d[8 * v + 6], d[8 * v + 7]));
                } else {
#pragma unroll
                    for (int i = 0; i < 32; i++) {
                        const float gv = d[i], gu = gv * d[32 + i];
                        const float z = gv * fmaf(gv * gv, 0.7978845608028654f * 0.044715f, 0.7978845608028654f);
                        d[i] = fmaf(gu, tanh_fast(z), gu);
                    }
                    if (ch == 8) break;
                    if (wg == 0) {
                        if (ch == 0) bar_arrive(7, 160);
                        if (ch == 2) bar_sync(10, 160);
                    }
#pragma unroll
                    for (int v = 0; v < 4; v++) {
                        const uint4 h4 = make_uint4(pack_bf16(d[8 * v], d[8 * v + 1]), pack_bf16(d[8 * v + 2], d[8 * v + 3]),
                                                    pack_bf16(d[8 * v + 4], d[8 * v + 5]), pack_bf16(d[8 * v + 6], d[8 * v + 7]));
                        if (ch < 2)
                            __stcg(hhbuf + (ch * 4 + v) * 256, h4);
                        else
                            sts128(spill + ((ch - 2) * 4 + v) * 2048, h4.x, h4.y, h4.z, h4.w);
                    }
                }
            }
            if (stage == 0) {
                uint32_t q[32];
#pragma unroll
                for (int i = 0; i < 32; i++) q[i] = pack_bf16(d[2 * i], d[2 * i + 1]);
                PROF(5);
                PROFG(23);
                if (wg == 0) bar_arrive(6, 160);
                {
                    float o[64], sa[32], sb[32];
                    uint32_t pa[16], pb[16];
#pragma unroll
                    for (int i = 0; i < 64; i++) o[i] = 0.f;
                    float n0 = 0.f, n1 = 0.f, l0 = 0.f, l1 = 0.f;
                    bool shifted = false;
                    const uint64_t dbase = desc_of(sbase);
                    const uint64_t dbk = dbase - (511u << 16);
                    const int my_bar = 1 + wg, other_bar = 2 - wg;

                    auto rebase = [&](bool first, float& s0, float& s1) {
                        float x0, x1, u0, u1;
                        row_max(sa, sb, x0, x1);
                        x0 = -x0;
                        x1 = -x1;
                        if (!first) {
                            x0 = fminf(x0, n0);
                            x1 = fminf(x1, n1);
                            const float al0 = ex2(x0 - n0), al1 = ex2(x1 - n1);
                            l0 *= al0;
                            l1 *= al1;
#pragma unroll
                            for (int i = 0; i < 16; i++) {
                                o[4 * i] *= al0;
                                o[4 * i + 1] *= al0;
                                o[4 * i + 2] *= al1;
                                o[4 * i + 3] *= al1;
                            }
                        }
                        n0 = x0;
                        n1 = x1;
                        shifted = true;
                        exp_step<true>(sa, pa, n0, n1, s0, s1);
                        exp_step<true>(sb, pb, n0, n1, u0, u1);
                        s0 += u0;
                        s1 += u1;
                    };
                    auto softmax_b = [&](bool first, float& s0, float& s1) {
                        float u0, u1;
                        exp_step<true>(sb, pb, n0, n1, u0, u1);
                        s0 += u0;
                        s1 += u1;
                        bool bad = !(fmaxf(s0, s1) <= SM_HI);
                        if (first) {
                            float r0 = s0 + __shfl_xor_sync(0xffffffffu, s0, 1), r1 = s1 + __shfl_xor_sync(0xffffffffu, s1, 1);
                            r0 += __shfl_xor_sync(0xffffffffu, r0, 2);
                            r1 += __shfl_xor_sync(0xffffffffu, r1, 2);
                            bad = bad || !(fminf(r0, r1) >= SM_LO);
                        }
                        return __any_sync(0xffffffffu, bad) != 0;
                    };

                    cx.wait_full(4, 0);
                    if (wg == 1) bar_sync(my_bar, 256);
                    wg_fence();
                    qk_step(sa, q, dbk + 4 * 1024);
                    qk_step(sb, q, dbk + 5 * 1024);
                    wg_commit();
                    bar_arrive(other_bar, 256);
                    wg_wait<0>();
                    pin(sa);
                    pin(sb);
                    cx.release(4);
                    cx.wait_full(6, 0);
                    {
                        float s0, s1;
                        exp_step<false>(sa, pa, n0, n1, s0, s1);
                        if (softmax_b(true, s0, s1)) rebase(true, s0, s1);
                        l0 += s0;
                        l1 += s1;
                    }
                    uint32_t alo = (uint32_t)dbase + 6 * 1024, blo = (uint32_t)dbase;
                    const uint32_t dhi = (uint32_t)(dbase >> 32);
                    auto issue_turn = [&](int t) {
                        const uint64_t da = ((uint64_t)dhi << 32) | alo, db = ((uint64_t)dhi << 32) | blo;
                        bar_sync(my_bar, 256);
                        wg_fence();
                        qk_step(sa, q, da - (511u << 16));
                        pv_step(o, pa, da + 1024, (t & 15) != 1);
                        wg_commit();
                        cx.wait_full(4 - 4 * (t & 1), ((36 + 4 * t) >> 3) & 1);
                        wg_fence();
                        qk_step(sb, q, db - (511u << 16));
                        pv_step(o, pb, db + 1024, 1);
                        wg_commit();
                        bar_arrive(other_bar, 256);
                        alo ^= 4096;
                        blo ^= 4096;
                        asm volatile("" : "+r"(alo), "+r"(blo));
                    };
                    float lp0 = 1.f, lp1 = 1.f;
                    int t = 1;
#pragma unroll 1
                    while (true) {
                        const int j = t & 15;
                        const uint32_t sA = 2 + 4 * (t & 1);
                        const uint32_t bn = sbase + OFF_FULL + (8 - sA) * 8, pn = ((38 + 4 * t) >> 3) & 1;
                        issue_turn(t);
                        const bool okn = mbar_try(bn, pn);
                        wg_wait<1>();
                        pin(sa);
                        pin(pa);
                        cx.release(sA);
                        float s0, s1;
                        if (shifted)
                            exp_step<true>(sa, pa, n0, n1, s0, s1);
                        else
                            exp_step<false>(sa, pa, n0, n1, s0, s1);
                        wg_wait<0>();
                        pin(o);
                        pin(sb);
                        pin(pb);
                        cx.release(6 - sA);
                        bool bad;
                        if (shifted || j == 0) {
                            if (j == 0) {
                                float i0, i1;
                                inv_row_sums(lp0, lp1, i0, i1);
                                const uint32_t dst = spill + ((t >> 4) - 1) * 16384;
#pragma unroll
                                for (int v = 0; v < 8; v++)
                                    sts128(dst + v * 2048, pack_bf16(o[8 * v] * i0, o[8 * v + 1] * i0),
                                           pack_bf16(o[8 * v + 2] * i1, o[8 * v + 3] * i1),
                                           pack_bf16(o[8 * v + 4] * i0, o[8 * v + 5] * i0),
                                           pack_bf16(o[8 * v + 6] * i1, o[8 * v + 7] * i1));
                            }
                            bad = softmax_b(j == 0, s0, s1);
                        } else {
                            float u0, u1;
                            exp_step<false>(sb, pb, n0, n1, u0, u1);
                            s0 += u0;
                            s1 += u1;
                            bad = __any_sync(0xffffffffu, !(fmaxf(s0, s1) <= SM_HI));
                        }
                        t++;
                        if (!bad && okn && j != 15) {
                            l0 += s0;
                            l1 += s1;
                            continue;
                        }
                        if (bad) rebase(j == 0, s0, s1);
                        l0 += s0;
                        l1 += s1;
                        mbar_wait(bn, pn);
                        if (j == 15) {
                            if (t == 64) break;
                            const uint32_t src = spill + ((t >> 4) - 1) * 16384;
#pragma unroll
                            for (int v = 0; v < 8; v++)
                                lds128(src + v * 2048, q[4 * v], q[4 * v + 1], q[4 * v + 2], q[4 * v + 3]);
                            if (t == 48 && wg == 0) bar_arrive(6, 160);
                            lp0 = l0;
                            lp1 = l1;
                            l0 = l1 = n0 = n1 = 0.f;
                            shifted = false;
                        }
                    }
                    bar_sync(my_bar, 256);
                    wg_fence();
                    pv_step(o, pa, dbase + 2 * 1024, 1);
                    pv_step(o, pb, dbase + 3 * 1024, 1);
                    wg_commit();
                    if (wg == 0) bar_arrive(other_bar, 256);
                    float i0, i1;
                    inv_row_sums(l0, l1, i0, i1);
                    wg_wait<0>();
                    pin(o);
                    cx.release(2);
#pragma unroll
                    for (int i = 0; i < 16; i++) {
                        a[2 * i] = pack_bf16(o[4 * i] * i0, o[4 * i + 1] * i0);
                        a[2 * i + 1] = pack_bf16(o[4 * i + 2] * i1, o[4 * i + 3] * i1);
                    }
#pragma unroll
                    for (int v = 0; v < 24; v++)
                        lds128(spill + v * 2048, a[32 + 4 * v], a[33 + 4 * v], a[34 + 4 * v], a[35 + 4 * v]);
#pragma unroll
                    for (int i = 128; i < 144; i++) a[i] = 0;
                }
                ring.slot = 4;
                ring.phase = 0;
                PROF(6);
                PROFG(24);
            } else {
#pragma unroll
                for (int v = 0; v < 8; v++) {
                    const uint4 t = __ldcg(hhbuf + v * 256);
                    a[112 + 4 * v] = t.x;
                    a[113 + 4 * v] = t.y;
                    a[114 + 4 * v] = t.z;
                    a[115 + 4 * v] = t.w;
                }
#pragma unroll
                for (int i = 0; i < 16; i++) a[i] = pack_bf16(d[2 * i], d[2 * i + 1]);
#pragma unroll
                for (int v = 0; v < 24; v++)
                    lds128(spill + v * 2048, a[16 + 4 * v], a[17 + 4 * v], a[18 + 4 * v], a[19 + 4 * v]);
                PROF(13);
            }

            {
                uint4* dst = sc_->part + ((size_t)wown * 8 + g) * 36 * 32 + lane;
                const uint32_t ptag = (stage + 1) & 1;
#pragma unroll 1
                for (int p = 0; p < 4; p++) {
                    TG(stage * 32 + 18 + p * 2);
                    gemm_n128(d, a, cx, ring, stage != 0, stage && wg);
                    TG(stage * 32 + 19 + p * 2);
#pragma unroll
                    for (int u = 0; u < 8; u++)
                        st128(dst + (p * 8 + u) * 32, (pack_bf16(d[8 * u], d[8 * u + 1]) & ~1u) | ptag,
                              pack_bf16(d[8 * u + 2], d[8 * u + 3]), pack_bf16(d[8 * u + 4], d[8 * u + 5]),
                              pack_bf16(d[8 * u + 6], d[8 * u + 7]));
                    if (p == 0 && wg == 0) bar_arrive(7, 160);
                }
                float e[32];
                TG(stage * 32 + 26);
                gemm_n64(e, a, cx, ring, stage != 0);
                TG(stage * 32 + 27);
                uint2* dst2 = reinterpret_cast<uint2*>(dst - lane + 32 * 32) + lane;
#pragma unroll
                for (int j = 0; j < 8; j++)
                    st64(dst2 + j * 32, (pack_bf16(e[4 * j], e[4 * j + 1]) & ~1u) | ptag, pack_bf16(e[4 * j + 2], e[4 * j + 3]));
            }
            PROF(stage == 0 ? 7 : 14);
            if (stage == 1) {
                PROFG(26);
                asm volatile("barrier.cluster.arrive.relaxed.aligned;" ::: "memory");
            }
        }
        if (wg == 0) bar_sync(8, 256);
        bar_sync(3, 256);
        if (tid == 32) sc_->epoch[b * 32] = get_epoch(sbase) + 1;
        if (tid == 0) {
            rows_store(sbase, &maps.rout, own * 16);
            rows_store_wait();
        }
        __syncwarp();
        PROF(16);
        PROFG(31);
        asm volatile("barrier.cluster.wait.aligned;" ::: "memory");
    }
}

typedef CUresult (*EncodeFn)(CUtensorMap*, CUtensorMapDataType, cuuint32_t, void*, const cuuint64_t*, const cuuint64_t*,
                             const cuuint32_t*, const cuuint32_t*, CUtensorMapInterleave, CUtensorMapSwizzle,
                             CUtensorMapL2promotion, CUtensorMapFloatOOBfill);

void make_map(EncodeFn enc, CUtensorMap* m, const void* ptr, uint64_t rows, uint64_t cols, bool narrow = false) {
    cuuint64_t gdim[2] = {cols, rows};
    cuuint64_t gstr[1] = {cols * 2};
    cuuint32_t box[2] = {narrow ? 16u : 64u, narrow ? 192u : 64u};
    cuuint32_t estr[2] = {1, 1};
    enc(m, CU_TENSOR_MAP_DATA_TYPE_BFLOAT16, 2, const_cast<void*>(ptr), gdim, gstr, box, estr,
        CU_TENSOR_MAP_INTERLEAVE_NONE, narrow ? CU_TENSOR_MAP_SWIZZLE_NONE : CU_TENSOR_MAP_SWIZZLE_128B,
        CU_TENSOR_MAP_L2_PROMOTION_L2_128B,
        CU_TENSOR_MAP_FLOAT_OOB_FILL_NONE);
}

void make_rows_map(EncodeFn enc, CUtensorMap* m, const void* ptr) {
    cuuint64_t gdim[3] = {64, 9, 2048};
    cuuint64_t gstr[2] = {128, DM * 2};
    cuuint32_t box[3] = {64, 9, 16};
    cuuint32_t estr[3] = {1, 1, 1};
    enc(m, CU_TENSOR_MAP_DATA_TYPE_BFLOAT16, 3, const_cast<void*>(ptr), gdim, gstr, box, estr,
        CU_TENSOR_MAP_INTERLEAVE_NONE, CU_TENSOR_MAP_SWIZZLE_128B, CU_TENSOR_MAP_L2_PROMOTION_L2_128B,
        CU_TENSOR_MAP_FLOAT_OOB_FILL_NONE);
}

}

extern "C" void kernel_launch(void* const* d_in, const int* in_sizes, int n_in, void* d_out, int out_size) {
    (void)in_sizes;
    (void)n_in;
    (void)out_size;
    void* fn = nullptr;
    cudaDriverEntryPointQueryResult qr;
    cudaGetDriverEntryPoint("cuTensorMapEncodeTiled", &fn, cudaEnableDefault, &qr);
    EncodeFn enc = (EncodeFn)fn;
    Params maps;
    maps.x = (const __nv_bfloat16*)d_in[0];
    maps.cvec = (const __nv_bfloat16*)d_in[9];
    maps.wmod = (const __nv_bfloat16*)d_in[10];
    maps.kc = (const __nv_bfloat16*)d_in[1];
    maps.vc = (const __nv_bfloat16*)d_in[2];
    maps.wq_p = (const __nv_bfloat16*)d_in[3];
    maps.wo_p = (const __nv_bfloat16*)d_in[4];
    maps.wg_p = (const __nv_bfloat16*)d_in[6];
    maps.wu_p = (const __nv_bfloat16*)d_in[7];
    maps.wd_p = (const __nv_bfloat16*)d_in[8];
    maps.out = (__nv_bfloat16*)d_out;
    void* scp = nullptr;
    cudaGetSymbolAddress(&scp, g_scratch);
    maps.sc = (Scratch*)scp;
    make_map(enc, &maps.k, d_in[1], 32 * 2048, 128);
    make_map(enc, &maps.v, d_in[2], 32 * 2048, 128);
    make_map(enc, &maps.wq, d_in[3], 576, 4096);
    make_map(enc, &maps.wo, d_in[4], 4096, 576);
    make_map(enc, &maps.wg, d_in[6], 576, 4608);
    make_map(enc, &maps.wu, d_in[7], 576, 4608);
    make_map(enc, &maps.wd, d_in[8], 4608, 576);
    make_rows_map(enc, &maps.rx, d_in[0]);
    make_rows_map(enc, &maps.rx2, (char*)scp + offsetof(Scratch, x2));
    make_rows_map(enc, &maps.rout, d_out);
    cudaFuncSetAttribute(fused_block_kernel, cudaFuncAttributeMaxDynamicSharedMemorySize, SMEM_BYTES);
    fused_block_kernel<<<128, 384, SMEM_BYTES>>>(maps);
}
```

```cpp
#include <cuda_runtime.h>
#include <cuda_bf16.h>
#include <cuda.h>
#include <stdint.h>
#include <stddef.h>

namespace {

constexpr int DM = 576;
constexpr int SLOT_BYTES = 16384;
constexpr int BOX_BYTES = 8192;
constexpr int NUNITS = 14;
constexpr int SMEM_TAIL = NUNITS * SLOT_BYTES;
constexpr int SMEM_BYTES = SMEM_TAIL + 2048 + 1024;
constexpr int OFF_FULL = SMEM_TAIL;
constexpr int OFF_EMPTY = SMEM_TAIL + 64;
constexpr int OFF_RED = SMEM_TAIL + 128;

constexpr int KV_AHEAD = 16;
#define GATE_SLOT 4
#define PROBE0_NS 700
#define PROBE_NS 300
#define GPOINT 1
constexpr int OFF_XBAR = SMEM_TAIL + 1792;
constexpr int OFF_ROWS = 8 * SLOT_BYTES;
constexpr int OFF_MODT = OFF_ROWS + 20480;
constexpr int OFF_GBAR = SMEM_TAIL + 1800;
constexpr int OFF_EPOCH = SMEM_TAIL + 1808;
constexpr int OFF_MRED = OFF_ROWS + 28672;

struct Scratch {
    unsigned epoch[128 * 32];
    uint32_t mod[6 * DM];
    uint32_t modp[3][2 * DM];
    uint4 h[2][2][128 * 36 * 32];
    uint4 part[128 * 8 * 36 * 32];
    uint4 hh[128 * 8 * 256];
    __nv_bfloat16 x2[2048 * DM];
};
__device__ Scratch g_scratch;

#define TG(i)
#define TL(i)
#define PROFR(i)
#define PROF(i)
#define PROFG(i)

struct Params {
    const __nv_bfloat16 *x, *cvec, *wmod, *kc, *vc, *wq_p, *wo_p, *wg_p, *wu_p, *wd_p;
    __nv_bfloat16* out;
    Scratch* sc;
    CUtensorMap k, v, wq, wo, wg, wu, wd, rx, rx2, rout;
};

__device__ __forceinline__ uint32_t smem_u32(const void* p) { return (uint32_t)__cvta_generic_to_shared(p); }
__device__ __forceinline__ void mbar_init(uint32_t a, uint32_t c) {
    asm volatile("mbarrier.init.shared::cta.b64 [%0], %1;" ::"r"(a), "r"(c) : "memory");
}
__device__ __forceinline__ void mbar_expect_tx(uint32_t a, uint32_t bytes) {
    asm volatile("mbarrier.arrive.expect_tx.shared::cta.b64 _, [%0], %1;" ::"r"(a), "r"(bytes) : "memory");
}
__device__ __forceinline__ bool mbar_try(uint32_t a, uint32_t ph) {
    uint32_t ok;
    asm volatile(
        "{\n.reg .pred p;\nmbarrier.try_wait.parity.shared::cta.b64 p, [%1], %2;\nselp.u32 %0, 1, 0, p;\n}"
        : "=r"(ok)
        : "r"(a), "r"(ph)
        : "memory");
    return ok != 0;
}
__device__ __forceinline__ uint32_t clk32() {
    uint32_t c;
    asm volatile("mov.u32 %0, %%clock;" : "=r"(c));
    return c;
}
constexpr uint32_t WAIT_LIMIT = 1u << 30;
__device__ __forceinline__ void mbar_wait(uint32_t a, uint32_t ph) {
    if (mbar_try(a, ph)) return;
    uint32_t t0 = clk32();
    while (!mbar_try(a, ph)) {
        if (clk32() - t0 > WAIT_LIMIT) break;
    }
}
__device__ __forceinline__ void mbar_arrive_cluster(uint32_t a, uint32_t cta) {
    asm volatile(
        "{\n.reg .b32 ra;\nmapa.shared::cluster.u32 ra, %0, %1;\nmbarrier.arrive.shared::cluster.b64 _, [ra];\n}" ::"r"(a),
        "r"(cta)
        : "memory");
}
__device__ __forceinline__ void tma_mc(uint32_t dst, const CUtensorMap* m, int c0, int c1, uint32_t bar) {
    asm volatile(
        "cp.async.bulk.tensor.2d.shared::cluster.global.mbarrier::complete_tx::bytes.multicast::cluster"
        " [%0], [%1, {%3, %4}], [%2], %5;" ::"r"(dst),
        "l"(m), "r"(bar), "r"(c0), "r"(c1), "h"((uint16_t)3)
        : "memory");
}
__device__ __forceinline__ void bulk_load(uint32_t dst, const void* src, uint32_t bytes, uint32_t bar) {
    asm volatile("cp.async.bulk.shared::cluster.global.mbarrier::complete_tx::bytes [%0], [%1], %2, [%3];" ::"r"(dst),
                 "l"(src), "r"(bytes), "r"(bar)
                 : "memory");
}
__device__ __forceinline__ void l2_prefetch(const void* p, uint32_t bytes) {
    asm volatile("cp.async.bulk.prefetch.L2.global [%0], %1;" ::"l"(p), "r"(bytes) : "memory");
}
__device__ __forceinline__ void bar_sync(int id, int n) { asm volatile("bar.sync %0, %1;" ::"r"(id), "r"(n) : "memory"); }
__device__ __forceinline__ void bar_arrive(int id, int n) {
    asm volatile("bar.arrive %0, %1;" ::"r"(id), "r"(n) : "memory");
}
__device__ __forceinline__ void wg_fence() { asm volatile("wgmma.fence.sync.aligned;" ::: "memory"); }
__device__ __forceinline__ void wg_commit() { asm volatile("wgmma.commit_group.sync.aligned;" ::: "memory"); }
template <int N>
__device__ __forceinline__ void wg_wait() {
    asm volatile("wgmma.wait_group.sync.aligned %0;" ::"n"(N) : "memory");
}
template <int N>
__device__ __forceinline__ void pin(float (&d)[N]) {
#pragma unroll
    for (int i = 0; i < N; i++) asm volatile("" : "+f"(d[i])::"memory");
}
template <int N>
__device__ __forceinline__ void pin(uint32_t (&d)[N]) {
#pragma unroll
    for (int i = 0; i < N; i++) asm volatile("" : "+r"(d[i])::"memory");
}
__device__ __forceinline__ uint32_t pack_bf16(float lo, float hi) {
    uint32_t r;
    asm("cvt.rn.bf16x2.f32 %0, %1, %2;" : "=r"(r) : "f"(hi), "f"(lo));
    return r;
}
__device__ __forceinline__ float bf_lo(uint32_t v) { return __uint_as_float(v << 16); }
__device__ __forceinline__ float bf_hi(uint32_t v) { return __uint_as_float(v & 0xffff0000u); }
__device__ __forceinline__ float round_bf16(float v) { return __bfloat162float(__float2bfloat16_rn(v)); }
__device__ __forceinline__ float ex2(float x) {
    float y;
    asm("ex2.approx.ftz.f32 %0, %1;" : "=f"(y) : "f"(x));
    return y;
}
__device__ __forceinline__ float rcp(float x) {
    float y;
    asm("rcp.approx.ftz.f32 %0, %1;" : "=f"(y) : "f"(x));
    return y;
}
__device__ __forceinline__ float tanh_fast(float x) {
    float y;
    asm("tanh.approx.f32 %0, %1;" : "=f"(y) : "f"(x));
    return y;
}
__device__ __forceinline__ void sts128(uint32_t a, uint32_t x, uint32_t y, uint32_t z, uint32_t w) {
    asm volatile("st.shared.v4.b32 [%0], {%1,%2,%3,%4};" ::"r"(a), "r"(x), "r"(y), "r"(z), "r"(w) : "memory");
}
__device__ __forceinline__ void lds128(uint32_t a, uint32_t& x, uint32_t& y, uint32_t& z, uint32_t& w) {
    asm volatile("ld.shared.v4.b32 {%0,%1,%2,%3}, [%4];" : "=r"(x), "=r"(y), "=r"(z), "=r"(w) : "r"(a) : "memory");
}
__device__ __forceinline__ void sts32f(uint32_t a, float v) {
    asm volatile("st.shared.f32 [%0], %1;" ::"r"(a), "f"(v) : "memory");
}
__device__ __forceinline__ float lds32f(uint32_t a) {
    float v;
    asm volatile("ld.shared.f32 %0, [%1];" : "=f"(v) : "r"(a) : "memory");
    return v;
}
#define F8(d, b) \
    "+f"(d[b]), "+f"(d[b + 1]), "+f"(d[b + 2]), "+f"(d[b + 3]), "+f"(d[b + 4]), "+f"(d[b + 5]), "+f"(d[b + 6]), "+f"(d[b + 7])

template <int TB>
__device__ __forceinline__ void wgmma_n128(float (&d)[64], uint32_t a0, uint32_t a1, uint32_t a2, uint32_t a3,
                                           uint64_t db, int sc) {
    asm volatile(
        "{\n.reg .pred p;\nsetp.ne.b32 p, %69, 0;\n"
        "wgmma.mma_async.sync.aligned.m64n128k16.f32.bf16.bf16 "
        "{%0,%1,%2,%3,%4,%5,%6,%7,%8,%9,%10,%11,%12,%13,%14,%15,%16,%17,%18,%19,%20,%21,%22,%23,%24,%25,%26,%27,%28,%29,%30,%31,"
        "%32,%33,%34,%35,%36,%37,%38,%39,%40,%41,%42,%43,%44,%45,%46,%47,%48,%49,%50,%51,%52,%53,%54,%55,%56,%57,%58,%59,%60,%61,%62,%63},"
        "{%64,%65,%66,%67}, %68, p, 1, 1, %70;\n}"
        : F8(d, 0), F8(d, 8), F8(d, 16), F8(d, 24), F8(d, 32), F8(d, 40), F8(d, 48), F8(d, 56)
        : "r"(a0), "r"(a1), "r"(a2), "r"(a3), "l"(db), "r"(sc), "n"(TB));
}
#define O8(d, b) \
    "=f"(d[b]), "=f"(d[b + 1]), "=f"(d[b + 2]), "=f"(d[b + 3]), "=f"(d[b + 4]), "=f"(d[b + 5]), "=f"(d[b + 6]), "=f"(d[b + 7])
template <int TB>
__device__ __forceinline__ void wgmma_n128_z(float (&d)[64], uint32_t a0, uint32_t a1, uint32_t a2, uint32_t a3,
                                             uint64_t db) {
    asm volatile(
        "wgmma.mma_async.sync.aligned.m64n128k16.f32.bf16.bf16 "
        "{%0,%1,%2,%3,%4,%5,%6,%7,%8,%9,%10,%11,%12,%13,%14,%15,%16,%17,%18,%19,%20,%21,%22,%23,%24,%25,%26,%27,%28,%29,%30,%31,"
        "%32,%33,%34,%35,%36,%37,%38,%39,%40,%41,%42,%43,%44,%45,%46,%47,%48,%49,%50,%51,%52,%53,%54,%55,%56,%57,%58,%59,%60,%61,%62,%63},"
        "{%64,%65,%66,%67}, %68, 0, 1, 1, %69;"
        : O8(d, 0), O8(d, 8), O8(d, 16), O8(d, 24), O8(d, 32), O8(d, 40), O8(d, 48), O8(d, 56)
        : "r"(a0), "r"(a1), "r"(a2), "r"(a3), "l"(db), "n"(TB));
}
template <int TB>
__device__ __forceinline__ void wgmma_n64_z(float (&d)[32], uint32_t a0, uint32_t a1, uint32_t a2, uint32_t a3,
                                            uint64_t db) {
    asm volatile(
        "wgmma.mma_async.sync.aligned.m64n64k16.f32.bf16.bf16 "
        "{%0,%1,%2,%3,%4,%5,%6,%7,%8,%9,%10,%11,%12,%13,%14,%15,%16,%17,%18,%19,%20,%21,%22,%23,%24,%25,%26,%27,%28,%29,%30,%31},"
        "{%32,%33,%34,%35}, %36, 0, 1, 1, %37;"
        : O8(d, 0), O8(d, 8), O8(d, 16), O8(d, 24)
        : "r"(a0), "r"(a1), "r"(a2), "r"(a3), "l"(db), "n"(TB));
}
template <int TB>
__device__ __forceinline__ void wgmma_n64(float (&d)[32], uint32_t a0, uint32_t a1, uint32_t a2, uint32_t a3,
                                          uint64_t db) {
    asm volatile(
        "wgmma.mma_async.sync.aligned.m64n64k16.f32.bf16.bf16 "
        "{%0,%1,%2,%3,%4,%5,%6,%7,%8,%9,%10,%11,%12,%13,%14,%15,%16,%17,%18,%19,%20,%21,%22,%23,%24,%25,%26,%27,%28,%29,%30,%31},"
        "{%32,%33,%34,%35}, %36, 1, 1, 1, %37;"
        : F8(d, 0), F8(d, 8), F8(d, 16), F8(d, 24)
        : "r"(a0), "r"(a1), "r"(a2), "r"(a3), "l"(db), "n"(TB));
}

__device__ __forceinline__ uint64_t desc_of(uint32_t saddr) {
    return (uint64_t)(((saddr >> 4) & 0x3FFFu) | (512u << 16)) | ((uint64_t)(64u | (1u << 30)) << 32);
}

struct Ring {
    uint32_t slot;
    uint32_t phase;
    __device__ __forceinline__ void next() {
        if (++slot == 8) {
            slot = 0;
            phase ^= 1;
        }
    }
};

struct Ctx {
    uint32_t sbase;
    int wg;
    uint32_t rel_cta;
    __device__ __forceinline__ void wait_full(uint32_t slot, uint32_t phase) const {
        mbar_wait(sbase + OFF_FULL + slot * 8, phase);
    }
    __device__ __forceinline__ void release(uint32_t slot) const {
        if (rel_cta < 2) mbar_arrive_cluster(sbase + OFF_EMPTY + slot * 8, rel_cta);
    }
};

__device__ __forceinline__ void gemm_n128(float (&d)[64], const uint32_t (&a)[144], const Ctx& c, Ring& r, bool nine,
                                          bool early) {
    uint32_t prev = 0;
#pragma unroll
    for (int s = 0; s < 9; s++) {
        if (s < 8 || nine) {
            if (s == GATE_SLOT) {
                if (early) {
                    wg_wait<0>();
                    c.release(prev);
                }
                bar_sync(8 + c.wg, 256);
            }
            c.wait_full(r.slot, r.phase);
            uint64_t db = desc_of(c.sbase + r.slot * SLOT_BYTES);
            wg_fence();
#pragma unroll
            for (int k = 0; k < 4; k++) {
                if ((s | k) == 0)
                    wgmma_n128_z<1>(d, a[0], a[1], a[2], a[3], db);
                else
                    wgmma_n128<1>(d, a[s * 16 + k * 4], a[s * 16 + k * 4 + 1], a[s * 16 + k * 4 + 2],
                                  a[s * 16 + k * 4 + 3], db + k * 128, 1);
            }
            wg_commit();
            if (s == 8 || (s == 7 && !nine)) bar_arrive(9 - c.wg, 256);
            if (s > 0) {
                wg_wait<1>();
                if (s != GATE_SLOT || !early) c.release(prev);
            }
            prev = r.slot;
            r.next();
        }
    }
    wg_wait<0>();
    c.release(prev);
    pin(d);
}
__device__ __forceinline__ void gemm_n64(float (&d)[32], const uint32_t (&a)[144], const Ctx& c, Ring& r, bool nine) {
    uint32_t prev = 0;
#pragma unroll
    for (int s = 0; s < 5; s++) {
        if (s < 4 || nine) {
            c.wait_full(r.slot, r.phase);
            uint64_t db = desc_of(c.sbase + r.slot * SLOT_BYTES);
            wg_fence();
#pragma unroll
            for (int k = 0; k < 8; k++) {
                if ((s | k) == 0)
                    wgmma_n64_z<1>(d, a[0], a[1], a[2], a[3], db);
                else if (s * 8 + k < 36)
                    wgmma_n64<1>(d, a[s * 32 + k * 4], a[s * 32 + k * 4 + 1], a[s * 32 + k * 4 + 2],
                                 a[s * 32 + k * 4 + 3], db + k * 128);
            }
            wg_commit();
            if (s > 0) {
                wg_wait<1>();
                c.release(prev);
            }
            prev = r.slot;
            r.next();
        }
    }
    wg_wait<0>();
    c.release(prev);
    pin(d);
}
__device__ __forceinline__ void st128(uint4* p, uint32_t x, uint32_t y, uint32_t z, uint32_t w) {
    asm volatile(
        "{\n.reg .b64 lo, hi;\n.reg .b128 t;\nmov.b64 lo, {%1, %2};\nmov.b64 hi, {%3, %4};\nmov.b128 t, {lo, hi};\n"
        "st.relaxed.gpu.global.b128 [%0], t;\n}" ::"l"(p),
        "r"(x), "r"(y), "r"(z), "r"(w)
        : "memory");
}
__device__ __forceinline__ uint4 ld128(const uint4* p) {
    uint4 r;
    asm volatile(
        "{\n.reg .b64 lo, hi;\n.reg .b128 t;\nld.relaxed.gpu.global.b128 t, [%4];\nmov.b128 {lo, hi}, t;\n"
        "mov.b64 {%0, %1}, lo;\nmov.b64 {%2, %3}, hi;\n}"
        : "=r"(r.x), "=r"(r.y), "=r"(r.z), "=r"(r.w)
        : "l"(p));
    return r;
}
__device__ __forceinline__ uint4 ldg128(const uint4* p) {
    uint4 r;
    asm volatile("ld.global.nc.v4.u32 {%0,%1,%2,%3}, [%4];" : "=r"(r.x), "=r"(r.y), "=r"(r.z), "=r"(r.w) : "l"(p));
    return r;
}
__device__ __forceinline__ void st64(void* p, uint32_t x, uint32_t y) {
    asm volatile("{\n.reg .b64 t;\nmov.b64 t, {%1, %2};\nst.relaxed.gpu.global.b64 [%0], t;\n}" ::"l"(p), "r"(x), "r"(y)
                 : "memory");
}
__device__ __forceinline__ uint2 ld64(const void* p) {
    uint2 r;
    asm volatile("{\n.reg .b64 t;\nld.relaxed.gpu.global.b64 t, [%2];\nmov.b64 {%0, %1}, t;\n}"
                 : "=r"(r.x), "=r"(r.y)
                 : "l"(p));
    return r;
}
__device__ __forceinline__ void rows_load(uint32_t sbase, const CUtensorMap* m, int row0) {
    mbar_expect_tx(sbase + OFF_XBAR, 16 * DM * 2);
    asm volatile(
        "cp.async.bulk.tensor.3d.shared::cluster.global.mbarrier::complete_tx::bytes [%0], [%1, {%3, %3, %4}], [%2];" ::"r"(
            sbase + OFF_ROWS),
        "l"(m), "r"(sbase + OFF_XBAR), "r"(0), "r"(row0)
        : "memory");
}
__device__ __forceinline__ void rows_store(uint32_t sbase, const CUtensorMap* m, int row0) {
    asm volatile("cp.async.bulk.tensor.3d.global.shared::cta.bulk_group [%0, {%2, %2, %3}], [%1];" ::"l"(m),
                 "r"(sbase + OFF_ROWS), "r"(0), "r"(row0)
                 : "memory");
    asm volatile("cp.async.bulk.commit_group;" ::: "memory");
}
__device__ __forceinline__ void rows_store_wait() { asm volatile("cp.async.bulk.wait_group 0;" ::: "memory"); }

__device__ __forceinline__ constexpr int own_col(int j) { return j < 8 ? (j >> 1) * 128 + (j & 1) * 8 : 512; }
__device__ __forceinline__ void row_reduce(float& s0, float& s1, uint32_t red, int warp, int lane) {
    s0 += __shfl_xor_sync(0xffffffffu, s0, 1);
    s1 += __shfl_xor_sync(0xffffffffu, s1, 1);
    s0 += __shfl_xor_sync(0xffffffffu, s0, 2);
    s1 += __shfl_xor_sync(0xffffffffu, s1, 2);
    if ((lane & 3) == 0) {
        sts32f(red + (warp * 16 + (lane >> 2)) * 4, s0);
        sts32f(red + (warp * 16 + 8 + (lane >> 2)) * 4, s1);
    }
    bar_sync(3, 256);
    s0 = 0.f;
    s1 = 0.f;
#pragma unroll
    for (int w = 0; w < 8; w++) {
        s0 += lds32f(red + (w * 16 + (lane >> 2)) * 4);
        s1 += lds32f(red + (w * 16 + 8 + (lane >> 2)) * 4);
    }
}
template <class F>
__device__ __forceinline__ void layernorm_rows(float (&v)[36], uint32_t red, int warp, int lane, F&& middle) {
    float s0 = 0.f, s1 = 0.f;
#pragma unroll
    for (int j = 0; j < 9; j++) {
        s0 += v[4 * j] + v[4 * j + 1];
        s1 += v[4 * j + 2] + v[4 * j + 3];
    }
    row_reduce(s0, s1, red, warp, lane);
    middle();
    const float m0 = s0 * (1.f / DM), m1 = s1 * (1.f / DM);
    s0 = 0.f;
    s1 = 0.f;
#pragma unroll
    for (int j = 0; j < 9; j++) {
        v[4 * j] -= m0;
        v[4 * j + 1] -= m0;
        v[4 * j + 2] -= m1;
        v[4 * j + 3] -= m1;
        s0 += v[4 * j] * v[4 * j] + v[4 * j + 1] * v[4 * j + 1];
        s1 += v[4 * j + 2] * v[4 * j + 2] + v[4 * j + 3] * v[4 * j + 3];
    }
    row_reduce(s0, s1, red + 512, warp, lane);
    const float r0 = rsqrtf(s0 * (1.f / DM) + 1e-5f), r1 = rsqrtf(s1 * (1.f / DM) + 1e-5f);
#pragma unroll
    for (int j = 0; j < 9; j++) {
        v[4 * j] *= r0;
        v[4 * j + 1] *= r0;
        v[4 * j + 2] *= r1;
        v[4 * j + 3] *= r1;
    }
}
__device__ __forceinline__ void mod_to_smem(uint32_t dst, const uint32_t* src, uint32_t tag) {
    const uint32_t t0 = clk32();
    uint4 u;
    while (true) {
        u = ld128(reinterpret_cast<const uint4*>(src));
        const uint32_t bad = ((u.x ^ tag) | (u.y ^ tag) | (u.z ^ tag) | (u.w ^ tag)) & 0xffffu;
        if (__all_sync(0xffffffffu, bad == 0) || clk32() - t0 > WAIT_LIMIT) break;
        __nanosleep(64);
    }
    sts128(dst, u.x & 0xffff0000u, u.y & 0xffff0000u, u.z & 0xffff0000u, u.w & 0xffff0000u);
}
__device__ __forceinline__ void lds_mod(float (&m)[18], uint32_t src  , int warp) {
#pragma unroll
    for (int j = 0; j < 9; j++)
        asm volatile("ld.shared.v2.f32 {%0,%1}, [%2];"
                     : "=f"(m[2 * j]), "=f"(m[2 * j + 1])
                     : "r"(src + own_col(j) * 4 - (j == 8 ? warp * 32 : 0))
                     : "memory");
}
__device__ __forceinline__ void modulate_store(const float (&v)[36], const float (&shift)[18], const float (&scale)[18],
                                               float post, uint4* hbuf  , int warp, int lane) {
    uint32_t o[18];
#pragma unroll
    for (int j = 0; j < 9; j++) {
        const uint32_t cc = pack_bf16(1.f + scale[2 * j], 1.f + scale[2 * j + 1]);
        const float c0 = bf_lo(cc) * post, c1 = bf_hi(cc) * post, s0 = shift[2 * j] * post, s1 = shift[2 * j + 1] * post;
        o[2 * j] = pack_bf16(fmaf(v[4 * j], c0, s0), fmaf(v[4 * j + 1], c1, s1));
        o[2 * j + 1] = pack_bf16(fmaf(v[4 * j + 2], c0, s0), fmaf(v[4 * j + 3], c1, s1));
        if ((j & 1) == 0) o[2 * j] = max(o[2 * j], 1u);
    }
#pragma unroll
    for (int i = 0; i < 4; i++) st128(hbuf + (i * 8 + warp) * 32 + lane, o[4 * i], o[4 * i + 1], o[4 * i + 2], o[4 * i + 3]);
    st64(reinterpret_cast<uint2*>(hbuf + 32 * 32) + warp * 32 + lane, o[16], o[17]);
}
__device__ __forceinline__ void sum_partials(float (&v)[36], const uint4* src  , uint32_t tag) {
    const uint32_t t0 = clk32();
    while (true) {
        uint4 t[8][4];
#pragma unroll
        for (int s = 0; s < 8; s++)
#pragma unroll
            for (int i = 0; i < 4; i++) t[s][i] = ld128(src + (s * 36 + i * 8) * 32);
        uint32_t bad = 0;
#pragma unroll
        for (int i = 0; i < 32; i++) v[i] = 0.f;
#pragma unroll
        for (int s = 0; s < 8; s++)
#pragma unroll
            for (int i = 0; i < 4; i++) {
                bad |= t[s][i].x ^ tag;
                v[8 * i] += bf_lo(t[s][i].x);
                v[8 * i + 1] += bf_hi(t[s][i].x);
                v[8 * i + 2] += bf_lo(t[s][i].y);
                v[8 * i + 3] += bf_hi(t[s][i].y);
                v[8 * i + 4] += bf_lo(t[s][i].z);
                v[8 * i + 5] += bf_hi(t[s][i].z);
                v[8 * i + 6] += bf_lo(t[s][i].w);
                v[8 * i + 7] += bf_hi(t[s][i].w);
                asm volatile("" : "+r"(bad));
            }
#pragma unroll
        for (int i = 0; i < 32; i++) asm volatile("" : "+f"(v[i]));
        if (__all_sync(0xffffffffu, (bad & 1u) == 0) || clk32() - t0 > WAIT_LIMIT) break;
    }
}
__device__ __forceinline__ void sum_tail(float (&v)[36], const uint2* src  , uint32_t tag) {
    const uint32_t t0 = clk32();
    while (true) {
        uint2 t[8];
#pragma unroll
        for (int s = 0; s < 8; s++) t[s] = ld64(src + s * 72 * 32);
        uint32_t bad = 0;
        v[32] = v[33] = v[34] = v[35] = 0.f;
#pragma unroll
        for (int s = 0; s < 8; s++) {
            bad |= t[s].x ^ tag;
            v[32] += bf_lo(t[s].x);
            v[33] += bf_hi(t[s].x);
            v[34] += bf_lo(t[s].y);
            v[35] += bf_hi(t[s].y);
        }
        if (__all_sync(0xffffffffu, (bad & 1u) == 0) || clk32() - t0 > WAIT_LIMIT) break;
    }
}
__device__ __forceinline__ void poll_tail(uint32_t (&a)[144], const uint2* src  ) {
    const uint32_t t0 = clk32();
    while (true) {
        uint32_t m = 0xffffffffu;
#pragma unroll
        for (int j = 0; j < 8; j++) {
            const uint2 t = ld64(src + j * 32);
            a[128 + 2 * j] = t.x;
            a[129 + 2 * j] = t.y;
        }
#pragma unroll
        for (int j = 0; j < 8; j++) m = min(m, a[128 + 2 * j]);
        if (__all_sync(0xffffffffu, m != 0) || clk32() - t0 > WAIT_LIMIT) break;
    }
}
template <int K0, int K1>
__device__ __forceinline__ void poll_frags(uint32_t (&a)[144], const uint4* src  , bool kick) {
    const uint32_t t0 = clk32();
    while (true) {
#pragma unroll
        for (int k = K0; k < K1; k++) {
            const uint4 t = ld128(src + k * 32);
            a[4 * k] = t.x;
            a[4 * k + 1] = t.y;
            a[4 * k + 2] = t.z;
            a[4 * k + 3] = t.w;
        }
        if (kick) bar_arrive(5, 256);
        kick = false;
        uint32_t m0 = a[4 * K0], m1 = a[4 * K0 + 4];
#pragma unroll
        for (int k = K0 + 2; k < K1; k += 2) {
            m0 = min(m0, a[4 * k]);
            m1 = min(m1, a[4 * k + 4]);
        }
        if (__all_sync(0xffffffffu, min(m0, m1) != 0) || clk32() - t0 > WAIT_LIMIT) break;
    }
}

constexpr float SM_SCALE = 0.08838834764831845f * 1.4426950408889634f;
constexpr float SM_HI = 1.2089258e24f;
constexpr float SM_LO = 9.0949470e-13f;
__device__ __forceinline__ void qk_step(float (&s)[32], const uint32_t (&q)[32], uint64_t dk) {
#pragma unroll
    for (int k = 0; k < 8; k++) {
        if (k == 0)
            wgmma_n64_z<0>(s, q[0], q[1], q[2], q[3], dk);
        else
            wgmma_n64<0>(s, q[4 * k], q[4 * k + 1], q[4 * k + 2], q[4 * k + 3], dk + (k >> 2) * 512 + (k & 3) * 2);
    }
}
__device__ __forceinline__ void pv_step(float (&o)[64], const uint32_t (&p)[16], uint64_t dv, int acc) {
#pragma unroll
    for (int k = 0; k < 4; k++)
        wgmma_n128<1>(o, p[4 * k], p[4 * k + 1], p[4 * k + 2], p[4 * k + 3], dv + k * 128, k != 0 ? 1 : acc);
}
template <bool SHIFT>
__device__ __forceinline__ void exp_step(const float (&s)[32], uint32_t (&p)[16], float n0, float n1, float& s0,
                                         float& s1) {
#pragma unroll
    for (int i = 0; i < 8; i++) {
        const float e0 = ex2(SHIFT ? s[4 * i] + n0 : s[4 * i]), e1 = ex2(SHIFT ? s[4 * i + 1] + n0 : s[4 * i + 1]);
        const float e2 = ex2(SHIFT ? s[4 * i + 2] + n1 : s[4 * i + 2]), e3 = ex2(SHIFT ? s[4 * i + 3] + n1 : s[4 * i + 3]);
        if (i == 0) {
            s0 = e0;
            s1 = e2;
        } else {
            s0 += e0;
            s1 += e2;
        }
        s0 += e1;
        s1 += e3;
        p[2 * i] = pack_bf16(e0, e1);
        p[2 * i + 1] = pack_bf16(e2, e3);
    }
}
__device__ __forceinline__ void row_max(const float (&sa)[32], const float (&sb)[32], float& x0, float& x1) {
    float xa[8];
#pragma unroll
    for (int i = 0; i < 8; i++) xa[i] = fmaxf(sa[i], sb[i]);
#pragma unroll
    for (int k = 1; k < 4; k++)
#pragma unroll
        for (int i = 0; i < 8; i++) xa[i] = fmaxf(xa[i], fmaxf(sa[8 * k + i], sb[8 * k + i]));
    x0 = fmaxf(fmaxf(xa[0], xa[1]), fmaxf(xa[4], xa[5]));
    x1 = fmaxf(fmaxf(xa[2], xa[3]), fmaxf(xa[6], xa[7]));
    x0 = fmaxf(x0, __shfl_xor_sync(0xffffffffu, x0, 1));
    x1 = fmaxf(x1, __shfl_xor_sync(0xffffffffu, x1, 1));
    x0 = fmaxf(x0, __shfl_xor_sync(0xffffffffu, x0, 2));
    x1 = fmaxf(x1, __shfl_xor_sync(0xffffffffu, x1, 2));
}
__device__ __forceinline__ void inv_row_sums(float l0, float l1, float& i0, float& i1) {
    l0 += __shfl_xor_sync(0xffffffffu, l0, 1);
    l1 += __shfl_xor_sync(0xffffffffu, l1, 1);
    l0 += __shfl_xor_sync(0xffffffffu, l0, 2);
    l1 += __shfl_xor_sync(0xffffffffu, l1, 2);
    i0 = rcp(l0);
    i1 = rcp(l1);
}

__device__ __forceinline__ uint32_t get_epoch(uint32_t sbase) { return __float_as_uint(lds32f(sbase + OFF_EPOCH)); }
__device__ __forceinline__ float silu_bf16(unsigned short c) {
    const float cv = bf_lo(c);
    return round_bf16(cv * rcp(1.f + ex2(-1.4426950408889634f * cv)));
}
__device__ __forceinline__ void st_mod(uint32_t* p, float v, uint32_t tag) {
    asm volatile("st.relaxed.gpu.global.u32 [%0], %1;" ::"l"(p), "r"(__float_as_uint(round_bf16(v)) | tag)
                 : "memory");
}
__device__ __forceinline__ void fma8(float (&acc)[8], float sc, const uint4& w) {
    acc[0] = fmaf(sc, bf_lo(w.x), acc[0]);
    acc[1] = fmaf(sc, bf_hi(w.x), acc[1]);
    acc[2] = fmaf(sc, bf_lo(w.y), acc[2]);
    acc[3] = fmaf(sc, bf_hi(w.y), acc[3]);
    acc[4] = fmaf(sc, bf_lo(w.z), acc[4]);
    acc[5] = fmaf(sc, bf_hi(w.z), acc[5]);
    acc[6] = fmaf(sc, bf_lo(w.w), acc[6]);
    acc[7] = fmaf(sc, bf_hi(w.w), acc[7]);
}
__device__ __forceinline__ void modp_load(uint4 (&u)[3], const uint32_t* src) {
#pragma unroll
    for (int i = 0; i < 3; i++) u[i] = ld128(reinterpret_cast<const uint4*>(src + i * 2 * DM));
}
__device__ __forceinline__ void modp_to_smem(uint4 (&u)[3], uint32_t dst, const uint32_t* src, uint32_t tag) {
    const uint32_t t0 = clk32();
    while (true) {
        uint32_t bad = 0;
#pragma unroll
        for (int i = 0; i < 3; i++) bad |= (u[i].x ^ tag) | (u[i].y ^ tag) | (u[i].z ^ tag) | (u[i].w ^ tag);
        if (__all_sync(0xffffffffu, (bad & 0xffu) == 0) || clk32() - t0 > WAIT_LIMIT) break;
        modp_load(u, src);
    }
    float s0 = 0.f, s1 = 0.f, s2 = 0.f, s3 = 0.f;
#pragma unroll
    for (int i = 0; i < 3; i++) {
        s0 += __uint_as_float(u[i].x & ~0xffu);
        s1 += __uint_as_float(u[i].y & ~0xffu);
        s2 += __uint_as_float(u[i].z & ~0xffu);
        s3 += __uint_as_float(u[i].w & ~0xffu);
    }
    const uint32_t p0 = pack_bf16(s0, s1), p1 = pack_bf16(s2, s3);
    sts128(dst, p0 << 16, p0 & 0xffff0000u, p1 << 16, p1 & 0xffff0000u);
}

__global__ void __cluster_dims__(2, 1, 1) __launch_bounds__(384, 1)
    fused_block_kernel(const __grid_constant__ Params maps) {
    extern __shared__ uint8_t smem_raw[];
    uint32_t sbase = (smem_u32(smem_raw) + 1023u) & ~1023u;
    asm volatile("" : "+r"(sbase));
    const int b = blockIdx.x;
    const int rank = b & 1;
    const int mt = ((b >> 1) & 7) * 2 + rank;
    const int g = b >> 4;
    const int warp = __shfl_sync(0xffffffffu, threadIdx.x >> 5, 0);
    const int lane = threadIdx.x & 31;
    Scratch* const sc_ = maps.sc;
    const __nv_bfloat16* const wmod = maps.wmod;
    const __nv_bfloat16* const cvec = maps.cvec;

#define SPROF(i)

    if (warp >= 8) {
        asm volatile("setmaxnreg.dec.sync.aligned.u32 24;");
        if (warp == 8 && lane == 0) {
#pragma unroll
            for (int i = 0; i < 8; i++) {
                mbar_init(sbase + OFF_FULL + i * 8, 1);
                mbar_init(sbase + OFF_EMPTY + i * 8, 4);
            }
            mbar_init(sbase + OFF_XBAR, 1);
            mbar_init(sbase + OFF_GBAR, 8);
            asm volatile("fence.mbarrier_init.release.cluster;" ::: "memory");
            asm volatile("barrier.cluster.arrive.relaxed;\nbarrier.cluster.wait;" ::: "memory");
            uint32_t slot = 0, phase = 1;
            const uint32_t dst0 = sbase + rank * BOX_BYTES;
            auto acquire = [&](uint32_t bytes) {
                mbar_wait(sbase + OFF_EMPTY + slot * 8, phase);
                mbar_expect_tx(sbase + OFF_FULL + slot * 8, bytes);
            };
            auto adv8 = [&]() {
                if (++slot == 8) {
                    slot = 0;
                    phase ^= 1;
                }
            };
#pragma unroll 1
            for (int hq = 0; hq < 4; hq++) {
                const int col = (g * 4 + ((hq + 1) & 3)) * 128 + rank * 64;
                if (hq == 2) {
                    l2_prefetch(maps.kc + (size_t)(g * 4 * 2048 + (b & 15) * 64) * 128, SLOT_BYTES);
                    l2_prefetch(maps.vc + (size_t)(g * 4 * 2048 + (b & 15) * 64) * 128, SLOT_BYTES);
                }
#pragma unroll 1
                for (int kc = 0; kc < 9; kc++) {
                    acquire(SLOT_BYTES);
                    tma_mc(dst0 + slot * SLOT_BYTES, &maps.wq, col, kc * 64, sbase + OFF_FULL + slot * 8);
                    adv8();
                }
            }
            const int row0 = g * 4 * 2048;
#pragma unroll 1
            for (int n = 0; n < 128; n++) {
                if (n < 4) mbar_wait(sbase + OFF_EMPTY + (slot + 1) * 8, phase);
                acquire(2 * SLOT_BYTES);
                const uint32_t bar = sbase + OFF_FULL + slot * 8;
                const int r0 = n == 0 ? 0 : (n == 127 ? 126 : n + 1);
                const int r1 = n == 0 ? 1 : (n == 127 ? 127 : n - 1);
                tma_mc(dst0 + slot * SLOT_BYTES, n == 127 ? &maps.v : &maps.k, rank * 64, row0 + r0 * 64, bar);
                tma_mc(dst0 + (slot + 1) * SLOT_BYTES, n == 0 ? &maps.k : &maps.v, rank * 64, row0 + r1 * 64, bar);
                adv8();
                adv8();
                const int u = n + KV_AHEAD;
                if (u < 128 && (u & 15) == (b & 15)) {
                    l2_prefetch(maps.kc + (size_t)(row0 + u * 64) * 128, SLOT_BYTES);
                    l2_prefetch(maps.vc + (size_t)(row0 + u * 64) * 128, SLOT_BYTES);
                }
            }
#pragma unroll 1
            for (int p = 0; p < 4; p++)
#pragma unroll 1
                for (int kc = 0; kc < 8; kc++) {
                    acquire(SLOT_BYTES);
                    tma_mc(dst0 + slot * SLOT_BYTES, &maps.wo, p * 128 + rank * 64, g * 512 + ((kc + 6) & 7) * 64,
                           sbase + OFF_FULL + slot * 8);
                    adv8();
                }
#pragma unroll 1
            for (int kc = 0; kc < 4; kc++) {
                acquire(SLOT_BYTES);
                tma_mc(dst0 + slot * SLOT_BYTES, &maps.wo, 512, g * 512 + ((kc + 3) & 3) * 128 + rank * 64,
                       sbase + OFF_FULL + slot * 8);
                adv8();
            }
            mbar_wait(sbase + OFF_GBAR, 0);
            const CUtensorMap* mg = rank ? &maps.wu : &maps.wg;
#pragma unroll 1
            for (int ch = 0; ch < 9; ch++)
#pragma unroll 1
                for (int kc = 0; kc < 9; kc++) {
                    acquire(SLOT_BYTES);
                    tma_mc(dst0 + slot * SLOT_BYTES, mg, g * 576 + ch * 64, kc * 64, sbase + OFF_FULL + slot * 8);
                    adv8();
                }
#pragma unroll 1
            for (int p = 0; p < 4; p++)
#pragma unroll 1
                for (int i = 0; i < 9; i++) {
                    acquire(SLOT_BYTES);
                    tma_mc(dst0 + slot * SLOT_BYTES, &maps.wd, p * 128 + rank * 64,
                           g * 576 + (i == 0 ? 8 : (i < 7 ? i + 1 : i - 7)) * 64, sbase + OFF_FULL + slot * 8);
                    adv8();
                }
#pragma unroll 1
            for (int i2 = 0; i2 < 5; i2++) {
                acquire(i2 < 4 ? SLOT_BYTES : BOX_BYTES);
                const int i = 2 * i2 + rank;
                if (i < 9)
                    tma_mc(dst0 + slot * SLOT_BYTES, &maps.wd, 512, g * 576 + (i == 0 ? 8 : (i < 7 ? i + 1 : i - 7)) * 64,
                           sbase + OFF_FULL + slot * 8);
                adv8();
            }
        } else if (warp == 11) {
            asm volatile("barrier.cluster.arrive.relaxed.aligned;" ::: "memory");
            bar_sync(6, 160);
            uint4* hz = sc_->h[(get_epoch(sbase) & 1) ^ 1][0] + (size_t)b * 72 * 32 + lane;
#pragma unroll 1
            for (int i = 0; i < 72; i++) {
                hz[i * 32] = make_uint4(0, 0, 0, 0);
                __nanosleep(200);
            }
            bar_sync(6, 160);
            if (lane == 0) {
#pragma unroll 1
                for (int i = 0; i < 9; i++) {
                    l2_prefetch((const char*)maps.wo_p + (size_t)b * 36864 + i * 4096, 4096);
                    __nanosleep(400);
                    l2_prefetch((const char*)maps.wg_p + (size_t)b * 41472 + i * 4608, 4608);
                    __nanosleep(400);
                    l2_prefetch((const char*)maps.wu_p + (size_t)b * 41472 + i * 4608, 4608);
                    __nanosleep(400);
                    l2_prefetch((const char*)maps.wd_p + (size_t)b * 41472 + i * 4608, 4608);
                    __nanosleep(400);
                }
            }
        } else if (warp == 9 || warp == 10) {
            asm volatile("barrier.cluster.arrive.relaxed.aligned;" ::: "memory");
            if (warp == 10) {
                bar_sync(11, 288);
                if (lane < 9) l2_prefetch((const char*)maps.wq_p + (size_t)b * 36864 + lane * 4096, 4096);
                __syncwarp();
            }
            bar_sync(4, 320);
            const uint32_t tag = (get_epoch(sbase) + 1) & 0xffffu;
            const int blk = warp == 9 ? 72 + b : 200 + b;
            if (blk < 216) {
                float acc[8];
#pragma unroll
                for (int e = 0; e < 8; e++) acc[e] = 0.f;
                const uint4* wp = reinterpret_cast<const uint4*>(wmod + (size_t)(lane >> 1) * (6 * DM) + blk * 16) + (lane & 1);
                const unsigned short* cp = reinterpret_cast<const unsigned short*>(cvec) + (lane >> 1);
#pragma unroll 1
                for (int i = 0; i < 36; i++) {
                    const uint4 w = __ldg(wp + (size_t)i * (16 * 6 * DM / 8));
                    const float sc = silu_bf16(__ldg(cp + i * 16));
                    fma8(acc, sc, w);
                }
#pragma unroll
                for (int o = 2; o < 32; o <<= 1)
#pragma unroll
                    for (int e = 0; e < 8; e++) acc[e] += __shfl_xor_sync(0xffffffffu, acc[e], o);
                if (lane < 2) {
#pragma unroll
                    for (int e = 0; e < 8; e++) st_mod(sc_->mod + blk * 16 + lane * 8 + e, acc[e], tag);
                }
            }
            if (warp == 9) {
#pragma unroll 1
                for (int st = 1; st <= 2; st++) {
                    bar_sync(7, 160);
                    const uint32_t* src = sc_->mod + (st * 3 - 1) * DM;
                    const int n = st == 1 ? 3 * DM : DM;
#pragma unroll 1
                    for (int i = lane * 4; i < n + 127 - ((n + 127) & 127); i += 128)
                        mod_to_smem(sbase + OFF_MODT + min(i, n - 4) * 4, src + min(i, n - 4), tag);
                    __syncwarp();
                    if (lane == 0) rows_load(sbase, st == 1 ? &maps.rx : &maps.rx2, (mt * 8 + g) * 16);
                    if (st == 1) {
                        bar_sync(7, 160);
                        if (lane == 0) {
                            rows_store(sbase, &maps.rx2, (mt * 8 + g) * 16);
                            rows_store_wait();
                        }
                        __syncwarp();
                        bar_arrive(10, 160);
                    }
                }
            }
        }
    } else {
        uint4 w1[3], xw[5], ew = make_uint4(0, 0, 0, 0);
        unsigned short cu[3];
        {
            const int t = threadIdx.x, bw = min(b, 107);
            const int row = (bw / 36) * 192 + (t >> 2);
#pragma unroll
            for (int i = 0; i < 3; i++) {
                w1[i] = ldg128(reinterpret_cast<const uint4*>(wmod + (size_t)(row + 64 * i) * (6 * DM)) + (bw % 36) * 4 + (t & 3));
                asm volatile("ld.global.nc.u16 %0, [%1];" : "=h"(cu[i]) : "l"(cvec + row + 64 * i));
            }
            if (t == 0) ew = ld128(reinterpret_cast<const uint4*>(&sc_->epoch[b * 32]));
        }
        if (threadIdx.x == 160) SPROF(5);
        asm volatile("setmaxnreg.inc.sync.aligned.u32 240;");
        if (threadIdx.x == 160) SPROF(6);
        const int wg = warp >> 2;
        const int tid = threadIdx.x;
        Ctx cx;
        cx.sbase = sbase;
        cx.wg = wg;
        if (wg == 1) bar_arrive(8, 256);
        cx.rel_cta = (lane == 0 && (warp & 3) < 2) ? (warp & 3) : 2;
        const uint32_t red = sbase + OFF_RED;
        const int own = mt * 8 + g;
        const int wown = mt * 8 + warp;
        PROF(0);
        PROFG(30);
        PROFR(17);
        {
            float acc[8];
#pragma unroll
            for (int e = 0; e < 8; e++) acc[e] = 0.f;
#pragma unroll
            for (int i = 0; i < 3; i++) fma8(acc, silu_bf16(cu[i]), w1[i]);
            {
                int off = tid;
                asm volatile("{\n.reg .pred p;\nsetp.gt.f32 p, %1, 0f00000000;\n@p add.s32 %0, %0, %2;\n}"
                             : "+r"(off)
                             : "f"(acc[7]), "r"((int)gridDim.y - 1));
#pragma unroll
                for (int i = 0; i < 5; i++)
                    xw[i] = ldg128(reinterpret_cast<const uint4*>(maps.x + (size_t)own * 16 * DM) + min(off + 256 * i, 1151));
                asm volatile("barrier.cluster.arrive.relaxed.aligned;" ::: "memory");
            }
#pragma unroll
            for (int o = 4; o < 32; o <<= 1)
#pragma unroll
                for (int e = 0; e < 8; e++) acc[e] += __shfl_xor_sync(0xffffffffu, acc[e], o);
            PROFR(19);
            if (lane < 4) {
                const uint32_t dst = sbase + OFF_MRED + warp * 128 + lane * 32;
                sts128(dst, __float_as_uint(acc[0]), __float_as_uint(acc[1]), __float_as_uint(acc[2]), __float_as_uint(acc[3]));
                sts128(dst + 16, __float_as_uint(acc[4]), __float_as_uint(acc[5]), __float_as_uint(acc[6]), __float_as_uint(acc[7]));
            }
            if (tid == 0) sts128(sbase + OFF_EPOCH, ew.x, ew.y, ew.z, ew.w);
            bar_sync(3, 256);
            PROFR(20);
            if (tid < 32 && b < 108) {
                float sum = 0.f;
#pragma unroll
                for (int w8 = 0; w8 < 8; w8++) sum += lds32f(sbase + OFF_MRED + w8 * 128 + tid * 4);
                asm volatile("st.relaxed.gpu.global.u32 [%0], %1;" ::"l"(&sc_->modp[b / 36][(b % 36) * 32 + tid]),
                             "r"((__float_as_uint(sum) & ~0xffu) | ((get_epoch(sbase) + 1) & 0xffu))
                             : "memory");
            }
            PROFR(21);
#pragma unroll
            for (int i = 0; i < 5; i++) {
                const int vi = min(tid + 256 * i, 1151), ln = vi >> 3;
                sts128(sbase + OFF_ROWS + ln * 128 + (((vi & 7) ^ (ln & 7)) << 4), xw[i].x, xw[i].y, xw[i].z, xw[i].w);
            }
            bar_sync(3, 256);
            bar_arrive(11, 288);
        }

        Ring ring{0u, 0u};
        int stage = 0;
        asm volatile("" : "+r"(stage));
#pragma unroll 1
        for (;; stage++) {
            int tid, lane;
            asm volatile("mov.u32 %0, %%tid.x;" : "=r"(tid));
            lane = tid & 31;
            const uint32_t epoch = get_epoch(sbase);
            {
                float v[36];
                const uint32_t modt = sbase + OFF_MODT + (warp * 16 + (lane & 3) * 2) * 4;
                if (stage == 0) {
#pragma unroll
                    for (int i = 0; i < 36; i++) v[i] = 0.f;
                } else {
                    const uint4* psrc = sc_->part + (size_t)own * 8 * 36 * 32;
                    sum_partials(v, psrc + tid, stage & 1);
                    PROF(stage == 1 ? 8 : 15);
                    if (lane == 0) asm volatile("mbarrier.arrive.shared::cta.b64 _, [%0];" ::"r"(sbase + OFF_GBAR) : "memory");
                    sum_tail(v, reinterpret_cast<const uint2*>(psrc + 32 * 32) + tid, stage & 1);
                }
                if (stage) mbar_wait(sbase + OFF_XBAR, stage - 1);
                if (stage == 0) PROFR(22);
                {
                    const float gs = stage == 2 ? 0.5f : 1.f;
                    float gate[18];
                    lds_mod(gate, modt, warp);
                    const int r = lane >> 2;
                    const uint32_t rows = sbase + OFF_ROWS + r * (DM * 2) + (lane & 3) * 4;
#pragma unroll
                    for (int j = 0; j < 9; j++) {
                        const int ch = j < 8 ? (j >> 1) * 2 + (warp >> 2) : 8, c16 = j < 8 ? (warp & 3) * 2 + (j & 1) : warp;
                        const uint32_t ad = rows + ch * 128 + ((c16 ^ ((r + ch) & 7)) << 4);
                        const uint32_t u0 = __float_as_uint(lds32f(ad)), u1 = __float_as_uint(lds32f(ad + 8 * DM * 2));
                        const float g0 = stage ? gate[2 * j] * gs : 0.f, g1 = stage ? gate[2 * j + 1] * gs : 0.f;
                        v[4 * j] = fmaf(g0, v[4 * j], bf_lo(u0));
                        v[4 * j + 1] = fmaf(g1, v[4 * j + 1], bf_hi(u0));
                        v[4 * j + 2] = fmaf(g0, v[4 * j + 2], bf_lo(u1));
                        v[4 * j + 3] = fmaf(g1, v[4 * j + 3], bf_hi(u1));
                        sts32f(ad, __uint_as_float(pack_bf16(v[4 * j], v[4 * j + 1])));
                        sts32f(ad + 8 * DM * 2, __uint_as_float(pack_bf16(v[4 * j + 2], v[4 * j + 3])));
                    }
                    asm volatile("fence.proxy.async.shared::cta;" ::: "memory");
                }
                if (stage == 2) break;
                PROF(stage == 0 ? 1 : 9);
                uint4 ua[3], ub[3];
#pragma unroll
                for (int i = 0; i < 3; i++) ua[i] = ub[i] = make_uint4(0, 0, 0, 0);
                layernorm_rows(v, red, warp, lane, [&]() {
                    if (stage == 0) {
                        modp_load(ua, sc_->modp[0] + tid * 4);
                        if (warp == 0) modp_load(ub, sc_->modp[0] + 1024 + tid * 4);
                    }
                });
                if (stage == 0) PROFR(27);
                if (stage == 0) {
                    const uint32_t tag = (epoch + 1) & 0xffu;
                    modp_to_smem(ua, sbase + OFF_MODT + (DM + tid * 4) * 4, sc_->modp[0] + tid * 4, tag);
                    if (warp == 0)
                        modp_to_smem(ub, sbase + OFF_MODT + (DM + 1024 + tid * 4) * 4, sc_->modp[0] + 1024 + tid * 4, tag);
                    bar_sync(3, 256);
                }
                float shift[18], scale[18];
                lds_mod(shift, modt + DM * 4, warp);
                lds_mod(scale, modt + 2 * DM * 4, warp);
                if (stage == 0) PROFR(28);
                PROF(stage == 0 ? 2 : 10);
                modulate_store(v, shift, scale, stage == 0 ? SM_SCALE : 1.f, sc_->h[epoch & 1][stage] + (size_t)own * 36 * 32, warp, lane);
                if (stage == 0) asm volatile("barrier.cluster.wait.aligned;" ::: "memory");
            }

            const uint32_t spill = sbase + 8 * SLOT_BYTES + wg * 3 * SLOT_BYTES + (tid & 127) * 16;
            uint32_t a[144];
            PROF(stage == 0 ? 3 : 11);
            {
                const uint4* hsrc = sc_->h[epoch & 1][stage] + (size_t)wown * 36 * 32 + lane;
                __nanosleep(stage == 0 ? PROBE0_NS : PROBE_NS);
                poll_tail(a, reinterpret_cast<const uint2*>(hsrc - lane + 32 * 32) + lane);
                PROF(stage == 0 ? 4 : 12);
                if (stage == 1) PROFG(25);
                TG(stage * 32 + 30);
                if (wg == 1) bar_sync(5, 256);
                poll_frags<0, 32>(a, hsrc, wg == 0);
                if (stage == 0) bar_arrive(4, 320);
            }
            uint4* hhbuf = sc_->hh + (size_t)b * 8 * 256 + tid;
            float d[64];
#pragma unroll 1
            for (int ch = 0;; ch++) {
                TG(stage * 32 + ch * 2);
                gemm_n128(d, a, cx, ring, true, stage && wg);
                TG(stage * 32 + ch * 2 + 1);
                if (stage == 0) {
                    if (ch == 3) break;
#pragma unroll
                    for (int v = 0; v < 8; v++)
                        sts128(spill + (ch * 8 + v) * 2048, pack_bf16(d[8 * v], d[8 * v + 1]),
                               pack_bf16(d[8 * v + 2], d[8 * v + 3]), pack_bf16(d[8 * v + 4], d[8 * v + 5]),
                               pack_bf16(d[8 * v + 6], d[8 * v + 7]));
                } else {
#pragma unroll
                    for (int i = 0; i < 32; i++) {
                        const float gv = d[i], gu = gv * d[32 + i];
                        const float z = gv * fmaf(gv * gv, 0.7978845608028654f * 0.044715f, 0.7978845608028654f);
                        d[i] = fmaf(gu, tanh_fast(z), gu);
                    }
                    if (ch == 8) break;
                    if (wg == 0) {
                        if (ch == 0) bar_arrive(7, 160);
                        if (ch == 2) bar_sync(10, 160);
                    }
#pragma unroll
                    for (int v = 0; v < 4; v++) {
                        const uint4 h4 = make_uint4(pack_bf16(d[8 * v], d[8 * v + 1]), pack_bf16(d[8 * v + 2], d[8 * v + 3]),
                                                    pack_bf16(d[8 * v + 4], d[8 * v + 5]), pack_bf16(d[8 * v + 6], d[8 * v + 7]));
                        if (ch < 2)
                            __stcg(hhbuf + (ch * 4 + v) * 256, h4);
                        else
                            sts128(spill + ((ch - 2) * 4 + v) * 2048, h4.x, h4.y, h4.z, h4.w);
                    }
                }
            }
            if (stage == 0) {
                uint32_t q[32];
#pragma unroll
                for (int i = 0; i < 32; i++) q[i] = pack_bf16(d[2 * i], d[2 * i + 1]);
                PROF(5);
                PROFG(23);
                if (wg == 0) bar_arrive(6, 160);
                {
                    float o[64], sa[32], sb[32];
                    uint32_t pa[16], pb[16];
#pragma unroll
                    for (int i = 0; i < 64; i++) o[i] = 0.f;
                    float n0 = 0.f, n1 = 0.f, l0 = 1.f, l1 = 1.f;
                    bool shifted = false;
                    const uint64_t dbase = desc_of(sbase);
                    const uint64_t dbk = dbase - (511u << 16);
                    const int my_bar = 1 + wg, other_bar = 2 - wg;

                    auto softmax_a = [&](bool first, float& s0, float& s1) {
                        if (first) {
                            shifted = false;
                            n0 = n1 = 0.f;
                            l0 = l1 = 0.f;
                        }
                        if (shifted)
                            exp_step<true>(sa, pa, n0, n1, s0, s1);
                        else
                            exp_step<false>(sa, pa, n0, n1, s0, s1);
                    };
                    auto softmax_b = [&](bool first, float s0, float s1) {
                        float u0, u1;
                        if (shifted)
                            exp_step<true>(sb, pb, n0, n1, u0, u1);
                        else
                            exp_step<false>(sb, pb, n0, n1, u0, u1);
                        s0 += u0;
                        s1 += u1;
                        bool bad = !(fmaxf(s0, s1) <= SM_HI);
                        if (first) {
                            float r0 = s0 + __shfl_xor_sync(0xffffffffu, s0, 1), r1 = s1 + __shfl_xor_sync(0xffffffffu, s1, 1);
                            r0 += __shfl_xor_sync(0xffffffffu, r0, 2);
                            r1 += __shfl_xor_sync(0xffffffffu, r1, 2);
                            bad = bad || !(fminf(r0, r1) >= SM_LO);
                        }
                        if (__any_sync(0xffffffffu, bad)) {
                            float x0, x1;
                            row_max(sa, sb, x0, x1);
                            x0 = -x0;
                            x1 = -x1;
                            if (!first) {
                                x0 = fminf(x0, n0);
                                x1 = fminf(x1, n1);
                                const float al0 = ex2(x0 - n0), al1 = ex2(x1 - n1);
                                l0 *= al0;
                                l1 *= al1;
#pragma unroll
                                for (int i = 0; i < 16; i++) {
                                    o[4 * i] *= al0;
                                    o[4 * i + 1] *= al0;
                                    o[4 * i + 2] *= al1;
                                    o[4 * i + 3] *= al1;
                                }
                            }
                            n0 = x0;
                            n1 = x1;
                            shifted = true;
                            exp_step<true>(sa, pa, n0, n1, s0, s1);
                            exp_step<true>(sb, pb, n0, n1, u0, u1);
                            s0 += u0;
                            s1 += u1;
                        }
                        l0 += s0;
                        l1 += s1;
                    };

                    cx.wait_full(4, 0);
                    if (wg == 1) bar_sync(my_bar, 256);
                    wg_fence();
                    qk_step(sa, q, dbk + 4 * 1024);
                    qk_step(sb, q, dbk + 5 * 1024);
                    wg_commit();
                    bar_arrive(other_bar, 256);
                    wg_wait<0>();
                    pin(sa);
                    pin(sb);
                    cx.release(4);
                    cx.wait_full(6, 0);
                    {
                        float s0, s1;
                        softmax_a(true, s0, s1);
                        softmax_b(true, s0, s1);
                    }
                    uint32_t alo = (uint32_t)dbase + 6 * 1024, blo = (uint32_t)dbase;
                    const uint32_t dhi = (uint32_t)(dbase >> 32);
#pragma unroll 1
                    for (int t = 1; t < 64; t++) {
                        const int j = t & 15;
                        const uint32_t sA = 2 + 4 * (t & 1), sB = 4 - 4 * (t & 1);
                        const uint64_t da = ((uint64_t)dhi << 32) | alo, db = ((uint64_t)dhi << 32) | blo;
                        TL(0);
                        bar_sync(my_bar, 256);
                        TL(2);
                        wg_fence();
                        qk_step(sa, q, da - (511u << 16));
                        pv_step(o, pa, da + 1024, j != 1);
                        wg_commit();
                        cx.wait_full(sB, ((36 + 4 * t) >> 3) & 1);
                        wg_fence();
                        qk_step(sb, q, db - (511u << 16));
                        pv_step(o, pb, db + 1024, 1);
                        wg_commit();
                        bar_arrive(other_bar, 256);
                        alo ^= 4096;
                        blo ^= 4096;
                        asm volatile("" : "+r"(alo), "+r"(blo));
                        TL(3);
                        wg_wait<1>();
                        pin(sa);
                        pin(pa);
                        TL(4);
                        cx.release(sA);
                        const float lp0 = l0, lp1 = l1;
                        float s0, s1;
                        softmax_a(j == 0, s0, s1);
                        TL(5);
                        wg_wait<0>();
                        pin(o);
                        pin(sb);
                        pin(pb);
                        TL(6);
                        cx.release(sB);
                        if (j == 0) {
                            float i0, i1;
                            inv_row_sums(lp0, lp1, i0, i1);
                            const uint32_t dst = spill + ((t >> 4) - 1) * 16384;
#pragma unroll
                            for (int v = 0; v < 8; v++)
                                sts128(dst + v * 2048, pack_bf16(o[8 * v] * i0, o[8 * v + 1] * i0),
                                       pack_bf16(o[8 * v + 2] * i1, o[8 * v + 3] * i1),
                                       pack_bf16(o[8 * v + 4] * i0, o[8 * v + 5] * i0),
                                       pack_bf16(o[8 * v + 6] * i1, o[8 * v + 7] * i1));
                        }
                        const uint32_t bn = sbase + OFF_FULL + (8 - sA) * 8, pn = ((38 + 4 * t) >> 3) & 1;
                        const bool okn = mbar_try(bn, pn);
                        TL(1);
                        softmax_b(j == 0, s0, s1);
                        if (!okn || j == 15) {
                            mbar_wait(bn, pn);
                            if (t == 47 && wg == 0) bar_arrive(6, 160);
                            if (j == 15 && t < 63) {
                                const uint32_t src = spill + (t >> 4) * 16384;
#pragma unroll
                                for (int v = 0; v < 8; v++)
                                    lds128(src + v * 2048, q[4 * v], q[4 * v + 1], q[4 * v + 2], q[4 * v + 3]);
                            }
                        }
                        TL(7);
                    }
                    bar_sync(my_bar, 256);
                    wg_fence();
                    pv_step(o, pa, dbase + 2 * 1024, 1);
                    pv_step(o, pb, dbase + 3 * 1024, 1);
                    wg_commit();
                    if (wg == 0) bar_arrive(other_bar, 256);
                    float i0, i1;
                    inv_row_sums(l0, l1, i0, i1);
                    wg_wait<0>();
                    pin(o);
                    cx.release(2);
#pragma unroll
                    for (int i = 0; i < 16; i++) {
                        a[2 * i] = pack_bf16(o[4 * i] * i0, o[4 * i + 1] * i0);
                        a[2 * i + 1] = pack_bf16(o[4 * i + 2] * i1, o[4 * i + 3] * i1);
                    }
#pragma unroll
                    for (int v = 0; v < 24; v++)
                        lds128(spill + v * 2048, a[32 + 4 * v], a[33 + 4 * v], a[34 + 4 * v], a[35 + 4 * v]);
#pragma unroll
                    for (int i = 128; i < 144; i++) a[i] = 0;
                }
                ring.slot = 4;
                ring.phase = 0;
                PROF(6);
                PROFG(24);
            } else {
#pragma unroll
                for (int v = 0; v < 8; v++) {
                    const uint4 t = __ldcg(hhbuf + v * 256);
                    a[112 + 4 * v] = t.x;
                    a[113 + 4 * v] = t.y;
                    a[114 + 4 * v] = t.z;
                    a[115 + 4 * v] = t.w;
                }
#pragma unroll
                for (int i = 0; i < 16; i++) a[i] = pack_bf16(d[2 * i], d[2 * i + 1]);
#pragma unroll
                for (int v = 0; v < 24; v++)
                    lds128(spill + v * 2048, a[16 + 4 * v], a[17 + 4 * v], a[18 + 4 * v], a[19 + 4 * v]);
                PROF(13);
            }

            {
                uint4* dst = sc_->part + ((size_t)wown * 8 + g) * 36 * 32 + lane;
                const uint32_t ptag = (stage + 1) & 1;
#pragma unroll 1
                for (int p = 0; p < 4; p++) {
                    TG(stage * 32 + 18 + p * 2);
                    gemm_n128(d, a, cx, ring, stage != 0, stage && wg);
                    TG(stage * 32 + 19 + p * 2);
#pragma unroll
                    for (int u = 0; u < 8; u++)
                        st128(dst + (p * 8 + u) * 32, (pack_bf16(d[8 * u], d[8 * u + 1]) & ~1u) | ptag,
                              pack_bf16(d[8 * u + 2], d[8 * u + 3]), pack_bf16(d[8 * u + 4], d[8 * u + 5]),
                              pack_bf16(d[8 * u + 6], d[8 * u + 7]));
                    if (p == 0 && wg == 0) bar_arrive(7, 160);
                }
                float e[32];
                TG(stage * 32 + 26);
                gemm_n64(e, a, cx, ring, stage != 0);
                TG(stage * 32 + 27);
                uint2* dst2 = reinterpret_cast<uint2*>(dst - lane + 32 * 32) + lane;
#pragma unroll
                for (int j = 0; j < 8; j++)
                    st64(dst2 + j * 32, (pack_bf16(e[4 * j], e[4 * j + 1]) & ~1u) | ptag, pack_bf16(e[4 * j + 2], e[4 * j + 3]));
            }
            PROF(stage == 0 ? 7 : 14);
            if (stage == 1) {
                PROFG(26);
                asm volatile("barrier.cluster.arrive.relaxed.aligned;" ::: "memory");
            }
        }
        if (wg == 0) bar_sync(8, 256);
        bar_sync(3, 256);
        if (tid == 32) sc_->epoch[b * 32] = get_epoch(sbase) + 1;
        if (tid == 0) {
            rows_store(sbase, &maps.rout, own * 16);
            rows_store_wait();
        }
        __syncwarp();
        PROF(16);
        PROFG(31);
        asm volatile("barrier.cluster.wait.aligned;" ::: "memory");
    }
}

typedef CUresult (*EncodeFn)(CUtensorMap*, CUtensorMapDataType, cuuint32_t, void*, const cuuint64_t*, const cuuint64_t*,
                             const cuuint32_t*, const cuuint32_t*, CUtensorMapInterleave, CUtensorMapSwizzle,
                             CUtensorMapL2promotion, CUtensorMapFloatOOBfill);

void make_map(EncodeFn enc, CUtensorMap* m, const void* ptr, uint64_t rows, uint64_t cols, bool narrow = false) {
    cuuint64_t gdim[2] = {cols, rows};
    cuuint64_t gstr[1] = {cols * 2};
    cuuint32_t box[2] = {narrow ? 16u : 64u, narrow ? 192u : 64u};
    cuuint32_t estr[2] = {1, 1};
    enc(m, CU_TENSOR_MAP_DATA_TYPE_BFLOAT16, 2, const_cast<void*>(ptr), gdim, gstr, box, estr,
        CU_TENSOR_MAP_INTERLEAVE_NONE, narrow ? CU_TENSOR_MAP_SWIZZLE_NONE : CU_TENSOR_MAP_SWIZZLE_128B,
        CU_TENSOR_MAP_L2_PROMOTION_L2_128B,
        CU_TENSOR_MAP_FLOAT_OOB_FILL_NONE);
}

void make_rows_map(EncodeFn enc, CUtensorMap* m, const void* ptr) {
    cuuint64_t gdim[3] = {64, 9, 2048};
    cuuint64_t gstr[2] = {128, DM * 2};
    cuuint32_t box[3] = {64, 9, 16};
    cuuint32_t estr[3] = {1, 1, 1};
    enc(m, CU_TENSOR_MAP_DATA_TYPE_BFLOAT16, 3, const_cast<void*>(ptr), gdim, gstr, box, estr,
        CU_TENSOR_MAP_INTERLEAVE_NONE, CU_TENSOR_MAP_SWIZZLE_128B, CU_TENSOR_MAP_L2_PROMOTION_L2_128B,
        CU_TENSOR_MAP_FLOAT_OOB_FILL_NONE);
}

}

extern "C" void kernel_launch(void* const* d_in, const int* in_sizes, int n_in, void* d_out, int out_size) {
    (void)in_sizes;
    (void)n_in;
    (void)out_size;
    void* fn = nullptr;
    cudaDriverEntryPointQueryResult qr;
    cudaGetDriverEntryPoint("cuTensorMapEncodeTiled", &fn, cudaEnableDefault, &qr);
    EncodeFn enc = (EncodeFn)fn;
    Params maps;
    maps.x = (const __nv_bfloat16*)d_in[0];
    maps.cvec = (const __nv_bfloat16*)d_in[9];
    maps.wmod = (const __nv_bfloat16*)d_in[10];
    maps.kc = (const __nv_bfloat16*)d_in[1];
    maps.vc = (const __nv_bfloat16*)d_in[2];
    maps.wq_p = (const __nv_bfloat16*)d_in[3];
    maps.wo_p = (const __nv_bfloat16*)d_in[4];
    maps.wg_p = (const __nv_bfloat16*)d_in[6];
    maps.wu_p = (const __nv_bfloat16*)d_in[7];
    maps.wd_p = (const __nv_bfloat16*)d_in[8];
    maps.out = (__nv_bfloat16*)d_out;
    void* scp = nullptr;
    cudaGetSymbolAddress(&scp, g_scratch);
    maps.sc = (Scratch*)scp;
    make_map(enc, &maps.k, d_in[1], 32 * 2048, 128);
    make_map(enc, &maps.v, d_in[2], 32 * 2048, 128);
    make_map(enc, &maps.wq, d_in[3], 576, 4096);
    make_map(enc, &maps.wo, d_in[4], 4096, 576);
    make_map(enc, &maps.wg, d_in[6], 576, 4608);
    make_map(enc, &maps.wu, d_in[7], 576, 4608);
    make_map(enc, &maps.wd, d_in[8], 4608, 576);
    make_rows_map(enc, &maps.rx, d_in[0]);
    make_rows_map(enc, &maps.rx2, (char*)scp + offsetof(Scratch, x2));
    make_rows_map(enc, &maps.rout, d_out);
    cudaFuncSetAttribute(fused_block_kernel, cudaFuncAttributeMaxDynamicSharedMemorySize, SMEM_BYTES);
    fused_block_kernel<<<128, 384, SMEM_BYTES>>>(maps);
}
```
